```python
import torch

def _softmax(x, axis=-1):
    return torch.softmax(x, dim=axis)

def _gelu(x):
    return torch.nn.functional.gelu(x, approximate='tanh')

def _silu(x):
    return torch.nn.functional.silu(x)

def _sigmoid(x):
    return torch.sigmoid(x)

def _layernorm(x, axis=-1, eps=1e-05):
    m = x.mean(dim=axis, keepdim=True)
    v = x.var(dim=axis, keepdim=True, unbiased=False)
    return (x - m) / torch.sqrt(v + eps)

def _scatter_add(tgt, idx, src, axis=0):
    return tgt.clone().index_add_(axis, idx, src)

def _segment_sum(src, seg, n):
    out = torch.zeros((n,) + src.shape[1:], dtype=src.dtype)
    return out.index_add_(0, seg, src)

def _pad(x, pw):
    flat = tuple((v for pair in reversed(pw) for v in pair))
    return torch.nn.functional.pad(x, flat)
kernel_name = 'concat_heads__memory_aug_recurrent_mem_tr__sliding_local_dilated__prompt'

def setup_inputs():

    _w = lambda a: (lambda t: t.to(torch.bfloat16) if t.is_floating_point() else t)(torch.as_tensor(a))

    def _A_setup():
        B, S, Dm = (1, 2048, 1024)
        H, Dh = (32, 128)
        M, seg = (8, 32)
        seg = min(seg, S)
        S = S // seg * seg
        return {'x': _w((lambda *s: torch.randn(*s, dtype=torch.bfloat16) * 0.05)(B, S, Dm)), 'mem0': _w((lambda *s: torch.randn(*s, dtype=torch.bfloat16) * 1.6)(B, M, Dm)), 'Wq': _w((lambda *s: torch.randn(*s, dtype=torch.bfloat16) * 0.8)(Dm, H, Dh) * Dm ** (-0.5)), 'Wk': _w((lambda *s: torch.randn(*s, dtype=torch.bfloat16) * 0.8)(Dm, H, Dh) * Dm ** (-0.5)), 'Wv': _w((lambda *s: torch.randn(*s, dtype=torch.bfloat16) * 1.6)(Dm, H, Dh) * Dm ** (-0.5)), 'Wo': _w((lambda *s: torch.randn(*s, dtype=torch.bfloat16) * 1.6)(H, Dh, Dm) * (H * Dh) ** (-0.5)), 'seg_len': seg}
    _A_in = _A_setup()

    def _B_setup():
        B, S, D = (1, 2048, 1024)
        return {'x': _w((lambda *s: torch.randn(*s, dtype=torch.bfloat16) * 0.2)(B, S, D)), 'wqkv': _w((lambda *s: torch.randn(*s, dtype=torch.bfloat16) * 0.2)(D, 3 * D)), 'wo': _w((lambda *s: torch.randn(*s, dtype=torch.bfloat16) * 0.05)(D, D))}
    _B_in = _B_setup()
    return {'A_x': _A_in['x'], 'A_mem0': _A_in['mem0'], 'A_Wq': _A_in['Wq'], 'A_Wk': _A_in['Wk'], 'A_Wv': _A_in['Wv'], 'A_Wo': _A_in['Wo'], 'A_seg_len': _A_in['seg_len'], 'B_x': _B_in['x'], 'B_wqkv': _B_in['wqkv'], 'B_wo': _B_in['wo']}

def reference(A_x, A_mem0, A_Wq, A_Wk, A_Wv, A_Wo, A_seg_len, B_x, B_wqkv, B_wo):

    def _A_ref(x, mem0, Wq, Wk, Wv, Wo, seg_len):
        B, S, Dm = x.shape
        H, Dh = (Wq.shape[1], Wq.shape[2])
        M = mem0.shape[1]
        scale = Dh ** (-0.5)
        n_seg = S // seg_len
        L = M + seg_len
        idx = torch.arange(L)
        mask = (idx[:, None] < M) | (idx[:, None] >= idx[None, :])
        mem = mem0
        outs = []
        for s in range(n_seg):
            xs = x[:, s * seg_len:(s + 1) * seg_len, :].clone()
            h = torch.concatenate([mem, xs], axis=1)
            q = torch.einsum('btd,dhe->bhte', h, Wq)
            k = torch.einsum('btd,dhe->bhte', h, Wk)
            v = torch.einsum('btd,dhe->bhte', h, Wv)
            scores = torch.einsum('bhqe,bhke->bhqk', q, k) * scale
            scores = torch.where(mask[None, None], scores, -1000000000.0)
            p = _softmax(scores, axis=-1)
            o = torch.einsum('bhqk,bhke->bhqe', p, v)
            o = torch.einsum('bhte,hed->btd', o, Wo)
            mem = o[:, :M, :].clone()
            outs.append(o[:, M:, :])
        return torch.concatenate(outs, axis=1)

    def _B_ref(x, wqkv, wo):
        B, S, D = x.shape
        H = 32
        Dh = D // H
        W, dil = (8, 2)
        qkv = (lambda x, *d: x.permute(*d))((x @ wqkv).reshape(B, S, 3, H, Dh), 2, 0, 3, 1, 4)
        q, k, v = (qkv[0], qkv[1], qkv[2])
        scale = Dh ** (-0.5)
        pos = torch.arange(S)
        off = torch.arange(W) * dil
        idx = pos[:, None] - off[None, :]
        mask = idx >= 0
        idx_c = torch.where(mask, idx, 0).reshape(-1)
        kg = k[:, :, idx_c, :].reshape(B, H, S, W, Dh)
        vg = v[:, :, idx_c, :].reshape(B, H, S, W, Dh)
        logits = torch.einsum('bhsd,bhswd->bhsw', q, kg) * scale
        logits = torch.where(mask[None, None, :, :], logits, -1000000000.0)
        attn = _softmax(logits, axis=-1)
        o = torch.einsum('bhsw,bhswd->bhsd', attn, vg)
        return (lambda x, *d: x.permute(*d))(o, 0, 2, 1, 3).reshape(B, S, D) @ wo
    a = _A_ref(A_x, A_mem0, A_Wq, A_Wk, A_Wv, A_Wo, A_seg_len)
    b = _B_ref(B_x, B_wqkv, B_wo)
    return torch.concatenate([a, b], axis=-1)
```

```cpp
#include <cuda_runtime.h>
#include <cuda_bf16.h>
#include <cuda.h>
#include <stdint.h>

typedef __nv_bfloat16 bf16;

constexpr int S_TOK = 2048;
constexpr int DM    = 1024;
constexpr int NH    = 32;
constexpr int DH    = 128;
constexpr int NSEG  = 64;
constexpr int HD    = NH * DH;

__device__ __align__(1024) bf16 g_qx[NSEG * NH * 4 * DH * 8];
__device__ __align__(1024) bf16 g_ox[S_TOK * HD];
__device__ __align__(1024) bf16 g_bqkv[S_TOK * 3 * DM];
__device__ __align__(1024) bf16 g_bo[S_TOK * DM];
__device__ __align__(1024) uint8_t g_acc[384 * 1024];

#define EV(cond, s, k) do {} while (0)
#define EVCAL(s) do {} while (0)

__device__ unsigned g_epoch, g_qctr, g_done, g_zero;
__device__ unsigned g_cnt_b1[8], g_cnt_b2[8], g_cnt_q[8], g_prog[16], g_cnt_sk[32];
__device__ __align__(1024) float g_skp[2 * 8 * 4 * 2 * 128 * 64];
#define TLOG(i, k, v) do {} while (0)
__device__ unsigned g_resident;

#define DEVI __device__ __forceinline__

DEVI uint32_t opaque(uint32_t v) { uint32_t r; asm volatile("mov.u32 %0, %1;" : "=r"(r) : "r"(v)); return r; }
DEVI uint32_t smem_u32(const void* p) { return (uint32_t)__cvta_generic_to_shared(p); }

#define TRAP(code) __trap()
constexpr int SPIN_LIMIT = 1 << 22;
#define MBAR_HINT_NS 20000u
constexpr int SPIN_LIMIT_MBAR = 1 << 17;

DEVI void mbar_init(uint32_t bar, uint32_t cnt) { asm volatile("mbarrier.init.shared::cta.b64 [%0], %1;" :: "r"(bar), "r"(cnt)); }
DEVI void mbar_expect_tx(uint32_t bar, uint32_t bytes) {
    asm volatile("mbarrier.arrive.expect_tx.shared::cta.b64 _, [%0], %1;" :: "r"(bar), "r"(bytes) : "memory");
}
DEVI void mbar_arrive(uint32_t bar) { asm volatile("mbarrier.arrive.shared::cta.b64 _, [%0];" :: "r"(bar) : "memory"); }
DEVI bool mbar_try(uint32_t bar, uint32_t parity) {
    uint32_t ok;
    asm volatile("{.reg .pred p; mbarrier.try_wait.parity.shared::cta.b64 p, [%1], %2; selp.u32 %0, 1, 0, p;}"
                 : "=r"(ok) : "r"(bar), "r"(parity) : "memory");
    return ok;
}
DEVI bool mbar_try_cluster(uint32_t bar, uint32_t parity) {
    uint32_t ok;
    asm volatile("{.reg .pred p; mbarrier.try_wait.parity.acquire.cluster.shared::cta.b64 p, [%1], %2; selp.u32 %0, 1, 0, p;}"
                 : "=r"(ok) : "r"(bar), "r"(parity) : "memory");
    return ok;
}
DEVI bool mbar_try_hint(uint32_t bar, uint32_t parity) {
    uint32_t ok;
    asm volatile("{.reg .pred p; mbarrier.try_wait.parity.shared::cta.b64 p, [%1], %2, %3; selp.u32 %0, 1, 0, p;}"
                 : "=r"(ok) : "r"(bar), "r"(parity), "r"(MBAR_HINT_NS) : "memory");
    return ok;
}
DEVI void mbar_wait(uint32_t bar, uint32_t parity) {
    int n = 0;
    while (!mbar_try(bar, parity)) { if (++n > SPIN_LIMIT) TRAP(bar | (parity << 31)); }
}
DEVI void mbar_wait_sleepy(uint32_t bar, uint32_t parity) {
    int n = 0;
    while (!mbar_try_hint(bar, parity)) { if (++n > SPIN_LIMIT_MBAR) __trap(); }
}
DEVI void mbar_wait_cluster(uint32_t bar, uint32_t parity) {
    int n = 0;
    while (!mbar_try_cluster(bar, parity)) { if (++n > SPIN_LIMIT) __trap(); }
}
DEVI void mbar_spin(uint32_t bar, uint32_t parity) {
    uint32_t ok; int n = 0;
    do {
        asm volatile("{.reg .pred p; mbarrier.test_wait.parity.shared::cta.b64 p, [%1], %2; selp.u32 %0, 1, 0, p;}"
                     : "=r"(ok) : "r"(bar), "r"(parity) : "memory");
        if (++n > SPIN_LIMIT) __trap();
    } while (!ok);
}
DEVI void fence_mbar_init() { asm volatile("fence.mbarrier_init.release.cluster;" ::: "memory"); }
DEVI void fence_proxy_async() { asm volatile("fence.proxy.async.shared::cta;" ::: "memory"); }
DEVI void cluster_sync() {
    asm volatile("barrier.cluster.arrive.release.aligned;\n barrier.cluster.wait.acquire.aligned;" ::: "memory");
}
DEVI void nbar_sync(int id, int n) { asm volatile("bar.sync %0, %1;" :: "r"(id), "r"(n) : "memory"); }
DEVI void nbar_arrive(int id, int n) { asm volatile("bar.arrive %0, %1;" :: "r"(id), "r"(n) : "memory"); }

DEVI void tma_load_2d(uint32_t dst, const CUtensorMap* map, int x, int y, uint32_t bar) {
    asm volatile("cp.async.bulk.tensor.2d.shared::cluster.global.mbarrier::complete_tx::bytes [%0], [%1, {%3, %4}], [%2];"
                 :: "r"(dst), "l"(map), "r"(bar), "r"(x), "r"(y) : "memory");
}
DEVI void tma_load_3d(uint32_t dst, const CUtensorMap* map, int x, int y, int z, uint32_t bar) {
    asm volatile("cp.async.bulk.tensor.3d.shared::cluster.global.mbarrier::complete_tx::bytes [%0], [%1, {%3, %4, %5}], [%2];"
                 :: "r"(dst), "l"(map), "r"(bar), "r"(x), "r"(y), "r"(z) : "memory");
}
DEVI void tma_store_2d(const CUtensorMap* map, uint32_t src, int x, int y) {
    asm volatile("cp.async.bulk.tensor.2d.global.shared::cta.bulk_group [%0, {%2, %3}], [%1];"
                 :: "l"(map), "r"(src), "r"(x), "r"(y) : "memory");
}
DEVI void bulk_load(uint32_t dst, const void* src, uint32_t bytes, uint32_t bar) {
    asm volatile("cp.async.bulk.shared::cluster.global.mbarrier::complete_tx::bytes [%0], [%1], %2, [%3];"
                 :: "r"(dst), "l"(src), "r"(bytes), "r"(bar) : "memory");
}
DEVI void tma_load_2d_mc(uint32_t dst, const CUtensorMap* map, int x, int y, uint32_t bar, uint16_t mask) {
    asm volatile("cp.async.bulk.tensor.2d.shared::cluster.global.mbarrier::complete_tx::bytes.multicast::cluster [%0], [%1, {%3, %4}], [%2], %5;"
                 :: "r"(dst), "l"(map), "r"(bar), "r"(x), "r"(y), "h"(mask) : "memory");
}
DEVI void bulk_copy_s2c(uint32_t dst_cluster, uint32_t src, uint32_t bytes, uint32_t bar_cluster) {
    asm volatile("cp.async.bulk.shared::cluster.shared::cta.mbarrier::complete_tx::bytes [%0], [%1], %2, [%3];"
                 :: "r"(dst_cluster), "r"(src), "r"(bytes), "r"(bar_cluster) : "memory");
}
DEVI void bulk_store(void* dst, uint32_t src, uint32_t bytes) {
    asm volatile("cp.async.bulk.global.shared::cta.bulk_group [%0], [%1], %2;" :: "l"(dst), "r"(src), "r"(bytes) : "memory");
}
DEVI void bulk_wait_read() { asm volatile("cp.async.bulk.wait_group.read 0;" ::: "memory"); }
DEVI void mbar_arrive_remote(uint32_t bar_cluster) {
    asm volatile("mbarrier.arrive.shared::cluster.b64 _, [%0];" :: "r"(bar_cluster) : "memory");
}
DEVI void mbar_expect_tx_remote(uint32_t bar_cluster, uint32_t bytes) {
    asm volatile("mbarrier.arrive.expect_tx.shared::cluster.b64 _, [%0], %1;" :: "r"(bar_cluster), "r"(bytes) : "memory");
}
DEVI void l2_prefetch(const void* p, uint32_t bytes) {
    asm volatile("cp.async.bulk.prefetch.L2.global [%0], %1;" :: "l"(p), "r"(bytes) : "memory");
}
DEVI void bulk_commit() { asm volatile("cp.async.bulk.commit_group;" ::: "memory"); }
DEVI void bulk_wait_all() { asm volatile("cp.async.bulk.wait_group 0;" ::: "memory"); }

DEVI void wg_fence() { asm volatile("wgmma.fence.sync.aligned;" ::: "memory"); }
DEVI void wg_commit() { asm volatile("wgmma.commit_group.sync.aligned;" ::: "memory"); }
template <int N> DEVI void wg_wait() { asm volatile("wgmma.wait_group.sync.aligned %0;" :: "n"(N) : "memory"); }

template <int R> DEVI void reg_dec() { asm volatile("setmaxnreg.dec.sync.aligned.u32 %0;" :: "n"(R)); }
template <int R> DEVI void reg_inc() { asm volatile("setmaxnreg.inc.sync.aligned.u32 %0;" :: "n"(R)); }

DEVI uint64_t mk_desc(uint32_t addr, uint32_t lbo, uint32_t sbo, uint32_t sw) {
    return (uint64_t)((addr & 0x3FFFF) >> 4) | ((uint64_t)(lbo >> 4) << 16) | ((uint64_t)(sbo >> 4) << 32) | ((uint64_t)sw << 62);
}

DEVI uint32_t desc_lo(uint32_t addr, uint32_t lbo) { return ((addr & 0x3FFFF) >> 4) | ((lbo >> 4) << 16); }
constexpr uint32_t DHI_SW128 = (1024u >> 4) | (1u << 30);
constexpr uint32_t DHI_SW64  = (512u >> 4) | (2u << 30);
constexpr uint32_t DHI_NONE  = (128u >> 4);

template <int TB, int SCALE_D>
DEVI void wgmma_n8_ss(float* d, uint32_t alo, uint32_t blo) {
    asm volatile("{.reg .b64 da, db; mov.b64 da, {%4, %6}; mov.b64 db, {%5, %7};\n"
                 "wgmma.mma_async.sync.aligned.m64n8k16.f32.bf16.bf16 {%0,%1,%2,%3}, da, db, %8, 1, 1, 1, %9;}"
                 : "+f"(d[0]), "+f"(d[1]), "+f"(d[2]), "+f"(d[3])
                 : "r"(alo), "r"(blo), "n"(DHI_SW128), "n"(DHI_NONE), "n"(SCALE_D), "n"(TB));
}

template <int TB>
DEVI void wgmma_n8_ss_first(float* d, uint32_t alo, uint32_t blo) {
    asm volatile("{.reg .b64 da, db; mov.b64 da, {%4, %6}; mov.b64 db, {%5, %7};\n"
                 "wgmma.mma_async.sync.aligned.m64n8k16.f32.bf16.bf16 {%0,%1,%2,%3}, da, db, 0, 1, 1, 1, %8;}"
                 : "=f"(d[0]), "=f"(d[1]), "=f"(d[2]), "=f"(d[3])
                 : "r"(alo), "r"(blo), "n"(DHI_SW128), "n"(DHI_NONE), "n"(TB));
}
DEVI void wgmma_n32_rs_first(float* d, const uint32_t* a, uint32_t blo) {
    asm volatile("{.reg .b64 db; mov.b64 db, {%20, %21};\n"
                 "wgmma.mma_async.sync.aligned.m64n32k16.f32.bf16.bf16 {%0,%1,%2,%3,%4,%5,%6,%7,%8,%9,%10,%11,%12,%13,%14,%15}, "
                 "{%16,%17,%18,%19}, db, 0, 1, 1, 0;}"
                 : "=f"(d[0]), "=f"(d[1]), "=f"(d[2]), "=f"(d[3]), "=f"(d[4]), "=f"(d[5]), "=f"(d[6]), "=f"(d[7]),
                   "=f"(d[8]), "=f"(d[9]), "=f"(d[10]), "=f"(d[11]), "=f"(d[12]), "=f"(d[13]), "=f"(d[14]), "=f"(d[15])
                 : "r"(a[0]), "r"(a[1]), "r"(a[2]), "r"(a[3]), "r"(blo), "n"(DHI_SW64));
}
template <int N> DEVI void reg_fence(float* d) {
#pragma unroll
    for (int i = 0; i < N; i++) asm volatile("" : "+f"(d[i]) :: "memory");
}
DEVI void wgmma_n32_rs(float* d, const uint32_t* a, uint32_t blo) {
    asm volatile("{.reg .b64 db; mov.b64 db, {%20, %21};\n"
                 "wgmma.mma_async.sync.aligned.m64n32k16.f32.bf16.bf16 {%0,%1,%2,%3,%4,%5,%6,%7,%8,%9,%10,%11,%12,%13,%14,%15}, "
                 "{%16,%17,%18,%19}, db, 1, 1, 1, 0;}"
                 : "+f"(d[0]), "+f"(d[1]), "+f"(d[2]), "+f"(d[3]), "+f"(d[4]), "+f"(d[5]), "+f"(d[6]), "+f"(d[7]),
                   "+f"(d[8]), "+f"(d[9]), "+f"(d[10]), "+f"(d[11]), "+f"(d[12]), "+f"(d[13]), "+f"(d[14]), "+f"(d[15])
                 : "r"(a[0]), "r"(a[1]), "r"(a[2]), "r"(a[3]), "r"(blo), "n"(DHI_SW64));
}
DEVI void wgmma_n32_ss(float* d, uint32_t alo, uint32_t blo) {
    asm volatile("{.reg .b64 da, db; mov.b64 da, {%16, %18}; mov.b64 db, {%17, %19};\n"
                 "wgmma.mma_async.sync.aligned.m64n32k16.f32.bf16.bf16 {%0,%1,%2,%3,%4,%5,%6,%7,%8,%9,%10,%11,%12,%13,%14,%15}, "
                 "da, db, 1, 1, 1, 1, 0;}"
                 : "+f"(d[0]), "+f"(d[1]), "+f"(d[2]), "+f"(d[3]), "+f"(d[4]), "+f"(d[5]), "+f"(d[6]), "+f"(d[7]),
                   "+f"(d[8]), "+f"(d[9]), "+f"(d[10]), "+f"(d[11]), "+f"(d[12]), "+f"(d[13]), "+f"(d[14]), "+f"(d[15])
                 : "r"(alo), "r"(blo), "n"(DHI_SW128), "n"(DHI_SW64));
}

DEVI void wgmma_n256_ss(float* d, uint64_t a, uint64_t b, int scale_d) {
    asm volatile("{.reg .pred p; setp.ne.b32 p, %130, 0;\n"
        "wgmma.mma_async.sync.aligned.m64n256k16.f32.bf16.bf16 "
        "{%0,%1,%2,%3,%4,%5,%6,%7,%8,%9,%10,%11,%12,%13,%14,%15,"
        "%16,%17,%18,%19,%20,%21,%22,%23,%24,%25,%26,%27,%28,%29,%30,%31,"
        "%32,%33,%34,%35,%36,%37,%38,%39,%40,%41,%42,%43,%44,%45,%46,%47,"
        "%48,%49,%50,%51,%52,%53,%54,%55,%56,%57,%58,%59,%60,%61,%62,%63,"
        "%64,%65,%66,%67,%68,%69,%70,%71,%72,%73,%74,%75,%76,%77,%78,%79,"
        "%80,%81,%82,%83,%84,%85,%86,%87,%88,%89,%90,%91,%92,%93,%94,%95,"
        "%96,%97,%98,%99,%100,%101,%102,%103,%104,%105,%106,%107,%108,%109,%110,%111,"
        "%112,%113,%114,%115,%116,%117,%118,%119,%120,%121,%122,%123,%124,%125,%126,%127},"
        " %128, %129, p, 1, 1, 1, 0;}"
        : "+f"(d[0]), "+f"(d[1]), "+f"(d[2]), "+f"(d[3]), "+f"(d[4]), "+f"(d[5]), "+f"(d[6]), "+f"(d[7]),
          "+f"(d[8]), "+f"(d[9]), "+f"(d[10]), "+f"(d[11]), "+f"(d[12]), "+f"(d[13]), "+f"(d[14]), "+f"(d[15]),
          "+f"(d[16]), "+f"(d[17]), "+f"(d[18]), "+f"(d[19]), "+f"(d[20]), "+f"(d[21]), "+f"(d[22]), "+f"(d[23]),
          "+f"(d[24]), "+f"(d[25]), "+f"(d[26]), "+f"(d[27]), "+f"(d[28]), "+f"(d[29]), "+f"(d[30]), "+f"(d[31]),
          "+f"(d[32]), "+f"(d[33]), "+f"(d[34]), "+f"(d[35]), "+f"(d[36]), "+f"(d[37]), "+f"(d[38]), "+f"(d[39]),
          "+f"(d[40]), "+f"(d[41]), "+f"(d[42]), "+f"(d[43]), "+f"(d[44]), "+f"(d[45]), "+f"(d[46]), "+f"(d[47]),
          "+f"(d[48]), "+f"(d[49]), "+f"(d[50]), "+f"(d[51]), "+f"(d[52]), "+f"(d[53]), "+f"(d[54]), "+f"(d[55]),
          "+f"(d[56]), "+f"(d[57]), "+f"(d[58]), "+f"(d[59]), "+f"(d[60]), "+f"(d[61]), "+f"(d[62]), "+f"(d[63]),
          "+f"(d[64]), "+f"(d[65]), "+f"(d[66]), "+f"(d[67]), "+f"(d[68]), "+f"(d[69]), "+f"(d[70]), "+f"(d[71]),
          "+f"(d[72]), "+f"(d[73]), "+f"(d[74]), "+f"(d[75]), "+f"(d[76]), "+f"(d[77]), "+f"(d[78]), "+f"(d[79]),
          "+f"(d[80]), "+f"(d[81]), "+f"(d[82]), "+f"(d[83]), "+f"(d[84]), "+f"(d[85]), "+f"(d[86]), "+f"(d[87]),
          "+f"(d[88]), "+f"(d[89]), "+f"(d[90]), "+f"(d[91]), "+f"(d[92]), "+f"(d[93]), "+f"(d[94]), "+f"(d[95]),
          "+f"(d[96]), "+f"(d[97]), "+f"(d[98]), "+f"(d[99]), "+f"(d[100]), "+f"(d[101]), "+f"(d[102]), "+f"(d[103]),
          "+f"(d[104]), "+f"(d[105]), "+f"(d[106]), "+f"(d[107]), "+f"(d[108]), "+f"(d[109]), "+f"(d[110]), "+f"(d[111]),
          "+f"(d[112]), "+f"(d[113]), "+f"(d[114]), "+f"(d[115]), "+f"(d[116]), "+f"(d[117]), "+f"(d[118]), "+f"(d[119]),
          "+f"(d[120]), "+f"(d[121]), "+f"(d[122]), "+f"(d[123]), "+f"(d[124]), "+f"(d[125]), "+f"(d[126]), "+f"(d[127])
        : "l"(a), "l"(b), "r"(scale_d));
}

DEVI void wgmma_n128_ss(float* d, uint64_t a, uint64_t b, int scale_d) {
    asm volatile("{.reg .pred p; setp.ne.b32 p, %66, 0;\n"
        "wgmma.mma_async.sync.aligned.m64n128k16.f32.bf16.bf16 "
        "{%0,%1,%2,%3,%4,%5,%6,%7,%8,%9,%10,%11,%12,%13,%14,%15,"
        "%16,%17,%18,%19,%20,%21,%22,%23,%24,%25,%26,%27,%28,%29,%30,%31,"
        "%32,%33,%34,%35,%36,%37,%38,%39,%40,%41,%42,%43,%44,%45,%46,%47,"
        "%48,%49,%50,%51,%52,%53,%54,%55,%56,%57,%58,%59,%60,%61,%62,%63},"
        " %64, %65, p, 1, 1, 1, 0;}"
        : "+f"(d[0]), "+f"(d[1]), "+f"(d[2]), "+f"(d[3]), "+f"(d[4]), "+f"(d[5]), "+f"(d[6]), "+f"(d[7]),
          "+f"(d[8]), "+f"(d[9]), "+f"(d[10]), "+f"(d[11]), "+f"(d[12]), "+f"(d[13]), "+f"(d[14]), "+f"(d[15]),
          "+f"(d[16]), "+f"(d[17]), "+f"(d[18]), "+f"(d[19]), "+f"(d[20]), "+f"(d[21]), "+f"(d[22]), "+f"(d[23]),
          "+f"(d[24]), "+f"(d[25]), "+f"(d[26]), "+f"(d[27]), "+f"(d[28]), "+f"(d[29]), "+f"(d[30]), "+f"(d[31]),
          "+f"(d[32]), "+f"(d[33]), "+f"(d[34]), "+f"(d[35]), "+f"(d[36]), "+f"(d[37]), "+f"(d[38]), "+f"(d[39]),
          "+f"(d[40]), "+f"(d[41]), "+f"(d[42]), "+f"(d[43]), "+f"(d[44]), "+f"(d[45]), "+f"(d[46]), "+f"(d[47]),
          "+f"(d[48]), "+f"(d[49]), "+f"(d[50]), "+f"(d[51]), "+f"(d[52]), "+f"(d[53]), "+f"(d[54]), "+f"(d[55]),
          "+f"(d[56]), "+f"(d[57]), "+f"(d[58]), "+f"(d[59]), "+f"(d[60]), "+f"(d[61]), "+f"(d[62]), "+f"(d[63])
        : "l"(a), "l"(b), "r"(scale_d));
}

DEVI void mma16816(float* d, const uint32_t* a, uint32_t b0, uint32_t b1) {
    asm volatile("mma.sync.aligned.m16n8k16.row.col.f32.bf16.bf16.f32 {%0,%1,%2,%3}, {%4,%5,%6,%7}, {%8,%9}, {%0,%1,%2,%3};"
                 : "+f"(d[0]), "+f"(d[1]), "+f"(d[2]), "+f"(d[3])
                 : "r"(a[0]), "r"(a[1]), "r"(a[2]), "r"(a[3]), "r"(b0), "r"(b1));
}
DEVI void mma1688(float* d, uint32_t a0, uint32_t a1, uint32_t b0) {
    asm volatile("mma.sync.aligned.m16n8k8.row.col.f32.bf16.bf16.f32 {%0,%1,%2,%3}, {%4,%5}, {%6}, {%0,%1,%2,%3};"
                 : "+f"(d[0]), "+f"(d[1]), "+f"(d[2]), "+f"(d[3]) : "r"(a0), "r"(a1), "r"(b0));
}
DEVI void ldsm4(uint32_t* r, uint32_t addr) {
    asm volatile("ldmatrix.sync.aligned.m8n8.x4.shared.b16 {%0,%1,%2,%3}, [%4];"
                 : "=r"(r[0]), "=r"(r[1]), "=r"(r[2]), "=r"(r[3]) : "r"(addr) : "memory");
}
DEVI void ldsm4t(uint32_t* r, uint32_t addr) {
    asm volatile("ldmatrix.sync.aligned.m8n8.x4.trans.shared.b16 {%0,%1,%2,%3}, [%4];"
                 : "=r"(r[0]), "=r"(r[1]), "=r"(r[2]), "=r"(r[3]) : "r"(addr) : "memory");
}
DEVI void ldsm2(uint32_t* r, uint32_t addr) {
    asm volatile("ldmatrix.sync.aligned.m8n8.x2.shared.b16 {%0,%1}, [%2];" : "=r"(r[0]), "=r"(r[1]) : "r"(addr) : "memory");
}
DEVI void ldsm1t(uint32_t& r, uint32_t addr) {
    asm volatile("ldmatrix.sync.aligned.m8n8.x1.trans.shared.b16 {%0}, [%1];" : "=r"(r) : "r"(addr) : "memory");
}
DEVI void stsm4(uint32_t addr, uint32_t r0, uint32_t r1, uint32_t r2, uint32_t r3) {
    asm volatile("stmatrix.sync.aligned.m8n8.x4.shared.b16 [%0], {%1,%2,%3,%4};" :: "r"(addr), "r"(r0), "r"(r1), "r"(r2), "r"(r3) : "memory");
}
DEVI void stsm4t(uint32_t addr, uint32_t r0, uint32_t r1, uint32_t r2, uint32_t r3) {
    asm volatile("stmatrix.sync.aligned.m8n8.x4.trans.shared.b16 [%0], {%1,%2,%3,%4};" :: "r"(addr), "r"(r0), "r"(r1), "r"(r2), "r"(r3) : "memory");
}
DEVI uint32_t movm_t(uint32_t a) {
    uint32_t d; asm volatile("movmatrix.sync.aligned.m8n8.trans.b16 %0, %1;" : "=r"(d) : "r"(a)); return d;
}
DEVI uint32_t pack_bf16(float lo, float hi) {
    uint32_t r; asm("cvt.rn.bf16x2.f32 %0, %1, %2;" : "=r"(r) : "f"(hi), "f"(lo)); return r;
}
DEVI float ex2(float x) { float y; asm("ex2.approx.ftz.f32 %0, %1;" : "=f"(y) : "f"(x)); return y; }

DEVI uint4 ld_rlx4(const void* p) {
    uint4 v;
    asm volatile("ld.relaxed.gpu.global.v4.u32 {%0,%1,%2,%3}, [%4];" : "=r"(v.x), "=r"(v.y), "=r"(v.z), "=r"(v.w) : "l"(p) : "memory");
    return v;
}
DEVI void ld_rlx4f(float* d, const void* p) {
    asm volatile("ld.relaxed.gpu.global.v4.f32 {%0,%1,%2,%3}, [%4];" : "=f"(d[0]), "=f"(d[1]), "=f"(d[2]), "=f"(d[3]) : "l"(p) : "memory");
}
DEVI bool all_nzf(const float* d) { return __float_as_uint(d[0]) && __float_as_uint(d[1]) && __float_as_uint(d[2]) && __float_as_uint(d[3]); }
DEVI void sts128f(uint32_t addr, const float* d) {
    asm volatile("st.shared.v4.f32 [%0], {%1,%2,%3,%4};" :: "r"(addr), "f"(d[0]), "f"(d[1]), "f"(d[2]), "f"(d[3]) : "memory");
}
DEVI void st_rlx4(void* p, uint32_t a, uint32_t b, uint32_t c, uint32_t d) {
    asm volatile("st.relaxed.gpu.global.v4.u32 [%0], {%1,%2,%3,%4};" :: "l"(p), "r"(a), "r"(b), "r"(c), "r"(d) : "memory");
}
DEVI void st_rlx(void* p, uint32_t v) { asm volatile("st.relaxed.gpu.global.u32 [%0], %1;" :: "l"(p), "r"(v) : "memory"); }
DEVI void sts128(uint32_t addr, uint4 v) {
    asm volatile("st.shared.v4.u32 [%0], {%1,%2,%3,%4};" :: "r"(addr), "r"(v.x), "r"(v.y), "r"(v.z), "r"(v.w) : "memory");
}
DEVI void sts32(uint32_t addr, uint32_t v) { asm volatile("st.shared.u32 [%0], %1;" :: "r"(addr), "r"(v) : "memory"); }
DEVI uint4 lds128(uint32_t addr) {
    uint4 v; asm volatile("ld.shared.v4.u32 {%0,%1,%2,%3}, [%4];" : "=r"(v.x), "=r"(v.y), "=r"(v.z), "=r"(v.w) : "r"(addr) : "memory"); return v;
}
DEVI float2 lds64f(uint32_t addr) {
    float2 v; asm volatile("ld.shared.v2.f32 {%0,%1}, [%2];" : "=f"(v.x), "=f"(v.y) : "r"(addr) : "memory"); return v;
}
DEVI void cp_async16(uint32_t dst, const void* src) {
    asm volatile("cp.async.cg.shared.global [%0], [%1], 16;" :: "r"(dst), "l"(src) : "memory");
}
DEVI void cp_async_commit() { asm volatile("cp.async.commit_group;" ::: "memory"); }
DEVI void cp_async_wait0() { asm volatile("cp.async.wait_group 0;" ::: "memory"); }
DEVI uint32_t lds32(uint32_t addr) { uint32_t v; asm volatile("ld.shared.u32 %0, [%1];" : "=r"(v) : "r"(addr) : "memory"); return v; }
DEVI float rcp_fast(float x) { float y; asm("rcp.approx.ftz.f32 %0, %1;" : "=f"(y) : "f"(x)); return y; }
DEVI bool all_nz(const uint4& v) { return v.x && v.y && v.z && v.w; }
DEVI uint32_t mapa(uint32_t addr, uint32_t rank) {
    uint32_t r; asm("mapa.shared::cluster.u32 %0, %1, %2;" : "=r"(r) : "r"(addr), "r"(rank)); return r;
}
DEVI void st_async64(uint32_t dst, uint32_t a, uint32_t b, uint32_t bar) {
    asm volatile("st.async.weak.shared::cluster.mbarrier::complete_tx::bytes.v2.b32 [%0], {%1,%2}, [%3];"
                 :: "r"(dst), "r"(a), "r"(b), "r"(bar) : "memory");
}

DEVI void st_async128(uint32_t dst, uint32_t a, uint32_t b, uint32_t c, uint32_t d, uint32_t bar) {
    asm volatile("st.async.weak.shared::cluster.mbarrier::complete_tx::bytes.v4.b32 [%0], {%1,%2,%3,%4}, [%5];"
                 :: "r"(dst), "r"(a), "r"(b), "r"(c), "r"(d), "r"(bar) : "memory");
}

DEVI uint32_t b_addr(uint32_t sb, int row, int which, int chunk) { const int l = 3 * row + which; return sb + l * 128 + ((chunk ^ (l & 7)) * 16); }
DEVI void battn_warp(uint32_t st, uint32_t so, int i0, int par, int head, int hh, int mt, int lane) {
    const int gq = lane >> 2, t = lane & 3;
    float s[3][4];
#pragma unroll
    for (int n = 0; n < 3; n++) { s[n][0] = s[n][1] = s[n][2] = s[n][3] = 0.f; }
    const int arow = 16 * mt + (lane & 7) + ((lane >> 3) & 1) * 8;
#pragma unroll
    for (int ks = 0; ks < 2; ks++) {
        uint32_t a[4], b[4], b2[2];
        ldsm4(a, b_addr(st, 8 + arow, 0, hh * 4 + ks * 2 + (lane >> 4)));
        const int brow = 16 * mt + (lane >> 4) * 8 + (lane & 7);
        ldsm4(b, b_addr(st, brow, 1, hh * 4 + ks * 2 + ((lane >> 3) & 1)));
        const int crow = 16 * mt + 16 + (lane & 7);
        ldsm2(b2, b_addr(st, crow, 1, hh * 4 + ks * 2 + ((lane >> 3) & 1)));
        mma16816(s[0], a, b[0], b[1]);
        mma16816(s[1], a, b[2], b[3]);
        mma16816(s[2], a, b2[0], b2[1]);
    }
    float m0 = -INFINITY, m1 = -INFINITY;
#pragma unroll
    for (int n = 0; n < 3; n++) {
#pragma unroll
        for (int c = 0; c < 2; c++) {
            const int dj = 8 * n - 8 + 2 * t + c;
            const bool ex = i0 + 16 * mt + dj >= 0;
            if (!(ex && gq - dj >= 0 && gq - dj <= 7)) s[n][c] = -INFINITY;
            if (!(ex && gq + 8 - dj >= 0 && gq + 8 - dj <= 7)) s[n][2 + c] = -INFINITY;
            m0 = fmaxf(m0, s[n][c]); m1 = fmaxf(m1, s[n][2 + c]);
        }
    }
    m0 = fmaxf(m0, __shfl_xor_sync(0xffffffffu, m0, 1)); m0 = fmaxf(m0, __shfl_xor_sync(0xffffffffu, m0, 2));
    m1 = fmaxf(m1, __shfl_xor_sync(0xffffffffu, m1, 1)); m1 = fmaxf(m1, __shfl_xor_sync(0xffffffffu, m1, 2));
    constexpr float C = 0.17677669529663687f * 1.4426950408889634f;
    float l0 = 0.f, l1 = 0.f;
    uint32_t p[3][2];
#pragma unroll
    for (int n = 0; n < 3; n++) {
        const float e0 = ex2((s[n][0] - m0) * C), e1 = ex2((s[n][1] - m0) * C), e2 = ex2((s[n][2] - m1) * C), e3 = ex2((s[n][3] - m1) * C);
        l0 += e0 + e1; l1 += e2 + e3;
        p[n][0] = pack_bf16(e0, e1); p[n][1] = pack_bf16(e2, e3);
    }
    l0 += __shfl_xor_sync(0xffffffffu, l0, 1); l0 += __shfl_xor_sync(0xffffffffu, l0, 2);
    l1 += __shfl_xor_sync(0xffffffffu, l1, 1); l1 += __shfl_xor_sync(0xffffffffu, l1, 2);
    const float i0f = rcp_fast(l0), i1f = rcp_fast(l1);
    float o[4][4];
#pragma unroll
    for (int n = 0; n < 4; n++) { o[n][0] = o[n][1] = o[n][2] = o[n][3] = 0.f; }
    {
        const uint32_t a0[4] = {p[0][0], p[0][1], p[1][0], p[1][1]}, a1[4] = {p[2][0], p[2][1], 0u, 0u};
#pragma unroll
        for (int n = 0; n < 4; n += 2) {
            uint32_t b[4], b2[4];
            const int vrow = 16 * mt + ((lane >> 3) & 1) * 8 + (lane & 7);
            ldsm4t(b, b_addr(st, vrow, 2, hh * 4 + n + (lane >> 4)));
            const int wrow = 16 * mt + 16 + (lane & 7);
            ldsm4t(b2, b_addr(st, wrow, 2, hh * 4 + n + (lane >> 4)));
            mma16816(o[n], a0, b[0], b[1]);
            mma16816(o[n + 1], a0, b[2], b[3]);
            mma16816(o[n], a1, b2[0], 0u);
            mma16816(o[n + 1], a1, b2[2], 0u);
        }
    }
    {
        const int row = (lane & 7) + ((lane >> 3) & 1) * 8;
#pragma unroll
        for (int n = 0; n < 4; n += 2)
            stsm4(so + row * 64 + (((n + (lane >> 4)) ^ ((row >> 1) & 3)) * 16),
                  pack_bf16(o[n][0] * i0f, o[n][1] * i0f), pack_bf16(o[n][2] * i1f, o[n][3] * i1f),
                  pack_bf16(o[n + 1][0] * i0f, o[n + 1][1] * i0f), pack_bf16(o[n + 1][2] * i1f, o[n + 1][3] * i1f));
    }
    __syncwarp();
#pragma unroll
    for (int i = 0; i < 2; i++) {
        const int idx = lane + i * 32, row = idx >> 2, ch = idx & 3;
        const uint4 v = lds128(so + row * 64 + ((ch ^ ((row >> 1) & 3)) * 16));
        *(uint4*)(g_bo + (size_t)(2 * (i0 + 16 * mt + row) + par) * 1024 + head * 32 + ch * 8) = v;
    }
    __syncwarp();
}

constexpr float SCALE_LOG2E = 0.08838834764831845f * 1.4426950408889634f;

constexpr int P_STAGES = 4, P_STAGE = 16384 + 32768;
constexpr int PS_STG = P_STAGES * P_STAGE;
constexpr int PS_BAR = PS_STG + 32768;
constexpr int P_SMEM = PS_BAR + 256;
static_assert(P_SMEM <= 232448, "smem");
constexpr int PT_B1 = 256, PT_A0 = PT_B1 + 192, PT_B2 = PT_A0 + 32, PT_A1 = PT_B2 + 32, PT_B3 = PT_A1 + 32, PT_A2 = PT_B3 + 64;
constexpr int PT_SK = PT_A2 + 48, P_NTASK = PT_SK + 64;
enum { K_B1, K_Q, K_B2, K_B3, K_A3, K_SK, K_END };
struct PTask { int kind, a, b, c; };
DEVI PTask p_decode(int id) {
    if (id < PT_B1) return {K_Q, id % 32, id / 32, 0};
    if (id < PT_A0) return {K_B1, (id - PT_B1) % 24, (id - PT_B1) / 24, 0};
    if (id < PT_B2) return {K_A3, (id - PT_A0) & 7, (id - PT_A0) >> 3, 0};
    if (id < PT_A1) return {K_B2, id - PT_B2, 0, 0};
    if (id < PT_B3) return {K_A3, (id - PT_A1) & 7, 4 + ((id - PT_A1) >> 3), 0};
    if (id < PT_A2) return {K_B3, (id - PT_B3) % 8, (id - PT_B3) / 8, 0};
    if (id < PT_SK) return {K_A3, (id - PT_A2) & 7, 8 + ((id - PT_A2) >> 3), 0};
    if (id >= P_NTASK) return {K_END, 0, 0, 0};
    const int j = id - PT_SK;
    return {K_SK, (j >> 2) & 7, 14 + (j >> 5), j & 3};
}
DEVI void wait_count(const unsigned* p, unsigned target) {
    int n = 0;
    while (true) {
        unsigned v; asm volatile("ld.acquire.gpu.global.u32 %0, [%1];" : "=r"(v) : "l"(p) : "memory");
        if ((int)(v - target) >= 0) break;
        __nanosleep(100);
        if (++n > SPIN_LIMIT) TRAP(0x10000000u | ((unsigned)(size_t)p & 0xFFFFu));
    }
}
DEVI void signal_count(unsigned* p) { __threadfence(); atomicAdd(p, 1u); }

struct PMaps { CUtensorMap wq, bw, bwo, wo, x, bx, bo, ox, cb, cout, b40; };

template <int BN>
DEVI void p_mainloop(float* d, uint32_t sb, int g, int nk, int& it, bool elected) {
#pragma unroll
    for (int i = 0; i < BN / 2; i++) d[i] = 0.f;
    for (int kb = 0; kb < nk; kb++, it++) {
        const int st = it % P_STAGES;
        mbar_wait(sb + PS_BAR + st * 8, (it / P_STAGES) & 1);
        const uint32_t a = sb + st * P_STAGE;
        const uint64_t da = mk_desc(a + g * 8192, 16, 1024, 1), db = mk_desc(a + 16384, 16, 1024, 1);
        wg_fence();
#pragma unroll
        for (int kk = 0; kk < 4; kk++) {
            if (BN == 256) wgmma_n256_ss(d, da + (uint64_t)(kk * 128), db + (uint64_t)(kk * 2), (kb | kk) != 0);
            else           wgmma_n128_ss(d, da + (uint64_t)(kk * 128), db + (uint64_t)(kk * 2), (kb | kk) != 0);
        }
        wg_commit();
        if (kb > 0) {
            wg_wait<1>();
            if (elected) mbar_arrive(sb + PS_BAR + 32 + ((it - 1) % P_STAGES) * 8);
        }
    }
    wg_wait<0>();
    if (elected) mbar_arrive(sb + PS_BAR + 32 + ((it - 1) % P_STAGES) * 8);
}
template <int BN>
DEVI void p_epi_row(const float* d, uint32_t stg, const CUtensorMap* tmC, int col, int tok0, int warp, int lane_, int barid, bool elected, int& nstore) {
    const int lane = (int)opaque((uint32_t)lane_);
    const int mi = lane >> 3, r = lane & 7;
#pragma unroll
    for (int c = 0; c < BN / 64; c++, nstore++) {
        const uint32_t buf = stg + (nstore & 1) * 8192;
        if (elected) asm volatile("cp.async.bulk.wait_group.read 1;" ::: "memory");
        nbar_sync(barid, 128);
#pragma unroll
        for (int j = 0; j < 8; j += 2) {
            const int jj = c * 8 + j;
            const int tok = 8 * (j + (mi >> 1)) + r;
            const int chunk = (2 * warp + (mi & 1)) ^ r;
            stsm4t(buf + tok * 128 + chunk * 16,
                   pack_bf16(d[4 * jj], d[4 * jj + 1]), pack_bf16(d[4 * jj + 2], d[4 * jj + 3]),
                   pack_bf16(d[4 * jj + 4], d[4 * jj + 5]), pack_bf16(d[4 * jj + 6], d[4 * jj + 7]));
        }
        fence_proxy_async();
        nbar_sync(barid, 128);
        if (elected) { tma_store_2d(tmC, buf, col, tok0 + c * 64); bulk_commit(); }
    }
}

__global__ void __launch_bounds__(384, 1) k_post(const __grid_constant__ PMaps mp) {
    extern __shared__ __align__(1024) uint8_t smem_raw[];
    const uint32_t sb = smem_u32(smem_raw);
    if (sb & 1023u) __trap();
    const int tid = threadIdx.x, lane = tid & 31;
    const int wg = __shfl_sync(0xffffffffu, tid >> 7, 0), warp = __shfl_sync(0xffffffffu, (tid >> 5) & 3, 0);
    const uint32_t bF = sb + PS_BAR, bE = bF + 32, bTF = bF + 64, bTE = bF + 80, sT = bF + 96;
    if (tid == 0) {
        for (int i = 0; i < P_STAGES; i++) { mbar_init(bF + i * 8, 1); mbar_init(bE + i * 8, 2); }
        for (int i = 0; i < 2; i++) { mbar_init(bTF + i * 8, 1); mbar_init(bTE + i * 8, 256); }
        fence_mbar_init();
    }
    __syncthreads();
    if (wg == 2) {
        reg_dec<40>();
        if (tid == 256) {
            const unsigned E = *(volatile unsigned*)&g_epoch + 1;
            const unsigned qbase = (E - 1) * (unsigned)(P_NTASK + gridDim.x);
            int it = 0;
            for (int i = 0;; i++) {
                mbar_wait(bTE + (i & 1) * 8, ((i >> 1) & 1) ^ 1);
                const int id = (int)(atomicAdd(&g_qctr, 1u) - qbase);
                const PTask tk = p_decode(id);
                if (tk.kind == K_B2) {
                    wait_count(&g_cnt_b1[tk.a >> 2], 48 * E);
                    if ((tk.a & 3) == 0 && tk.a > 0) wait_count(&g_cnt_b1[(tk.a >> 2) - 1], 48 * E);
                } else if (tk.kind == K_B3) wait_count(&g_cnt_b2[tk.b], 4 * E);
                else if (tk.kind == K_A3 || tk.kind == K_SK) wait_count(&g_prog[tk.b], 128 * E);
                asm volatile("fence.proxy.async;" ::: "memory");
                sts32(sT + (i & 1) * 4, (uint32_t)id);
                mbar_arrive(bTF + (i & 1) * 8);
                if (tk.kind == K_END) break;
                if (tk.kind == K_B2) {
                    const int i0 = tk.a * 32;
                    for (int j = 0; j < 16; j++, it++) {
                        const int st = it % P_STAGES;
                        mbar_wait(bE + st * 8, ((it / P_STAGES) & 1) ^ 1);
                        const uint32_t a = sb + st * P_STAGE, bar = bF + st * 8;
                        mbar_expect_tx(bar, 2 * 15360);
                        for (int u = 0; u < 2; u++)
                            asm volatile("cp.async.bulk.tensor.4d.shared::cluster.global.mbarrier::complete_tx::bytes [%0], [%1, {%3, %4, %5, %6}], [%2];"
                                         :: "r"(a + u * 15360), "l"(&mp.b40), "r"(bar), "r"(j * 64), "r"(0), "r"(u), "r"(i0 - 8) : "memory");
                    }
                    continue;
                }
                const CUtensorMap* tw = tk.kind == K_B1 ? &mp.bw : (tk.kind == K_Q ? &mp.wq : (tk.kind == K_B3 ? &mp.bwo : &mp.wo));
                const CUtensorMap* tx = tk.kind == K_B1 ? &mp.bx : (tk.kind == K_Q ? &mp.x : (tk.kind == K_B3 ? &mp.bo : &mp.ox));
                const bool a3 = tk.kind == K_A3 || tk.kind == K_SK;
                const int nk = tk.kind == K_A3 ? HD / 64 : DM / 64, kb0 = tk.kind == K_SK ? tk.c * 16 : 0;
                for (int kb = kb0; kb < kb0 + nk; kb++, it++) {
                    const int st = it % P_STAGES;
                    mbar_wait(bE + st * 8, ((it / P_STAGES) & 1) ^ 1);
                    const uint32_t a = sb + st * P_STAGE, bar = bF + st * 8;
                    mbar_expect_tx(bar, a3 ? 32768 : P_STAGE);
                    tma_load_2d(a, tw, tk.a * 128, kb * 64, bar);
                    tma_load_2d(a + 8192, tw, tk.a * 128 + 64, kb * 64, bar);
                    tma_load_2d(a + 16384, tx, kb * 64, tk.b * (a3 ? 128 : 256), bar);
                }
            }
            __threadfence();
            if (atomicAdd(&g_done, 1u) == E * gridDim.x - 1) { __threadfence(); *(volatile unsigned*)&g_epoch = E; }
        }
    } else {
        reg_inc<232>();
        const int g = wg, ct = tid, barid = 1 + g;
        const bool elected = (tid & 127) == 0;
        const uint32_t stg = sb + PS_STG + g * 16384;
        int it = 0, nstore = 0;
        unsigned* pending = nullptr;
        for (int i = 0;; i++) {
            if (elected && pending && !mbar_try(bTF + (i & 1) * 8, (i >> 1) & 1)) { bulk_wait_all(); signal_count(pending); pending = nullptr; }
            mbar_wait(bTF + (i & 1) * 8, (i >> 1) & 1);
            const int id = (int)lds32(sT + (i & 1) * 4);
            mbar_arrive(bTE + (i & 1) * 8);
            const PTask tk = p_decode(id);
            if (tk.kind == K_END) break;
            if (tk.kind == K_B2) {
                if (elected && pending) { bulk_wait_all(); signal_count(pending); }
                pending = nullptr;
                if (elected) bulk_wait_all();
                nbar_sync(barid, 128);
#pragma unroll 1
                for (int j = 0; j < 16; j++, it++) {
                    const int st = it % P_STAGES;
                    mbar_wait(bF + st * 8, (it / P_STAGES) & 1);
                    const uint32_t a = sb + st * P_STAGE + g * 15360;
                    battn_warp(a, stg + warp * 1024, tk.a * 32, g, j * 2 + (warp >> 1), warp >> 1, warp & 1, (int)opaque((uint32_t)lane));
                    nbar_sync(barid, 128);
                    if (elected) mbar_arrive(bE + st * 8);
                }
                nbar_sync(3, 256);
                if (ct == 0) signal_count(&g_cnt_b2[tk.a >> 2]);
            } else if (tk.kind == K_A3 || tk.kind == K_SK) {
                float d[64];
                p_mainloop<128>(d, sb, g, tk.kind == K_A3 ? HD / 64 : DM / 64, it, elected);
                if (elected && pending) { bulk_wait_all(); signal_count(pending); }
                pending = nullptr;
                bool finish = true;
                if (tk.kind == K_SK) {
                    const int tile = ((tk.b - 14) * 8 + tk.a);
                    float4* mine = (float4*)(g_skp + ((size_t)(tile * 4 + tk.c) * 2 + g) * 8192) + (tid & 127);
#pragma unroll
                    for (int j = 0; j < 16; j++) mine[j * 128] = make_float4(d[4 * j], d[4 * j + 1], d[4 * j + 2], d[4 * j + 3]);
                    nbar_sync(barid, 128);
                    if (elected) { __threadfence(); const unsigned old = atomicAdd(&g_cnt_sk[tile * 2 + g], 1u); __threadfence(); sts32(sT + 16 + g * 4, old & 3u); }
                    nbar_sync(barid, 128);
                    finish = lds32(sT + 16 + g * 4) == 3u;
                    if (finish) {
#pragma unroll 1
                        for (int q = 1; q < 4; q++) {
                            const float4* o = (const float4*)(g_skp + ((size_t)(tile * 4 + ((tk.c + q) & 3)) * 2 + g) * 8192) + (tid & 127);
#pragma unroll
                            for (int j = 0; j < 16; j++) {
                                const float4 v = __ldcg(o + j * 128);
                                d[4 * j] += v.x; d[4 * j + 1] += v.y; d[4 * j + 2] += v.z; d[4 * j + 3] += v.w;
                            }
                        }
                    }
                    nbar_sync(barid, 128);
                }
                if (finish) p_epi_row<128>(d, stg, &mp.cout, tk.a * 128 + g * 64, tk.b * 128, warp, lane, barid, elected, nstore);
            } else {
                float d[128];
                p_mainloop<256>(d, sb, g, DM / 64, it, elected);
                if (elected && pending) { bulk_wait_all(); signal_count(pending); }
                pending = nullptr;
                if (tk.kind == K_Q) {
                    const int ln = (int)opaque((uint32_t)lane), gq = ln >> 2, t = ln & 3, dim = g * 64 + warp * 16 + gq;
#pragma unroll
                    for (int j = 0; j < 32; j++) {
                        const int seg = tk.b * 8 + (j >> 2), blk = j & 3;
                        uint32_t* p = (uint32_t*)(g_qx + ((((size_t)seg * NH + tk.a) * 4 + blk) * DH + dim) * 8 + 2 * t);
                        p[0]  = pack_bf16(d[4 * j], d[4 * j + 1]);
                        p[32] = pack_bf16(d[4 * j + 2], d[4 * j + 3]);
                    }
                    nbar_sync(barid, 128);
                    if (elected) signal_count(&g_cnt_q[tk.b]);
                } else if (tk.kind == K_B1) {
                    p_epi_row<256>(d, stg, &mp.cb, tk.a * 128 + g * 64, tk.b * 256, warp, lane, barid, elected, nstore);
                    pending = &g_cnt_b1[tk.b];
                } else {
                    p_epi_row<256>(d, stg, &mp.cout, DM + tk.a * 128 + g * 64, tk.b * 256, warp, lane, barid, elected, nstore);
                }
            }
        }
        if (elected) { bulk_wait_all(); if (pending) signal_count(pending); }
    }
    __syncthreads();
}

constexpr unsigned long long R_TORD_PACK = 0xFAE954DC873B6210ull;
__host__ __device__ constexpr int r_tord(int pos) { return (int)((R_TORD_PACK >> (4 * pos)) & 15ull); }
__host__ __device__ constexpr int r_tinv(int T) { for (int p = 0; p < 16; p++) if (r_tord(p) == T) return p; return 0; }
__host__ __device__ constexpr bool r_pos_ss(int pos) { return pos % 3 == 2; }
__host__ __device__ constexpr int r_ss(int pos) { return pos / 3; }
__host__ __device__ constexpr int r_rs(int pos) { return pos - pos / 3; }
constexpr int R_NRS = 11, R_NSS = 5;
constexpr int R_G1 = 5, R_G2 = 10;
#define REG_KB 232
#define REG_QB 224
#define X_NA_DEF 3
constexpr int X_SLOTS = 5;
constexpr int X_NST = 8;
constexpr int X_NA = X_NA_DEF;

constexpr int RS_WSS  = 0;
constexpr int RS_WO   = RS_WSS + R_NSS * 16384;
constexpr int RS_MEM  = RS_WO + 5 * 16384;
constexpr int RS_O    = RS_MEM + 16384;
constexpr int RS_SX   = RS_O + 2048;
constexpr int RS_BAR  = RS_SX + 2048;
constexpr int RS_TAIL = RS_BAR + 1024;
constexpr int RS_WO5  = RS_TAIL;
constexpr int RS_K    = RS_WO5 + 16384;
constexpr int RS_V    = RS_K + 10240;
constexpr int RS_Q    = RS_V + 10240;
constexpr int RS_QX   = RS_Q + 2048;
constexpr int RS_QEND = RS_QX + 8192;
constexpr int RS_X    = RS_TAIL;
constexpr int RS_WX   = RS_X + 2 * X_SLOTS * 4096;
constexpr int RS_KEND = RS_WX + 4096;
constexpr int RS_EV   = RS_BAR + 256;
constexpr int R_SMEM  = RS_KEND > RS_QEND ? RS_KEND : RS_QEND;
static_assert(R_SMEM <= 232448, "smem");
static_assert(RS_TAIL % 1024 == 0 && RS_MEM % 1024 == 0, "alignment");

constexpr int RB_G = RS_BAR, RB_K = RS_BAR + 24, RB_V = RS_BAR + 32, RB_KV = RS_BAR + 40, RB_QX = RS_BAR + 48, RB_O = RS_BAR + 56;
constexpr int RB_ATT = RS_BAR + 64, RB_W = RS_BAR + 72, RB_SF = RS_BAR + 80, RB_SE = RB_SF + 40, RB_XF = RB_SE + 40;
static_assert(RB_XF + 80 <= RS_EV, "barriers");
constexpr int NB_BIG = 1, NB_Q = 2, NB_AUX = 3, NB_WO = 4, NB_WG = 5;

DEVI int tid_now() { int t; asm volatile("mov.u32 %0, %%tid.x;" : "=r"(t)); return t; }
DEVI uint32_t a_frag_off(int lane, int warp) { return (uint32_t)((((lane >> 4) * 8 + (lane & 7)) * 128) + (((2 * warp + ((lane >> 3) & 1)) ^ (lane & 7)) * 16)); }
DEVI uint32_t clk32() { uint32_t c; asm volatile("mov.u32 %0, %%clock;" : "=r"(c)); return c; }
DEVI void spin_until(uint32_t t) { while ((int)(clk32() - t) < 0) { } }
DEVI int v_row(int d) { return (d & ~30) | ((d & 6) << 2) | ((d & 24) >> 2); }

DEVI void x_load(uint32_t sb, int Jn, int g, const CUtensorMap* tmX) {
    const int sl = g * X_SLOTS + Jn % X_SLOTS;
    mbar_expect_tx(sb + RB_XF + 8 * sl, 4096);
    tma_load_3d(sb + RS_X + sl * 4096, tmX, g * 32, (Jn / X_NST) * 32, (Jn % X_NST) * 2, sb + RB_XF + 8 * sl);
}
DEVI void x_refill(uint32_t sb, int Jr, int g, const CUtensorMap* tmX) {
    if ((tid_now() & 127) == 0 && Jr + X_SLOTS < NSEG * X_NST) x_load(sb, Jr + X_SLOTS, g, tmX);
}
template <int J0, int J1>
DEVI void x_stages(float* xa, const uint32_t* w, uint32_t sb0, int seg, int g, const CUtensorMap* tmX) {
#pragma unroll
    for (int j = J0; j < J1; j++) {
        const uint32_t sb = opaque(sb0);
        const uint32_t dW0 = desc_lo(sb + RS_WSS + g * (8192 + 4096), 16), dW1 = desc_lo(sb + RS_WSS + 8192 - g * 4096, 16);
        const int J = seg * X_NST + j, sl = g * X_SLOTS + J % X_SLOTS;
        mbar_wait(sb + RB_XF + 8 * sl, (J / X_SLOTS) & 1);
        const uint32_t dX = desc_lo(sb + RS_X + sl * 4096, 16);
        wg_fence();
#pragma unroll
        for (int q = 0; q < 8; q++) {
            const int pos = r_tinv(2 * j + (q >> 2)), kk = (q >> 1) & 1, mt = q & 1;
            const uint32_t db = dX + (q >> 2) * 128 + kk * 2;
            if (j == 0 && q < 2)   wgmma_n32_rs_first(xa + 16 * mt, &w[((r_rs(pos) * 2 + kk) * 2 + mt) * 4], db);
            else if (j == 0 && q == 3) wgmma_n32_ss(xa + 16, desc_lo(sb + RS_WX + g * 2048, 16), db);
            else if (r_pos_ss(pos)) wgmma_n32_ss(xa + 16 * mt, (mt ? dW1 : dW0) + r_ss(pos) * 1024 + kk * 128, db);
            else                   wgmma_n32_rs(xa + 16 * mt, &w[((r_rs(pos) * 2 + kk) * 2 + mt) * 4], db);
        }
        wg_commit();
        if (j > J0 && j - 1 < X_NST - 2) { wg_wait<1>(); x_refill(sb, J - 1, g, tmX); }
    }
    wg_wait<0>();
    reg_fence<32>(xa);
    if (J1 - 1 < X_NST - 2) x_refill(sb0, seg * X_NST + J1 - 1, g, tmX);
}
DEVI void x_finish(float* xa, uint32_t sb, int seg, int g, int warp, uint32_t rank) {
    {
        const int t7 = tid_now() & 127;
        const int sA = (seg * X_NST + 6) % X_SLOTS, sB = (seg * X_NST + 7) % X_SLOTS;
        const uint32_t mine = sb + RS_X + g * (X_SLOTS * 4096) + t7 * 16, other = sb + RS_X + (g ^ 1) * (X_SLOTS * 4096) + t7 * 16;
        nbar_sync(NB_WG + g, 128);
        sts128f(mine + sA * 4096, xa + 16); sts128f(mine + sA * 4096 + 2048, xa + 20);
        sts128f(mine + sB * 4096, xa + 24); sts128f(mine + sB * 4096 + 2048, xa + 28);
        nbar_sync(NB_BIG, 256);
#pragma unroll
        for (int i = 0; i < 4; i++) {
            const uint4 v = lds128(other + (i < 2 ? sA : sB) * 4096 + (i & 1) * 2048);
            xa[4 * i] += __uint_as_float(v.x); xa[4 * i + 1] += __uint_as_float(v.y); xa[4 * i + 2] += __uint_as_float(v.z); xa[4 * i + 3] += __uint_as_float(v.w);
        }
    }
    const int ln = tid_now() & 31, gq = ln >> 2, t = ln & 3;
    const int dim = g * 64 + warp * 16 + gq + ((t & 1) ? 8 : 0);
    const uint32_t off = (uint32_t)((rank == 1 ? RS_K + dim * 16 : RS_V + v_row(dim) * 16) + (t & 2) * 4);
    const uint32_t rd = mapa(sb + 2048 + off, 0), rb = mapa(sb + RB_KV, 0);
    if (seg > 0) mbar_wait(sb + RB_ATT, (seg - 1) & 1);
#pragma unroll
    for (int j = 0; j < 4; j++) {
        const uint32_t p0 = pack_bf16(xa[4 * j], xa[4 * j + 1]), p1 = pack_bf16(xa[4 * j + 2], xa[4 * j + 3]);
        const uint32_t rcv = __shfl_xor_sync(0xffffffffu, (t & 1) ? p0 : p1, 1);
        st_async64(rd + j * 2048, (t & 1) ? rcv : p0, (t & 1) ? p1 : rcv, rb);
    }
    fence_proxy_async();
}

template <bool XP>
DEVI void mem_pass(float* c0, float* c1, const uint32_t* w, uint32_t sb, int g, int warp, int s) {
    const int lane = tid_now() & 31;
    const uint32_t aB = sb + RS_MEM + (g * 32 + lane) * 16;
    const uint32_t aA0 = sb + RS_WSS + g * (8192 + 4096) + a_frag_off(lane, warp), aA1 = aA0 + 8192 - g * 16384;
    uint32_t a[16], b[2][4], e[4];
    if (XP) ldsm4t(e, aA0 + (RS_WX - RS_WSS) - g * (8192 + 2048));
#pragma unroll
    for (int q = 0; q < 4; q++) ldsm4t(a + 4 * q, ((q & 1) ? aA1 : aA0) + (q >> 1) * 2048);
#pragma unroll
    for (int i = 0; i < 4; i++) { c0[i] = 0.f; c1[i] = 0.f; }
    EV(tid_now() == 0, s, 0);
    if (s > 0) mbar_wait(sb + RB_G, (s - 1) & 1);
    EV(tid_now() == 0, s, 1);
    ldsm4t(b[0], aB + r_tord(0) * 1024);
#pragma unroll
    for (int pos = 0; pos < 16; pos++) {
        if (pos + 1 < 16) {
            if (pos + 1 == R_G1 && s > 0) mbar_wait(sb + RB_G + 8, (s - 1) & 1);
            if (pos + 1 == R_G2 && s > 0) { mbar_wait(sb + RB_G + 16, (s - 1) & 1); EV(tid_now() == 0, s, 2); }
            ldsm4t(b[(pos + 1) & 1], aB + r_tord(pos + 1) * 1024);
        }
        const uint32_t* bb = b[pos & 1];
        const uint32_t* aa = r_pos_ss(pos) ? a : &w[r_rs(pos) * 16];
        mma16816(c0, aa, bb[0], bb[1]);
        mma16816(c1, aa + 4, bb[0], bb[1]);
        mma16816(c0, aa + 8, bb[2], bb[3]);
        mma16816(c1, XP && pos == 0 ? e : aa + 12, bb[2], bb[3]);
        if (r_pos_ss(pos) && pos + 3 < 16) {
#pragma unroll
            for (int q = 0; q < 4; q++) ldsm4t(a + 4 * q, ((q & 1) ? aA1 : aA0) + (r_ss(pos) + 1) * 16384 + (q >> 1) * 2048);
        }
    }
}

DEVI uint32_t k_frag_off(int lane) { return (uint32_t)((((lane >> 3) & 1) * 16 + (lane >> 4) * 8 + (lane & 7)) * 16); }
template <int NQ>
DEVI void s_tile(const uint32_t* qa, uint32_t kaddr, float& s0, float& s1) {
    float c[4] = {0.f, 0.f, 0.f, 0.f}, d[4] = {0.f, 0.f, 0.f, 0.f};
#pragma unroll
    for (int i = 0; i < NQ; i++) {
        uint32_t b[4];
        ldsm4t(b, kaddr + i * 512);
        mma16816(c, qa + 4 * i, b[0], b[1]);
        mma16816(d, qa + 4 * i, b[2], b[3]);
    }
    s0 = c[0] + d[2]; s1 = c[1] + d[3];
}
DEVI uint32_t v_frag_off(int lane) { return (uint32_t)(((lane >> 3) & 1) * 2048 + ((lane >> 4) * 8 + (lane & 7)) * 16); }
DEVI void pv_pair(float (*o)[4], const uint32_t* p, const uint32_t* v) {
#pragma unroll
    for (int n = 0; n < 4; n++) mma16816(o[n], p, v[2 * n], v[2 * n + 1]);
}
DEVI void pv_single(float (*o)[4], const uint32_t* p, const uint32_t* v) {
#pragma unroll
    for (int n = 0; n < 4; n++) mma1688(o[n], p[0], p[1], v[n]);
}
DEVI float softmax10(const float* sc, uint32_t* p) {
    float m = fmaxf(fmaxf(fmaxf(sc[2], sc[3]), fmaxf(sc[4], sc[5])), fmaxf(fmaxf(sc[6], sc[7]), fmaxf(sc[8], sc[9])));
    m = fmaxf(m, fmaxf(sc[0], sc[1]));
    m = fmaxf(m, __shfl_xor_sync(0xffffffffu, m, 1));
    m = fmaxf(m, __shfl_xor_sync(0xffffffffu, m, 2));
    const float nm = -m * SCALE_LOG2E;
    float l = 0.f;
#pragma unroll
    for (int n = 0; n < 5; n++) {
        const float e0 = ex2(fmaf(sc[2 * n], SCALE_LOG2E, nm)), e1 = ex2(fmaf(sc[2 * n + 1], SCALE_LOG2E, nm));
        l += e0 + e1;
        p[2 * n] = pack_bf16(e0, e1); p[2 * n + 1] = __float_as_uint(e0);
    }
    return l;
}
DEVI float inv_sum4(float l) {
    l += __shfl_xor_sync(0xffffffffu, l, 1);
    l += __shfl_xor_sync(0xffffffffu, l, 2);
    return rcp_fast(l);
}
DEVI uint4 pack_o(const float (*o)[4], float inv) {
    return make_uint4(pack_bf16(o[0][0] * inv, o[0][1] * inv), pack_bf16(o[1][0] * inv, o[1][1] * inv),
                      pack_bf16(o[2][0] * inv, o[2][1] * inv), pack_bf16(o[3][0] * inv, o[3][1] * inv));
}

DEVI void token_attn(uint32_t sb, int seg, int head, int i, int hf) {
    uint32_t p[10];
    float inv;
    {
        const int lane = tid_now() & 31;
        float sc[10];
#pragma unroll
        for (int n = 0; n < 5; n++) {
            const int over = 8 * (n - 1 - i) + 2 * (lane & 3) - (lane >> 2);
            sc[2 * n] = over > 0 ? -INFINITY : 0.f;
            sc[2 * n + 1] = over >= 0 ? -INFINITY : 0.f;
        }
#pragma unroll 1
        for (int h = 0; h < 2; h++) {
            uint32_t qa[8];
            ldsm4t(qa, sb + RS_QX + i * 2048 + h * 1024 + lane * 16);
            ldsm4t(qa + 4, sb + RS_QX + i * 2048 + h * 1024 + 512 + lane * 16);
            const uint32_t ka = sb + RS_K + h * 1024 + k_frag_off(lane);
#pragma unroll
            for (int n = 0; n < 5; n++) {
                if (n < 1 || n <= i + 1) { float s0, s1; s_tile<2>(qa, ka + n * 2048, s0, s1); sc[2 * n] += s0; sc[2 * n + 1] += s1; }
            }
        }
        inv = inv_sum4(softmax10(sc, p));
    }
#pragma unroll 1
    for (int j = 0; j < 2; j++) {
        const int lane = tid_now() & 31;
        const uint32_t vb = sb + RS_V + (2 * hf + j) * 512;
        float o[4][4];
#pragma unroll
        for (int n = 0; n < 4; n++) { o[n][0] = o[n][1] = o[n][2] = o[n][3] = 0.f; }
#pragma unroll 1
        for (int kt = 0; 2 * kt <= i + 1; kt++) {
            const uint32_t a[4] = {kt == 0 ? p[0] : (kt == 1 ? p[4] : p[8]), p[1], kt == 0 ? p[2] : (kt == 1 ? p[6] : 0u), p[3]};
            const uint32_t va = vb + kt * 4096 + (v_frag_off(lane) & (kt == 2 ? 2047u : 4095u));
            uint32_t v[8];
            ldsm4(v, va); ldsm4(v + 4, va + 256);
            pv_pair(o, a, v);
        }
        const uint4 u = pack_o(o, inv);
        const uint32_t off = (uint32_t)((seg * 32 + i * 8 + (lane >> 2)) * HD + head * DH + (2 * hf + j) * 32 + (lane & 3) * 8);
        asm volatile("st.global.v4.u32 [%0], {%1,%2,%3,%4};" :: "l"(g_ox + off), "r"(u.x), "r"(u.y), "r"(u.z), "r"(u.w) : "memory");
    }
}

template <bool XP>
DEVI void big_main(const uint32_t* w, const uint32_t sb, const int g, const int warp, const uint32_t rank, const int head,
                   const CUtensorMap* tmX, const bf16* xg, const unsigned E) {
    float xa[32];
    if constexpr (XP) {
        x_stages<0, X_NST>(xa, w, sb, 0, g, tmX);
        x_finish(xa, sb, 0, g, warp, rank);
    } else nbar_sync(NB_BIG, 256);
    for (int s = 0; s < NSEG; s++) {
        {
            float c0[4], c1[4];
            mem_pass<XP>(c0, c1, w, sb, g, warp, s);
            EV(tid_now() == 0 && c0[0] != 1.2345e30f, s, 3);
            const int lane = tid_now() & 31, gq = lane >> 2, t = lane & 3;
            const uint32_t xs = sb + RS_O + warp * 512 + lane * 16;
            sts128f(xs + g * 2048, c1);
            const int dim = g * 64 + warp * 16 + gq + ((t & 1) ? 8 : 0);
            const uint32_t off = (uint32_t)((XP ? (rank == 1 ? RS_K + dim * 16 : RS_V + v_row(dim) * 16) : RS_Q + dim * 16) + (t & 2) * 4);
            const uint32_t dst = XP ? mapa(sb + off, 0) : sb + off;
            const uint32_t rbar = XP ? mapa(sb + (rank == 1 ? RB_K : RB_V), 0) : 0u;
            nbar_sync(NB_BIG, 256);
            const uint4 v = lds128(xs + (g ^ 1) * 2048);
            const uint32_t p0 = pack_bf16(c0[0] + __uint_as_float(v.x), c0[1] + __uint_as_float(v.y));
            const uint32_t p1 = pack_bf16(c0[2] + __uint_as_float(v.z), c0[3] + __uint_as_float(v.w));
            const uint32_t rcv = __shfl_xor_sync(0xffffffffu, (t & 1) ? p0 : p1, 1);
            const uint32_t lo = (t & 1) ? rcv : p0, hi = (t & 1) ? p1 : rcv;
            if constexpr (XP) st_async64(dst, lo, hi, rbar);
            else if (s < NSEG - 1) {
                asm volatile("st.shared.v2.u32 [%0], {%1,%2};" :: "r"(dst), "r"(lo), "r"(hi) : "memory");
                nbar_arrive(NB_Q, 384);
            }
            EV(tid_now() == 0, s, 4);
        }
        if constexpr (XP) {
            if (s == NSEG - 1) break;
            x_refill(sb, s * X_NST + 6, g, tmX);
            x_refill(sb, s * X_NST + 7, g, tmX);
            x_stages<0, X_NA>(xa, w, sb, s + 1, g, tmX);
            EV(tid_now() == 0, s, 5);
            EVCAL(s);
            nbar_sync(NB_WO, 384);
            EV(tid_now() == 0, s, 6);
            x_stages<X_NA, X_NST>(xa, w, sb, s + 1, g, tmX);
            EV(tid_now() == 0, s, 7);
            x_finish(xa, sb, s + 1, g, warp, rank);
        } else {
            if (tid_now() == 0) {
                if (s > 0) signal_count(&g_prog[(s - 1) >> 2]);
                if (s == 0) {
                    wait_count(&g_cnt_q[0], 64 * E);
                    asm volatile("fence.proxy.async;" ::: "memory");
                    mbar_expect_tx(sb + RB_QX, 8192);
                    bulk_load(sb + RS_QX, g_qx + (size_t)head * 4096, 8192, sb + RB_QX);
                }
                if ((s & 7) == 7 && s + 1 < NSEG) { wait_count(&g_cnt_q[(s + 1) >> 3], 64 * E); asm volatile("fence.proxy.async;" ::: "memory"); }
                if (s + 4 < NSEG) l2_prefetch(xg + (size_t)((s + 4) * 32 + head) * DM, 2048);
            }
            __syncwarp();
            EVCAL(s);
            if (s < NSEG - 1) nbar_sync(NB_WO, 384);
            EV(tid_now() == 0, s, 6);
            mbar_wait(sb + RB_KV, s & 1);
            mbar_wait(sb + RB_K, s & 1);
            mbar_wait(sb + RB_V, s & 1);
            mbar_wait(sb + RB_QX, s & 1);
            token_attn(sb, s, head, g == 0 ? 3 - (warp >> 1) : (warp >> 1), warp & 1);
            fence_proxy_async();
            nbar_sync(NB_BIG, 256);
            EV(tid_now() == 0, s, 7);
            if (tid_now() == 128 && s + 1 < NSEG) {
                mbar_expect_tx(sb + RB_KV, 16384);
                mbar_arrive_remote(mapa(sb + RB_ATT, 1));
                mbar_arrive_remote(mapa(sb + RB_ATT, 2));
                mbar_expect_tx(sb + RB_QX, 8192);
                bulk_load(sb + RS_QX, g_qx + ((size_t)(s + 1) * NH + head) * 4096, 8192, sb + RB_QX);
            }
            __syncwarp();
        }
    }
    if constexpr (!XP) { if (tid_now() == 0) signal_count(&g_prog[(NSEG - 1) >> 2]); }
}

template <bool FIRST>
DEVI void wo_tile(float* acc, uint32_t dWo, uint32_t dO) {
#pragma unroll
    for (int kk = 0; kk < 8; kk++) {
        if (kk == 0) { if (FIRST) wgmma_n8_ss_first<0>(acc, dWo, dO); else wgmma_n8_ss<0, 0>(acc, dWo, dO); }
        else wgmma_n8_ss<0, 1>(acc, dWo + kk * 128, dO + kk * 16);
    }
    wg_commit();
}
DEVI void red3(uint8_t* p, float a, float b, float c) {
    asm volatile("red.relaxed.gpu.global.add.v4.f32 [%0], {%1,%2,%3,%4};" :: "l"(p), "f"(a), "f"(b), "f"(c), "f"(1.0f) : "memory");
}
constexpr int ACC_CH = 3 * 16 * 1024;
template <bool Q>
DEVI void wo_phase(uint32_t sb0, int s, uint32_t rank, int warp) {
    const uint32_t sb = opaque(sb0);
    const uint32_t dWo = desc_lo(sb + RS_WO, 16), dO = desc_lo(sb + RS_O, 128);
    float a0[4], a1[4], a2[4];
    float *a3 = a0, *a4 = a1, *a5 = a2;
    wg_fence();
    wo_tile<true>(a0, dWo, dO);
    wo_tile<true>(a1, dWo + 1024, dO);
    wo_tile<true>(a2, dWo + 2048, dO);
    const int lane = tid_now() & 31;
    uint8_t* p = g_acc + (s & 3) * 128 + ((rank * 4 + warp) * 4 + (lane & 3)) * 1024 + (lane >> 2) * 16;
    wg_wait<2>(); reg_fence<4>(a0);
    red3(p, a0[0], a0[1], a0[2]);
    EV(tid_now() == 256, s, 11);
    wg_wait<1>(); reg_fence<4>(a1);
    red3(p + ACC_CH, a1[0], a1[1], a0[3]);
    wg_fence();
    wo_tile<false>(a3, dWo + 3072, dO);
    wg_wait<1>(); reg_fence<4>(a2);
    red3(p + 2 * ACC_CH, a1[2], a1[3], a2[0]);
    red3(p + 3 * ACC_CH, a2[2], a2[3], a2[1]);
    wg_fence();
    wo_tile<false>(a4, dWo + 4096, dO);
    if (Q) {
        wo_tile<false>(a5, desc_lo(sb + RS_WO5, 16), dO);
        wg_wait<2>(); reg_fence<4>(a3);
        red3(p + 4 * ACC_CH, a3[0], a3[1], a3[2]);
        wg_wait<1>(); reg_fence<4>(a4);
        nbar_arrive(NB_WO, 384);
        red3(p + 5 * ACC_CH, a4[0], a4[1], a3[3]);
        wg_wait<0>(); reg_fence<4>(a5);
        red3(p + 6 * ACC_CH, a4[2], a4[3], a5[0]);
        red3(p + 7 * ACC_CH, a5[2], a5[3], a5[1]);
    } else {
        wg_wait<1>(); reg_fence<4>(a3);
        nbar_arrive(NB_WO, 384);
        red3(p + 4 * ACC_CH, a3[0], a3[1], a3[2]);
        wg_wait<0>(); reg_fence<4>(a4);
        red3(p + 5 * ACC_CH, a4[0], a4[1], a3[3]);
        red3(p + 6 * ACC_CH, a4[2], a4[3], 0.f);
    }
}
template <bool Q>
DEVI void stage_chunk(uint32_t sb0, int s, uint32_t rank, int warp, int second, uint32_t gate) {
    const uint32_t sb = opaque(sb0);
    const int lane = tid_now() & 31, c = warp + 4 * second;
    const uint8_t* src = g_acc + (s & 3) * 128 + c * ACC_CH + (rank * 4 + (lane >> 3)) * 4096 + (lane & 7) * 16;
    float v[4][4];
    spin_until(gate);
    int n = 0;
    while (true) {
#pragma unroll
        for (int j = 0; j < 4; j++) ld_rlx4f(v[j], src + j * 1024);
        if (v[0][3] == 32.f && v[1][3] == 32.f && v[2][3] == 32.f && v[3][3] == 32.f) break;
        if (++n > SPIN_LIMIT) TRAP(0x20000000u | (s << 8) | c);
    }
    const uint32_t f0 = pack_bf16(v[0][0], v[1][0]), f1 = pack_bf16(v[2][0], v[3][0]), f2 = pack_bf16(v[0][1], v[1][1]), f3 = pack_bf16(v[2][1], v[3][1]);
    const uint32_t h0 = pack_bf16(v[0][2], v[1][2]), h1 = pack_bf16(v[2][2], v[3][2]);
    const int tile0 = Q ? 0 : (rank == 1 ? 6 : 11);
    const uint32_t col = sb + RS_MEM + (tile0 + 3 * second) * 1024 + ((lane >> 3) * 16 + (lane & 7)) * 16;
    const uint32_t df = col + ((warp + 1) >> 1) * 1024 + (warp >> 1) * 128;
    const uint32_t dh = col + (warp >> 1) * 2048 + (warp < 2 ? 128 : 0) + (warp & 1) * 8;
    const int grp = Q ? (c < 4 ? 0 : (c >> 1) - 1) : (c < 6 ? c >> 1 : 2);
    const uint32_t bar = sb + RB_G + 8 * grp;
    const bool half = Q || c != 6;
#pragma unroll
    for (int d = 1; d < 3; d++) {
        const uint32_t r = Q ? d : (d == 1 ? 0 : 3 - rank);
        const uint32_t rb = mapa(bar, r);
        st_async128(mapa(df, r), f0, f1, f2, f3, rb);
        if (half) st_async64(mapa(dh, r), h0, h1, rb);
    }
    sts128(df, make_uint4(f0, f1, f2, f3));
    if (half) asm volatile("st.shared.v2.u32 [%0], {%1,%2};" :: "r"(dh), "r"(h0), "r"(h1) : "memory");
    __syncwarp();
    if (lane == 0) {
        const bool first = Q ? (c == 0 || c == 4 || c == 6) : (c == 0 || c == 2 || c == 4);
        const uint32_t bytes = Q ? (grp == 2 ? 4096u : 3072u) : (grp == 0 ? 4608u : (grp == 1 ? 3072u : 3584u));
        if (first) mbar_expect_tx(bar, bytes); else mbar_arrive(bar);
    }
}
DEVI void acc_clear(int slot, int idx) {
    const int lane = tid_now() & 31;
    uint8_t* p = g_acc + slot * 128 + (idx * 6 + (lane >> 3)) * 1024 + (lane & 7) * 16;
    st_rlx4(p, 0u, 0u, 0u, 0u);
    if (lane < 16) st_rlx4(p + 4096, 0u, 0u, 0u, 0u);
}

DEVI void load_weights(uint32_t sb, const CUtensorMap* tmW, const CUtensorMap* tmWo, int head, uint32_t rank) {
    const uint32_t bW = sb + RB_W, bSF = sb + RB_SF, bSE = sb + RB_SE;
    const int ntile = rank == 0 ? 6 : 5, tile0 = rank == 0 ? 0 : (rank == 1 ? 6 : 11);
    mbar_expect_tx(bW, R_NSS * 16384 + ntile * 16384);
    if (rank == 0) tma_load_2d(sb + RS_WO5, tmWo, 5 * 64, head * DH, bW);
    for (int pos = 0; pos < 16; pos++) {
        const int k = (int)((R_TORD_PACK >> (4 * pos)) & 15ull) * 64;
        if (r_pos_ss(pos)) {
            const uint32_t dst = sb + RS_WSS + (pos / 3) * 16384;
            tma_load_2d(dst, tmW, head * DH, k, bW);
            tma_load_2d(dst + 8192, tmW, head * DH + 64, k, bW);
        } else {
            const int rd = pos - pos / 3, slot = rd % 5;
            if (rd >= 5) mbar_wait(bSE + 8 * slot, ((rd / 5) - 1) & 1);
            mbar_expect_tx(bSF + 8 * slot, 16384);
            const uint32_t dst = sb + RS_WO + slot * 16384;
            tma_load_2d(dst, tmW, head * DH, k, bSF + 8 * slot);
            tma_load_2d(dst + 8192, tmW, head * DH + 64, k, bSF + 8 * slot);
        }
    }
    for (int slot = 0; slot < 5; slot++) {
        const int last = slot + 10 < R_NRS ? slot + 10 : slot + 5;
        mbar_wait(bSE + 8 * slot, (last / 5) & 1);
        tma_load_2d(sb + RS_WO + slot * 16384, tmWo, (tile0 + slot) * 64, head * DH, bW);
    }
}
template <bool XP>
DEVI void big_prologue(uint32_t* w, uint32_t sb, int g, int warp, const bf16* __restrict__ mem0) {
    const int tid = tid_now(), lane = tid & 31;
#pragma unroll 1
    for (int j = 0; j < 4; j++) {
        const int c = tid + j * 256;
        const uint4 v = *(const uint4*)(mem0 + (c & 7) * DM + (c >> 3) * 8);
        const uint32_t d = sb + RS_MEM + (c >> 3) * 128 + (c & 7) * 2;
        const uint32_t u[4] = {v.x, v.y, v.z, v.w};
#pragma unroll
        for (int e = 0; e < 4; e++) {
            asm volatile("st.shared.u16 [%0], %1;" :: "r"(d + e * 32), "h"((uint16_t)(u[e] & 0xFFFFu)) : "memory");
            asm volatile("st.shared.u16 [%0], %1;" :: "r"(d + e * 32 + 16), "h"((uint16_t)(u[e] >> 16)) : "memory");
        }
    }
    const uint32_t a0 = sb + RS_WO + g * (8192 + 4096) + a_frag_off(lane, warp), a1 = a0 + 8192 - g * 16384;
#pragma unroll
    for (int rd = 0; rd < R_NRS; rd++) {
        const int slot = rd % 5;
        mbar_wait(sb + RB_SF + 8 * slot, (rd / 5) & 1);
#pragma unroll
        for (int q = 0; q < 4; q++) {
            if (XP && rd == 0 && q == 3) {
                sts128(sb + RS_WX + g * 2048 + (tid & 127) * 16, lds128(sb + RS_WO + 8192 - g * 4096 + 2048 + (tid & 127) * 16));
                fence_proxy_async();
                nbar_sync(NB_WG + g, 128);
            } else ldsm4t(&w[rd * 16 + q * 4], ((q & 1) ? a1 : a0) + slot * 16384 + (q >> 1) * 2048);
        }
        mbar_arrive(sb + RB_SE + 8 * slot);
    }
    mbar_wait(sb + RB_W, 0);
}

__global__ void __cluster_dims__(3, 1, 1) __launch_bounds__(384, 1)
k_rec(const __grid_constant__ CUtensorMap tmWq, const __grid_constant__ CUtensorMap tmWk, const __grid_constant__ CUtensorMap tmWv,
      const __grid_constant__ CUtensorMap tmWo, const __grid_constant__ CUtensorMap tmX, const bf16* __restrict__ mem0, const bf16* __restrict__ xg,
      int hq0, int hqw, int hk0, int hkw) {
    extern __shared__ __align__(1024) uint8_t smem_raw[];
    const uint32_t sb = smem_u32(smem_raw);
    if (sb & 1023u) __trap();
    const int tid = threadIdx.x;
    const int wg = __shfl_sync(0xffffffffu, tid >> 7, 0), warp = __shfl_sync(0xffffffffu, (tid >> 5) & 3, 0);
    uint32_t rank; asm("mov.u32 %0, %%cluster_ctarank;" : "=r"(rank));
    const int head = blockIdx.x / 3;
    if (tid == 0) {
        mbar_init(sb + RB_G, rank == 0 ? 4 : 2);
        mbar_init(sb + RB_G + 8, 2);
        mbar_init(sb + RB_G + 16, rank == 0 ? 2 : 3);
        mbar_init(sb + RB_K, 1); mbar_init(sb + RB_V, 1); mbar_init(sb + RB_KV, 1); mbar_init(sb + RB_QX, 1);
        mbar_init(sb + RB_O, 1); mbar_init(sb + RB_ATT, 1); mbar_init(sb + RB_W, 1);
        for (int i = 0; i < 5; i++) { mbar_init(sb + RB_SF + 8 * i, 1); mbar_init(sb + RB_SE + 8 * i, 256); }
        for (int i = 0; i < 2 * X_SLOTS; i++) mbar_init(sb + RB_XF + 8 * i, 1);
        fence_mbar_init();
        if (rank == 0) mbar_expect_tx(sb + RB_KV, 16384);
        atomicAdd(&g_resident, 1u);
    }
    __syncthreads();
    cluster_sync();

    if (wg < 2) {
        reg_inc<REG_KB>();
        if (rank != 0) {
            uint32_t w[R_NRS * 16];
            if ((tid & 127) == 0) for (int j = 0; j < X_SLOTS; j++) x_load(sb, j, wg, &tmX);
            __syncwarp();
            big_prologue<true>(w, sb, wg, warp, mem0);
            big_main<true>(w, sb, wg, warp, rank, head, &tmX, xg, 0u);
        } else {
            reg_dec<REG_QB>();
            uint32_t w[R_NRS * 16];
            big_prologue<false>(w, sb, wg, warp, mem0);
            big_main<false>(w, sb, wg, warp, rank, head, &tmX, xg, *(volatile unsigned*)&g_epoch + 1);
        }
    } else if (rank == 0) {
        reg_dec<504 - 2 * REG_KB>();
        if (tid == 256) {
            for (int sg = 0; sg < 4; sg++) l2_prefetch(xg + (size_t)(sg * 32 + head) * DM, 2048);
            load_weights(sb, &tmWq, &tmWo, head, rank);
            wait_count(&g_zero, (*(volatile unsigned*)&g_epoch + 1) * 64u);
        }
        __syncwarp();
        mbar_wait(sb + RB_W, 0);
        reg_inc<504 - 2 * REG_QB>();
        for (int s = (int)opaque(0u); s < NSEG - 1; s++) {
            if (tid_now() == 256) { mbar_expect_tx(sb + RB_K, 2048); mbar_expect_tx(sb + RB_V, 2048); }
            __syncwarp();
            {
                const int lane = tid_now() & 31;
                const uint32_t ka = sb + RS_K + k_frag_off(lane), va = sb + RS_V + warp * 512;
                uint32_t qa[16], vx[16];
                float sc[10];
                mbar_wait(sb + RB_KV, s & 1);
                {
                    uint32_t kx[16];
#pragma unroll
                    for (int q = 0; q < 4; q++) ldsm4t(kx + 4 * q, ka + (1 + warp) * 2048 + q * 512);
                    nbar_sync(NB_Q, 384);
                    EV(tid_now() == 256, s, 8);
#pragma unroll
                    for (int q = 0; q < 4; q++) ldsm4t(qa + 4 * q, sb + RS_Q + q * 512 + lane * 16);
                    float c[4] = {0.f, 0.f, 0.f, 0.f}, d[4] = {0.f, 0.f, 0.f, 0.f};
#pragma unroll
                    for (int q = 0; q < 4; q++) { mma16816(c, qa + 4 * q, kx[4 * q], kx[4 * q + 1]); mma16816(d, qa + 4 * q, kx[4 * q + 2], kx[4 * q + 3]); }
                    asm volatile("st.shared.v2.f32 [%0], {%1,%2};" :: "r"(sb + RS_SX + warp * 256 + lane * 8), "f"(c[0] + d[2]), "f"(c[1] + d[3]) : "memory");
                }
                nbar_sync(NB_AUX, 128);
#pragma unroll
                for (int n = 0; n < 4; n++) { const float2 v = lds64f(sb + RS_SX + n * 256 + lane * 8); sc[2 + 2 * n] = v.x; sc[3 + 2 * n] = v.y; }
                const uint32_t dst = sb + RS_O + warp * 512 + (lane & 3) * 128 + (lane >> 2) * 16;
                mbar_wait(sb + RB_K, s & 1);
                EV(tid_now() == 256, s, 9);
                s_tile<4>(qa, ka, sc[0], sc[1]);
#pragma unroll
                for (int q = 0; q < 4; q++) ldsm4(vx + 4 * q, va + 2048 + (q >> 1) * 4096 + (q & 1) * 256 + v_frag_off(lane));
                mbar_wait(sb + RB_V, s & 1);
                uint32_t vm[4], p[10];
                ldsm4(vm, va + lane * 16);
                const float l = softmax10(sc, p);
                float o[4][4];
#pragma unroll
                for (int n = 0; n < 4; n++) { o[n][0] = o[n][1] = o[n][2] = o[n][3] = 0.f; }
                pv_single(o, p, vm);
                pv_pair(o, p + 2, vx);
                pv_pair(o, p + 6, vx + 8);
                const uint4 u = pack_o(o, inv_sum4(l));
                st_async128(mapa(dst, 1), u.x, u.y, u.z, u.w, mapa(sb + RB_O, 1));
                st_async128(mapa(dst, 2), u.x, u.y, u.z, u.w, mapa(sb + RB_O, 2));
                sts128(dst, u);
                fence_proxy_async();
                nbar_sync(NB_AUX, 128);
            }
            const uint32_t t_o = clk32();
            EV(tid_now() == 256, s, 10);
            wo_phase<true>(sb, s, 0, warp);
            EV(tid_now() == 256, s, 12);
            stage_chunk<true>(sb, s, 0, warp, 0, t_o + hq0 + warp * hqw);
            EV(tid_now() == 256 + 96, s, 13);
            stage_chunk<true>(sb, s, 0, warp, 1, t_o + hq0 + (warp + 4) * hqw);
            EV(tid_now() == 256 + 96, s, 14);
        }
        if (tid_now() == 256) { mbar_expect_tx(sb + RB_K, 2048); mbar_expect_tx(sb + RB_V, 2048); }
    } else {
        reg_dec<504 - 2 * REG_KB>();
        const int idx = 2 * head + (int)rank - 1;
        if (warp == 3) {
            acc_clear(0, idx); acc_clear(1, idx);
            __threadfence();
            __syncwarp();
            if (tid == 256 + 96) atomicAdd(&g_zero, 1u);
        }
        if (tid == 256) {
            load_weights(sb, rank == 1 ? &tmWk : &tmWv, &tmWo, head, rank);
            wait_count(&g_zero, (*(volatile unsigned*)&g_epoch + 1) * 64u);
        }
        __syncwarp();
        mbar_wait(sb + RB_W, 0);
        nbar_sync(NB_AUX, 128);
        for (int s = 0; s < NSEG - 1; s++) {
            if (tid_now() == 256) mbar_expect_tx(sb + RB_O, 2048);
            __syncwarp();
            mbar_wait(sb + RB_O, s & 1);
            fence_proxy_async();
            const uint32_t t_o = clk32();
            EV(tid_now() == 256, s, 10);
            wo_phase<false>(sb, s, rank, warp);
            EV(tid_now() == 256, s, 12);
            stage_chunk<false>(sb, s, rank, warp, 0, t_o + hk0 + warp * hkw);
            EV(tid_now() == 256 + 32, s, 13);
            if (warp < 3) stage_chunk<false>(sb, s, rank, warp, 1, t_o + hk0 + (warp + 4) * hkw);
            else if (s + 2 < NSEG - 1) { acc_clear((s + 2) & 3, idx); __threadfence(); }
            EV(tid_now() == 256 + 64, s, 14);
        }
    }
    __syncthreads();
    cluster_sync();
}

__global__ void k_gate() {
    if (threadIdx.x == 0) {
        int n = 0;
        while (*(volatile unsigned*)&g_resident < 96u) { __nanosleep(200); if (++n > (1 << 22)) __trap(); }
        g_resident = 0;
    }
}

typedef CUresult (*EncodeFn)(CUtensorMap*, CUtensorMapDataType, cuuint32_t, void*, const cuuint64_t*, const cuuint64_t*,
                             const cuuint32_t*, const cuuint32_t*, CUtensorMapInterleave, CUtensorMapSwizzle,
                             CUtensorMapL2promotion, CUtensorMapFloatOOBfill);

static CUtensorMap make_map(EncodeFn fn, const void* ptr, uint64_t inner, uint64_t outer, uint32_t box_inner, uint32_t box_outer) {
    CUtensorMap m;
    cuuint64_t dims[2] = {inner, outer};
    cuuint64_t strides[1] = {inner * 2};
    cuuint32_t box[2] = {box_inner, box_outer};
    cuuint32_t es[2] = {1, 1};
    fn(&m, CU_TENSOR_MAP_DATA_TYPE_BFLOAT16, 2, const_cast<void*>(ptr), dims, strides, box, es,
       CU_TENSOR_MAP_INTERLEAVE_NONE, CU_TENSOR_MAP_SWIZZLE_128B, CU_TENSOR_MAP_L2_PROMOTION_L2_256B, CU_TENSOR_MAP_FLOAT_OOB_FILL_NONE);
    return m;
}

struct Maps {
    PMaps post;
    CUtensorMap wq16, wk16, wv16, wo128, x32;
};

extern "C" void kernel_launch(void* const* d_in, const int* in_sizes, int n_in, void* d_out, int out_size) {
    const bf16* A_x   = (const bf16*)d_in[0];
    const bf16* A_mem = (const bf16*)d_in[1];
    const bf16* A_Wq  = (const bf16*)d_in[2];
    const bf16* A_Wk  = (const bf16*)d_in[3];
    const bf16* A_Wv  = (const bf16*)d_in[4];
    const bf16* A_Wo  = (const bf16*)d_in[5];
    const bf16* B_x   = (const bf16*)d_in[7];
    const bf16* B_w   = (const bf16*)d_in[8];
    const bf16* B_wo  = (const bf16*)d_in[9];

    static EncodeFn fn = nullptr;
    static Maps mp;
    static const void* cached[10];
    const void* cur[10] = {A_x, A_mem, A_Wq, A_Wk, A_Wv, A_Wo, B_x, B_w, B_wo, d_out};
    bool same = fn != nullptr;
    for (int i = 0; i < 10 && same; i++) same = cached[i] == cur[i];
    if (!same) {
        if (!fn) {
            void* p = nullptr; cudaDriverEntryPointQueryResult qr;
            cudaGetDriverEntryPoint("cuTensorMapEncodeTiled", &p, cudaEnableDefault, &qr);
            fn = (EncodeFn)p;
            cudaFuncSetAttribute(k_post, cudaFuncAttributeMaxDynamicSharedMemorySize, P_SMEM);
            cudaFuncSetAttribute(k_rec, cudaFuncAttributeMaxDynamicSharedMemorySize, R_SMEM);
            cudaFuncAttributes fa; cudaFuncGetAttributes(&fa, k_gate);
        }
        void *p_ox, *p_bqkv, *p_bo;
        cudaGetSymbolAddress(&p_ox, g_ox); cudaGetSymbolAddress(&p_bqkv, g_bqkv); cudaGetSymbolAddress(&p_bo, g_bo);
        mp.post.wq   = make_map(fn, A_Wq, HD, DM, 64, 64);
        mp.post.wo   = make_map(fn, A_Wo, DM, HD, 64, 64);
        mp.post.bw   = make_map(fn, B_w, 3 * DM, DM, 64, 64);
        mp.post.bwo  = make_map(fn, B_wo, DM, DM, 64, 64);
        mp.post.x    = make_map(fn, A_x, DM, S_TOK, 64, 256);
        mp.post.bx   = make_map(fn, B_x, DM, S_TOK, 64, 256);
        mp.post.bo   = make_map(fn, p_bo, DM, S_TOK, 64, 256);
        mp.post.ox   = make_map(fn, p_ox, HD, S_TOK, 64, 128);
        mp.post.cb   = make_map(fn, p_bqkv, 3 * DM, S_TOK, 64, 64);
        mp.post.cout = make_map(fn, d_out, 2 * DM, S_TOK, 64, 64);
        {
            cuuint64_t dims[4] = {DM, 3, 2, S_TOK / 2};
            cuuint64_t strides[3] = {DM * 2, 3 * DM * 2, 3 * DM * 4};
            cuuint32_t box[4] = {64, 3, 1, 40};
            cuuint32_t es[4] = {1, 1, 1, 1};
            fn(&mp.post.b40, CU_TENSOR_MAP_DATA_TYPE_BFLOAT16, 4, p_bqkv, dims, strides, box, es,
               CU_TENSOR_MAP_INTERLEAVE_NONE, CU_TENSOR_MAP_SWIZZLE_128B, CU_TENSOR_MAP_L2_PROMOTION_L2_256B, CU_TENSOR_MAP_FLOAT_OOB_FILL_NONE);
        }
        mp.wq16 = make_map(fn, A_Wq, HD, DM, 64, 64);
        mp.wk16 = make_map(fn, A_Wk, HD, DM, 64, 64);
        mp.wv16 = make_map(fn, A_Wv, HD, DM, 64, 64);
        mp.wo128 = make_map(fn, A_Wo, DM, HD, 64, 128);
        {
            cuuint64_t dims[3] = {64, S_TOK, DM / 64};
            cuuint64_t strides[2] = {DM * 2, 128};
            cuuint32_t box[3] = {32, 32, 2};
            cuuint32_t es[3] = {1, 1, 1};
            fn(&mp.x32, CU_TENSOR_MAP_DATA_TYPE_BFLOAT16, 3, const_cast<bf16*>(A_x), dims, strides, box, es,
               CU_TENSOR_MAP_INTERLEAVE_NONE, CU_TENSOR_MAP_SWIZZLE_64B, CU_TENSOR_MAP_L2_PROMOTION_L2_128B, CU_TENSOR_MAP_FLOAT_OOB_FILL_NONE);
        }
        for (int i = 0; i < 10; i++) cached[i] = cur[i];
    }

    cudaStream_t st = cudaStreamPerThread;
    static cudaStream_t side = nullptr;
    static cudaEvent_t evFork, evSide;
    if (!side) {
        cudaStreamCreateWithFlags(&side, cudaStreamNonBlocking);
        cudaEventCreateWithFlags(&evFork, cudaEventDisableTiming);
        cudaEventCreateWithFlags(&evSide, cudaEventDisableTiming);
    }
    cudaEventRecord(evFork, st);
    int hq0 = 800, hqw = 145, hk0 = 800, hkw = 145;
    k_rec<<<96, 384, R_SMEM, st>>>(mp.wq16, mp.wk16, mp.wv16, mp.wo128, mp.x32, A_mem, A_x, hq0, hqw, hk0, hkw);
    cudaStreamWaitEvent(side, evFork, 0);
    k_gate<<<1, 32, 0, side>>>();
    k_post<<<132, 384, P_SMEM, side>>>(mp.post);
    cudaEventRecord(evSide, side);
    cudaStreamWaitEvent(st, evSide, 0);
}
```

```cpp
#include <cuda_runtime.h>
#include <cuda_bf16.h>
#include <cuda.h>
#include <stdint.h>

typedef __nv_bfloat16 bf16;

constexpr int S_TOK = 2048;
constexpr int DM    = 1024;
constexpr int NH    = 32;
constexpr int DH    = 128;
constexpr int NSEG  = 64;
constexpr int HD    = NH * DH;

__device__ __align__(1024) bf16 g_qx[NSEG * NH * 4 * DH * 8];
__device__ __align__(1024) bf16 g_ox[S_TOK * HD];
__device__ __align__(1024) bf16 g_bqkv[S_TOK * 3 * DM];
__device__ __align__(1024) bf16 g_bo[S_TOK * DM];
__device__ __align__(1024) uint8_t g_acc[384 * 1024];

#define EV(cond, s, k) do {} while (0)
#define EVCAL(s) do {} while (0)

__device__ unsigned g_epoch, g_qctr, g_done, g_zero;
__device__ unsigned g_cnt_b1[8], g_cnt_b2[8], g_cnt_q[8], g_prog[16], g_cnt_sk[32];
__device__ __align__(1024) float g_skp[2 * 8 * 4 * 2 * 128 * 64];
#define TLOG(i, k, v) do {} while (0)
__device__ unsigned g_resident;

#define DEVI __device__ __forceinline__

DEVI uint32_t opaque(uint32_t v) { uint32_t r; asm volatile("mov.u32 %0, %1;" : "=r"(r) : "r"(v)); return r; }
DEVI uint32_t smem_u32(const void* p) { return (uint32_t)__cvta_generic_to_shared(p); }

#define TRAP(code) __trap()
constexpr int SPIN_LIMIT = 1 << 22;
#define MBAR_HINT_NS 20000u
constexpr int SPIN_LIMIT_MBAR = 1 << 17;

DEVI void mbar_init(uint32_t bar, uint32_t cnt) { asm volatile("mbarrier.init.shared::cta.b64 [%0], %1;" :: "r"(bar), "r"(cnt)); }
DEVI void mbar_expect_tx(uint32_t bar, uint32_t bytes) {
    asm volatile("mbarrier.arrive.expect_tx.shared::cta.b64 _, [%0], %1;" :: "r"(bar), "r"(bytes) : "memory");
}
DEVI void mbar_arrive(uint32_t bar) { asm volatile("mbarrier.arrive.shared::cta.b64 _, [%0];" :: "r"(bar) : "memory"); }
DEVI bool mbar_try(uint32_t bar, uint32_t parity) {
    uint32_t ok;
    asm volatile("{.reg .pred p; mbarrier.try_wait.parity.shared::cta.b64 p, [%1], %2; selp.u32 %0, 1, 0, p;}"
                 : "=r"(ok) : "r"(bar), "r"(parity) : "memory");
    return ok;
}
DEVI bool mbar_try_cluster(uint32_t bar, uint32_t parity) {
    uint32_t ok;
    asm volatile("{.reg .pred p; mbarrier.try_wait.parity.acquire.cluster.shared::cta.b64 p, [%1], %2; selp.u32 %0, 1, 0, p;}"
                 : "=r"(ok) : "r"(bar), "r"(parity) : "memory");
    return ok;
}
DEVI bool mbar_try_hint(uint32_t bar, uint32_t parity) {
    uint32_t ok;
    asm volatile("{.reg .pred p; mbarrier.try_wait.parity.shared::cta.b64 p, [%1], %2, %3; selp.u32 %0, 1, 0, p;}"
                 : "=r"(ok) : "r"(bar), "r"(parity), "r"(MBAR_HINT_NS) : "memory");
    return ok;
}
DEVI void mbar_wait(uint32_t bar, uint32_t parity) {
    int n = 0;
    while (!mbar_try(bar, parity)) { if (++n > SPIN_LIMIT) TRAP(bar | (parity << 31)); }
}
DEVI void mbar_wait_sleepy(uint32_t bar, uint32_t parity) {
    int n = 0;
    while (!mbar_try_hint(bar, parity)) { if (++n > SPIN_LIMIT_MBAR) __trap(); }
}
DEVI void mbar_wait_cluster(uint32_t bar, uint32_t parity) {
    int n = 0;
    while (!mbar_try_cluster(bar, parity)) { if (++n > SPIN_LIMIT) __trap(); }
}
DEVI void mbar_spin(uint32_t bar, uint32_t parity) {
    uint32_t ok; int n = 0;
    do {
        asm volatile("{.reg .pred p; mbarrier.test_wait.parity.shared::cta.b64 p, [%1], %2; selp.u32 %0, 1, 0, p;}"
                     : "=r"(ok) : "r"(bar), "r"(parity) : "memory");
        if (++n > SPIN_LIMIT) __trap();
    } while (!ok);
}
DEVI void fence_mbar_init() { asm volatile("fence.mbarrier_init.release.cluster;" ::: "memory"); }
DEVI void fence_proxy_async() { asm volatile("fence.proxy.async.shared::cta;" ::: "memory"); }
DEVI void cluster_sync() {
    asm volatile("barrier.cluster.arrive.release.aligned;\n barrier.cluster.wait.acquire.aligned;" ::: "memory");
}
DEVI void nbar_sync(int id, int n) { asm volatile("bar.sync %0, %1;" :: "r"(id), "r"(n) : "memory"); }
DEVI void nbar_arrive(int id, int n) { asm volatile("bar.arrive %0, %1;" :: "r"(id), "r"(n) : "memory"); }

DEVI void tma_load_2d(uint32_t dst, const CUtensorMap* map, int x, int y, uint32_t bar) {
    asm volatile("cp.async.bulk.tensor.2d.shared::cluster.global.mbarrier::complete_tx::bytes [%0], [%1, {%3, %4}], [%2];"
                 :: "r"(dst), "l"(map), "r"(bar), "r"(x), "r"(y) : "memory");
}
DEVI void tma_load_3d(uint32_t dst, const CUtensorMap* map, int x, int y, int z, uint32_t bar) {
    asm volatile("cp.async.bulk.tensor.3d.shared::cluster.global.mbarrier::complete_tx::bytes [%0], [%1, {%3, %4, %5}], [%2];"
                 :: "r"(dst), "l"(map), "r"(bar), "r"(x), "r"(y), "r"(z) : "memory");
}
DEVI void tma_load_wo(uint32_t dst, const CUtensorMap* map, int col, int k32, uint32_t bar) {
    asm volatile("cp.async.bulk.tensor.5d.shared::cluster.global.mbarrier::complete_tx::bytes [%0], [%1, {%3, %5, %5, %5, %4}], [%2];"
                 :: "r"(dst), "l"(map), "r"(bar), "r"(col), "r"(k32), "r"(0) : "memory");
}
DEVI void tma_store_2d(const CUtensorMap* map, uint32_t src, int x, int y) {
    asm volatile("cp.async.bulk.tensor.2d.global.shared::cta.bulk_group [%0, {%2, %3}], [%1];"
                 :: "l"(map), "r"(src), "r"(x), "r"(y) : "memory");
}
DEVI void bulk_load(uint32_t dst, const void* src, uint32_t bytes, uint32_t bar) {
    asm volatile("cp.async.bulk.shared::cluster.global.mbarrier::complete_tx::bytes [%0], [%1], %2, [%3];"
                 :: "r"(dst), "l"(src), "r"(bytes), "r"(bar) : "memory");
}
DEVI void tma_load_2d_mc(uint32_t dst, const CUtensorMap* map, int x, int y, uint32_t bar, uint16_t mask) {
    asm volatile("cp.async.bulk.tensor.2d.shared::cluster.global.mbarrier::complete_tx::bytes.multicast::cluster [%0], [%1, {%3, %4}], [%2], %5;"
                 :: "r"(dst), "l"(map), "r"(bar), "r"(x), "r"(y), "h"(mask) : "memory");
}
DEVI void bulk_copy_s2c(uint32_t dst_cluster, uint32_t src, uint32_t bytes, uint32_t bar_cluster) {
    asm volatile("cp.async.bulk.shared::cluster.shared::cta.mbarrier::complete_tx::bytes [%0], [%1], %2, [%3];"
                 :: "r"(dst_cluster), "r"(src), "r"(bytes), "r"(bar_cluster) : "memory");
}
DEVI void bulk_store(void* dst, uint32_t src, uint32_t bytes) {
    asm volatile("cp.async.bulk.global.shared::cta.bulk_group [%0], [%1], %2;" :: "l"(dst), "r"(src), "r"(bytes) : "memory");
}
DEVI void bulk_wait_read() { asm volatile("cp.async.bulk.wait_group.read 0;" ::: "memory"); }
DEVI void mbar_arrive_remote(uint32_t bar_cluster) {
    asm volatile("mbarrier.arrive.shared::cluster.b64 _, [%0];" :: "r"(bar_cluster) : "memory");
}
DEVI void mbar_expect_tx_remote(uint32_t bar_cluster, uint32_t bytes) {
    asm volatile("mbarrier.arrive.expect_tx.shared::cluster.b64 _, [%0], %1;" :: "r"(bar_cluster), "r"(bytes) : "memory");
}
DEVI void l2_prefetch(const void* p, uint32_t bytes) {
    asm volatile("cp.async.bulk.prefetch.L2.global [%0], %1;" :: "l"(p), "r"(bytes) : "memory");
}
DEVI void bulk_commit() { asm volatile("cp.async.bulk.commit_group;" ::: "memory"); }
DEVI void bulk_wait_all() { asm volatile("cp.async.bulk.wait_group 0;" ::: "memory"); }

DEVI void wg_fence() { asm volatile("wgmma.fence.sync.aligned;" ::: "memory"); }
DEVI void wg_commit() { asm volatile("wgmma.commit_group.sync.aligned;" ::: "memory"); }
template <int N> DEVI void wg_wait() { asm volatile("wgmma.wait_group.sync.aligned %0;" :: "n"(N) : "memory"); }

template <int R> DEVI void reg_dec() { asm volatile("setmaxnreg.dec.sync.aligned.u32 %0;" :: "n"(R)); }
template <int R> DEVI void reg_inc() { asm volatile("setmaxnreg.inc.sync.aligned.u32 %0;" :: "n"(R)); }

DEVI uint64_t mk_desc(uint32_t addr, uint32_t lbo, uint32_t sbo, uint32_t sw) {
    return (uint64_t)((addr & 0x3FFFF) >> 4) | ((uint64_t)(lbo >> 4) << 16) | ((uint64_t)(sbo >> 4) << 32) | ((uint64_t)sw << 62);
}

DEVI uint32_t desc_lo(uint32_t addr, uint32_t lbo) { return ((addr & 0x3FFFF) >> 4) | ((lbo >> 4) << 16); }
constexpr uint32_t DHI_SW128 = (1024u >> 4) | (1u << 30);
constexpr uint32_t DHI_SW64  = (512u >> 4) | (2u << 30);
constexpr uint32_t DHI_NONE  = (128u >> 4);

template <int TB, int SCALE_D>
DEVI void wgmma_n8_ss(float* d, uint32_t alo, uint32_t blo) {
    asm volatile("{.reg .b64 da, db; mov.b64 da, {%4, %6}; mov.b64 db, {%5, %7};\n"
                 "wgmma.mma_async.sync.aligned.m64n8k16.f32.bf16.bf16 {%0,%1,%2,%3}, da, db, %8, 1, 1, 1, %9;}"
                 : "+f"(d[0]), "+f"(d[1]), "+f"(d[2]), "+f"(d[3])
                 : "r"(alo), "r"(blo), "n"(DHI_SW128), "n"(DHI_NONE), "n"(SCALE_D), "n"(TB));
}

template <int TB>
DEVI void wgmma_n8_ss_first(float* d, uint32_t alo, uint32_t blo) {
    asm volatile("{.reg .b64 da, db; mov.b64 da, {%4, %6}; mov.b64 db, {%5, %7};\n"
                 "wgmma.mma_async.sync.aligned.m64n8k16.f32.bf16.bf16 {%0,%1,%2,%3}, da, db, 0, 1, 1, 1, %8;}"
                 : "=f"(d[0]), "=f"(d[1]), "=f"(d[2]), "=f"(d[3])
                 : "r"(alo), "r"(blo), "n"(DHI_SW128), "n"(DHI_NONE), "n"(TB));
}
DEVI void wgmma_n32_rs_first(float* d, const uint32_t* a, uint32_t blo) {
    asm volatile("{.reg .b64 db; mov.b64 db, {%20, %21};\n"
                 "wgmma.mma_async.sync.aligned.m64n32k16.f32.bf16.bf16 {%0,%1,%2,%3,%4,%5,%6,%7,%8,%9,%10,%11,%12,%13,%14,%15}, "
                 "{%16,%17,%18,%19}, db, 0, 1, 1, 0;}"
                 : "=f"(d[0]), "=f"(d[1]), "=f"(d[2]), "=f"(d[3]), "=f"(d[4]), "=f"(d[5]), "=f"(d[6]), "=f"(d[7]),
                   "=f"(d[8]), "=f"(d[9]), "=f"(d[10]), "=f"(d[11]), "=f"(d[12]), "=f"(d[13]), "=f"(d[14]), "=f"(d[15])
                 : "r"(a[0]), "r"(a[1]), "r"(a[2]), "r"(a[3]), "r"(blo), "n"(DHI_SW64));
}
template <int N> DEVI void reg_fence(float* d) {
#pragma unroll
    for (int i = 0; i < N; i++) asm volatile("" : "+f"(d[i]) :: "memory");
}
DEVI void wgmma_n32_rs(float* d, const uint32_t* a, uint32_t blo) {
    asm volatile("{.reg .b64 db; mov.b64 db, {%20, %21};\n"
                 "wgmma.mma_async.sync.aligned.m64n32k16.f32.bf16.bf16 {%0,%1,%2,%3,%4,%5,%6,%7,%8,%9,%10,%11,%12,%13,%14,%15}, "
                 "{%16,%17,%18,%19}, db, 1, 1, 1, 0;}"
                 : "+f"(d[0]), "+f"(d[1]), "+f"(d[2]), "+f"(d[3]), "+f"(d[4]), "+f"(d[5]), "+f"(d[6]), "+f"(d[7]),
                   "+f"(d[8]), "+f"(d[9]), "+f"(d[10]), "+f"(d[11]), "+f"(d[12]), "+f"(d[13]), "+f"(d[14]), "+f"(d[15])
                 : "r"(a[0]), "r"(a[1]), "r"(a[2]), "r"(a[3]), "r"(blo), "n"(DHI_SW64));
}
DEVI void wgmma_n32_ss(float* d, uint32_t alo, uint32_t blo) {
    asm volatile("{.reg .b64 da, db; mov.b64 da, {%16, %18}; mov.b64 db, {%17, %19};\n"
                 "wgmma.mma_async.sync.aligned.m64n32k16.f32.bf16.bf16 {%0,%1,%2,%3,%4,%5,%6,%7,%8,%9,%10,%11,%12,%13,%14,%15}, "
                 "da, db, 1, 1, 1, 1, 0;}"
                 : "+f"(d[0]), "+f"(d[1]), "+f"(d[2]), "+f"(d[3]), "+f"(d[4]), "+f"(d[5]), "+f"(d[6]), "+f"(d[7]),
                   "+f"(d[8]), "+f"(d[9]), "+f"(d[10]), "+f"(d[11]), "+f"(d[12]), "+f"(d[13]), "+f"(d[14]), "+f"(d[15])
                 : "r"(alo), "r"(blo), "n"(DHI_SW128), "n"(DHI_SW64));
}

DEVI void wgmma_n256_ss(float* d, uint64_t a, uint64_t b, int scale_d) {
    asm volatile("{.reg .pred p; setp.ne.b32 p, %130, 0;\n"
        "wgmma.mma_async.sync.aligned.m64n256k16.f32.bf16.bf16 "
        "{%0,%1,%2,%3,%4,%5,%6,%7,%8,%9,%10,%11,%12,%13,%14,%15,"
        "%16,%17,%18,%19,%20,%21,%22,%23,%24,%25,%26,%27,%28,%29,%30,%31,"
        "%32,%33,%34,%35,%36,%37,%38,%39,%40,%41,%42,%43,%44,%45,%46,%47,"
        "%48,%49,%50,%51,%52,%53,%54,%55,%56,%57,%58,%59,%60,%61,%62,%63,"
        "%64,%65,%66,%67,%68,%69,%70,%71,%72,%73,%74,%75,%76,%77,%78,%79,"
        "%80,%81,%82,%83,%84,%85,%86,%87,%88,%89,%90,%91,%92,%93,%94,%95,"
        "%96,%97,%98,%99,%100,%101,%102,%103,%104,%105,%106,%107,%108,%109,%110,%111,"
        "%112,%113,%114,%115,%116,%117,%118,%119,%120,%121,%122,%123,%124,%125,%126,%127},"
        " %128, %129, p, 1, 1, 1, 0;}"
        : "+f"(d[0]), "+f"(d[1]), "+f"(d[2]), "+f"(d[3]), "+f"(d[4]), "+f"(d[5]), "+f"(d[6]), "+f"(d[7]),
          "+f"(d[8]), "+f"(d[9]), "+f"(d[10]), "+f"(d[11]), "+f"(d[12]), "+f"(d[13]), "+f"(d[14]), "+f"(d[15]),
          "+f"(d[16]), "+f"(d[17]), "+f"(d[18]), "+f"(d[19]), "+f"(d[20]), "+f"(d[21]), "+f"(d[22]), "+f"(d[23]),
          "+f"(d[24]), "+f"(d[25]), "+f"(d[26]), "+f"(d[27]), "+f"(d[28]), "+f"(d[29]), "+f"(d[30]), "+f"(d[31]),
          "+f"(d[32]), "+f"(d[33]), "+f"(d[34]), "+f"(d[35]), "+f"(d[36]), "+f"(d[37]), "+f"(d[38]), "+f"(d[39]),
          "+f"(d[40]), "+f"(d[41]), "+f"(d[42]), "+f"(d[43]), "+f"(d[44]), "+f"(d[45]), "+f"(d[46]), "+f"(d[47]),
          "+f"(d[48]), "+f"(d[49]), "+f"(d[50]), "+f"(d[51]), "+f"(d[52]), "+f"(d[53]), "+f"(d[54]), "+f"(d[55]),
          "+f"(d[56]), "+f"(d[57]), "+f"(d[58]), "+f"(d[59]), "+f"(d[60]), "+f"(d[61]), "+f"(d[62]), "+f"(d[63]),
          "+f"(d[64]), "+f"(d[65]), "+f"(d[66]), "+f"(d[67]), "+f"(d[68]), "+f"(d[69]), "+f"(d[70]), "+f"(d[71]),
          "+f"(d[72]), "+f"(d[73]), "+f"(d[74]), "+f"(d[75]), "+f"(d[76]), "+f"(d[77]), "+f"(d[78]), "+f"(d[79]),
          "+f"(d[80]), "+f"(d[81]), "+f"(d[82]), "+f"(d[83]), "+f"(d[84]), "+f"(d[85]), "+f"(d[86]), "+f"(d[87]),
          "+f"(d[88]), "+f"(d[89]), "+f"(d[90]), "+f"(d[91]), "+f"(d[92]), "+f"(d[93]), "+f"(d[94]), "+f"(d[95]),
          "+f"(d[96]), "+f"(d[97]), "+f"(d[98]), "+f"(d[99]), "+f"(d[100]), "+f"(d[101]), "+f"(d[102]), "+f"(d[103]),
          "+f"(d[104]), "+f"(d[105]), "+f"(d[106]), "+f"(d[107]), "+f"(d[108]), "+f"(d[109]), "+f"(d[110]), "+f"(d[111]),
          "+f"(d[112]), "+f"(d[113]), "+f"(d[114]), "+f"(d[115]), "+f"(d[116]), "+f"(d[117]), "+f"(d[118]), "+f"(d[119]),
          "+f"(d[120]), "+f"(d[121]), "+f"(d[122]), "+f"(d[123]), "+f"(d[124]), "+f"(d[125]), "+f"(d[126]), "+f"(d[127])
        : "l"(a), "l"(b), "r"(scale_d));
}

DEVI void wgmma_n128_ss(float* d, uint64_t a, uint64_t b, int scale_d) {
    asm volatile("{.reg .pred p; setp.ne.b32 p, %66, 0;\n"
        "wgmma.mma_async.sync.aligned.m64n128k16.f32.bf16.bf16 "
        "{%0,%1,%2,%3,%4,%5,%6,%7,%8,%9,%10,%11,%12,%13,%14,%15,"
        "%16,%17,%18,%19,%20,%21,%22,%23,%24,%25,%26,%27,%28,%29,%30,%31,"
        "%32,%33,%34,%35,%36,%37,%38,%39,%40,%41,%42,%43,%44,%45,%46,%47,"
        "%48,%49,%50,%51,%52,%53,%54,%55,%56,%57,%58,%59,%60,%61,%62,%63},"
        " %64, %65, p, 1, 1, 1, 0;}"
        : "+f"(d[0]), "+f"(d[1]), "+f"(d[2]), "+f"(d[3]), "+f"(d[4]), "+f"(d[5]), "+f"(d[6]), "+f"(d[7]),
          "+f"(d[8]), "+f"(d[9]), "+f"(d[10]), "+f"(d[11]), "+f"(d[12]), "+f"(d[13]), "+f"(d[14]), "+f"(d[15]),
          "+f"(d[16]), "+f"(d[17]), "+f"(d[18]), "+f"(d[19]), "+f"(d[20]), "+f"(d[21]), "+f"(d[22]), "+f"(d[23]),
          "+f"(d[24]), "+f"(d[25]), "+f"(d[26]), "+f"(d[27]), "+f"(d[28]), "+f"(d[29]), "+f"(d[30]), "+f"(d[31]),
          "+f"(d[32]), "+f"(d[33]), "+f"(d[34]), "+f"(d[35]), "+f"(d[36]), "+f"(d[37]), "+f"(d[38]), "+f"(d[39]),
          "+f"(d[40]), "+f"(d[41]), "+f"(d[42]), "+f"(d[43]), "+f"(d[44]), "+f"(d[45]), "+f"(d[46]), "+f"(d[47]),
          "+f"(d[48]), "+f"(d[49]), "+f"(d[50]), "+f"(d[51]), "+f"(d[52]), "+f"(d[53]), "+f"(d[54]), "+f"(d[55]),
          "+f"(d[56]), "+f"(d[57]), "+f"(d[58]), "+f"(d[59]), "+f"(d[60]), "+f"(d[61]), "+f"(d[62]), "+f"(d[63])
        : "l"(a), "l"(b), "r"(scale_d));
}

DEVI void mma16816(float* d, const uint32_t* a, uint32_t b0, uint32_t b1) {
    asm volatile("mma.sync.aligned.m16n8k16.row.col.f32.bf16.bf16.f32 {%0,%1,%2,%3}, {%4,%5,%6,%7}, {%8,%9}, {%0,%1,%2,%3};"
                 : "+f"(d[0]), "+f"(d[1]), "+f"(d[2]), "+f"(d[3])
                 : "r"(a[0]), "r"(a[1]), "r"(a[2]), "r"(a[3]), "r"(b0), "r"(b1));
}
DEVI void mma1688(float* d, uint32_t a0, uint32_t a1, uint32_t b0) {
    asm volatile("mma.sync.aligned.m16n8k8.row.col.f32.bf16.bf16.f32 {%0,%1,%2,%3}, {%4,%5}, {%6}, {%0,%1,%2,%3};"
                 : "+f"(d[0]), "+f"(d[1]), "+f"(d[2]), "+f"(d[3]) : "r"(a0), "r"(a1), "r"(b0));
}
DEVI void ldsm4(uint32_t* r, uint32_t addr) {
    asm volatile("ldmatrix.sync.aligned.m8n8.x4.shared.b16 {%0,%1,%2,%3}, [%4];"
                 : "=r"(r[0]), "=r"(r[1]), "=r"(r[2]), "=r"(r[3]) : "r"(addr) : "memory");
}
DEVI void ldsm4t(uint32_t* r, uint32_t addr) {
    asm volatile("ldmatrix.sync.aligned.m8n8.x4.trans.shared.b16 {%0,%1,%2,%3}, [%4];"
                 : "=r"(r[0]), "=r"(r[1]), "=r"(r[2]), "=r"(r[3]) : "r"(addr) : "memory");
}
DEVI void ldsm2(uint32_t* r, uint32_t addr) {
    asm volatile("ldmatrix.sync.aligned.m8n8.x2.shared.b16 {%0,%1}, [%2];" : "=r"(r[0]), "=r"(r[1]) : "r"(addr) : "memory");
}
DEVI void ldsm1t(uint32_t& r, uint32_t addr) {
    asm volatile("ldmatrix.sync.aligned.m8n8.x1.trans.shared.b16 {%0}, [%1];" : "=r"(r) : "r"(addr) : "memory");
}
DEVI void stsm4(uint32_t addr, uint32_t r0, uint32_t r1, uint32_t r2, uint32_t r3) {
    asm volatile("stmatrix.sync.aligned.m8n8.x4.shared.b16 [%0], {%1,%2,%3,%4};" :: "r"(addr), "r"(r0), "r"(r1), "r"(r2), "r"(r3) : "memory");
}
DEVI void stsm4t(uint32_t addr, uint32_t r0, uint32_t r1, uint32_t r2, uint32_t r3) {
    asm volatile("stmatrix.sync.aligned.m8n8.x4.trans.shared.b16 [%0], {%1,%2,%3,%4};" :: "r"(addr), "r"(r0), "r"(r1), "r"(r2), "r"(r3) : "memory");
}
DEVI uint32_t movm_t(uint32_t a) {
    uint32_t d; asm volatile("movmatrix.sync.aligned.m8n8.trans.b16 %0, %1;" : "=r"(d) : "r"(a)); return d;
}
DEVI uint32_t pack_bf16(float lo, float hi) {
    uint32_t r; asm("cvt.rn.bf16x2.f32 %0, %1, %2;" : "=r"(r) : "f"(hi), "f"(lo)); return r;
}
DEVI float ex2(float x) { float y; asm("ex2.approx.ftz.f32 %0, %1;" : "=f"(y) : "f"(x)); return y; }

DEVI uint4 ld_rlx4(const void* p) {
    uint4 v;
    asm volatile("ld.relaxed.gpu.global.v4.u32 {%0,%1,%2,%3}, [%4];" : "=r"(v.x), "=r"(v.y), "=r"(v.z), "=r"(v.w) : "l"(p) : "memory");
    return v;
}
DEVI void ld_rlx4f(float* d, const void* p) {
    asm volatile("ld.relaxed.gpu.global.v4.f32 {%0,%1,%2,%3}, [%4];" : "=f"(d[0]), "=f"(d[1]), "=f"(d[2]), "=f"(d[3]) : "l"(p) : "memory");
}
DEVI bool all_nzf(const float* d) { return __float_as_uint(d[0]) && __float_as_uint(d[1]) && __float_as_uint(d[2]) && __float_as_uint(d[3]); }
DEVI void sts128f(uint32_t addr, const float* d) {
    asm volatile("st.shared.v4.f32 [%0], {%1,%2,%3,%4};" :: "r"(addr), "f"(d[0]), "f"(d[1]), "f"(d[2]), "f"(d[3]) : "memory");
}
DEVI void st_rlx4(void* p, uint32_t a, uint32_t b, uint32_t c, uint32_t d) {
    asm volatile("st.relaxed.gpu.global.v4.u32 [%0], {%1,%2,%3,%4};" :: "l"(p), "r"(a), "r"(b), "r"(c), "r"(d) : "memory");
}
DEVI void st_rlx(void* p, uint32_t v) { asm volatile("st.relaxed.gpu.global.u32 [%0], %1;" :: "l"(p), "r"(v) : "memory"); }
DEVI void sts128(uint32_t addr, uint4 v) {
    asm volatile("st.shared.v4.u32 [%0], {%1,%2,%3,%4};" :: "r"(addr), "r"(v.x), "r"(v.y), "r"(v.z), "r"(v.w) : "memory");
}
DEVI void sts32(uint32_t addr, uint32_t v) { asm volatile("st.shared.u32 [%0], %1;" :: "r"(addr), "r"(v) : "memory"); }
DEVI uint4 lds128(uint32_t addr) {
    uint4 v; asm volatile("ld.shared.v4.u32 {%0,%1,%2,%3}, [%4];" : "=r"(v.x), "=r"(v.y), "=r"(v.z), "=r"(v.w) : "r"(addr) : "memory"); return v;
}
DEVI float2 lds64f(uint32_t addr) {
    float2 v; asm volatile("ld.shared.v2.f32 {%0,%1}, [%2];" : "=f"(v.x), "=f"(v.y) : "r"(addr) : "memory"); return v;
}
DEVI void cp_async16(uint32_t dst, const void* src) {
    asm volatile("cp.async.cg.shared.global [%0], [%1], 16;" :: "r"(dst), "l"(src) : "memory");
}
DEVI void cp_async_commit() { asm volatile("cp.async.commit_group;" ::: "memory"); }
DEVI void cp_async_wait0() { asm volatile("cp.async.wait_group 0;" ::: "memory"); }
DEVI uint32_t lds32(uint32_t addr) { uint32_t v; asm volatile("ld.shared.u32 %0, [%1];" : "=r"(v) : "r"(addr) : "memory"); return v; }
DEVI float rcp_fast(float x) { float y; asm("rcp.approx.ftz.f32 %0, %1;" : "=f"(y) : "f"(x)); return y; }
DEVI bool all_nz(const uint4& v) { return v.x && v.y && v.z && v.w; }
DEVI uint32_t mapa(uint32_t addr, uint32_t rank) {
    uint32_t r; asm("mapa.shared::cluster.u32 %0, %1, %2;" : "=r"(r) : "r"(addr), "r"(rank)); return r;
}
DEVI void st_async64(uint32_t dst, uint32_t a, uint32_t b, uint32_t bar) {
    asm volatile("st.async.weak.shared::cluster.mbarrier::complete_tx::bytes.v2.b32 [%0], {%1,%2}, [%3];"
                 :: "r"(dst), "r"(a), "r"(b), "r"(bar) : "memory");
}

DEVI void st_async128(uint32_t dst, uint32_t a, uint32_t b, uint32_t c, uint32_t d, uint32_t bar) {
    asm volatile("st.async.weak.shared::cluster.mbarrier::complete_tx::bytes.v4.b32 [%0], {%1,%2,%3,%4}, [%5];"
                 :: "r"(dst), "r"(a), "r"(b), "r"(c), "r"(d), "r"(bar) : "memory");
}

DEVI uint32_t b_addr(uint32_t sb, int row, int which, int chunk) { const int l = 3 * row + which; return sb + l * 128 + ((chunk ^ (l & 7)) * 16); }
DEVI void battn_warp(uint32_t st, uint32_t so, int i0, int par, int head, int hh, int mt, int lane) {
    const int gq = lane >> 2, t = lane & 3;
    float s[3][4];
#pragma unroll
    for (int n = 0; n < 3; n++) { s[n][0] = s[n][1] = s[n][2] = s[n][3] = 0.f; }
    const int arow = 16 * mt + (lane & 7) + ((lane >> 3) & 1) * 8;
#pragma unroll
    for (int ks = 0; ks < 2; ks++) {
        uint32_t a[4], b[4], b2[2];
        ldsm4(a, b_addr(st, 8 + arow, 0, hh * 4 + ks * 2 + (lane >> 4)));
        const int brow = 16 * mt + (lane >> 4) * 8 + (lane & 7);
        ldsm4(b, b_addr(st, brow, 1, hh * 4 + ks * 2 + ((lane >> 3) & 1)));
        const int crow = 16 * mt + 16 + (lane & 7);
        ldsm2(b2, b_addr(st, crow, 1, hh * 4 + ks * 2 + ((lane >> 3) & 1)));
        mma16816(s[0], a, b[0], b[1]);
        mma16816(s[1], a, b[2], b[3]);
        mma16816(s[2], a, b2[0], b2[1]);
    }
    float m0 = -INFINITY, m1 = -INFINITY;
#pragma unroll
    for (int n = 0; n < 3; n++) {
#pragma unroll
        for (int c = 0; c < 2; c++) {
            const int dj = 8 * n - 8 + 2 * t + c;
            const bool ex = i0 + 16 * mt + dj >= 0;
            if (!(ex && gq - dj >= 0 && gq - dj <= 7)) s[n][c] = -INFINITY;
            if (!(ex && gq + 8 - dj >= 0 && gq + 8 - dj <= 7)) s[n][2 + c] = -INFINITY;
            m0 = fmaxf(m0, s[n][c]); m1 = fmaxf(m1, s[n][2 + c]);
        }
    }
    m0 = fmaxf(m0, __shfl_xor_sync(0xffffffffu, m0, 1)); m0 = fmaxf(m0, __shfl_xor_sync(0xffffffffu, m0, 2));
    m1 = fmaxf(m1, __shfl_xor_sync(0xffffffffu, m1, 1)); m1 = fmaxf(m1, __shfl_xor_sync(0xffffffffu, m1, 2));
    constexpr float C = 0.17677669529663687f * 1.4426950408889634f;
    float l0 = 0.f, l1 = 0.f;
    uint32_t p[3][2];
#pragma unroll
    for (int n = 0; n < 3; n++) {
        const float e0 = ex2((s[n][0] - m0) * C), e1 = ex2((s[n][1] - m0) * C), e2 = ex2((s[n][2] - m1) * C), e3 = ex2((s[n][3] - m1) * C);
        l0 += e0 + e1; l1 += e2 + e3;
        p[n][0] = pack_bf16(e0, e1); p[n][1] = pack_bf16(e2, e3);
    }
    l0 += __shfl_xor_sync(0xffffffffu, l0, 1); l0 += __shfl_xor_sync(0xffffffffu, l0, 2);
    l1 += __shfl_xor_sync(0xffffffffu, l1, 1); l1 += __shfl_xor_sync(0xffffffffu, l1, 2);
    const float i0f = rcp_fast(l0), i1f = rcp_fast(l1);
    float o[4][4];
#pragma unroll
    for (int n = 0; n < 4; n++) { o[n][0] = o[n][1] = o[n][2] = o[n][3] = 0.f; }
    {
        const uint32_t a0[4] = {p[0][0], p[0][1], p[1][0], p[1][1]}, a1[4] = {p[2][0], p[2][1], 0u, 0u};
#pragma unroll
        for (int n = 0; n < 4; n += 2) {
            uint32_t b[4], b2[4];
            const int vrow = 16 * mt + ((lane >> 3) & 1) * 8 + (lane & 7);
            ldsm4t(b, b_addr(st, vrow, 2, hh * 4 + n + (lane >> 4)));
            const int wrow = 16 * mt + 16 + (lane & 7);
            ldsm4t(b2, b_addr(st, wrow, 2, hh * 4 + n + (lane >> 4)));
            mma16816(o[n], a0, b[0], b[1]);
            mma16816(o[n + 1], a0, b[2], b[3]);
            mma16816(o[n], a1, b2[0], 0u);
            mma16816(o[n + 1], a1, b2[2], 0u);
        }
    }
    {
        const int row = (lane & 7) + ((lane >> 3) & 1) * 8;
#pragma unroll
        for (int n = 0; n < 4; n += 2)
            stsm4(so + row * 64 + (((n + (lane >> 4)) ^ ((row >> 1) & 3)) * 16),
                  pack_bf16(o[n][0] * i0f, o[n][1] * i0f), pack_bf16(o[n][2] * i1f, o[n][3] * i1f),
                  pack_bf16(o[n + 1][0] * i0f, o[n + 1][1] * i0f), pack_bf16(o[n + 1][2] * i1f, o[n + 1][3] * i1f));
    }
    __syncwarp();
#pragma unroll
    for (int i = 0; i < 2; i++) {
        const int idx = lane + i * 32, row = idx >> 2, ch = idx & 3;
        const uint4 v = lds128(so + row * 64 + ((ch ^ ((row >> 1) & 3)) * 16));
        *(uint4*)(g_bo + (size_t)(2 * (i0 + 16 * mt + row) + par) * 1024 + head * 32 + ch * 8) = v;
    }
    __syncwarp();
}

constexpr float SCALE_LOG2E = 0.08838834764831845f * 1.4426950408889634f;

constexpr int P_STAGES = 4, P_STAGE = 16384 + 32768;
constexpr int PS_STG = P_STAGES * P_STAGE;
constexpr int PS_BAR = PS_STG + 32768;
constexpr int P_SMEM = PS_BAR + 256;
static_assert(P_SMEM <= 232448, "smem");
constexpr int PT_B1 = 256, PT_A0 = PT_B1 + 192, PT_B2 = PT_A0 + 32, PT_A1 = PT_B2 + 32, PT_B3 = PT_A1 + 32, PT_A2 = PT_B3 + 64;
constexpr int PT_SK = PT_A2 + 48, P_NTASK = PT_SK + 64;
enum { K_B1, K_Q, K_B2, K_B3, K_A3, K_SK, K_END };
struct PTask { int kind, a, b, c; };
DEVI PTask p_decode(int id) {
    if (id < PT_B1) return {K_Q, id % 32, id / 32, 0};
    if (id < PT_A0) return {K_B1, (id - PT_B1) % 24, (id - PT_B1) / 24, 0};
    if (id < PT_B2) return {K_A3, (id - PT_A0) & 7, (id - PT_A0) >> 3, 0};
    if (id < PT_A1) return {K_B2, id - PT_B2, 0, 0};
    if (id < PT_B3) return {K_A3, (id - PT_A1) & 7, 4 + ((id - PT_A1) >> 3), 0};
    if (id < PT_A2) return {K_B3, (id - PT_B3) % 8, (id - PT_B3) / 8, 0};
    if (id < PT_SK) return {K_A3, (id - PT_A2) & 7, 8 + ((id - PT_A2) >> 3), 0};
    if (id >= P_NTASK) return {K_END, 0, 0, 0};
    const int j = id - PT_SK;
    return {K_SK, (j >> 2) & 7, 14 + (j >> 5), j & 3};
}
DEVI void wait_count(const unsigned* p, unsigned target) {
    int n = 0;
    while (true) {
        unsigned v; asm volatile("ld.acquire.gpu.global.u32 %0, [%1];" : "=r"(v) : "l"(p) : "memory");
        if ((int)(v - target) >= 0) break;
        __nanosleep(100);
        if (++n > SPIN_LIMIT) TRAP(0x10000000u | ((unsigned)(size_t)p & 0xFFFFu));
    }
}
DEVI void signal_count(unsigned* p) { __threadfence(); atomicAdd(p, 1u); }

struct PMaps { CUtensorMap wq, bw, bwo, wo, x, bx, bo, ox, cb, cout, b40; };

template <int BN>
DEVI void p_mainloop(float* d, uint32_t sb, int g, int nk, int& it, bool elected) {
#pragma unroll
    for (int i = 0; i < BN / 2; i++) d[i] = 0.f;
    for (int kb = 0; kb < nk; kb++, it++) {
        const int st = it % P_STAGES;
        mbar_wait(sb + PS_BAR + st * 8, (it / P_STAGES) & 1);
        const uint32_t a = sb + st * P_STAGE;
        const uint64_t da = mk_desc(a + g * 8192, 16, 1024, 1), db = mk_desc(a + 16384, 16, 1024, 1);
        wg_fence();
#pragma unroll
        for (int kk = 0; kk < 4; kk++) {
            if (BN == 256) wgmma_n256_ss(d, da + (uint64_t)(kk * 128), db + (uint64_t)(kk * 2), (kb | kk) != 0);
            else           wgmma_n128_ss(d, da + (uint64_t)(kk * 128), db + (uint64_t)(kk * 2), (kb | kk) != 0);
        }
        wg_commit();
        if (kb > 0) {
            wg_wait<1>();
            if (elected) mbar_arrive(sb + PS_BAR + 32 + ((it - 1) % P_STAGES) * 8);
        }
    }
    wg_wait<0>();
    if (elected) mbar_arrive(sb + PS_BAR + 32 + ((it - 1) % P_STAGES) * 8);
}
template <int BN>
DEVI void p_epi_row(const float* d, uint32_t stg, const CUtensorMap* tmC, int col, int tok0, int warp, int lane_, int barid, bool elected, int& nstore) {
    const int lane = (int)opaque((uint32_t)lane_);
    const int mi = lane >> 3, r = lane & 7;
#pragma unroll
    for (int c = 0; c < BN / 64; c++, nstore++) {
        const uint32_t buf = stg + (nstore & 1) * 8192;
        if (elected) asm volatile("cp.async.bulk.wait_group.read 1;" ::: "memory");
        nbar_sync(barid, 128);
#pragma unroll
        for (int j = 0; j < 8; j += 2) {
            const int jj = c * 8 + j;
            const int tok = 8 * (j + (mi >> 1)) + r;
            const int chunk = (2 * warp + (mi & 1)) ^ r;
            stsm4t(buf + tok * 128 + chunk * 16,
                   pack_bf16(d[4 * jj], d[4 * jj + 1]), pack_bf16(d[4 * jj + 2], d[4 * jj + 3]),
                   pack_bf16(d[4 * jj + 4], d[4 * jj + 5]), pack_bf16(d[4 * jj + 6], d[4 * jj + 7]));
        }
        fence_proxy_async();
        nbar_sync(barid, 128);
        if (elected) { tma_store_2d(tmC, buf, col, tok0 + c * 64); bulk_commit(); }
    }
}

__global__ void __launch_bounds__(384, 1) k_post(const __grid_constant__ PMaps mp) {
    extern __shared__ __align__(1024) uint8_t smem_raw[];
    const uint32_t sb = smem_u32(smem_raw);
    if (sb & 1023u) __trap();
    const int tid = threadIdx.x, lane = tid & 31;
    const int wg = __shfl_sync(0xffffffffu, tid >> 7, 0), warp = __shfl_sync(0xffffffffu, (tid >> 5) & 3, 0);
    const uint32_t bF = sb + PS_BAR, bE = bF + 32, bTF = bF + 64, bTE = bF + 80, sT = bF + 96;
    if (tid == 0) {
        for (int i = 0; i < P_STAGES; i++) { mbar_init(bF + i * 8, 1); mbar_init(bE + i * 8, 2); }
        for (int i = 0; i < 2; i++) { mbar_init(bTF + i * 8, 1); mbar_init(bTE + i * 8, 256); }
        fence_mbar_init();
    }
    __syncthreads();
    if (wg == 2) {
        reg_dec<40>();
        if (tid == 256) {
            const unsigned E = *(volatile unsigned*)&g_epoch + 1;
            const unsigned qbase = (E - 1) * (unsigned)(P_NTASK + gridDim.x);
            int it = 0;
            for (int i = 0;; i++) {
                mbar_wait(bTE + (i & 1) * 8, ((i >> 1) & 1) ^ 1);
                const int id = (int)(atomicAdd(&g_qctr, 1u) - qbase);
                const PTask tk = p_decode(id);
                if (tk.kind == K_B2) {
                    wait_count(&g_cnt_b1[tk.a >> 2], 48 * E);
                    if ((tk.a & 3) == 0 && tk.a > 0) wait_count(&g_cnt_b1[(tk.a >> 2) - 1], 48 * E);
                } else if (tk.kind == K_B3) wait_count(&g_cnt_b2[tk.b], 4 * E);
                else if (tk.kind == K_A3 || tk.kind == K_SK) wait_count(&g_prog[tk.b], 128 * E);
                asm volatile("fence.proxy.async;" ::: "memory");
                sts32(sT + (i & 1) * 4, (uint32_t)id);
                mbar_arrive(bTF + (i & 1) * 8);
                if (tk.kind == K_END) break;
                if (tk.kind == K_B2) {
                    const int i0 = tk.a * 32;
                    for (int j = 0; j < 16; j++, it++) {
                        const int st = it % P_STAGES;
                        mbar_wait(bE + st * 8, ((it / P_STAGES) & 1) ^ 1);
                        const uint32_t a = sb + st * P_STAGE, bar = bF + st * 8;
                        mbar_expect_tx(bar, 2 * 15360);
                        for (int u = 0; u < 2; u++)
                            asm volatile("cp.async.bulk.tensor.4d.shared::cluster.global.mbarrier::complete_tx::bytes [%0], [%1, {%3, %4, %5, %6}], [%2];"
                                         :: "r"(a + u * 15360), "l"(&mp.b40), "r"(bar), "r"(j * 64), "r"(0), "r"(u), "r"(i0 - 8) : "memory");
                    }
                    continue;
                }
                const CUtensorMap* tw = tk.kind == K_B1 ? &mp.bw : (tk.kind == K_Q ? &mp.wq : (tk.kind == K_B3 ? &mp.bwo : &mp.wo));
                const CUtensorMap* tx = tk.kind == K_B1 ? &mp.bx : (tk.kind == K_Q ? &mp.x : (tk.kind == K_B3 ? &mp.bo : &mp.ox));
                const bool a3 = tk.kind == K_A3 || tk.kind == K_SK;
                const int nk = tk.kind == K_A3 ? HD / 64 : DM / 64, kb0 = tk.kind == K_SK ? tk.c * 16 : 0;
                for (int kb = kb0; kb < kb0 + nk; kb++, it++) {
                    const int st = it % P_STAGES;
                    mbar_wait(bE + st * 8, ((it / P_STAGES) & 1) ^ 1);
                    const uint32_t a = sb + st * P_STAGE, bar = bF + st * 8;
                    mbar_expect_tx(bar, a3 ? 32768 : P_STAGE);
                    if (a3) {
                        tma_load_wo(a, tw, tk.a * 128, kb * 2, bar);
                        tma_load_wo(a + 8192, tw, tk.a * 128 + 64, kb * 2, bar);
                    } else {
                        tma_load_2d(a, tw, tk.a * 128, kb * 64, bar);
                        tma_load_2d(a + 8192, tw, tk.a * 128 + 64, kb * 64, bar);
                    }
                    tma_load_2d(a + 16384, tx, kb * 64, tk.b * (a3 ? 128 : 256), bar);
                }
            }
            __threadfence();
            if (atomicAdd(&g_done, 1u) == E * gridDim.x - 1) { __threadfence(); *(volatile unsigned*)&g_epoch = E; }
        }
    } else {
        reg_inc<232>();
        const int g = wg, ct = tid, barid = 1 + g;
        const bool elected = (tid & 127) == 0;
        const uint32_t stg = sb + PS_STG + g * 16384;
        int it = 0, nstore = 0;
        unsigned* pending = nullptr;
        for (int i = 0;; i++) {
            if (elected && pending && !mbar_try(bTF + (i & 1) * 8, (i >> 1) & 1)) { bulk_wait_all(); signal_count(pending); pending = nullptr; }
            mbar_wait(bTF + (i & 1) * 8, (i >> 1) & 1);
            const int id = (int)lds32(sT + (i & 1) * 4);
            mbar_arrive(bTE + (i & 1) * 8);
            const PTask tk = p_decode(id);
            if (tk.kind == K_END) break;
            if (tk.kind == K_B2) {
                if (elected && pending) { bulk_wait_all(); signal_count(pending); }
                pending = nullptr;
                if (elected) bulk_wait_all();
                nbar_sync(barid, 128);
#pragma unroll 1
                for (int j = 0; j < 16; j++, it++) {
                    const int st = it % P_STAGES;
                    mbar_wait(bF + st * 8, (it / P_STAGES) & 1);
                    const uint32_t a = sb + st * P_STAGE + g * 15360;
                    battn_warp(a, stg + warp * 1024, tk.a * 32, g, j * 2 + (warp >> 1), warp >> 1, warp & 1, (int)opaque((uint32_t)lane));
                    nbar_sync(barid, 128);
                    if (elected) mbar_arrive(bE + st * 8);
                }
                nbar_sync(3, 256);
                if (ct == 0) signal_count(&g_cnt_b2[tk.a >> 2]);
            } else if (tk.kind == K_A3 || tk.kind == K_SK) {
                float d[64];
                p_mainloop<128>(d, sb, g, tk.kind == K_A3 ? HD / 64 : DM / 64, it, elected);
                if (elected && pending) { bulk_wait_all(); signal_count(pending); }
                pending = nullptr;
                bool finish = true;
                if (tk.kind == K_SK) {
                    const int tile = ((tk.b - 14) * 8 + tk.a);
                    float4* mine = (float4*)(g_skp + ((size_t)(tile * 4 + tk.c) * 2 + g) * 8192) + (tid & 127);
#pragma unroll
                    for (int j = 0; j < 16; j++) mine[j * 128] = make_float4(d[4 * j], d[4 * j + 1], d[4 * j + 2], d[4 * j + 3]);
                    nbar_sync(barid, 128);
                    if (elected) { __threadfence(); const unsigned old = atomicAdd(&g_cnt_sk[tile * 2 + g], 1u); __threadfence(); sts32(sT + 16 + g * 4, old & 3u); }
                    nbar_sync(barid, 128);
                    finish = lds32(sT + 16 + g * 4) == 3u;
                    if (finish) {
#pragma unroll 1
                        for (int q = 1; q < 4; q++) {
                            const float4* o = (const float4*)(g_skp + ((size_t)(tile * 4 + ((tk.c + q) & 3)) * 2 + g) * 8192) + (tid & 127);
#pragma unroll
                            for (int j = 0; j < 16; j++) {
                                const float4 v = __ldcg(o + j * 128);
                                d[4 * j] += v.x; d[4 * j + 1] += v.y; d[4 * j + 2] += v.z; d[4 * j + 3] += v.w;
                            }
                        }
                    }
                    nbar_sync(barid, 128);
                }
                if (finish) p_epi_row<128>(d, stg, &mp.cout, tk.a * 128 + g * 64, tk.b * 128, warp, lane, barid, elected, nstore);
            } else {
                float d[128];
                p_mainloop<256>(d, sb, g, DM / 64, it, elected);
                if (elected && pending) { bulk_wait_all(); signal_count(pending); }
                pending = nullptr;
                if (tk.kind == K_Q) {
                    const int ln = (int)opaque((uint32_t)lane), gq = ln >> 2, t = ln & 3, dim = g * 64 + warp * 16 + gq;
#pragma unroll
                    for (int j = 0; j < 32; j++) {
                        const int seg = tk.b * 8 + (j >> 2), blk = j & 3;
                        uint32_t* p = (uint32_t*)(g_qx + ((((size_t)seg * NH + tk.a) * 4 + blk) * DH + dim) * 8 + 2 * t);
                        p[0]  = pack_bf16(d[4 * j], d[4 * j + 1]);
                        p[32] = pack_bf16(d[4 * j + 2], d[4 * j + 3]);
                    }
                    nbar_sync(barid, 128);
                    if (elected) signal_count(&g_cnt_q[tk.b]);
                } else if (tk.kind == K_B1) {
                    p_epi_row<256>(d, stg, &mp.cb, tk.a * 128 + g * 64, tk.b * 256, warp, lane, barid, elected, nstore);
                    pending = &g_cnt_b1[tk.b];
                } else {
                    p_epi_row<256>(d, stg, &mp.cout, DM + tk.a * 128 + g * 64, tk.b * 256, warp, lane, barid, elected, nstore);
                }
            }
        }
        if (elected) { bulk_wait_all(); if (pending) signal_count(pending); }
    }
    __syncthreads();
}

constexpr unsigned long long R_TORD_PACK = 0xFAE954DC873B6210ull;
__host__ __device__ constexpr int r_tord(int pos) { return (int)((R_TORD_PACK >> (4 * pos)) & 15ull); }
__host__ __device__ constexpr int r_tinv(int T) { for (int p = 0; p < 16; p++) if (r_tord(p) == T) return p; return 0; }
__host__ __device__ constexpr bool r_pos_ss(int pos) { return pos % 3 == 2; }
__host__ __device__ constexpr int r_ss(int pos) { return pos / 3; }
__host__ __device__ constexpr int r_rs(int pos) { return pos - pos / 3; }
constexpr int R_NRS = 11, R_NSS = 5;
constexpr int R_G1 = 5, R_G2 = 10;
#define REG_KB 232
#define REG_QB 224
#define X_NA_DEF 3
constexpr int X_SLOTS = 4;
constexpr int X_NST = 8;
constexpr int X_NA = X_NA_DEF;

constexpr int RS_WSS  = 0;
constexpr int RS_WO   = RS_WSS + R_NSS * 16384;
constexpr int RS_MEM  = RS_WO + 5 * 16384;
constexpr int RS_O    = RS_MEM + 16384;
constexpr int RS_SX   = RS_O + 2048;
constexpr int RS_BAR  = RS_SX + 2048;
constexpr int RS_TAIL = RS_BAR + 1024;
constexpr int RS_WO5  = RS_TAIL;
constexpr int RS_K    = RS_WO5 + 16384;
constexpr int RS_V    = RS_K + 10240;
constexpr int RS_Q    = RS_V + 10240;
constexpr int RS_QX   = RS_Q + 2048;
constexpr int RS_QEND = RS_QX + 8192;
constexpr int RS_X    = RS_TAIL;
constexpr int X_PITCH = (X_SLOTS + 1) * 4096;
constexpr int RS_WX   = RS_X + 2 * X_PITCH;
constexpr int RS_KEND = RS_WX + 4096;
constexpr int RS_EV   = RS_BAR + 256;
constexpr int R_SMEM  = RS_KEND > RS_QEND ? RS_KEND : RS_QEND;
static_assert(R_SMEM <= 232448, "smem");
static_assert(RS_TAIL % 1024 == 0 && RS_MEM % 1024 == 0, "alignment");

constexpr int RB_G = RS_BAR, RB_K = RS_BAR + 24, RB_V = RS_BAR + 32, RB_KV = RS_BAR + 40, RB_QX = RS_BAR + 48, RB_O = RS_BAR + 56;
constexpr int RB_ATT = RS_BAR + 64, RB_W = RS_BAR + 72, RB_SF = RS_BAR + 80, RB_SE = RB_SF + 40, RB_XF = RB_SE + 40;
static_assert(RB_XF + 80 <= RS_EV, "barriers");
constexpr uint32_t SB0 = 1024;
__host__ __device__ constexpr uint32_t cdesc(uint32_t off, uint32_t lbo) { return ((SB0 + off) >> 4) | ((lbo >> 4) << 16); }
#define SCHED_FENCE() __syncwarp()
constexpr int NB_BIG = 1, NB_Q = 2, NB_AUX = 3, NB_WO = 4, NB_XS = 5, NB_WG = 6;

DEVI int tid_now() { int t; asm volatile("mov.u32 %0, %%tid.x;" : "=r"(t)); return t; }
DEVI uint32_t a_frag_off(int lane, int warp) { return (uint32_t)((((lane >> 4) * 8 + (lane & 7)) * 128) + (((2 * warp + ((lane >> 3) & 1)) ^ (lane & 7)) * 16)); }
DEVI uint32_t clk32() { uint32_t c; asm volatile("mov.u32 %0, %%clock;" : "=r"(c)); return c; }
DEVI void spin_until(uint32_t t) { while ((int)(clk32() - t) < 0) { } }

DEVI void x_load(uint32_t sb, int seg, int j, int g, const CUtensorMap* tmX) {
    const uint32_t bar = sb + RB_XF + g * (8 * X_SLOTS) + 8 * (j % X_SLOTS);
    mbar_expect_tx(bar, 4096);
    tma_load_3d(sb + RS_X + g * X_PITCH + (j % X_SLOTS) * 4096, tmX, g * 32, seg * 32, j * 2, bar);
}
DEVI void x_refill(uint32_t sb, int seg, int j, int g, const CUtensorMap* tmX) {
    const int sn = j + X_SLOTS < X_NST ? seg : seg + 1;
    if ((tid_now() & 127) == 0 && sn < NSEG) x_load(sb, sn, (j + X_SLOTS) % X_NST, g, tmX);
}
template <int J0, int J1>
DEVI void x_stages(float* xa, const uint32_t* w, uint32_t sb, int seg, int g0, const CUtensorMap* tmX) {
#pragma unroll
    for (int j = J0; j < J1; j++) {
        const int g = (int)opaque((uint32_t)g0);
        const uint32_t dW0 = cdesc(RS_WSS, 16) + g * 768, dW1 = cdesc(RS_WSS + 8192, 16) - g * 256;
        const uint32_t dX = cdesc(RS_X + (j % X_SLOTS) * 4096, 16) + g * (X_PITCH >> 4);
        mbar_wait(sb + RB_XF + g * (8 * X_SLOTS) + 8 * (j % X_SLOTS), (j / X_SLOTS) & 1);
        wg_fence();
#pragma unroll
        for (int q = 0; q < 8; q++) {
            const int pos = r_tinv(2 * j + (q >> 2)), kk = (q >> 1) & 1, mt = q & 1;
            const uint32_t db = dX + (q >> 2) * 128 + kk * 2;
            if (j == 0 && q < 2)   wgmma_n32_rs_first(xa + 16 * mt, &w[((r_rs(pos) * 2 + kk) * 2 + mt) * 4], db);
            else if (j == 0 && q == 3) wgmma_n32_ss(xa + 16, cdesc(RS_WX, 16) + g * 128, db);
            else if (r_pos_ss(pos)) wgmma_n32_ss(xa + 16 * mt, (mt ? dW1 : dW0) + r_ss(pos) * 1024 + kk * 128, db);
            else                   wgmma_n32_rs(xa + 16 * mt, &w[((r_rs(pos) * 2 + kk) * 2 + mt) * 4], db);
        }
        wg_commit();
        if (j == 0 && seg > 0) x_refill(sb, seg - 1, X_NST - 1, g, tmX);
        if (j > J0) { wg_wait<1>(); x_refill(sb, seg, j - 1, g, tmX); }
    }
    wg_wait<0>();
    reg_fence<32>(xa);
    if (J1 < X_NST) x_refill(sb, seg, J1 - 1, (int)opaque((uint32_t)g0), tmX);
}
DEVI void x_finish(float* xa, uint32_t sb, int g, int warp) {
    const int lane = tid_now() & 31;
    const uint32_t base = sb + RS_X + (X_SLOTS - 1) * 4096 + (lane >> 4) * 1024 + warp * 256 + (lane & 15) * 16;
    const uint32_t mine = base + g * X_PITCH, other = base + (g ^ 1) * X_PITCH;
    sts128f(mine + 4096, xa + 24); sts128f(mine + 6144, xa + 28);
    nbar_sync(NB_WG + g, 128);
    sts128f(mine, xa + 16); sts128f(mine + 2048, xa + 20);
    nbar_sync(NB_BIG, 256);
    uint32_t p[8];
#pragma unroll
    for (int i = 0; i < 4; i++) {
        const uint4 v = lds128(other + i * 2048);
        p[2 * i]     = pack_bf16(xa[4 * i] + __uint_as_float(v.x), xa[4 * i + 1] + __uint_as_float(v.y));
        p[2 * i + 1] = pack_bf16(xa[4 * i + 2] + __uint_as_float(v.z), xa[4 * i + 3] + __uint_as_float(v.w));
    }
    __syncwarp();
    stsm4(other + 4096, p[0], p[1], p[2], p[3]);
    stsm4(other + 6144, p[4], p[5], p[6], p[7]);
    fence_proxy_async();
    nbar_arrive(NB_XS, 256 + 32);
}
DEVI void x_send(uint32_t sb, int seg, uint32_t rank) {
    nbar_sync(NB_XS, 256 + 32);
    if (seg > 0) mbar_wait(sb + RB_ATT, (seg - 1) & 1);
    const int lane = tid_now() & 31;
    if (lane < 8) {
        const int g = lane >> 2, j = lane & 3;
        bulk_copy_s2c(mapa(sb + (rank == 1 ? RS_K : RS_V) + (j + 1) * 2048 + g * 1024, 0),
                      sb + RS_X + (g ^ 1) * X_PITCH + X_SLOTS * 4096 + j * 1024, 1024, mapa(sb + RB_KV, 0));
    }
    __syncwarp();
}

template <bool XP>
DEVI void mem_pass(float* c0, float* c1, const uint32_t* w, uint32_t sb, int g, int warp, int s) {
    const int lane = tid_now() & 31;
    const uint32_t aB = sb + RS_MEM + (g * 32 + lane) * 16;
    const uint32_t aA0 = sb + RS_WSS + g * (8192 + 4096) + a_frag_off(lane, warp), aA1 = aA0 + 8192 - g * 16384;
    uint32_t a[16], b[2][4], e[4];
    if (XP) ldsm4t(e, aA0 + (RS_WX - RS_WSS) - g * (8192 + 2048));
#pragma unroll
    for (int q = 0; q < 4; q++) ldsm4t(a + 4 * q, ((q & 1) ? aA1 : aA0) + (q >> 1) * 2048);
#pragma unroll
    for (int i = 0; i < 4; i++) { c0[i] = 0.f; c1[i] = 0.f; }
    EV(tid_now() == 0, s, 0);
    if (s > 0) mbar_wait(sb + RB_G, (s - 1) & 1);
    EV(tid_now() == 0, s, 1);
    ldsm4t(b[0], aB + r_tord(0) * 1024);
#pragma unroll
    for (int pos = 0; pos < 16; pos++) {
        if (pos + 1 < 16) {
            if (pos + 1 == R_G1 && s > 0) mbar_wait(sb + RB_G + 8, (s - 1) & 1);
            if (pos + 1 == R_G2 && s > 0) { mbar_wait(sb + RB_G + 16, (s - 1) & 1); EV(tid_now() == 0, s, 2); }
            ldsm4t(b[(pos + 1) & 1], aB + r_tord(pos + 1) * 1024);
        }
        const uint32_t* bb = b[pos & 1];
        const uint32_t* aa = r_pos_ss(pos) ? a : &w[r_rs(pos) * 16];
        mma16816(c0, aa, bb[0], bb[1]);
        mma16816(c1, aa + 4, bb[0], bb[1]);
        mma16816(c0, aa + 8, bb[2], bb[3]);
        mma16816(c1, XP && pos == 0 ? e : aa + 12, bb[2], bb[3]);
        if (r_pos_ss(pos) && pos + 3 < 16) {
#pragma unroll
            for (int q = 0; q < 4; q++) ldsm4t(a + 4 * q, ((q & 1) ? aA1 : aA0) + (r_ss(pos) + 1) * 16384 + (q >> 1) * 2048);
        }
    }
}

DEVI uint32_t k_frag_off(int lane) { return (uint32_t)((((lane >> 3) & 1) * 16 + (lane >> 4) * 8 + (lane & 7)) * 16); }
template <int NQ>
DEVI void s_tile(const uint32_t* qa, uint32_t kaddr, float& s0, float& s1) {
    float c[4] = {0.f, 0.f, 0.f, 0.f}, d[4] = {0.f, 0.f, 0.f, 0.f};
#pragma unroll
    for (int i = 0; i < NQ; i++) {
        uint32_t b[4];
        ldsm4t(b, kaddr + i * 512);
        mma16816(c, qa + 4 * i, b[0], b[1]);
        mma16816(d, qa + 4 * i, b[2], b[3]);
    }
    s0 = c[0] + d[2]; s1 = c[1] + d[3];
}
DEVI uint32_t v_frag_off(int lane) { return (uint32_t)(((lane >> 3) & 1) * 2048 + ((lane >> 4) * 8 + (lane & 7)) * 16); }
DEVI void pv_pair(float (*o)[4], const uint32_t* p, const uint32_t* v) {
#pragma unroll
    for (int n = 0; n < 4; n++) mma16816(o[n], p, v[2 * n], v[2 * n + 1]);
}
DEVI void pv_single(float (*o)[4], const uint32_t* p, const uint32_t* v) {
#pragma unroll
    for (int n = 0; n < 4; n++) mma1688(o[n], p[0], p[1], v[n]);
}
DEVI float softmax10(const float* sc, uint32_t* p) {
    float m = fmaxf(fmaxf(fmaxf(sc[2], sc[3]), fmaxf(sc[4], sc[5])), fmaxf(fmaxf(sc[6], sc[7]), fmaxf(sc[8], sc[9])));
    m = fmaxf(m, fmaxf(sc[0], sc[1]));
    m = fmaxf(m, __shfl_xor_sync(0xffffffffu, m, 1));
    m = fmaxf(m, __shfl_xor_sync(0xffffffffu, m, 2));
    const float nm = -m * SCALE_LOG2E;
    float l = 0.f;
#pragma unroll
    for (int n = 0; n < 5; n++) {
        const float e0 = ex2(fmaf(sc[2 * n], SCALE_LOG2E, nm)), e1 = ex2(fmaf(sc[2 * n + 1], SCALE_LOG2E, nm));
        l += e0 + e1;
        p[2 * n] = pack_bf16(e0, e1); p[2 * n + 1] = __float_as_uint(e0);
    }
    return l;
}
DEVI float inv_sum4(float l) {
    l += __shfl_xor_sync(0xffffffffu, l, 1);
    l += __shfl_xor_sync(0xffffffffu, l, 2);
    return rcp_fast(l);
}
DEVI uint4 pack_o(const float (*o)[4], float inv) {
    return make_uint4(pack_bf16(o[0][0] * inv, o[0][1] * inv), pack_bf16(o[1][0] * inv, o[1][1] * inv),
                      pack_bf16(o[2][0] * inv, o[2][1] * inv), pack_bf16(o[3][0] * inv, o[3][1] * inv));
}

DEVI void ta_scores(float* c, uint32_t sb, int seg, int cw) {
    const int lane = tid_now() & 31, mt = cw >= 3, n = cw - 3 * mt;
    const uint32_t qa = sb + RS_QX + (2 * mt + ((lane >> 3) & 1)) * 2048 + ((lane >> 4) * 8 + (lane & 7)) * 16;
    const uint32_t ka = sb + RS_K + n * 2048 + lane * 16;
    float d[4] = {0.f, 0.f, 0.f, 0.f};
    c[0] = c[1] = c[2] = c[3] = 0.f;
    mbar_wait(sb + RB_QX, seg & 1);
    mbar_wait(sb + (n == 0 ? RB_K : RB_KV), seg & 1);
#pragma unroll
    for (int j = 0; j < 4; j++) {
        uint32_t a0[4], a1[4], b[4];
        ldsm4t(a0, qa + j * 512);
        ldsm4t(b, ka + j * 512);
        ldsm4t(a1, qa + j * 512 + 256);
        mma16816(c, a0, b[0], b[1]);
        mma16816(d, a1, b[2], b[3]);
    }
    const int over = 8 * (n - 1) + 2 * (lane & 3) - 16 * mt - (lane >> 2);
    c[0] = over > 0 ? -INFINITY : c[0] + d[0];
    c[1] = over >= 0 ? -INFINITY : c[1] + d[1];
    c[2] = over > 8 ? -INFINITY : c[2] + d[2];
    c[3] = over >= 8 ? -INFINITY : c[3] + d[3];
}
DEVI void ta_output(uint32_t sb, int seg, int head, int mt, int j) {
    const int lane = tid_now() & 31;
    const uint32_t sa = sb + RS_QX + mt * 1536 + lane * 16;
    float sc[5][4];
#pragma unroll
    for (int n = 0; n < 5; n++) {
        uint4 v = make_uint4(0xFF800000u, 0xFF800000u, 0xFF800000u, 0xFF800000u);
        if (n < 2 || n == 4 || mt) v = lds128(sa + (n == 4 ? 1024 + mt * 1024 : n * 512));
        sc[n][0] = __uint_as_float(v.x); sc[n][1] = __uint_as_float(v.y); sc[n][2] = __uint_as_float(v.z); sc[n][3] = __uint_as_float(v.w);
    }
    fence_proxy_async();
    float m0 = -INFINITY, m1 = -INFINITY;
#pragma unroll
    for (int n = 0; n < 5; n++) { m0 = fmaxf(m0, fmaxf(sc[n][0], sc[n][1])); m1 = fmaxf(m1, fmaxf(sc[n][2], sc[n][3])); }
    m0 = fmaxf(m0, __shfl_xor_sync(0xffffffffu, m0, 1)); m1 = fmaxf(m1, __shfl_xor_sync(0xffffffffu, m1, 1));
    m0 = fmaxf(m0, __shfl_xor_sync(0xffffffffu, m0, 2)); m1 = fmaxf(m1, __shfl_xor_sync(0xffffffffu, m1, 2));
    m0 *= -SCALE_LOG2E; m1 *= -SCALE_LOG2E;
    float l0 = 0.f, l1 = 0.f;
    uint32_t p[10];
#pragma unroll
    for (int n = 0; n < 5; n++) {
        const float e0 = ex2(fmaf(sc[n][0], SCALE_LOG2E, m0)), e1 = ex2(fmaf(sc[n][1], SCALE_LOG2E, m0));
        const float e2 = ex2(fmaf(sc[n][2], SCALE_LOG2E, m1)), e3 = ex2(fmaf(sc[n][3], SCALE_LOG2E, m1));
        l0 += e0 + e1; l1 += e2 + e3;
        p[2 * n] = pack_bf16(e0, e1); p[2 * n + 1] = pack_bf16(e2, e3);
    }
    const float i0 = inv_sum4(l0), i1 = inv_sum4(l1);
    mbar_wait(sb + RB_V, seg & 1);
    mbar_wait(sb + RB_KV, seg & 1);
    const uint32_t vb = sb + RS_V + j * 512;
    float o[4][4];
#pragma unroll
    for (int n = 0; n < 4; n++) { o[n][0] = o[n][1] = o[n][2] = o[n][3] = 0.f; }
    uint32_t v[8];
    ldsm4(v, vb + v_frag_off(lane)); ldsm4(v + 4, vb + v_frag_off(lane) + 256);
    pv_pair(o, p, v);
    SCHED_FENCE();
    ldsm4(v, vb + 4096 + v_frag_off(lane)); ldsm4(v + 4, vb + 4096 + v_frag_off(lane) + 256);
    pv_pair(o, p + 4, v);
    SCHED_FENCE();
    ldsm4(v, vb + 4096 + mt * 4096 + lane * 16);
    pv_single(o, p + 8, v);
    bf16* dst = g_ox + (uint32_t)((seg * 32 + mt * 16 + (lane >> 2)) * HD + head * DH + j * 32 + (lane & 3) * 8);
    asm volatile("st.global.v4.u32 [%0], {%1,%2,%3,%4};" :: "l"(dst), "r"(pack_bf16(o[0][0] * i0, o[0][1] * i0)), "r"(pack_bf16(o[1][0] * i0, o[1][1] * i0)),
                 "r"(pack_bf16(o[2][0] * i0, o[2][1] * i0)), "r"(pack_bf16(o[3][0] * i0, o[3][1] * i0)) : "memory");
    asm volatile("st.global.v4.u32 [%0], {%1,%2,%3,%4};" :: "l"(dst + 8 * HD), "r"(pack_bf16(o[0][2] * i1, o[0][3] * i1)), "r"(pack_bf16(o[1][2] * i1, o[1][3] * i1)),
                 "r"(pack_bf16(o[2][2] * i1, o[2][3] * i1)), "r"(pack_bf16(o[3][2] * i1, o[3][3] * i1)) : "memory");
}

template <bool XP>
DEVI void big_main(const uint32_t* w, const uint32_t sb, const int g, const int warp, const uint32_t rank, const int head,
                   const CUtensorMap* tmX, const bf16* xg, const unsigned E) {
    float xa[32];
    if constexpr (XP) {
        x_stages<0, X_NST>(xa, w, sb, 0, g, tmX);
        x_finish(xa, sb, g, warp);
    } else nbar_sync(NB_BIG, 256);
    for (int s = 0; s < NSEG; s++) {
        {
            float c0[4], c1[4];
            mem_pass<XP>(c0, c1, w, sb, g, warp, s);
            EV(tid_now() == 0 && c0[0] != 1.2345e30f, s, 3);
            const int lane = tid_now() & 31, gq = lane >> 2, t = lane & 3;
            const uint32_t xs = sb + RS_O + warp * 512 + lane * 16;
            sts128f(xs + g * 2048, c1);
            const int dim = g * 64 + warp * 16 + gq + ((t & 1) ? 8 : 0);
            const uint32_t off = (uint32_t)((XP ? (rank == 1 ? RS_K : RS_V) : RS_Q) + dim * 16 + (t & 2) * 4);
            const uint32_t dst = XP ? mapa(sb + off, 0) : sb + off;
            const uint32_t rbar = XP ? mapa(sb + (rank == 1 ? RB_K : RB_V), 0) : 0u;
            if (XP && s > 0) mbar_wait(sb + RB_ATT, (s - 1) & 1);
            nbar_sync(NB_BIG, 256);
            const uint4 v = lds128(xs + (g ^ 1) * 2048);
            const uint32_t p0 = pack_bf16(c0[0] + __uint_as_float(v.x), c0[1] + __uint_as_float(v.y));
            const uint32_t p1 = pack_bf16(c0[2] + __uint_as_float(v.z), c0[3] + __uint_as_float(v.w));
            const uint32_t rcv = __shfl_xor_sync(0xffffffffu, (t & 1) ? p0 : p1, 1);
            const uint32_t lo = (t & 1) ? rcv : p0, hi = (t & 1) ? p1 : rcv;
            if constexpr (XP) st_async64(dst, lo, hi, rbar);
            else if (s < NSEG - 1) {
                asm volatile("st.shared.v2.u32 [%0], {%1,%2};" :: "r"(dst), "r"(lo), "r"(hi) : "memory");
                nbar_arrive(NB_Q, 384);
            }
            EV(tid_now() == 0, s, 4);
        }
        if constexpr (XP) {
            if (s == NSEG - 1) break;
            x_stages<0, X_NA>(xa, w, sb, s + 1, g, tmX);
            EV(tid_now() == 0, s, 5);
            EVCAL(s);
            nbar_sync(NB_WO, 384);
            EV(tid_now() == 0 && lds32(sb + RS_O) != 0x12345678u, s, 6);
            x_stages<X_NA, X_NST>(xa, w, sb, s + 1, g, tmX);
            EV(tid_now() == 0, s, 7);
            x_finish(xa, sb, g, warp);
        } else {
            if (s == 0 && tid_now() == 128) {
                wait_count(&g_cnt_q[0], 64 * E);
                asm volatile("fence.proxy.async;" ::: "memory");
                mbar_expect_tx(sb + RB_QX, 8192);
                bulk_load(sb + RS_QX, g_qx + (size_t)head * 4096, 8192, sb + RB_QX);
            }
            __syncwarp();
            float sc[4];
            ta_scores(sc, sb, s, g * 4 + warp);
            if (tid_now() == 128) {
                if (s > 0) signal_count(&g_prog[(s - 1) >> 2]);
                if (s + 4 < NSEG) l2_prefetch(xg + (size_t)((s + 4) * 32 + head) * DM, 2048);
            }
            if (tid_now() == 160 && (s & 7) == 7 && s + 1 < NSEG) { wait_count(&g_cnt_q[(s + 1) >> 3], 64 * E); asm volatile("fence.proxy.async;" ::: "memory"); }
            __syncwarp();
            EVCAL(s);
            if (s < NSEG - 1) nbar_sync(NB_WO, 384); else nbar_sync(NB_BIG, 256);
            sts128f(sb + RS_QX + tid_now() * 16, sc);
            nbar_sync(NB_BIG, 256);
            EV(tid_now() == 0 && lds32(sb + RS_O) != 0x12345678u, s, 6);
            ta_output(sb, s, head, g, warp);
            nbar_sync(NB_BIG, 256);
            EV(tid_now() == 0 && lds32(sb + RS_O) != 0x12345678u, s, 7);
            if (tid_now() == 160 && s + 1 < NSEG) {
                mbar_expect_tx(sb + RB_KV, 16384);
                mbar_arrive_remote(mapa(sb + RB_ATT, 1));
                mbar_arrive_remote(mapa(sb + RB_ATT, 2));
                mbar_expect_tx(sb + RB_QX, 8192);
                bulk_load(sb + RS_QX, g_qx + ((size_t)(s + 1) * NH + head) * 4096, 8192, sb + RB_QX);
            }
            __syncwarp();
        }
    }
    if constexpr (!XP) { if (tid_now() == 0) signal_count(&g_prog[(NSEG - 1) >> 2]); }
}

template <int T, int H>
DEVI void wo_half(float* acc) {
    constexpr uint32_t dWo = cdesc(T < 5 ? RS_WO + T * 16384 : RS_WO5, 16), dO = cdesc(RS_O, 128);
    if (H == 0) wg_fence();
#pragma unroll
    for (int kk = 4 * H; kk < 4 * H + 4; kk++) {
        if (kk == 0) { if (T < 3) wgmma_n8_ss_first<0>(acc, dWo, dO); else wgmma_n8_ss<0, 0>(acc, dWo, dO); }
        else wgmma_n8_ss<0, 1>(acc, dWo + kk * 128, dO + kk * 16);
    }
    wg_commit();
}
DEVI void red3(uint8_t* p, float a, float b, float c) {
    asm volatile("red.relaxed.gpu.global.add.v4.f32 [%0], {%1,%2,%3,%4};" :: "l"(p), "f"(a), "f"(b), "f"(c), "f"(1.0f) : "memory");
}
constexpr int ACC_CH = 3 * 16 * 1024;
DEVI uint8_t* acc_ptr(int s, uint32_t rank, int warp) {
    const int lane = tid_now() & 31;
    return g_acc + (s & 3) * 128 + ((rank * 4 + warp) * 4 + (lane & 3)) * 1024 + (lane >> 2) * 16;
}
template <bool Q>
DEVI void wo_phase(uint32_t sb, int s, uint8_t* p) {
    float a0[4], a1[4], a2[4];
    wo_half<0, 0>(a0); wo_half<0, 1>(a0); wo_half<1, 0>(a1);
    wg_wait<1>(); reg_fence<4>(a0);
    red3(p, a0[0], a0[1], a0[2]);
    SCHED_FENCE();
    EV(tid_now() == 256, s, 11);
    wo_half<1, 1>(a1); wo_half<2, 0>(a2);
    wg_wait<1>(); reg_fence<4>(a1);
    red3(p + ACC_CH, a1[0], a1[1], a0[3]);
    SCHED_FENCE();
    wo_half<2, 1>(a2); wo_half<3, 0>(a0);
    wg_wait<1>(); reg_fence<4>(a2);
    red3(p + 2 * ACC_CH, a1[2], a1[3], a2[0]);
    red3(p + 3 * ACC_CH, a2[2], a2[3], a2[1]);
    SCHED_FENCE();
    wo_half<3, 1>(a0); wo_half<4, 0>(a1);
    wg_wait<1>(); reg_fence<4>(a0);
    red3(p + 4 * ACC_CH, a0[0], a0[1], a0[2]);
    SCHED_FENCE();
    wo_half<4, 1>(a1);
    if (Q) {
        wo_half<5, 0>(a2);
        wg_wait<1>(); reg_fence<4>(a1);
        red3(p + 5 * ACC_CH, a1[0], a1[1], a0[3]);
        SCHED_FENCE();
        wo_half<5, 1>(a2);
        wg_wait<0>(); reg_fence<4>(a2);
        red3(p + 6 * ACC_CH, a1[2], a1[3], a2[0]);
        red3(p + 7 * ACC_CH, a2[2], a2[3], a2[1]);
    } else {
        nbar_arrive(NB_WO, 384);
        wg_wait<0>(); reg_fence<4>(a1);
        red3(p + 5 * ACC_CH, a1[0], a1[1], a0[3]);
        red3(p + 6 * ACC_CH, a1[2], a1[3], 0.f);
    }
}
template <bool Q>
DEVI void stage_chunk(uint32_t sb0, int s, uint32_t rank, int warp, int second, uint32_t gate) {
    const uint32_t sb = opaque(sb0);
    const int lane = tid_now() & 31, c = warp + 4 * second;
    const uint8_t* src = g_acc + (s & 3) * 128 + c * ACC_CH + (rank * 4 + (lane >> 3)) * 4096 + (lane & 7) * 16;
    float v[4][4];
    spin_until(gate);
    EV(lane == 0, s, 16 + c);
    int n = 0;
    while (true) {
#pragma unroll
        for (int j = 0; j < 4; j++) ld_rlx4f(v[j], src + j * 1024);
        if (v[0][3] == 32.f && v[1][3] == 32.f && v[2][3] == 32.f && v[3][3] == 32.f) break;
        if (++n > SPIN_LIMIT) TRAP(0x20000000u | (s << 8) | c);
    }
    __syncwarp();
    EV(lane == 0, s, 24 + c);
    const uint32_t f0 = pack_bf16(v[0][0], v[1][0]), f1 = pack_bf16(v[2][0], v[3][0]), f2 = pack_bf16(v[0][1], v[1][1]), f3 = pack_bf16(v[2][1], v[3][1]);
    const uint32_t h0 = pack_bf16(v[0][2], v[1][2]), h1 = pack_bf16(v[2][2], v[3][2]);
    const int tile0 = Q ? 0 : (rank == 1 ? 6 : 11);
    const uint32_t col = sb + RS_MEM + (tile0 + 3 * second) * 1024 + ((lane >> 3) * 16 + (lane & 7)) * 16;
    const uint32_t df = col + ((warp + 1) >> 1) * 1024 + (warp >> 1) * 128;
    const uint32_t dh = col + (warp >> 1) * 2048 + (warp < 2 ? 128 : 0) + (warp & 1) * 8;
    const int grp = Q ? (c < 4 ? 0 : (c >> 1) - 1) : (c < 6 ? c >> 1 : 2);
    const uint32_t bar = sb + RB_G + 8 * grp;
    const bool half = Q || c != 6;
#pragma unroll
    for (int d = 1; d < 3; d++) {
        const uint32_t r = Q ? d : (d == 1 ? 0 : 3 - rank);
        const uint32_t rb = mapa(bar, r);
        st_async128(mapa(df, r), f0, f1, f2, f3, rb);
        if (half) st_async64(mapa(dh, r), h0, h1, rb);
    }
    sts128(df, make_uint4(f0, f1, f2, f3));
    if (half) asm volatile("st.shared.v2.u32 [%0], {%1,%2};" :: "r"(dh), "r"(h0), "r"(h1) : "memory");
    __syncwarp();
    if (lane == 0) {
        const bool first = Q ? (c == 0 || c == 4 || c == 6) : (c == 0 || c == 2 || c == 4);
        const uint32_t bytes = Q ? (grp == 2 ? 4096u : 3072u) : (grp == 0 ? 4608u : (grp == 1 ? 3072u : 3584u));
        if (first) mbar_expect_tx(bar, bytes); else mbar_arrive(bar);
    }
}
DEVI void acc_clear(int slot, int idx) {
    const int lane = tid_now() & 31;
    uint8_t* p = g_acc + slot * 128 + (idx * 6 + (lane >> 3)) * 1024 + (lane & 7) * 16;
    st_rlx4(p, 0u, 0u, 0u, 0u);
    if (lane < 16) st_rlx4(p + 4096, 0u, 0u, 0u, 0u);
}

DEVI void load_weights(uint32_t sb, const CUtensorMap* tmW, const CUtensorMap* tmWo, int head, uint32_t rank) {
    const uint32_t bW = sb + RB_W, bSF = sb + RB_SF, bSE = sb + RB_SE;
    const int ntile = rank == 0 ? 6 : 5, tile0 = rank == 0 ? 0 : (rank == 1 ? 6 : 11);
    mbar_expect_tx(bW, R_NSS * 16384 + ntile * 16384);
    if (rank == 0) tma_load_wo(sb + RS_WO5, tmWo, 5 * 64, head * 4, bW);
    for (int pos = 0; pos < 16; pos++) {
        const int k = (int)((R_TORD_PACK >> (4 * pos)) & 15ull) * 64;
        if (r_pos_ss(pos)) {
            const uint32_t dst = sb + RS_WSS + (pos / 3) * 16384;
            tma_load_2d(dst, tmW, head * DH, k, bW);
            tma_load_2d(dst + 8192, tmW, head * DH + 64, k, bW);
        } else {
            const int rd = pos - pos / 3, slot = rd % 5;
            if (rd >= 5) mbar_wait(bSE + 8 * slot, ((rd / 5) - 1) & 1);
            mbar_expect_tx(bSF + 8 * slot, 16384);
            const uint32_t dst = sb + RS_WO + slot * 16384;
            tma_load_2d(dst, tmW, head * DH, k, bSF + 8 * slot);
            tma_load_2d(dst + 8192, tmW, head * DH + 64, k, bSF + 8 * slot);
        }
    }
    for (int slot = 0; slot < 5; slot++) {
        const int last = slot + 10 < R_NRS ? slot + 10 : slot + 5;
        mbar_wait(bSE + 8 * slot, (last / 5) & 1);
        tma_load_wo(sb + RS_WO + slot * 16384, tmWo, (tile0 + slot) * 64, head * 4, bW);
    }
}
template <bool XP>
DEVI void big_prologue(uint32_t* w, uint32_t sb, int g, int warp, const bf16* __restrict__ mem0) {
    const int tid = tid_now(), lane = tid & 31;
#pragma unroll 1
    for (int j = 0; j < 4; j++) {
        const int c = tid + j * 256;
        const uint4 v = *(const uint4*)(mem0 + (c & 7) * DM + (c >> 3) * 8);
        const uint32_t d = sb + RS_MEM + (c >> 3) * 128 + (c & 7) * 2;
        const uint32_t u[4] = {v.x, v.y, v.z, v.w};
#pragma unroll
        for (int e = 0; e < 4; e++) {
            asm volatile("st.shared.u16 [%0], %1;" :: "r"(d + e * 32), "h"((uint16_t)(u[e] & 0xFFFFu)) : "memory");
            asm volatile("st.shared.u16 [%0], %1;" :: "r"(d + e * 32 + 16), "h"((uint16_t)(u[e] >> 16)) : "memory");
        }
    }
    const uint32_t a0 = sb + RS_WO + g * (8192 + 4096) + a_frag_off(lane, warp), a1 = a0 + 8192 - g * 16384;
#pragma unroll
    for (int rd = 0; rd < R_NRS; rd++) {
        const int slot = rd % 5;
        mbar_wait(sb + RB_SF + 8 * slot, (rd / 5) & 1);
#pragma unroll
        for (int q = 0; q < 4; q++) {
            if (XP && rd == 0 && q == 3) {
                sts128(sb + RS_WX + g * 2048 + (tid & 127) * 16, lds128(sb + RS_WO + 8192 - g * 4096 + 2048 + (tid & 127) * 16));
                fence_proxy_async();
                nbar_sync(NB_WG + g, 128);
            } else ldsm4t(&w[rd * 16 + q * 4], ((q & 1) ? a1 : a0) + slot * 16384 + (q >> 1) * 2048);
        }
        mbar_arrive(sb + RB_SE + 8 * slot);
    }
    mbar_wait(sb + RB_W, 0);
}

__global__ void __cluster_dims__(3, 1, 1) __launch_bounds__(384, 1)
k_rec(const __grid_constant__ CUtensorMap tmWq, const __grid_constant__ CUtensorMap tmWk, const __grid_constant__ CUtensorMap tmWv,
      const __grid_constant__ CUtensorMap tmWo, const __grid_constant__ CUtensorMap tmX, const bf16* __restrict__ mem0, const bf16* __restrict__ xg,
      int hq0, int hqw, int hk0, int hkw) {
    extern __shared__ __align__(1024) uint8_t smem_raw[];
    const uint32_t sb = smem_u32(smem_raw);
    if ((sb & 0x3FFFFu) != SB0) __trap();
    const int tid = threadIdx.x;
    const int wg = __shfl_sync(0xffffffffu, tid >> 7, 0), warp = __shfl_sync(0xffffffffu, (tid >> 5) & 3, 0);
    uint32_t rank; asm("mov.u32 %0, %%cluster_ctarank;" : "=r"(rank));
    const int head = blockIdx.x / 3;
    if (tid == 0) {
        mbar_init(sb + RB_G, rank == 0 ? 4 : 2);
        mbar_init(sb + RB_G + 8, 2);
        mbar_init(sb + RB_G + 16, rank == 0 ? 2 : 3);
        mbar_init(sb + RB_K, 1); mbar_init(sb + RB_V, 1); mbar_init(sb + RB_KV, 1); mbar_init(sb + RB_QX, 1);
        mbar_init(sb + RB_O, 1); mbar_init(sb + RB_ATT, 1); mbar_init(sb + RB_W, 1);
        for (int i = 0; i < 5; i++) { mbar_init(sb + RB_SF + 8 * i, 1); mbar_init(sb + RB_SE + 8 * i, 256); }
        for (int i = 0; i < 2 * X_SLOTS; i++) mbar_init(sb + RB_XF + 8 * i, 1);
        fence_mbar_init();
        if (rank == 0) mbar_expect_tx(sb + RB_KV, 16384);
        atomicAdd(&g_resident, 1u);
    }
    __syncthreads();
    cluster_sync();

    if (wg < 2) {
        reg_inc<REG_KB>();
        if (rank != 0) {
            uint32_t w[R_NRS * 16];
            if ((tid & 127) == 0) for (int j = 0; j < X_SLOTS; j++) x_load(sb, 0, j, wg, &tmX);
            __syncwarp();
            big_prologue<true>(w, sb, wg, warp, mem0);
            big_main<true>(w, sb, wg, warp, rank, head, &tmX, xg, 0u);
        } else {
            reg_dec<REG_QB>();
            uint32_t w[R_NRS * 16];
            big_prologue<false>(w, sb, wg, warp, mem0);
            big_main<false>(w, sb, wg, warp, rank, head, &tmX, xg, *(volatile unsigned*)&g_epoch + 1);
        }
    } else if (rank == 0) {
        reg_dec<504 - 2 * REG_KB>();
        if (tid == 256) {
            for (int sg = 0; sg < 4; sg++) l2_prefetch(xg + (size_t)(sg * 32 + head) * DM, 2048);
            load_weights(sb, &tmWq, &tmWo, head, rank);
            wait_count(&g_zero, (*(volatile unsigned*)&g_epoch + 1) * 64u);
        }
        __syncwarp();
        mbar_wait(sb + RB_W, 0);
        reg_inc<504 - 2 * REG_QB>();
        for (int s = (int)opaque(0u); s < NSEG - 1; s++) {
            if (tid_now() == 256) { mbar_expect_tx(sb + RB_K, 2048); mbar_expect_tx(sb + RB_V, 2048); }
            __syncwarp();
            {
                const int lane = tid_now() & 31;
                const uint32_t ka = sb + RS_K + k_frag_off(lane), va = sb + RS_V + warp * 512;
                uint32_t qa[16], vx[16];
                float sc[10];
                mbar_wait(sb + RB_KV, s & 1);
                {
                    uint32_t kx[16];
#pragma unroll
                    for (int q = 0; q < 4; q++) ldsm4t(kx + 4 * q, ka + (1 + warp) * 2048 + q * 512);
                    nbar_sync(NB_Q, 384);
                    EV(tid_now() == 256 && lds32(sb + RS_Q) != 0x12345678u, s, 8);
#pragma unroll
                    for (int q = 0; q < 4; q++) ldsm4t(qa + 4 * q, sb + RS_Q + q * 512 + lane * 16);
                    float c[4] = {0.f, 0.f, 0.f, 0.f}, d[4] = {0.f, 0.f, 0.f, 0.f};
#pragma unroll
                    for (int q = 0; q < 4; q++) { mma16816(c, qa + 4 * q, kx[4 * q], kx[4 * q + 1]); mma16816(d, qa + 4 * q, kx[4 * q + 2], kx[4 * q + 3]); }
                    asm volatile("st.shared.v2.f32 [%0], {%1,%2};" :: "r"(sb + RS_SX + warp * 256 + lane * 8), "f"(c[0] + d[2]), "f"(c[1] + d[3]) : "memory");
                }
                nbar_sync(NB_AUX, 128);
#pragma unroll
                for (int n = 0; n < 4; n++) { const float2 v = lds64f(sb + RS_SX + n * 256 + lane * 8); sc[2 + 2 * n] = v.x; sc[3 + 2 * n] = v.y; }
                const uint32_t dst = sb + RS_O + warp * 512 + (lane & 3) * 128 + (lane >> 2) * 16;
                mbar_wait(sb + RB_K, s & 1);
                EV(tid_now() == 256, s, 9);
                s_tile<4>(qa, ka, sc[0], sc[1]);
#pragma unroll
                for (int q = 0; q < 4; q++) ldsm4(vx + 4 * q, va + 2048 + (q >> 1) * 4096 + (q & 1) * 256 + v_frag_off(lane));
                mbar_wait(sb + RB_V, s & 1);
                uint32_t vm[4], p[10];
                ldsm4(vm, va + lane * 16);
                const float l = softmax10(sc, p);
                float o[4][4];
#pragma unroll
                for (int n = 0; n < 4; n++) { o[n][0] = o[n][1] = o[n][2] = o[n][3] = 0.f; }
                pv_single(o, p, vm);
                pv_pair(o, p + 2, vx);
                pv_pair(o, p + 6, vx + 8);
                const uint4 u = pack_o(o, inv_sum4(l));
                st_async128(mapa(dst, 1), u.x, u.y, u.z, u.w, mapa(sb + RB_O, 1));
                st_async128(mapa(dst, 2), u.x, u.y, u.z, u.w, mapa(sb + RB_O, 2));
                sts128(dst, u);
                fence_proxy_async();
                nbar_sync(NB_AUX, 128);
                nbar_arrive(NB_WO, 384);
            }
            EV(tid_now() == 256, s, 10);
            wo_phase<true>(sb, s, acc_ptr(s, 0, warp));
            SCHED_FENCE();
            const uint32_t t_o = clk32();
            EV(tid_now() == 256, s, 12);
            stage_chunk<true>(sb, s, 0, warp, 0, t_o + hq0 + warp * hqw);
            EV(tid_now() == 256 + 96, s, 13);
            stage_chunk<true>(sb, s, 0, warp, 1, t_o + hq0 + (warp + 4) * hqw);
            EV(tid_now() == 256 + 96, s, 14);
        }
        if (tid_now() == 256) { mbar_expect_tx(sb + RB_K, 2048); mbar_expect_tx(sb + RB_V, 2048); }
    } else {
        reg_dec<504 - 2 * REG_KB>();
        const int idx = 2 * head + (int)rank - 1;
        if (warp == 3) {
            acc_clear(0, idx); acc_clear(1, idx);
            __threadfence();
            __syncwarp();
            if (tid == 256 + 96) atomicAdd(&g_zero, 1u);
        }
        if (tid == 256) {
            load_weights(sb, rank == 1 ? &tmWk : &tmWv, &tmWo, head, rank);
            wait_count(&g_zero, (*(volatile unsigned*)&g_epoch + 1) * 64u);
        }
        __syncwarp();
        mbar_wait(sb + RB_W, 0);
        nbar_sync(NB_AUX, 128);
        if (warp == 3) x_send(sb, 0, rank);
        for (int s = 0; s < NSEG - 1; s++) {
            if (tid_now() == 256) mbar_expect_tx(sb + RB_O, 2048);
            __syncwarp();
            uint8_t* const pacc = acc_ptr(s, rank, warp);
            mbar_wait(sb + RB_O, s & 1);
            fence_proxy_async();
            EV(tid_now() == 256, s, 10);
            wo_phase<false>(sb, s, pacc);
            SCHED_FENCE();
            const uint32_t t_o = clk32();
            EV(tid_now() == 256, s, 12);
            stage_chunk<false>(sb, s, rank, warp, 0, t_o + hk0 + warp * hkw);
            EV(tid_now() == 256 + 32, s, 13);
            if (warp < 3) stage_chunk<false>(sb, s, rank, warp, 1, t_o + hk0 + (warp + 4) * hkw);
            else {
                x_send(sb, s + 1, rank);
                if (s + 2 < NSEG - 1) { acc_clear((s + 2) & 3, idx); __threadfence(); }
            }
            EV(tid_now() == 256 + 64, s, 14);
        }
    }
    __syncthreads();
    cluster_sync();
}

__global__ void k_gate() {
    if (threadIdx.x == 0) {
        int n = 0;
        while (*(volatile unsigned*)&g_resident < 96u) { __nanosleep(200); if (++n > (1 << 22)) __trap(); }
        g_resident = 0;
    }
}

typedef CUresult (*EncodeFn)(CUtensorMap*, CUtensorMapDataType, cuuint32_t, void*, const cuuint64_t*, const cuuint64_t*,
                             const cuuint32_t*, const cuuint32_t*, CUtensorMapInterleave, CUtensorMapSwizzle,
                             CUtensorMapL2promotion, CUtensorMapFloatOOBfill);

static CUtensorMap make_map(EncodeFn fn, const void* ptr, uint64_t inner, uint64_t outer, uint32_t box_inner, uint32_t box_outer) {
    CUtensorMap m;
    cuuint64_t dims[2] = {inner, outer};
    cuuint64_t strides[1] = {inner * 2};
    cuuint32_t box[2] = {box_inner, box_outer};
    cuuint32_t es[2] = {1, 1};
    fn(&m, CU_TENSOR_MAP_DATA_TYPE_BFLOAT16, 2, const_cast<void*>(ptr), dims, strides, box, es,
       CU_TENSOR_MAP_INTERLEAVE_NONE, CU_TENSOR_MAP_SWIZZLE_128B, CU_TENSOR_MAP_L2_PROMOTION_L2_256B, CU_TENSOR_MAP_FLOAT_OOB_FILL_NONE);
    return m;
}

static CUtensorMap make_wo_map(EncodeFn fn, const void* ptr, uint32_t ngrp) {
    CUtensorMap m;
    cuuint64_t dims[5] = {DM, 2, 4, 4, HD / 32};
    cuuint64_t strides[4] = {DM * 2, 8 * DM * 2, 2 * DM * 2, 32 * DM * 2};
    cuuint32_t box[5] = {64, 2, 4, 4, ngrp};
    cuuint32_t es[5] = {1, 1, 1, 1, 1};
    fn(&m, CU_TENSOR_MAP_DATA_TYPE_BFLOAT16, 5, const_cast<void*>(ptr), dims, strides, box, es,
       CU_TENSOR_MAP_INTERLEAVE_NONE, CU_TENSOR_MAP_SWIZZLE_128B, CU_TENSOR_MAP_L2_PROMOTION_L2_256B, CU_TENSOR_MAP_FLOAT_OOB_FILL_NONE);
    return m;
}

struct Maps {
    PMaps post;
    CUtensorMap wq16, wk16, wv16, wo128, x32;
};

extern "C" void kernel_launch(void* const* d_in, const int* in_sizes, int n_in, void* d_out, int out_size) {
    const bf16* A_x   = (const bf16*)d_in[0];
    const bf16* A_mem = (const bf16*)d_in[1];
    const bf16* A_Wq  = (const bf16*)d_in[2];
    const bf16* A_Wk  = (const bf16*)d_in[3];
    const bf16* A_Wv  = (const bf16*)d_in[4];
    const bf16* A_Wo  = (const bf16*)d_in[5];
    const bf16* B_x   = (const bf16*)d_in[7];
    const bf16* B_w   = (const bf16*)d_in[8];
    const bf16* B_wo  = (const bf16*)d_in[9];

    static EncodeFn fn = nullptr;
    static Maps mp;
    static const void* cached[10];
    const void* cur[10] = {A_x, A_mem, A_Wq, A_Wk, A_Wv, A_Wo, B_x, B_w, B_wo, d_out};
    bool same = fn != nullptr;
    for (int i = 0; i < 10 && same; i++) same = cached[i] == cur[i];
    if (!same) {
        if (!fn) {
            void* p = nullptr; cudaDriverEntryPointQueryResult qr;
            cudaGetDriverEntryPoint("cuTensorMapEncodeTiled", &p, cudaEnableDefault, &qr);
            fn = (EncodeFn)p;
            cudaFuncSetAttribute(k_post, cudaFuncAttributeMaxDynamicSharedMemorySize, P_SMEM);
            cudaFuncSetAttribute(k_rec, cudaFuncAttributeMaxDynamicSharedMemorySize, R_SMEM);
            cudaFuncAttributes fa; cudaFuncGetAttributes(&fa, k_gate);
        }
        void *p_ox, *p_bqkv, *p_bo;
        cudaGetSymbolAddress(&p_ox, g_ox); cudaGetSymbolAddress(&p_bqkv, g_bqkv); cudaGetSymbolAddress(&p_bo, g_bo);
        mp.post.wq   = make_map(fn, A_Wq, HD, DM, 64, 64);
        mp.post.wo   = make_wo_map(fn, A_Wo, 2);
        mp.post.bw   = make_map(fn, B_w, 3 * DM, DM, 64, 64);
        mp.post.bwo  = make_map(fn, B_wo, DM, DM, 64, 64);
        mp.post.x    = make_map(fn, A_x, DM, S_TOK, 64, 256);
        mp.post.bx   = make_map(fn, B_x, DM, S_TOK, 64, 256);
        mp.post.bo   = make_map(fn, p_bo, DM, S_TOK, 64, 256);
        mp.post.ox   = make_map(fn, p_ox, HD, S_TOK, 64, 128);
        mp.post.cb   = make_map(fn, p_bqkv, 3 * DM, S_TOK, 64, 64);
        mp.post.cout = make_map(fn, d_out, 2 * DM, S_TOK, 64, 64);
        {
            cuuint64_t dims[4] = {DM, 3, 2, S_TOK / 2};
            cuuint64_t strides[3] = {DM * 2, 3 * DM * 2, 3 * DM * 4};
            cuuint32_t box[4] = {64, 3, 1, 40};
            cuuint32_t es[4] = {1, 1, 1, 1};
            fn(&mp.post.b40, CU_TENSOR_MAP_DATA_TYPE_BFLOAT16, 4, p_bqkv, dims, strides, box, es,
               CU_TENSOR_MAP_INTERLEAVE_NONE, CU_TENSOR_MAP_SWIZZLE_128B, CU_TENSOR_MAP_L2_PROMOTION_L2_256B, CU_TENSOR_MAP_FLOAT_OOB_FILL_NONE);
        }
        mp.wq16 = make_map(fn, A_Wq, HD, DM, 64, 64);
        mp.wk16 = make_map(fn, A_Wk, HD, DM, 64, 64);
        mp.wv16 = make_map(fn, A_Wv, HD, DM, 64, 64);
        mp.wo128 = make_wo_map(fn, A_Wo, 4);
        {
            cuuint64_t dims[3] = {64, S_TOK, DM / 64};
            cuuint64_t strides[2] = {DM * 2, 128};
            cuuint32_t box[3] = {32, 32, 2};
            cuuint32_t es[3] = {1, 1, 1};
            fn(&mp.x32, CU_TENSOR_MAP_DATA_TYPE_BFLOAT16, 3, const_cast<bf16*>(A_x), dims, strides, box, es,
               CU_TENSOR_MAP_INTERLEAVE_NONE, CU_TENSOR_MAP_SWIZZLE_64B, CU_TENSOR_MAP_L2_PROMOTION_L2_128B, CU_TENSOR_MAP_FLOAT_OOB_FILL_NONE);
        }
        for (int i = 0; i < 10; i++) cached[i] = cur[i];
    }

    cudaStream_t st = cudaStreamPerThread;
    static cudaStream_t side = nullptr;
    static cudaEvent_t evFork, evSide;
    if (!side) {
        cudaStreamCreateWithFlags(&side, cudaStreamNonBlocking);
        cudaEventCreateWithFlags(&evFork, cudaEventDisableTiming);
        cudaEventCreateWithFlags(&evSide, cudaEventDisableTiming);
    }
    cudaEventRecord(evFork, st);
    int hq0 = 0, hqw = 100, hk0 = 0, hkw = 100;
    k_rec<<<96, 384, R_SMEM, st>>>(mp.wq16, mp.wk16, mp.wv16, mp.wo128, mp.x32, A_mem, A_x, hq0, hqw, hk0, hkw);
    cudaStreamWaitEvent(side, evFork, 0);
    k_gate<<<1, 32, 0, side>>>();
    k_post<<<132, 384, P_SMEM, side>>>(mp.post);
    cudaEventRecord(evSide, side);
    cudaStreamWaitEvent(st, evSide, 0);
}
```

```cpp
#include <cuda_runtime.h>
#include <cuda_bf16.h>
#include <cuda.h>
#include <stdint.h>

typedef __nv_bfloat16 bf16;

constexpr int S_TOK = 2048;
constexpr int DM    = 1024;
constexpr int NH    = 32;
constexpr int DH    = 128;
constexpr int NSEG  = 64;
constexpr int HD    = NH * DH;

__device__ __align__(1024) bf16 g_qx[NSEG * NH * 4 * DH * 8];
__device__ __align__(1024) bf16 g_ox[S_TOK * HD];
__device__ __align__(1024) bf16 g_bqkv[S_TOK * 3 * DM];
__device__ __align__(1024) bf16 g_bo[S_TOK * DM];
__device__ __align__(1024) uint8_t g_acc[384 * 1024];

#define EV(cond, s, k) do {} while (0)
#define EVCAL(s) do {} while (0)

__device__ unsigned g_epoch, g_qctr, g_done, g_zero;
__device__ unsigned g_cnt_b1[8], g_cnt_b2[8], g_cnt_q[8], g_prog[16], g_cnt_sk[32];
__device__ __align__(1024) float g_skp[2 * 8 * 4 * 2 * 128 * 64];
#define TLOG(i, k, v) do {} while (0)
__device__ unsigned g_resident;

#define DEVI __device__ __forceinline__

DEVI uint32_t opaque(uint32_t v) { uint32_t r; asm volatile("mov.u32 %0, %1;" : "=r"(r) : "r"(v)); return r; }
DEVI uint32_t smem_u32(const void* p) { return (uint32_t)__cvta_generic_to_shared(p); }

#define TRAP(code) __trap()
constexpr int SPIN_LIMIT = 1 << 22;
#define MBAR_HINT_NS 20000u
constexpr int SPIN_LIMIT_MBAR = 1 << 17;

DEVI void mbar_init(uint32_t bar, uint32_t cnt) { asm volatile("mbarrier.init.shared::cta.b64 [%0], %1;" :: "r"(bar), "r"(cnt)); }
DEVI void mbar_expect_tx(uint32_t bar, uint32_t bytes) {
    asm volatile("mbarrier.arrive.expect_tx.shared::cta.b64 _, [%0], %1;" :: "r"(bar), "r"(bytes) : "memory");
}
DEVI void mbar_arrive(uint32_t bar) { asm volatile("mbarrier.arrive.shared::cta.b64 _, [%0];" :: "r"(bar) : "memory"); }
DEVI bool mbar_try(uint32_t bar, uint32_t parity) {
    uint32_t ok;
    asm volatile("{.reg .pred p; mbarrier.try_wait.parity.shared::cta.b64 p, [%1], %2; selp.u32 %0, 1, 0, p;}"
                 : "=r"(ok) : "r"(bar), "r"(parity) : "memory");
    return ok;
}
DEVI bool mbar_try_cluster(uint32_t bar, uint32_t parity) {
    uint32_t ok;
    asm volatile("{.reg .pred p; mbarrier.try_wait.parity.acquire.cluster.shared::cta.b64 p, [%1], %2; selp.u32 %0, 1, 0, p;}"
                 : "=r"(ok) : "r"(bar), "r"(parity) : "memory");
    return ok;
}
DEVI bool mbar_try_hint(uint32_t bar, uint32_t parity) {
    uint32_t ok;
    asm volatile("{.reg .pred p; mbarrier.try_wait.parity.shared::cta.b64 p, [%1], %2, %3; selp.u32 %0, 1, 0, p;}"
                 : "=r"(ok) : "r"(bar), "r"(parity), "r"(MBAR_HINT_NS) : "memory");
    return ok;
}
DEVI void mbar_wait(uint32_t bar, uint32_t parity) {
    int n = 0;
    while (!mbar_try(bar, parity)) { if (++n > SPIN_LIMIT) TRAP(bar | (parity << 31)); }
}
DEVI void mbar_wait_sleepy(uint32_t bar, uint32_t parity) {
    int n = 0;
    while (!mbar_try_hint(bar, parity)) { if (++n > SPIN_LIMIT_MBAR) __trap(); }
}
DEVI void mbar_wait_cluster(uint32_t bar, uint32_t parity) {
    int n = 0;
    while (!mbar_try_cluster(bar, parity)) { if (++n > SPIN_LIMIT) __trap(); }
}
DEVI void mbar_spin(uint32_t bar, uint32_t parity) {
    uint32_t ok; int n = 0;
    do {
        asm volatile("{.reg .pred p; mbarrier.test_wait.parity.shared::cta.b64 p, [%1], %2; selp.u32 %0, 1, 0, p;}"
                     : "=r"(ok) : "r"(bar), "r"(parity) : "memory");
        if (++n > SPIN_LIMIT) __trap();
    } while (!ok);
}
DEVI void fence_mbar_init() { asm volatile("fence.mbarrier_init.release.cluster;" ::: "memory"); }
DEVI void fence_proxy_async() { asm volatile("fence.proxy.async.shared::cta;" ::: "memory"); }
DEVI void cluster_sync() {
    asm volatile("barrier.cluster.arrive.release.aligned;\n barrier.cluster.wait.acquire.aligned;" ::: "memory");
}
DEVI void nbar_sync(int id, int n) { asm volatile("bar.sync %0, %1;" :: "r"(id), "r"(n) : "memory"); }
DEVI void nbar_arrive(int id, int n) { asm volatile("bar.arrive %0, %1;" :: "r"(id), "r"(n) : "memory"); }

DEVI void tma_load_2d(uint32_t dst, const CUtensorMap* map, int x, int y, uint32_t bar) {
    asm volatile("cp.async.bulk.tensor.2d.shared::cluster.global.mbarrier::complete_tx::bytes [%0], [%1, {%3, %4}], [%2];"
                 :: "r"(dst), "l"(map), "r"(bar), "r"(x), "r"(y) : "memory");
}
DEVI void tma_load_3d(uint32_t dst, const CUtensorMap* map, int x, int y, int z, uint32_t bar) {
    asm volatile("cp.async.bulk.tensor.3d.shared::cluster.global.mbarrier::complete_tx::bytes [%0], [%1, {%3, %4, %5}], [%2];"
                 :: "r"(dst), "l"(map), "r"(bar), "r"(x), "r"(y), "r"(z) : "memory");
}
DEVI void tma_load_wo(uint32_t dst, const CUtensorMap* map, int col, int k32, uint32_t bar) {
    asm volatile("cp.async.bulk.tensor.5d.shared::cluster.global.mbarrier::complete_tx::bytes [%0], [%1, {%3, %5, %5, %5, %4}], [%2];"
                 :: "r"(dst), "l"(map), "r"(bar), "r"(col), "r"(k32), "r"(0) : "memory");
}
DEVI void tma_store_2d(const CUtensorMap* map, uint32_t src, int x, int y) {
    asm volatile("cp.async.bulk.tensor.2d.global.shared::cta.bulk_group [%0, {%2, %3}], [%1];"
                 :: "l"(map), "r"(src), "r"(x), "r"(y) : "memory");
}
DEVI void bulk_load(uint32_t dst, const void* src, uint32_t bytes, uint32_t bar) {
    asm volatile("cp.async.bulk.shared::cluster.global.mbarrier::complete_tx::bytes [%0], [%1], %2, [%3];"
                 :: "r"(dst), "l"(src), "r"(bytes), "r"(bar) : "memory");
}
DEVI void tma_load_2d_mc(uint32_t dst, const CUtensorMap* map, int x, int y, uint32_t bar, uint16_t mask) {
    asm volatile("cp.async.bulk.tensor.2d.shared::cluster.global.mbarrier::complete_tx::bytes.multicast::cluster [%0], [%1, {%3, %4}], [%2], %5;"
                 :: "r"(dst), "l"(map), "r"(bar), "r"(x), "r"(y), "h"(mask) : "memory");
}
DEVI void bulk_copy_s2c(uint32_t dst_cluster, uint32_t src, uint32_t bytes, uint32_t bar_cluster) {
    asm volatile("cp.async.bulk.shared::cluster.shared::cta.mbarrier::complete_tx::bytes [%0], [%1], %2, [%3];"
                 :: "r"(dst_cluster), "r"(src), "r"(bytes), "r"(bar_cluster) : "memory");
}
DEVI void bulk_store(void* dst, uint32_t src, uint32_t bytes) {
    asm volatile("cp.async.bulk.global.shared::cta.bulk_group [%0], [%1], %2;" :: "l"(dst), "r"(src), "r"(bytes) : "memory");
}
DEVI void bulk_wait_read() { asm volatile("cp.async.bulk.wait_group.read 0;" ::: "memory"); }
DEVI void mbar_arrive_remote(uint32_t bar_cluster) {
    asm volatile("mbarrier.arrive.shared::cluster.b64 _, [%0];" :: "r"(bar_cluster) : "memory");
}
DEVI void mbar_expect_tx_remote(uint32_t bar_cluster, uint32_t bytes) {
    asm volatile("mbarrier.arrive.expect_tx.shared::cluster.b64 _, [%0], %1;" :: "r"(bar_cluster), "r"(bytes) : "memory");
}
DEVI void l2_prefetch(const void* p, uint32_t bytes) {
    asm volatile("cp.async.bulk.prefetch.L2.global [%0], %1;" :: "l"(p), "r"(bytes) : "memory");
}
DEVI void bulk_commit() { asm volatile("cp.async.bulk.commit_group;" ::: "memory"); }
DEVI void bulk_wait_all() { asm volatile("cp.async.bulk.wait_group 0;" ::: "memory"); }

DEVI void wg_fence() { asm volatile("wgmma.fence.sync.aligned;" ::: "memory"); }
DEVI void wg_commit() { asm volatile("wgmma.commit_group.sync.aligned;" ::: "memory"); }
template <int N> DEVI void wg_wait() { asm volatile("wgmma.wait_group.sync.aligned %0;" :: "n"(N) : "memory"); }

template <int R> DEVI void reg_dec() { asm volatile("setmaxnreg.dec.sync.aligned.u32 %0;" :: "n"(R)); }
template <int R> DEVI void reg_inc() { asm volatile("setmaxnreg.inc.sync.aligned.u32 %0;" :: "n"(R)); }

DEVI uint64_t mk_desc(uint32_t addr, uint32_t lbo, uint32_t sbo, uint32_t sw) {
    return (uint64_t)((addr & 0x3FFFF) >> 4) | ((uint64_t)(lbo >> 4) << 16) | ((uint64_t)(sbo >> 4) << 32) | ((uint64_t)sw << 62);
}

DEVI uint32_t desc_lo(uint32_t addr, uint32_t lbo) { return ((addr & 0x3FFFF) >> 4) | ((lbo >> 4) << 16); }
constexpr uint32_t DHI_SW128 = (1024u >> 4) | (1u << 30);
constexpr uint32_t DHI_SW64  = (512u >> 4) | (2u << 30);
constexpr uint32_t DHI_NONE  = (128u >> 4);

template <int TB, int SCALE_D>
DEVI void wgmma_n8_ss(float* d, uint32_t alo, uint32_t blo) {
    asm volatile("{.reg .b64 da, db; mov.b64 da, {%4, %6}; mov.b64 db, {%5, %7};\n"
                 "wgmma.mma_async.sync.aligned.m64n8k16.f32.bf16.bf16 {%0,%1,%2,%3}, da, db, %8, 1, 1, 1, %9;}"
                 : "+f"(d[0]), "+f"(d[1]), "+f"(d[2]), "+f"(d[3])
                 : "r"(alo), "r"(blo), "n"(DHI_SW128), "n"(DHI_NONE), "n"(SCALE_D), "n"(TB));
}

template <int TB>
DEVI void wgmma_n8_ss_first(float* d, uint32_t alo, uint32_t blo) {
    asm volatile("{.reg .b64 da, db; mov.b64 da, {%4, %6}; mov.b64 db, {%5, %7};\n"
                 "wgmma.mma_async.sync.aligned.m64n8k16.f32.bf16.bf16 {%0,%1,%2,%3}, da, db, 0, 1, 1, 1, %8;}"
                 : "=f"(d[0]), "=f"(d[1]), "=f"(d[2]), "=f"(d[3])
                 : "r"(alo), "r"(blo), "n"(DHI_SW128), "n"(DHI_NONE), "n"(TB));
}
DEVI void wgmma_n32_rs_first(float* d, const uint32_t* a, uint32_t blo) {
    asm volatile("{.reg .b64 db; mov.b64 db, {%20, %21};\n"
                 "wgmma.mma_async.sync.aligned.m64n32k16.f32.bf16.bf16 {%0,%1,%2,%3,%4,%5,%6,%7,%8,%9,%10,%11,%12,%13,%14,%15}, "
                 "{%16,%17,%18,%19}, db, 0, 1, 1, 0;}"
                 : "=f"(d[0]), "=f"(d[1]), "=f"(d[2]), "=f"(d[3]), "=f"(d[4]), "=f"(d[5]), "=f"(d[6]), "=f"(d[7]),
                   "=f"(d[8]), "=f"(d[9]), "=f"(d[10]), "=f"(d[11]), "=f"(d[12]), "=f"(d[13]), "=f"(d[14]), "=f"(d[15])
                 : "r"(a[0]), "r"(a[1]), "r"(a[2]), "r"(a[3]), "r"(blo), "n"(DHI_SW64));
}
template <int N> DEVI void reg_fence(float* d) {
#pragma unroll
    for (int i = 0; i < N; i++) asm volatile("" : "+f"(d[i]) :: "memory");
}
DEVI void wgmma_n32_rs(float* d, const uint32_t* a, uint32_t blo) {
    asm volatile("{.reg .b64 db; mov.b64 db, {%20, %21};\n"
                 "wgmma.mma_async.sync.aligned.m64n32k16.f32.bf16.bf16 {%0,%1,%2,%3,%4,%5,%6,%7,%8,%9,%10,%11,%12,%13,%14,%15}, "
                 "{%16,%17,%18,%19}, db, 1, 1, 1, 0;}"
                 : "+f"(d[0]), "+f"(d[1]), "+f"(d[2]), "+f"(d[3]), "+f"(d[4]), "+f"(d[5]), "+f"(d[6]), "+f"(d[7]),
                   "+f"(d[8]), "+f"(d[9]), "+f"(d[10]), "+f"(d[11]), "+f"(d[12]), "+f"(d[13]), "+f"(d[14]), "+f"(d[15])
                 : "r"(a[0]), "r"(a[1]), "r"(a[2]), "r"(a[3]), "r"(blo), "n"(DHI_SW64));
}
DEVI void wgmma_n32_ss(float* d, uint32_t alo, uint32_t blo) {
    asm volatile("{.reg .b64 da, db; mov.b64 da, {%16, %18}; mov.b64 db, {%17, %19};\n"
                 "wgmma.mma_async.sync.aligned.m64n32k16.f32.bf16.bf16 {%0,%1,%2,%3,%4,%5,%6,%7,%8,%9,%10,%11,%12,%13,%14,%15}, "
                 "da, db, 1, 1, 1, 1, 0;}"
                 : "+f"(d[0]), "+f"(d[1]), "+f"(d[2]), "+f"(d[3]), "+f"(d[4]), "+f"(d[5]), "+f"(d[6]), "+f"(d[7]),
                   "+f"(d[8]), "+f"(d[9]), "+f"(d[10]), "+f"(d[11]), "+f"(d[12]), "+f"(d[13]), "+f"(d[14]), "+f"(d[15])
                 : "r"(alo), "r"(blo), "n"(DHI_SW128), "n"(DHI_SW64));
}

DEVI void wgmma_n256_ss(float* d, uint64_t a, uint64_t b, int scale_d) {
    asm volatile("{.reg .pred p; setp.ne.b32 p, %130, 0;\n"
        "wgmma.mma_async.sync.aligned.m64n256k16.f32.bf16.bf16 "
        "{%0,%1,%2,%3,%4,%5,%6,%7,%8,%9,%10,%11,%12,%13,%14,%15,"
        "%16,%17,%18,%19,%20,%21,%22,%23,%24,%25,%26,%27,%28,%29,%30,%31,"
        "%32,%33,%34,%35,%36,%37,%38,%39,%40,%41,%42,%43,%44,%45,%46,%47,"
        "%48,%49,%50,%51,%52,%53,%54,%55,%56,%57,%58,%59,%60,%61,%62,%63,"
        "%64,%65,%66,%67,%68,%69,%70,%71,%72,%73,%74,%75,%76,%77,%78,%79,"
        "%80,%81,%82,%83,%84,%85,%86,%87,%88,%89,%90,%91,%92,%93,%94,%95,"
        "%96,%97,%98,%99,%100,%101,%102,%103,%104,%105,%106,%107,%108,%109,%110,%111,"
        "%112,%113,%114,%115,%116,%117,%118,%119,%120,%121,%122,%123,%124,%125,%126,%127},"
        " %128, %129, p, 1, 1, 1, 0;}"
        : "+f"(d[0]), "+f"(d[1]), "+f"(d[2]), "+f"(d[3]), "+f"(d[4]), "+f"(d[5]), "+f"(d[6]), "+f"(d[7]),
          "+f"(d[8]), "+f"(d[9]), "+f"(d[10]), "+f"(d[11]), "+f"(d[12]), "+f"(d[13]), "+f"(d[14]), "+f"(d[15]),
          "+f"(d[16]), "+f"(d[17]), "+f"(d[18]), "+f"(d[19]), "+f"(d[20]), "+f"(d[21]), "+f"(d[22]), "+f"(d[23]),
          "+f"(d[24]), "+f"(d[25]), "+f"(d[26]), "+f"(d[27]), "+f"(d[28]), "+f"(d[29]), "+f"(d[30]), "+f"(d[31]),
          "+f"(d[32]), "+f"(d[33]), "+f"(d[34]), "+f"(d[35]), "+f"(d[36]), "+f"(d[37]), "+f"(d[38]), "+f"(d[39]),
          "+f"(d[40]), "+f"(d[41]), "+f"(d[42]), "+f"(d[43]), "+f"(d[44]), "+f"(d[45]), "+f"(d[46]), "+f"(d[47]),
          "+f"(d[48]), "+f"(d[49]), "+f"(d[50]), "+f"(d[51]), "+f"(d[52]), "+f"(d[53]), "+f"(d[54]), "+f"(d[55]),
          "+f"(d[56]), "+f"(d[57]), "+f"(d[58]), "+f"(d[59]), "+f"(d[60]), "+f"(d[61]), "+f"(d[62]), "+f"(d[63]),
          "+f"(d[64]), "+f"(d[65]), "+f"(d[66]), "+f"(d[67]), "+f"(d[68]), "+f"(d[69]), "+f"(d[70]), "+f"(d[71]),
          "+f"(d[72]), "+f"(d[73]), "+f"(d[74]), "+f"(d[75]), "+f"(d[76]), "+f"(d[77]), "+f"(d[78]), "+f"(d[79]),
          "+f"(d[80]), "+f"(d[81]), "+f"(d[82]), "+f"(d[83]), "+f"(d[84]), "+f"(d[85]), "+f"(d[86]), "+f"(d[87]),
          "+f"(d[88]), "+f"(d[89]), "+f"(d[90]), "+f"(d[91]), "+f"(d[92]), "+f"(d[93]), "+f"(d[94]), "+f"(d[95]),
          "+f"(d[96]), "+f"(d[97]), "+f"(d[98]), "+f"(d[99]), "+f"(d[100]), "+f"(d[101]), "+f"(d[102]), "+f"(d[103]),
          "+f"(d[104]), "+f"(d[105]), "+f"(d[106]), "+f"(d[107]), "+f"(d[108]), "+f"(d[109]), "+f"(d[110]), "+f"(d[111]),
          "+f"(d[112]), "+f"(d[113]), "+f"(d[114]), "+f"(d[115]), "+f"(d[116]), "+f"(d[117]), "+f"(d[118]), "+f"(d[119]),
          "+f"(d[120]), "+f"(d[121]), "+f"(d[122]), "+f"(d[123]), "+f"(d[124]), "+f"(d[125]), "+f"(d[126]), "+f"(d[127])
        : "l"(a), "l"(b), "r"(scale_d));
}

DEVI void wgmma_n128_ss(float* d, uint64_t a, uint64_t b, int scale_d) {
    asm volatile("{.reg .pred p; setp.ne.b32 p, %66, 0;\n"
        "wgmma.mma_async.sync.aligned.m64n128k16.f32.bf16.bf16 "
        "{%0,%1,%2,%3,%4,%5,%6,%7,%8,%9,%10,%11,%12,%13,%14,%15,"
        "%16,%17,%18,%19,%20,%21,%22,%23,%24,%25,%26,%27,%28,%29,%30,%31,"
        "%32,%33,%34,%35,%36,%37,%38,%39,%40,%41,%42,%43,%44,%45,%46,%47,"
        "%48,%49,%50,%51,%52,%53,%54,%55,%56,%57,%58,%59,%60,%61,%62,%63},"
        " %64, %65, p, 1, 1, 1, 0;}"
        : "+f"(d[0]), "+f"(d[1]), "+f"(d[2]), "+f"(d[3]), "+f"(d[4]), "+f"(d[5]), "+f"(d[6]), "+f"(d[7]),
          "+f"(d[8]), "+f"(d[9]), "+f"(d[10]), "+f"(d[11]), "+f"(d[12]), "+f"(d[13]), "+f"(d[14]), "+f"(d[15]),
          "+f"(d[16]), "+f"(d[17]), "+f"(d[18]), "+f"(d[19]), "+f"(d[20]), "+f"(d[21]), "+f"(d[22]), "+f"(d[23]),
          "+f"(d[24]), "+f"(d[25]), "+f"(d[26]), "+f"(d[27]), "+f"(d[28]), "+f"(d[29]), "+f"(d[30]), "+f"(d[31]),
          "+f"(d[32]), "+f"(d[33]), "+f"(d[34]), "+f"(d[35]), "+f"(d[36]), "+f"(d[37]), "+f"(d[38]), "+f"(d[39]),
          "+f"(d[40]), "+f"(d[41]), "+f"(d[42]), "+f"(d[43]), "+f"(d[44]), "+f"(d[45]), "+f"(d[46]), "+f"(d[47]),
          "+f"(d[48]), "+f"(d[49]), "+f"(d[50]), "+f"(d[51]), "+f"(d[52]), "+f"(d[53]), "+f"(d[54]), "+f"(d[55]),
          "+f"(d[56]), "+f"(d[57]), "+f"(d[58]), "+f"(d[59]), "+f"(d[60]), "+f"(d[61]), "+f"(d[62]), "+f"(d[63])
        : "l"(a), "l"(b), "r"(scale_d));
}

DEVI void mma16816(float* d, const uint32_t* a, uint32_t b0, uint32_t b1) {
    asm volatile("mma.sync.aligned.m16n8k16.row.col.f32.bf16.bf16.f32 {%0,%1,%2,%3}, {%4,%5,%6,%7}, {%8,%9}, {%0,%1,%2,%3};"
                 : "+f"(d[0]), "+f"(d[1]), "+f"(d[2]), "+f"(d[3])
                 : "r"(a[0]), "r"(a[1]), "r"(a[2]), "r"(a[3]), "r"(b0), "r"(b1));
}
DEVI void mma1688(float* d, uint32_t a0, uint32_t a1, uint32_t b0) {
    asm volatile("mma.sync.aligned.m16n8k8.row.col.f32.bf16.bf16.f32 {%0,%1,%2,%3}, {%4,%5}, {%6}, {%0,%1,%2,%3};"
                 : "+f"(d[0]), "+f"(d[1]), "+f"(d[2]), "+f"(d[3]) : "r"(a0), "r"(a1), "r"(b0));
}
DEVI void ldsm4(uint32_t* r, uint32_t addr) {
    asm volatile("ldmatrix.sync.aligned.m8n8.x4.shared.b16 {%0,%1,%2,%3}, [%4];"
                 : "=r"(r[0]), "=r"(r[1]), "=r"(r[2]), "=r"(r[3]) : "r"(addr) : "memory");
}
DEVI void ldsm4t(uint32_t* r, uint32_t addr) {
    asm volatile("ldmatrix.sync.aligned.m8n8.x4.trans.shared.b16 {%0,%1,%2,%3}, [%4];"
                 : "=r"(r[0]), "=r"(r[1]), "=r"(r[2]), "=r"(r[3]) : "r"(addr) : "memory");
}
DEVI void ldsm2(uint32_t* r, uint32_t addr) {
    asm volatile("ldmatrix.sync.aligned.m8n8.x2.shared.b16 {%0,%1}, [%2];" : "=r"(r[0]), "=r"(r[1]) : "r"(addr) : "memory");
}
DEVI void ldsm1t(uint32_t& r, uint32_t addr) {
    asm volatile("ldmatrix.sync.aligned.m8n8.x1.trans.shared.b16 {%0}, [%1];" : "=r"(r) : "r"(addr) : "memory");
}
DEVI void stsm4(uint32_t addr, uint32_t r0, uint32_t r1, uint32_t r2, uint32_t r3) {
    asm volatile("stmatrix.sync.aligned.m8n8.x4.shared.b16 [%0], {%1,%2,%3,%4};" :: "r"(addr), "r"(r0), "r"(r1), "r"(r2), "r"(r3) : "memory");
}
DEVI void stsm4t(uint32_t addr, uint32_t r0, uint32_t r1, uint32_t r2, uint32_t r3) {
    asm volatile("stmatrix.sync.aligned.m8n8.x4.trans.shared.b16 [%0], {%1,%2,%3,%4};" :: "r"(addr), "r"(r0), "r"(r1), "r"(r2), "r"(r3) : "memory");
}
DEVI uint32_t movm_t(uint32_t a) {
    uint32_t d; asm volatile("movmatrix.sync.aligned.m8n8.trans.b16 %0, %1;" : "=r"(d) : "r"(a)); return d;
}
DEVI uint32_t pack_bf16(float lo, float hi) {
    uint32_t r; asm("cvt.rn.bf16x2.f32 %0, %1, %2;" : "=r"(r) : "f"(hi), "f"(lo)); return r;
}
DEVI float ex2(float x) { float y; asm("ex2.approx.ftz.f32 %0, %1;" : "=f"(y) : "f"(x)); return y; }

DEVI uint4 ld_rlx4(const void* p) {
    uint4 v;
    asm volatile("ld.relaxed.gpu.global.v4.u32 {%0,%1,%2,%3}, [%4];" : "=r"(v.x), "=r"(v.y), "=r"(v.z), "=r"(v.w) : "l"(p) : "memory");
    return v;
}
DEVI void ld_rlx4f(float* d, const void* p) {
    asm volatile("ld.relaxed.gpu.global.v4.f32 {%0,%1,%2,%3}, [%4];" : "=f"(d[0]), "=f"(d[1]), "=f"(d[2]), "=f"(d[3]) : "l"(p) : "memory");
}
DEVI bool all_nzf(const float* d) { return __float_as_uint(d[0]) && __float_as_uint(d[1]) && __float_as_uint(d[2]) && __float_as_uint(d[3]); }
DEVI void sts128f(uint32_t addr, const float* d) {
    asm volatile("st.shared.v4.f32 [%0], {%1,%2,%3,%4};" :: "r"(addr), "f"(d[0]), "f"(d[1]), "f"(d[2]), "f"(d[3]) : "memory");
}
DEVI void st_rlx4(void* p, uint32_t a, uint32_t b, uint32_t c, uint32_t d) {
    asm volatile("st.relaxed.gpu.global.v4.u32 [%0], {%1,%2,%3,%4};" :: "l"(p), "r"(a), "r"(b), "r"(c), "r"(d) : "memory");
}
DEVI void st_rlx(void* p, uint32_t v) { asm volatile("st.relaxed.gpu.global.u32 [%0], %1;" :: "l"(p), "r"(v) : "memory"); }
DEVI void sts128(uint32_t addr, uint4 v) {
    asm volatile("st.shared.v4.u32 [%0], {%1,%2,%3,%4};" :: "r"(addr), "r"(v.x), "r"(v.y), "r"(v.z), "r"(v.w) : "memory");
}
DEVI void sts64(uint32_t addr, uint32_t a, uint32_t b) { asm volatile("st.shared.v2.u32 [%0], {%1,%2};" :: "r"(addr), "r"(a), "r"(b) : "memory"); }
DEVI void sts32(uint32_t addr, uint32_t v) { asm volatile("st.shared.u32 [%0], %1;" :: "r"(addr), "r"(v) : "memory"); }
DEVI uint4 lds128(uint32_t addr) {
    uint4 v; asm volatile("ld.shared.v4.u32 {%0,%1,%2,%3}, [%4];" : "=r"(v.x), "=r"(v.y), "=r"(v.z), "=r"(v.w) : "r"(addr) : "memory"); return v;
}
DEVI float2 lds64f(uint32_t addr) {
    float2 v; asm volatile("ld.shared.v2.f32 {%0,%1}, [%2];" : "=f"(v.x), "=f"(v.y) : "r"(addr) : "memory"); return v;
}
DEVI void cp_async16(uint32_t dst, const void* src) {
    asm volatile("cp.async.cg.shared.global [%0], [%1], 16;" :: "r"(dst), "l"(src) : "memory");
}
DEVI void cp_async_commit() { asm volatile("cp.async.commit_group;" ::: "memory"); }
DEVI void cp_async_wait0() { asm volatile("cp.async.wait_group 0;" ::: "memory"); }
DEVI uint32_t lds32(uint32_t addr) { uint32_t v; asm volatile("ld.shared.u32 %0, [%1];" : "=r"(v) : "r"(addr) : "memory"); return v; }
DEVI float rcp_fast(float x) { float y; asm("rcp.approx.ftz.f32 %0, %1;" : "=f"(y) : "f"(x)); return y; }
DEVI bool all_nz(const uint4& v) { return v.x && v.y && v.z && v.w; }
DEVI uint32_t mapa(uint32_t addr, uint32_t rank) {
    uint32_t r; asm("mapa.shared::cluster.u32 %0, %1, %2;" : "=r"(r) : "r"(addr), "r"(rank)); return r;
}
DEVI void st_async64(uint32_t dst, uint32_t a, uint32_t b, uint32_t bar) {
    asm volatile("st.async.weak.shared::cluster.mbarrier::complete_tx::bytes.v2.b32 [%0], {%1,%2}, [%3];"
                 :: "r"(dst), "r"(a), "r"(b), "r"(bar) : "memory");
}

DEVI void st_async128(uint32_t dst, uint32_t a, uint32_t b, uint32_t c, uint32_t d, uint32_t bar) {
    asm volatile("st.async.weak.shared::cluster.mbarrier::complete_tx::bytes.v4.b32 [%0], {%1,%2,%3,%4}, [%5];"
                 :: "r"(dst), "r"(a), "r"(b), "r"(c), "r"(d), "r"(bar) : "memory");
}

DEVI uint32_t b_addr(uint32_t sb, int row, int which, int chunk) { const int l = 3 * row + which; return sb + l * 128 + ((chunk ^ (l & 7)) * 16); }
DEVI void battn_warp(uint32_t st, uint32_t so, int i0, int par, int head, int hh, int mt, int lane) {
    const int gq = lane >> 2, t = lane & 3;
    float s[3][4];
#pragma unroll
    for (int n = 0; n < 3; n++) { s[n][0] = s[n][1] = s[n][2] = s[n][3] = 0.f; }
    const int arow = 16 * mt + (lane & 7) + ((lane >> 3) & 1) * 8;
#pragma unroll
    for (int ks = 0; ks < 2; ks++) {
        uint32_t a[4], b[4], b2[2];
        ldsm4(a, b_addr(st, 8 + arow, 0, hh * 4 + ks * 2 + (lane >> 4)));
        const int brow = 16 * mt + (lane >> 4) * 8 + (lane & 7);
        ldsm4(b, b_addr(st, brow, 1, hh * 4 + ks * 2 + ((lane >> 3) & 1)));
        const int crow = 16 * mt + 16 + (lane & 7);
        ldsm2(b2, b_addr(st, crow, 1, hh * 4 + ks * 2 + ((lane >> 3) & 1)));
        mma16816(s[0], a, b[0], b[1]);
        mma16816(s[1], a, b[2], b[3]);
        mma16816(s[2], a, b2[0], b2[1]);
    }
    float m0 = -INFINITY, m1 = -INFINITY;
#pragma unroll
    for (int n = 0; n < 3; n++) {
#pragma unroll
        for (int c = 0; c < 2; c++) {
            const int dj = 8 * n - 8 + 2 * t + c;
            const bool ex = i0 + 16 * mt + dj >= 0;
            if (!(ex && gq - dj >= 0 && gq - dj <= 7)) s[n][c] = -INFINITY;
            if (!(ex && gq + 8 - dj >= 0 && gq + 8 - dj <= 7)) s[n][2 + c] = -INFINITY;
            m0 = fmaxf(m0, s[n][c]); m1 = fmaxf(m1, s[n][2 + c]);
        }
    }
    m0 = fmaxf(m0, __shfl_xor_sync(0xffffffffu, m0, 1)); m0 = fmaxf(m0, __shfl_xor_sync(0xffffffffu, m0, 2));
    m1 = fmaxf(m1, __shfl_xor_sync(0xffffffffu, m1, 1)); m1 = fmaxf(m1, __shfl_xor_sync(0xffffffffu, m1, 2));
    constexpr float C = 0.17677669529663687f * 1.4426950408889634f;
    float l0 = 0.f, l1 = 0.f;
    uint32_t p[3][2];
#pragma unroll
    for (int n = 0; n < 3; n++) {
        const float e0 = ex2((s[n][0] - m0) * C), e1 = ex2((s[n][1] - m0) * C), e2 = ex2((s[n][2] - m1) * C), e3 = ex2((s[n][3] - m1) * C);
        l0 += e0 + e1; l1 += e2 + e3;
        p[n][0] = pack_bf16(e0, e1); p[n][1] = pack_bf16(e2, e3);
    }
    l0 += __shfl_xor_sync(0xffffffffu, l0, 1); l0 += __shfl_xor_sync(0xffffffffu, l0, 2);
    l1 += __shfl_xor_sync(0xffffffffu, l1, 1); l1 += __shfl_xor_sync(0xffffffffu, l1, 2);
    const float i0f = rcp_fast(l0), i1f = rcp_fast(l1);
    float o[4][4];
#pragma unroll
    for (int n = 0; n < 4; n++) { o[n][0] = o[n][1] = o[n][2] = o[n][3] = 0.f; }
    {
        const uint32_t a0[4] = {p[0][0], p[0][1], p[1][0], p[1][1]}, a1[4] = {p[2][0], p[2][1], 0u, 0u};
#pragma unroll
        for (int n = 0; n < 4; n += 2) {
            uint32_t b[4], b2[4];
            const int vrow = 16 * mt + ((lane >> 3) & 1) * 8 + (lane & 7);
            ldsm4t(b, b_addr(st, vrow, 2, hh * 4 + n + (lane >> 4)));
            const int wrow = 16 * mt + 16 + (lane & 7);
            ldsm4t(b2, b_addr(st, wrow, 2, hh * 4 + n + (lane >> 4)));
            mma16816(o[n], a0, b[0], b[1]);
            mma16816(o[n + 1], a0, b[2], b[3]);
            mma16816(o[n], a1, b2[0], 0u);
            mma16816(o[n + 1], a1, b2[2], 0u);
        }
    }
    {
        const int row = (lane & 7) + ((lane >> 3) & 1) * 8;
#pragma unroll
        for (int n = 0; n < 4; n += 2)
            stsm4(so + row * 64 + (((n + (lane >> 4)) ^ ((row >> 1) & 3)) * 16),
                  pack_bf16(o[n][0] * i0f, o[n][1] * i0f), pack_bf16(o[n][2] * i1f, o[n][3] * i1f),
                  pack_bf16(o[n + 1][0] * i0f, o[n + 1][1] * i0f), pack_bf16(o[n + 1][2] * i1f, o[n + 1][3] * i1f));
    }
    __syncwarp();
#pragma unroll
    for (int i = 0; i < 2; i++) {
        const int idx = lane + i * 32, row = idx >> 2, ch = idx & 3;
        const uint4 v = lds128(so + row * 64 + ((ch ^ ((row >> 1) & 3)) * 16));
        *(uint4*)(g_bo + (size_t)(2 * (i0 + 16 * mt + row) + par) * 1024 + head * 32 + ch * 8) = v;
    }
    __syncwarp();
}

constexpr float SCALE_LOG2E = 0.08838834764831845f * 1.4426950408889634f;

constexpr int P_STAGES = 4, P_STAGE = 16384 + 32768;
constexpr int PS_STG = P_STAGES * P_STAGE;
constexpr int PS_BAR = PS_STG + 32768;
constexpr int P_SMEM = PS_BAR + 256;
static_assert(P_SMEM <= 232448, "smem");
constexpr int PT_B1 = 256, PT_A0 = PT_B1 + 192, PT_B2 = PT_A0 + 32, PT_A1 = PT_B2 + 32, PT_B3 = PT_A1 + 32, PT_A2 = PT_B3 + 64;
constexpr int PT_SK = PT_A2 + 48, P_NTASK = PT_SK + 64;
enum { K_B1, K_Q, K_B2, K_B3, K_A3, K_SK, K_END };
struct PTask { int kind, a, b, c; };
DEVI PTask p_decode(int id) {
    if (id < PT_B1) return {K_Q, id % 32, id / 32, 0};
    if (id < PT_A0) return {K_B1, (id - PT_B1) % 24, (id - PT_B1) / 24, 0};
    if (id < PT_B2) return {K_A3, (id - PT_A0) & 7, (id - PT_A0) >> 3, 0};
    if (id < PT_A1) return {K_B2, id - PT_B2, 0, 0};
    if (id < PT_B3) return {K_A3, (id - PT_A1) & 7, 4 + ((id - PT_A1) >> 3), 0};
    if (id < PT_A2) return {K_B3, (id - PT_B3) % 8, (id - PT_B3) / 8, 0};
    if (id < PT_SK) return {K_A3, (id - PT_A2) & 7, 8 + ((id - PT_A2) >> 3), 0};
    if (id >= P_NTASK) return {K_END, 0, 0, 0};
    const int j = id - PT_SK;
    return {K_SK, (j >> 2) & 7, 14 + (j >> 5), j & 3};
}
DEVI void wait_count(const unsigned* p, unsigned target) {
    int n = 0;
    while (true) {
        unsigned v; asm volatile("ld.acquire.gpu.global.u32 %0, [%1];" : "=r"(v) : "l"(p) : "memory");
        if ((int)(v - target) >= 0) break;
        __nanosleep(100);
        if (++n > SPIN_LIMIT) TRAP(0x10000000u | ((unsigned)(size_t)p & 0xFFFFu));
    }
}
DEVI void wait_count_warp(const unsigned* p, unsigned target) {
    int n = 0;
    while (true) {
        unsigned v; asm volatile("ld.acquire.gpu.global.u32 %0, [%1];" : "=r"(v) : "l"(p) : "memory");
        if (__all_sync(0xffffffffu, (int)(v - target) >= 0)) break;
        __nanosleep(100);
        if (++n > SPIN_LIMIT) TRAP(0x10000000u | ((unsigned)(size_t)p & 0xFFFFu));
    }
}
DEVI void signal_count(unsigned* p) { __threadfence(); atomicAdd(p, 1u); }

struct PMaps { CUtensorMap wq, bw, bwo, wo, x, bx, bo, ox, cb, cout, b40; };

template <int BN>
DEVI void p_mainloop(float* d, uint32_t sb, int g, int nk, int& it, bool elected) {
#pragma unroll
    for (int i = 0; i < BN / 2; i++) d[i] = 0.f;
    for (int kb = 0; kb < nk; kb++, it++) {
        const int st = it % P_STAGES;
        mbar_wait(sb + PS_BAR + st * 8, (it / P_STAGES) & 1);
        const uint32_t a = sb + st * P_STAGE;
        const uint64_t da = mk_desc(a + g * 8192, 16, 1024, 1), db = mk_desc(a + 16384, 16, 1024, 1);
        wg_fence();
#pragma unroll
        for (int kk = 0; kk < 4; kk++) {
            if (BN == 256) wgmma_n256_ss(d, da + (uint64_t)(kk * 128), db + (uint64_t)(kk * 2), (kb | kk) != 0);
            else           wgmma_n128_ss(d, da + (uint64_t)(kk * 128), db + (uint64_t)(kk * 2), (kb | kk) != 0);
        }
        wg_commit();
        if (kb > 0) {
            wg_wait<1>();
            if (elected) mbar_arrive(sb + PS_BAR + 32 + ((it - 1) % P_STAGES) * 8);
        }
    }
    wg_wait<0>();
    if (elected) mbar_arrive(sb + PS_BAR + 32 + ((it - 1) % P_STAGES) * 8);
}
template <int BN>
DEVI void p_epi_row(const float* d, uint32_t stg, const CUtensorMap* tmC, int col, int tok0, int warp, int lane_, int barid, bool elected, int& nstore) {
    const int lane = (int)opaque((uint32_t)lane_);
    const int mi = lane >> 3, r = lane & 7;
#pragma unroll
    for (int c = 0; c < BN / 64; c++, nstore++) {
        const uint32_t buf = stg + (nstore & 1) * 8192;
        if (elected) asm volatile("cp.async.bulk.wait_group.read 1;" ::: "memory");
        nbar_sync(barid, 128);
#pragma unroll
        for (int j = 0; j < 8; j += 2) {
            const int jj = c * 8 + j;
            const int tok = 8 * (j + (mi >> 1)) + r;
            const int chunk = (2 * warp + (mi & 1)) ^ r;
            stsm4t(buf + tok * 128 + chunk * 16,
                   pack_bf16(d[4 * jj], d[4 * jj + 1]), pack_bf16(d[4 * jj + 2], d[4 * jj + 3]),
                   pack_bf16(d[4 * jj + 4], d[4 * jj + 5]), pack_bf16(d[4 * jj + 6], d[4 * jj + 7]));
        }
        fence_proxy_async();
        nbar_sync(barid, 128);
        if (elected) { tma_store_2d(tmC, buf, col, tok0 + c * 64); bulk_commit(); }
    }
}

__global__ void __launch_bounds__(384, 1) k_post(const __grid_constant__ PMaps mp) {
    extern __shared__ __align__(1024) uint8_t smem_raw[];
    const uint32_t sb = smem_u32(smem_raw);
    if (sb & 1023u) __trap();
    const int tid = threadIdx.x, lane = tid & 31;
    const int wg = __shfl_sync(0xffffffffu, tid >> 7, 0), warp = __shfl_sync(0xffffffffu, (tid >> 5) & 3, 0);
    const uint32_t bF = sb + PS_BAR, bE = bF + 32, bTF = bF + 64, bTE = bF + 80, sT = bF + 96;
    if (tid == 0) {
        for (int i = 0; i < P_STAGES; i++) { mbar_init(bF + i * 8, 1); mbar_init(bE + i * 8, 2); }
        for (int i = 0; i < 2; i++) { mbar_init(bTF + i * 8, 1); mbar_init(bTE + i * 8, 256); }
        fence_mbar_init();
    }
    __syncthreads();
    if (wg == 2) {
        reg_dec<40>();
        if (tid == 256) {
            const unsigned E = *(volatile unsigned*)&g_epoch + 1;
            const unsigned qbase = (E - 1) * (unsigned)(P_NTASK + gridDim.x);
            int it = 0;
            for (int i = 0;; i++) {
                mbar_wait(bTE + (i & 1) * 8, ((i >> 1) & 1) ^ 1);
                const int id = (int)(atomicAdd(&g_qctr, 1u) - qbase);
                const PTask tk = p_decode(id);
                if (tk.kind == K_B2) {
                    wait_count(&g_cnt_b1[tk.a >> 2], 48 * E);
                    if ((tk.a & 3) == 0 && tk.a > 0) wait_count(&g_cnt_b1[(tk.a >> 2) - 1], 48 * E);
                } else if (tk.kind == K_B3) wait_count(&g_cnt_b2[tk.b], 4 * E);
                else if (tk.kind == K_A3 || tk.kind == K_SK) wait_count(&g_prog[tk.b], 128 * E);
                asm volatile("fence.proxy.async;" ::: "memory");
                sts32(sT + (i & 1) * 4, (uint32_t)id);
                mbar_arrive(bTF + (i & 1) * 8);
                if (tk.kind == K_END) break;
                if (tk.kind == K_B2) {
                    const int i0 = tk.a * 32;
                    for (int j = 0; j < 16; j++, it++) {
                        const int st = it % P_STAGES;
                        mbar_wait(bE + st * 8, ((it / P_STAGES) & 1) ^ 1);
                        const uint32_t a = sb + st * P_STAGE, bar = bF + st * 8;
                        mbar_expect_tx(bar, 2 * 15360);
                        for (int u = 0; u < 2; u++)
                            asm volatile("cp.async.bulk.tensor.4d.shared::cluster.global.mbarrier::complete_tx::bytes [%0], [%1, {%3, %4, %5, %6}], [%2];"
                                         :: "r"(a + u * 15360), "l"(&mp.b40), "r"(bar), "r"(j * 64), "r"(0), "r"(u), "r"(i0 - 8) : "memory");
                    }
                    continue;
                }
                const CUtensorMap* tw = tk.kind == K_B1 ? &mp.bw : (tk.kind == K_Q ? &mp.wq : (tk.kind == K_B3 ? &mp.bwo : &mp.wo));
                const CUtensorMap* tx = tk.kind == K_B1 ? &mp.bx : (tk.kind == K_Q ? &mp.x : (tk.kind == K_B3 ? &mp.bo : &mp.ox));
                const bool a3 = tk.kind == K_A3 || tk.kind == K_SK;
                const int nk = tk.kind == K_A3 ? HD / 64 : DM / 64, kb0 = tk.kind == K_SK ? tk.c * 16 : 0;
                for (int kb = kb0; kb < kb0 + nk; kb++, it++) {
                    const int st = it % P_STAGES;
                    mbar_wait(bE + st * 8, ((it / P_STAGES) & 1) ^ 1);
                    const uint32_t a = sb + st * P_STAGE, bar = bF + st * 8;
                    mbar_expect_tx(bar, a3 ? 32768 : P_STAGE);
                    if (a3) {
                        tma_load_wo(a, tw, tk.a * 128, kb * 2, bar);
                        tma_load_wo(a + 8192, tw, tk.a * 128 + 64, kb * 2, bar);
                    } else {
                        tma_load_2d(a, tw, tk.a * 128, kb * 64, bar);
                        tma_load_2d(a + 8192, tw, tk.a * 128 + 64, kb * 64, bar);
                    }
                    tma_load_2d(a + 16384, tx, kb * 64, tk.b * (a3 ? 128 : 256), bar);
                }
            }
            __threadfence();
            if (atomicAdd(&g_done, 1u) == E * gridDim.x - 1) { __threadfence(); *(volatile unsigned*)&g_epoch = E; }
        }
    } else {
        reg_inc<232>();
        const int g = wg, ct = tid, barid = 1 + g;
        const bool elected = (tid & 127) == 0;
        const uint32_t stg = sb + PS_STG + g * 16384;
        int it = 0, nstore = 0;
        unsigned* pending = nullptr;
        for (int i = 0;; i++) {
            if (elected && pending && !mbar_try(bTF + (i & 1) * 8, (i >> 1) & 1)) { bulk_wait_all(); signal_count(pending); pending = nullptr; }
            mbar_wait(bTF + (i & 1) * 8, (i >> 1) & 1);
            const int id = (int)lds32(sT + (i & 1) * 4);
            mbar_arrive(bTE + (i & 1) * 8);
            const PTask tk = p_decode(id);
            if (tk.kind == K_END) break;
            if (tk.kind == K_B2) {
                if (elected && pending) { bulk_wait_all(); signal_count(pending); }
                pending = nullptr;
                if (elected) bulk_wait_all();
                nbar_sync(barid, 128);
#pragma unroll 1
                for (int j = 0; j < 16; j++, it++) {
                    const int st = it % P_STAGES;
                    mbar_wait(bF + st * 8, (it / P_STAGES) & 1);
                    const uint32_t a = sb + st * P_STAGE + g * 15360;
                    battn_warp(a, stg + warp * 1024, tk.a * 32, g, j * 2 + (warp >> 1), warp >> 1, warp & 1, (int)opaque((uint32_t)lane));
                    nbar_sync(barid, 128);
                    if (elected) mbar_arrive(bE + st * 8);
                }
                nbar_sync(3, 256);
                if (ct == 0) signal_count(&g_cnt_b2[tk.a >> 2]);
            } else if (tk.kind == K_A3 || tk.kind == K_SK) {
                float d[64];
                p_mainloop<128>(d, sb, g, tk.kind == K_A3 ? HD / 64 : DM / 64, it, elected);
                if (elected && pending) { bulk_wait_all(); signal_count(pending); }
                pending = nullptr;
                bool finish = true;
                if (tk.kind == K_SK) {
                    const int tile = ((tk.b - 14) * 8 + tk.a);
                    float4* mine = (float4*)(g_skp + ((size_t)(tile * 4 + tk.c) * 2 + g) * 8192) + (tid & 127);
#pragma unroll
                    for (int j = 0; j < 16; j++) mine[j * 128] = make_float4(d[4 * j], d[4 * j + 1], d[4 * j + 2], d[4 * j + 3]);
                    nbar_sync(barid, 128);
                    if (elected) { __threadfence(); const unsigned old = atomicAdd(&g_cnt_sk[tile * 2 + g], 1u); __threadfence(); sts32(sT + 16 + g * 4, old & 3u); }
                    nbar_sync(barid, 128);
                    finish = lds32(sT + 16 + g * 4) == 3u;
                    if (finish) {
#pragma unroll 1
                        for (int q = 1; q < 4; q++) {
                            const float4* o = (const float4*)(g_skp + ((size_t)(tile * 4 + ((tk.c + q) & 3)) * 2 + g) * 8192) + (tid & 127);
#pragma unroll
                            for (int j = 0; j < 16; j++) {
                                const float4 v = __ldcg(o + j * 128);
                                d[4 * j] += v.x; d[4 * j + 1] += v.y; d[4 * j + 2] += v.z; d[4 * j + 3] += v.w;
                            }
                        }
                    }
                    nbar_sync(barid, 128);
                }
                if (finish) p_epi_row<128>(d, stg, &mp.cout, tk.a * 128 + g * 64, tk.b * 128, warp, lane, barid, elected, nstore);
            } else {
                float d[128];
                p_mainloop<256>(d, sb, g, DM / 64, it, elected);
                if (elected && pending) { bulk_wait_all(); signal_count(pending); }
                pending = nullptr;
                if (tk.kind == K_Q) {
                    const int ln = (int)opaque((uint32_t)lane), gq = ln >> 2, t = ln & 3, dim = g * 64 + warp * 16 + gq;
#pragma unroll
                    for (int j = 0; j < 32; j++) {
                        const int seg = tk.b * 8 + (j >> 2), blk = j & 3;
                        uint32_t* p = (uint32_t*)(g_qx + ((((size_t)seg * NH + tk.a) * 4 + blk) * DH + dim) * 8 + 2 * t);
                        p[0]  = pack_bf16(d[4 * j], d[4 * j + 1]);
                        p[32] = pack_bf16(d[4 * j + 2], d[4 * j + 3]);
                    }
                    nbar_sync(barid, 128);
                    if (elected) signal_count(&g_cnt_q[tk.b]);
                } else if (tk.kind == K_B1) {
                    p_epi_row<256>(d, stg, &mp.cb, tk.a * 128 + g * 64, tk.b * 256, warp, lane, barid, elected, nstore);
                    pending = &g_cnt_b1[tk.b];
                } else {
                    p_epi_row<256>(d, stg, &mp.cout, DM + tk.a * 128 + g * 64, tk.b * 256, warp, lane, barid, elected, nstore);
                }
            }
        }
        if (elected) { bulk_wait_all(); if (pending) signal_count(pending); }
    }
    __syncthreads();
}

constexpr unsigned long long R_TORD_PACK = 0xf4a53e92dc7816b0ull;
__host__ __device__ constexpr int r_tord(int pos) { return (int)((R_TORD_PACK >> (4 * pos)) & 15ull); }
__host__ __device__ constexpr int r_tinv(int T) { for (int p = 0; p < 16; p++) if (r_tord(p) == T) return p; return 0; }
__host__ __device__ constexpr bool r_pos_ss(int pos) { return pos % 3 == 2; }
__host__ __device__ constexpr int r_ss(int pos) { return pos / 3; }
__host__ __device__ constexpr int r_rs(int pos) { return pos - pos / 3; }
constexpr int R_NRS = 11, R_NSS = 5;
constexpr int R_G1 = 3, R_G2 = 9;
#define REG_KB 232
#define X_NA_DEF 4
constexpr int X_SLOTS = 4;
constexpr int X_NST = 8;
constexpr int X_NA = X_NA_DEF;

constexpr int RS_WSS  = 0;
constexpr int RS_WO   = RS_WSS + R_NSS * 16384;
constexpr int RS_MEM  = RS_WO + 5 * 16384;
constexpr int RS_O    = RS_MEM + 16384;
constexpr int RS_SX   = RS_O + 2048;
constexpr int RS_BAR  = RS_SX + 2048;
constexpr int RS_TAIL = RS_BAR + 1024;
constexpr int RS_WO5  = RS_TAIL;
constexpr int RS_K    = RS_WO5 + 16384;
constexpr int RS_V    = RS_K + 10240;
constexpr int RS_Q    = RS_V + 10240;
constexpr int RS_QX   = RS_Q + 2048;
constexpr int RS_QEND = RS_QX + 8192;
constexpr int RS_X    = RS_TAIL;
constexpr int X_PITCH = (X_SLOTS + 1) * 4096;
constexpr int RS_WX   = RS_X + 2 * X_PITCH;
constexpr int RS_KEND = RS_WX + 4096;
constexpr int RS_EV   = RS_BAR + 256;
constexpr int R_SMEM  = RS_KEND > RS_QEND ? RS_KEND : RS_QEND;
static_assert(R_SMEM <= 232448, "smem");
static_assert(RS_TAIL % 1024 == 0 && RS_MEM % 1024 == 0, "alignment");

constexpr int RB_G = RS_BAR, RB_K = RS_BAR + 24, RB_V = RS_BAR + 32, RB_KV = RS_BAR + 40, RB_QX = RS_BAR + 48, RB_O = RS_BAR + 56;
constexpr int RB_ATT = RS_BAR + 64, RB_W = RS_BAR + 72, RB_SF = RS_BAR + 80, RB_SE = RB_SF + 40, RB_XF = RB_SE + 40;
constexpr int RB_T = RB_XF + 64, RS_INV = RB_SF;
static_assert(RB_T + 8 <= RS_EV, "barriers");
constexpr uint32_t SB0 = 1024;
__host__ __device__ constexpr uint32_t cdesc(uint32_t off, uint32_t lbo) { return ((SB0 + off) >> 4) | ((lbo >> 4) << 16); }
#define SCHED_FENCE() __syncwarp()
constexpr int NB_BIG = 1, NB_Q = 2, NB_AUX = 3, NB_WO = 4, NB_XS = 5, NB_WG = 6, NB_PAIR = 8;

DEVI int tid_now() { int t; asm volatile("mov.u32 %0, %%tid.x;" : "=r"(t)); return t; }
DEVI uint32_t a_frag_off(int lane, int warp) { return (uint32_t)((((lane >> 4) * 8 + (lane & 7)) * 128) + (((2 * warp + ((lane >> 3) & 1)) ^ (lane & 7)) * 16)); }
DEVI uint32_t clk32() { unsigned long long c; asm volatile("mov.u64 %0, %%clock64;" : "=l"(c)); return (uint32_t)c; }
DEVI bool elect_one() {
    uint32_t e; asm volatile("{.reg .pred p; elect.sync _|p, 0xffffffff; selp.u32 %0, 1, 0, p;}" : "=r"(e)); return e;
}
DEVI void spin_until(uint32_t t) { while ((int)(clk32() - t) < 0) { } }

DEVI void x_load(uint32_t sb, int seg, int j, int g, const CUtensorMap* tmX) {
    const uint32_t bar = sb + RB_XF + g * (8 * X_SLOTS) + 8 * (j % X_SLOTS);
    mbar_expect_tx(bar, 4096);
    tma_load_3d(sb + RS_X + g * X_PITCH + (j % X_SLOTS) * 4096, tmX, g * 32, seg * 32, j * 2, bar);
}
DEVI void x_refill(uint32_t sb, int seg, int j, int g, int warp, const CUtensorMap* tmX) {
    const int sn = j + X_SLOTS < X_NST ? seg : seg + 1;
    if (warp == (j & 3) && sn < NSEG) {
        if (elect_one()) x_load(sb, sn, (j + X_SLOTS) % X_NST, g, tmX);
    }
}
template <int J0, int J1>
DEVI void x_stages(float* xa, const uint32_t* w, uint32_t sb, int seg, int g0, int warp, const CUtensorMap* tmX) {
#pragma unroll
    for (int j = J0; j < J1; j++) {
        const int g = (int)opaque((uint32_t)g0);
        const uint32_t dW0 = cdesc(RS_WSS, 16) + g * 768, dW1 = cdesc(RS_WSS + 8192, 16) - g * 256;
        const uint32_t dX = cdesc(RS_X + (j % X_SLOTS) * 4096, 16) + g * (X_PITCH >> 4);
        mbar_wait(sb + RB_XF + g * (8 * X_SLOTS) + 8 * (j % X_SLOTS), (j / X_SLOTS) & 1);
        wg_fence();
#pragma unroll
        for (int q = 0; q < 8; q++) {
            const int pos = r_tinv(2 * j + (q >> 2)), kk = (q >> 1) & 1, mt = q & 1;
            const uint32_t db = dX + (q >> 2) * 128 + kk * 2;
            if (j == 0 && q < 2)   wgmma_n32_rs_first(xa + 16 * mt, &w[((r_rs(pos) * 2 + kk) * 2 + mt) * 4], db);
            else if (j == 0 && q == 3) wgmma_n32_ss(xa + 16, cdesc(RS_WX, 16) + g * 128, db);
            else if (r_pos_ss(pos)) wgmma_n32_ss(xa + 16 * mt, (mt ? dW1 : dW0) + r_ss(pos) * 1024 + kk * 128, db);
            else                   wgmma_n32_rs(xa + 16 * mt, &w[((r_rs(pos) * 2 + kk) * 2 + mt) * 4], db);
        }
        wg_commit();
        if (j > J0) { wg_wait<1>(); x_refill(sb, seg, j - 1, g, warp, tmX); }
    }
    wg_wait<0>();
    reg_fence<32>(xa);
    if (J1 < X_NST) x_refill(sb, seg, J1 - 1, (int)opaque((uint32_t)g0), warp, tmX);
}
DEVI void x_finish(float* xa, uint32_t sb, int g, int warp, int lane) {
    const uint32_t base = sb + RS_X + (X_SLOTS - 1) * 4096 + (lane >> 4) * 1024 + warp * 256 + (lane & 15) * 16;
    const uint32_t mine = base + g * X_PITCH, other = base + (g ^ 1) * X_PITCH;
    sts128f(mine + 4096, xa + 24); sts128f(mine + 6144, xa + 28);
    nbar_sync(NB_WG + g, 128);
    sts128f(mine, xa + 16); sts128f(mine + 2048, xa + 20);
    nbar_sync(NB_BIG, 256);
    uint32_t p[8];
#pragma unroll
    for (int i = 0; i < 4; i++) {
        const uint4 v = lds128(other + i * 2048);
        p[2 * i]     = pack_bf16(xa[4 * i] + __uint_as_float(v.x), xa[4 * i + 1] + __uint_as_float(v.y));
        p[2 * i + 1] = pack_bf16(xa[4 * i + 2] + __uint_as_float(v.z), xa[4 * i + 3] + __uint_as_float(v.w));
    }
    __syncwarp();
    stsm4(other + 4096, p[0], p[1], p[2], p[3]);
    stsm4(other + 6144, p[4], p[5], p[6], p[7]);
    nbar_arrive(NB_XS, 256 + 32);
}
DEVI void x_send(uint32_t sb, int seg, uint32_t rank, const CUtensorMap* tmX) {
    const int lane = tid_now() & 31;
    nbar_sync(NB_XS, 256 + 32);
    fence_proxy_async();
    if (lane < 2 && seg + 1 < NSEG) x_load(sb, seg + 1, X_SLOTS - 1, lane, tmX);
    __syncwarp();
    mbar_wait(sb + RB_ATT, (seg - 1) & 1);
    if (lane < 8) {
        const int g = lane >> 2, j = lane & 3;
        bulk_copy_s2c(mapa(sb + (rank == 1 ? RS_K : RS_V) + (j + 1) * 2048 + g * 1024, 0),
                      sb + RS_X + (g ^ 1) * X_PITCH + X_SLOTS * 4096 + j * 1024, 1024, mapa(sb + RB_KV, 0));
    }
    __syncwarp();
}

template <bool XP>
DEVI void mem_pass(float* c0, float* c1, const uint32_t* w, uint32_t sb, uint32_t aA0, uint32_t aB, int g, int s) {
    const uint32_t aA1 = aA0 + 8192 - g * 16384, par = (s - 1) & 1;
    uint32_t a[16], b[2][4], e[4];
    float d0[4], d1[4];
    if (XP) ldsm4t(e, aA0 + (RS_WX - RS_WSS) - g * (8192 + 2048));
#pragma unroll
    for (int q = 0; q < 4; q++) ldsm4t(a + 4 * q, ((q & 1) ? aA1 : aA0) + (q >> 1) * 2048);
#pragma unroll
    for (int i = 0; i < 4; i++) { c0[i] = 0.f; c1[i] = 0.f; d0[i] = 0.f; d1[i] = 0.f; }
    EV(tid_now() == 0, s, 0);
    mbar_wait(sb + RB_G, par);
    EV(tid_now() == 0, s, 1);
    ldsm4(b[0], aB + r_tord(0) * 1024);
    bool in = false;
#pragma unroll
    for (int pos = 0; pos < 16; pos++) {
        if (pos + 1 < 16) {
            if (pos + 1 == R_G1 && !in) mbar_wait(sb + RB_G + 8, par);
            if (pos + 1 == R_G2) { if (!in) mbar_wait(sb + RB_G + 16, par); EV(tid_now() == 0, s, 2); }
            ldsm4(b[(pos + 1) & 1], aB + r_tord(pos + 1) * 1024);
        }
        if (pos + 2 == R_G1) in = mbar_try(sb + RB_G + 8, par);
        if (pos + 2 == R_G2) in = mbar_try(sb + RB_G + 16, par);
        if (XP && pos == 14) in = mbar_try(sb + RB_ATT, par);
        const uint32_t* bb = b[pos & 1];
        const uint32_t* aa = r_pos_ss(pos) ? a : &w[r_rs(pos) * 16];
        mma16816(c1, aa + 4, bb[0], bb[1]);
        mma16816(d1, XP && pos == 0 ? e : aa + 12, bb[2], bb[3]);
        mma16816(c0, aa, bb[0], bb[1]);
        mma16816(d0, aa + 8, bb[2], bb[3]);
        if (r_pos_ss(pos) && pos + 3 < 16) {
#pragma unroll
            for (int q = 0; q < 4; q++) ldsm4t(a + 4 * q, ((q & 1) ? aA1 : aA0) + (r_ss(pos) + 1) * 16384 + (q >> 1) * 2048);
        }
        SCHED_FENCE();
    }
    if (XP && !in) mbar_wait(sb + RB_ATT, par);
#pragma unroll
    for (int i = 0; i < 4; i++) { c1[i] += d1[i]; c0[i] += d0[i]; }
}

DEVI uint32_t k_frag_off(int lane) { return (uint32_t)((((lane >> 3) & 1) * 16 + (lane >> 4) * 8 + (lane & 7)) * 16); }
DEVI uint32_t v_frag_off(int lane) { return (uint32_t)(((lane >> 3) & 1) * 2048 + ((lane >> 4) * 8 + (lane & 7)) * 16); }
DEVI void pv_pair(float (*o)[4], const uint32_t* p, const uint32_t* v) {
#pragma unroll
    for (int n = 0; n < 4; n++) mma16816(o[n], p, v[2 * n], v[2 * n + 1]);
}
DEVI void pv_single(float (*o)[4], const uint32_t* p, const uint32_t* v) {
#pragma unroll
    for (int n = 0; n < 4; n++) mma1688(o[n], p[0], p[1], v[n]);
}
DEVI float inv_sum4(float l) {
    l += __shfl_xor_sync(0xffffffffu, l, 1);
    l += __shfl_xor_sync(0xffffffffu, l, 2);
    return rcp_fast(l);
}

DEVI void mem_attn(uint32_t sb, int s, int warp, int lane) {
    const uint32_t ka = sb + RS_K + k_frag_off(lane), va = sb + RS_V + warp * 512;
    uint32_t qa[16], vx[16];
    float sc[10];
    mbar_wait(sb + RB_KV, s & 1);
    {
        uint32_t kx[16];
#pragma unroll
        for (int q = 0; q < 4; q++) ldsm4t(kx + 4 * q, ka + (1 + warp) * 2048 + q * 512);
        nbar_sync(NB_Q, 256);
        EV(tid_now() == 0 && lds32(sb + RS_Q) != 0x12345678u, s, 8);
#pragma unroll
        for (int q = 0; q < 4; q++) ldsm4t(qa + 4 * q, sb + RS_Q + q * 512 + lane * 16);
        float c[4] = {0.f, 0.f, 0.f, 0.f}, d[4] = {0.f, 0.f, 0.f, 0.f};
#pragma unroll
        for (int q = 0; q < 4; q++) { mma16816(c, qa + 4 * q, kx[4 * q], kx[4 * q + 1]); mma16816(d, qa + 4 * q, kx[4 * q + 2], kx[4 * q + 3]); }
        asm volatile("st.shared.v2.f32 [%0], {%1,%2};" :: "r"(sb + RS_SX + warp * 256 + lane * 8), "f"(c[0] + d[2]), "f"(c[1] + d[3]) : "memory");
    }
    nbar_sync(NB_WG, 128);
#pragma unroll
    for (int n = 0; n < 4; n++) { const float2 v = lds64f(sb + RS_SX + n * 256 + lane * 8); sc[2 + 2 * n] = v.x; sc[3 + 2 * n] = v.y; }
    const uint32_t dst = sb + RS_O + warp * 512 + (lane & 3) * 128 + (lane >> 2) * 16;
    float m = fmaxf(fmaxf(fmaxf(sc[2], sc[3]), fmaxf(sc[4], sc[5])), fmaxf(fmaxf(sc[6], sc[7]), fmaxf(sc[8], sc[9])));
    mbar_wait(sb + RB_K, s & 1);
    EV(tid_now() == 0, s, 9);
    {
        float c[4][4];
#pragma unroll
        for (int q = 0; q < 4; q++) { c[q][0] = c[q][1] = c[q][2] = c[q][3] = 0.f; }
        uint32_t km[16];
#pragma unroll
        for (int q = 0; q < 4; q++) ldsm4t(km + 4 * q, ka + q * 512);
        SCHED_FENCE();
#pragma unroll
        for (int q = 0; q < 4; q++) {
            mma16816(c[2 * (q & 1)], qa + 4 * q, km[4 * q], km[4 * q + 1]);
            mma16816(c[2 * (q & 1) + 1], qa + 4 * q, km[4 * q + 2], km[4 * q + 3]);
        }
        sc[0] = (c[0][0] + c[1][2]) + (c[2][0] + c[3][2]);
        sc[1] = (c[0][1] + c[1][3]) + (c[2][1] + c[3][3]);
    }
    const bool v_in = mbar_try(sb + RB_V, s & 1);
#pragma unroll
    for (int q = 0; q < 4; q++) ldsm4(vx + 4 * q, va + 2048 + (q >> 1) * 4096 + (q & 1) * 256 + v_frag_off(lane));
    m = fmaxf(m, fmaxf(sc[0], sc[1]));
    m = fmaxf(fmaxf(m, __shfl_xor_sync(0xffffffffu, m, 1)), fmaxf(__shfl_xor_sync(0xffffffffu, m, 2), __shfl_xor_sync(0xffffffffu, m, 3)));
    if (!v_in) mbar_wait(sb + RB_V, s & 1);
    uint32_t vm[4], p[10];
    ldsm4(vm, va + lane * 16);
    const float nm = -m * SCALE_LOG2E;
    float l = 0.f;
#pragma unroll
    for (int n = 4; n >= 0; n--) {
        const float e0 = ex2(fmaf(sc[2 * n], SCALE_LOG2E, nm)), e1 = ex2(fmaf(sc[2 * n + 1], SCALE_LOG2E, nm));
        l += e0 + e1;
        p[2 * n] = pack_bf16(e0, e1); p[2 * n + 1] = __float_as_uint(e0);
    }
    float o[4][4];
#pragma unroll
    for (int n = 0; n < 4; n++) { o[n][0] = o[n][1] = o[n][2] = o[n][3] = 0.f; }
    pv_pair(o, p + 6, vx + 8);
    pv_pair(o, p + 2, vx);
    pv_single(o, p, vm);
    l = (l + __shfl_xor_sync(0xffffffffu, l, 1)) + (__shfl_xor_sync(0xffffffffu, l, 2) + __shfl_xor_sync(0xffffffffu, l, 3));
    if ((lane & 3) == 0) {
        if (warp == 0) sts32(sb + RS_INV + lane, __float_as_uint(l));
        else if (warp < 3)
            asm volatile("st.async.weak.shared::cluster.mbarrier::complete_tx::bytes.b32 [%0], %1, [%2];"
                         :: "r"(mapa(sb + RS_INV + lane, warp)), "r"(__float_as_uint(l)), "r"(mapa(sb + RB_O, warp)) : "memory");
    }
    const uint4 u = make_uint4(pack_bf16(o[0][0], o[0][1]), pack_bf16(o[1][0], o[1][1]), pack_bf16(o[2][0], o[2][1]), pack_bf16(o[3][0], o[3][1]));
    st_async128(mapa(dst, 1), u.x, u.y, u.z, u.w, mapa(sb + RB_O, 1));
    st_async128(mapa(dst, 2), u.x, u.y, u.z, u.w, mapa(sb + RB_O, 2));
    sts128(dst, u);
    __syncwarp();
    if (elect_one()) mbar_arrive(sb + RB_O);
}

DEVI void ta_scores(float* c, uint32_t sb, int seg, int cw, int lane) {
    const int mt = cw >= 3, n = cw - 3 * mt;
    const uint32_t qa = sb + RS_QX + (2 * mt + ((lane >> 3) & 1)) * 2048 + ((lane >> 4) * 8 + (lane & 7)) * 16;
    const uint32_t ka = sb + RS_K + n * 2048 + lane * 16;
    float d[4] = {0.f, 0.f, 0.f, 0.f};
    c[0] = c[1] = c[2] = c[3] = 0.f;
    mbar_wait(sb + RB_QX, seg & 1);
    mbar_wait(sb + (n == 0 ? RB_K : RB_KV), seg & 1);
#pragma unroll
    for (int j = 0; j < 4; j++) {
        uint32_t a0[4], a1[4], b[4];
        ldsm4t(a0, qa + j * 512);
        ldsm4t(b, ka + j * 512);
        ldsm4t(a1, qa + j * 512 + 256);
        mma16816(c, a0, b[0], b[1]);
        mma16816(d, a1, b[2], b[3]);
    }
    const int over = 8 * (n - 1) + 2 * (lane & 3) - 16 * mt - (lane >> 2);
    c[0] = over > 0 ? -INFINITY : c[0] + d[0];
    c[1] = over >= 0 ? -INFINITY : c[1] + d[1];
    c[2] = over > 8 ? -INFINITY : c[2] + d[2];
    c[3] = over >= 8 ? -INFINITY : c[3] + d[3];
}
DEVI void ta_output(uint32_t sb, int seg, int head, int mt, int j, int lane) {
    const uint32_t sa = sb + RS_QX + mt * 1536 + lane * 16;
    float sc[5][4];
#pragma unroll
    for (int n = 0; n < 5; n++) {
        uint4 v = make_uint4(0xFF800000u, 0xFF800000u, 0xFF800000u, 0xFF800000u);
        if (n < 2 || n == 4 || mt) v = lds128(sa + (n == 4 ? 1024 + mt * 1024 : n * 512));
        sc[n][0] = __uint_as_float(v.x); sc[n][1] = __uint_as_float(v.y); sc[n][2] = __uint_as_float(v.z); sc[n][3] = __uint_as_float(v.w);
    }
    float m0 = -INFINITY, m1 = -INFINITY;
#pragma unroll
    for (int n = 0; n < 5; n++) { m0 = fmaxf(m0, fmaxf(sc[n][0], sc[n][1])); m1 = fmaxf(m1, fmaxf(sc[n][2], sc[n][3])); }
    m0 = fmaxf(m0, __shfl_xor_sync(0xffffffffu, m0, 1)); m1 = fmaxf(m1, __shfl_xor_sync(0xffffffffu, m1, 1));
    m0 = fmaxf(m0, __shfl_xor_sync(0xffffffffu, m0, 2)); m1 = fmaxf(m1, __shfl_xor_sync(0xffffffffu, m1, 2));
    m0 *= -SCALE_LOG2E; m1 *= -SCALE_LOG2E;
    float l0 = 0.f, l1 = 0.f;
    uint32_t p[10];
#pragma unroll
    for (int n = 0; n < 5; n++) {
        const float e0 = ex2(fmaf(sc[n][0], SCALE_LOG2E, m0)), e1 = ex2(fmaf(sc[n][1], SCALE_LOG2E, m0));
        const float e2 = ex2(fmaf(sc[n][2], SCALE_LOG2E, m1)), e3 = ex2(fmaf(sc[n][3], SCALE_LOG2E, m1));
        l0 += e0 + e1; l1 += e2 + e3;
        p[2 * n] = pack_bf16(e0, e1); p[2 * n + 1] = pack_bf16(e2, e3);
    }
    const float i0 = inv_sum4(l0), i1 = inv_sum4(l1);
    mbar_wait(sb + RB_V, seg & 1);
    mbar_wait(sb + RB_KV, seg & 1);
    const uint32_t vb = sb + RS_V + j * 512;
    float o[4][4];
#pragma unroll
    for (int n = 0; n < 4; n++) { o[n][0] = o[n][1] = o[n][2] = o[n][3] = 0.f; }
    uint32_t v[8];
    ldsm4(v, vb + v_frag_off(lane)); ldsm4(v + 4, vb + v_frag_off(lane) + 256);
    pv_pair(o, p, v);
    SCHED_FENCE();
    ldsm4(v, vb + 4096 + v_frag_off(lane)); ldsm4(v + 4, vb + 4096 + v_frag_off(lane) + 256);
    pv_pair(o, p + 4, v);
    SCHED_FENCE();
    ldsm4(v, vb + 4096 + mt * 4096 + lane * 16);
    pv_single(o, p + 8, v);
    bf16* dst = g_ox + (uint32_t)((seg * 32 + mt * 16 + (lane >> 2)) * HD + head * DH + j * 32 + (lane & 3) * 8);
    asm volatile("st.global.v4.u32 [%0], {%1,%2,%3,%4};" :: "l"(dst), "r"(pack_bf16(o[0][0] * i0, o[0][1] * i0)), "r"(pack_bf16(o[1][0] * i0, o[1][1] * i0)),
                 "r"(pack_bf16(o[2][0] * i0, o[2][1] * i0)), "r"(pack_bf16(o[3][0] * i0, o[3][1] * i0)) : "memory");
    asm volatile("st.global.v4.u32 [%0], {%1,%2,%3,%4};" :: "l"(dst + 8 * HD), "r"(pack_bf16(o[0][2] * i1, o[0][3] * i1)), "r"(pack_bf16(o[1][2] * i1, o[1][3] * i1)),
                 "r"(pack_bf16(o[2][2] * i1, o[2][3] * i1)), "r"(pack_bf16(o[3][2] * i1, o[3][3] * i1)) : "memory");
}

template <bool XP>
DEVI void big_main(const uint32_t* w, const uint32_t sb, const int g, const int warp, const uint32_t rank, const int head,
                   const CUtensorMap* tmX, const bf16* xg, const unsigned E) {
    float xa[32];
    const uint32_t aB = __shfl_sync(0xffffffffu, sb + RS_MEM + (g * 32 + (tid_now() & 31)) * 16, tid_now() & 31);
#define lane0 ((int)(opaque(aB) >> 4) & 31)
    const uint32_t aA0 = sb + RS_WSS + g * (8192 + 4096) + a_frag_off(lane0, warp);
    if constexpr (XP) {
        x_stages<0, X_NST>(xa, w, sb, 0, g, warp, tmX);
        x_finish(xa, sb, g, warp, lane0);
    } else nbar_sync(NB_BIG, 256);
    for (int s = 0; s < NSEG; s++) {
        {
            float c0[4], c1[4];
            mem_pass<XP>(c0, c1, w, sb, aA0, aB, g, s);
            const int lane = lane0, t = lane & 3;
            const uint32_t xs = aB + (RS_O - RS_MEM) + (warp - g) * 512;
            const int dim = g * 64 + warp * 16 + (lane >> 2) + ((t & 1) ? 8 : 0);
            const uint32_t off = (uint32_t)((XP ? (rank == 1 ? RS_K : RS_V) : RS_Q) + dim * 16 + (t & 2) * 4);
            const uint32_t dst = XP ? mapa(sb + off, 0) : sb + off;
            const uint32_t rbar = XP ? mapa(sb + (rank == 1 ? RB_K : RB_V), 0) : 0u;
            EV(tid_now() == 0 && c0[0] != 1.2345e30f, s, 3);
            sts128f(xs + g * 2048, c1);
            nbar_sync(NB_PAIR + warp, 64);
            const uint4 v = lds128(xs + (g ^ 1) * 2048);
            const uint32_t p0 = pack_bf16(c0[0] + __uint_as_float(v.x), c0[1] + __uint_as_float(v.y));
            const uint32_t p1 = pack_bf16(c0[2] + __uint_as_float(v.z), c0[3] + __uint_as_float(v.w));
            const uint32_t rcv = __shfl_xor_sync(0xffffffffu, (t & 1) ? p0 : p1, 1);
            const uint32_t lo = (t & 1) ? rcv : p0, hi = (t & 1) ? p1 : rcv;
            if constexpr (XP) st_async64(dst, lo, hi, rbar);
            else if (s < NSEG - 1) {
                asm volatile("st.shared.v2.u32 [%0], {%1,%2};" :: "r"(dst), "r"(lo), "r"(hi) : "memory");
                if (g == 1) nbar_arrive(NB_Q, 256);
            }
            EV(tid_now() == 0, s, 4);
        }
        if constexpr (XP) {
            if (s == NSEG - 1) break;
            x_stages<0, X_NA>(xa, w, sb, s + 1, g, warp, tmX);
            EV(tid_now() == 0, s, 5);
            EVCAL(s);
            nbar_sync(NB_WO, 384);
            EV(tid_now() == 0 && lds32(sb + RS_O) != 0x12345678u, s, 6);
            x_stages<X_NA, X_NST>(xa, w, sb, s + 1, g, warp, tmX);
            EV(tid_now() == 0, s, 7);
            x_finish(xa, sb, g, warp, lane0);
        } else {
            if (g == 0) {
                if (s < NSEG - 1) mem_attn(sb, s, warp, lane0);
            } else {
                if (s == 0 && warp == 0) {
                    wait_count_warp(&g_cnt_q[0], 64 * E);
                    if (elect_one()) {
                        asm volatile("fence.proxy.async;" ::: "memory");
                        mbar_expect_tx(sb + RB_QX, 8192);
                        bulk_load(sb + RS_QX, g_qx + (size_t)head * 4096, 8192, sb + RB_QX);
                    }
                    __syncwarp();
                }
                float sc[8];
                const int t2 = warp == 3 ? 3 : (warp + 1) % 3;
                ta_scores(sc, sb, s, 4 + warp, lane0);
                ta_scores(sc + 4, sb, s, t2, lane0);
                nbar_sync(NB_WG + 1, 128);
                sts128f(aB + (RS_QX - RS_MEM) + (3 + warp) * 512, sc);
                sts128f(aB + (RS_QX - RS_MEM) + (t2 - 1) * 512, sc + 4);
            }
            EVCAL(s);
            nbar_sync(NB_BIG, 256);
            EV(tid_now() == 0 && lds32(sb + RS_O) != 0x12345678u, s, 6);
            ta_output(sb, s, head, g, warp, lane0);
            nbar_sync(NB_BIG, 256);
            EV(tid_now() == 0 && lds32(sb + RS_O) != 0x12345678u, s, 7);
            if (g == 0 && warp == 0 && s + 1 < NSEG) {
                if (elect_one()) {
                    mbar_arrive_remote(mapa(sb + RB_ATT, 1));
                    mbar_arrive_remote(mapa(sb + RB_ATT, 2));
                    mbar_expect_tx(sb + RB_KV, 16384);
                    mbar_expect_tx(sb + RB_K, 2048);
                    mbar_expect_tx(sb + RB_V, 2048);
                    mbar_arrive(sb + RB_T);
                }
                __syncwarp();
            }
        }
    }
    if constexpr (!XP) { if (tid_now() == 0) signal_count(&g_prog[(NSEG - 1) >> 2]); }
#undef lane0
}

template <int T, int K0, int K1>
DEVI void wo_part(float* acc) {
    constexpr uint32_t dWo = cdesc(T < 5 ? RS_WO + T * 16384 : RS_WO5, 16), dO = cdesc(RS_O, 128);
#pragma unroll
    for (int kk = K0; kk < K1; kk++) {
        if (kk == 0) { if (T < 3) wgmma_n8_ss_first<0>(acc, dWo, dO); else wgmma_n8_ss<0, 0>(acc, dWo, dO); }
        else wgmma_n8_ss<0, 1>(acc, dWo + kk * 128, dO + kk * 16);
    }
    wg_commit();
}
DEVI void red3(uint8_t* p, float a, float b, float c, float one) {
    asm volatile("red.relaxed.gpu.global.add.v4.f32 [%0], {%1,%2,%3,%4};" :: "l"(p), "f"(a), "f"(b), "f"(c), "f"(one) : "memory");
}
constexpr int ACC_CH = 3 * 16 * 1024;
#define WO_LA 2
template <bool Q>
DEVI void wo_phase(uint32_t sb, int s, uint8_t* p, uint32_t ainv, uint32_t z) {
    float a0[4], a1[4], a2[4];
    const float cu = __uint_as_float(z | 0x3F800000u), cv = __uint_as_float(z + 0x3F800000u);
    const float2 iv = lds64f(ainv);
    fence_proxy_async();
    const float i0 = rcp_fast(iv.x), i1 = rcp_fast(iv.y);
    wg_fence();
    wo_part<0, 0, 8>(a0); wo_part<1, 0, 8>(a1); wo_part<2, 0, WO_LA>(a2);
    wg_wait<2>(); reg_fence<4>(a0);
    red3(p, a0[0] * i0, a0[1] * i1, a0[2] * i0, cu);
    SCHED_FENCE();
    EV(tid_now() == 256, s, 11);
    wg_wait<1>(); reg_fence<4>(a1);
    red3(p + ACC_CH, a1[0] * i0, a1[1] * i1, a0[3] * i1, cv);
    SCHED_FENCE();
    wg_fence();
    wo_part<2, WO_LA, 8>(a2); wo_part<3, 0, WO_LA>(a0);
    wg_wait<1>(); reg_fence<4>(a2);
    red3(p + 2 * ACC_CH, a1[2] * i0, a1[3] * i1, a2[0] * i0, cu);
    red3(p + 3 * ACC_CH, a2[2] * i0, a2[3] * i1, a2[1] * i1, cv);
    SCHED_FENCE();
    wg_fence();
    wo_part<3, WO_LA, 8>(a0); wo_part<4, 0, 8>(a1);
    if (Q) {
        wo_part<5, 0, 8>(a2);
        wg_wait<2>(); reg_fence<4>(a0);
        red3(p + 4 * ACC_CH, a0[0] * i0, a0[1] * i1, a0[2] * i0, cu);
        SCHED_FENCE();
        wg_wait<1>(); reg_fence<4>(a1);
        red3(p + 5 * ACC_CH, a1[0] * i0, a1[1] * i1, a0[3] * i1, cv);
        SCHED_FENCE();
        wg_wait<0>(); reg_fence<4>(a2);
        red3(p + 6 * ACC_CH, a1[2] * i0, a1[3] * i1, a2[0] * i0, cu);
        red3(p + 7 * ACC_CH, a2[2] * i0, a2[3] * i1, a2[1] * i1, cv);
    } else {
        wg_wait<1>(); reg_fence<4>(a0);
        nbar_arrive(NB_WO, 384);
        red3(p + 4 * ACC_CH, a0[0] * i0, a0[1] * i1, a0[2] * i0, cu);
        SCHED_FENCE();
        wg_wait<0>(); reg_fence<4>(a1);
        red3(p + 5 * ACC_CH, a1[0] * i0, a1[1] * i1, a0[3] * i1, cv);
        red3(p + 6 * ACC_CH, a1[2] * i0, a1[3] * i1, 0.f, cu);
    }
}
DEVI void acc_load(float (*v)[4], const uint8_t* src) {
#pragma unroll
    for (int j = 0; j < 4; j++) ld_rlx4f(v[j], src + j * 1024);
}
DEVI void acc_check(float (*v)[4], const uint8_t* src, uint32_t* u, int s, int c) {
    int n = 0;
    while (!__all_sync(0xffffffffu, v[0][3] == 32.f && v[1][3] == 32.f && v[2][3] == 32.f && v[3][3] == 32.f)) {
        acc_load(v, src);
        if (++n > SPIN_LIMIT) TRAP(0x20000000u | (s << 8) | c);
    }
    u[0] = pack_bf16(v[0][0], v[1][0]); u[1] = pack_bf16(v[2][0], v[3][0]); u[2] = pack_bf16(v[0][1], v[1][1]); u[3] = pack_bf16(v[2][1], v[3][1]);
    u[4] = pack_bf16(v[0][2], v[1][2]); u[5] = pack_bf16(v[2][2], v[3][2]);
}
DEVI void acc_send(const uint32_t* u, uint32_t df, uint32_t dh, uint32_t bar, uint32_t r1, uint32_t r2, bool half, uint32_t bytes) {
    st_async64(mapa(df, r1), u[0], u[1], mapa(bar, r1));
    st_async64(mapa(df, r2), u[0], u[1], mapa(bar, r2));
    st_async64(mapa(df + 64, r1), u[2], u[3], mapa(bar, r1));
    st_async64(mapa(df + 64, r2), u[2], u[3], mapa(bar, r2));
    if (half) {
        st_async64(mapa(dh, r1), u[4], u[5], mapa(bar, r1));
        st_async64(mapa(dh, r2), u[4], u[5], mapa(bar, r2));
    }
    sts64(df, u[0], u[1]);
    sts64(df + 64, u[2], u[3]);
    if (half) sts64(dh, u[4], u[5]);
    __syncwarp();
    if (elect_one()) mbar_expect_tx(bar, bytes);
}
template <bool Q, bool SECOND>
DEVI void stage_sums(uint32_t sb, int s, uint32_t rank, int warp, const uint8_t* src, uint32_t col, uint32_t gate) {
    float v[4][4];
    uint32_t u[6];
    spin_until(gate);
    EV(elect_one(), s, 16 + warp);
    acc_load(v, src);
    const uint32_t df = col + ((warp + 1) >> 1) * 1024 + (warp >> 1) * 128;
    const uint32_t dh = col + (warp >> 1) * 2048 + (warp < 2 ? 128 : 0) + (warp & 1) * 64;
    const uint32_t r1 = Q ? 1 : 0, r2 = Q ? 2 : 3 - rank;
    acc_check(v, src, u, s, warp + (Q ? 0 : 8));
    EV(elect_one(), s, 24 + warp);
    acc_send(u, df, dh, sb + RB_G + 8 * (warp >> 1), r1, r2, true, (warp & 1) ? 0u : 3072u);
    SCHED_FENCE();
    if (SECOND) acc_load(v, src + 4 * ACC_CH);
    EV(elect_one(), s, 20 + warp);
    if (SECOND) {
        acc_check(v, src + 4 * ACC_CH, u, s, warp + 4 + (Q ? 0 : 8));
        EV(elect_one(), s, 28 + warp);
        acc_send(u, df + 3072, dh + 3072, sb + RB_G + 16, r1, r2, Q || warp != 2, warp ? 0u : (Q ? 4096u : 5120u));
    }
}
DEVI void wo_permute(uint32_t a, int n) {
#pragma unroll 4
    for (int i = 0; i < n; i++, a += 2048) {
        const uint4 v = lds128(a);
        sts128(a, make_uint4(__byte_perm(v.x, v.z, 0x5410), __byte_perm(v.x, v.z, 0x7632), __byte_perm(v.y, v.w, 0x5410), __byte_perm(v.y, v.w, 0x7632)));
    }
}
DEVI void acc_clear(int slot, int idx) {
    const int lane = tid_now() & 31;
    uint8_t* p = g_acc + slot * 128 + (idx * 6 + (lane >> 3)) * 1024 + (lane & 7) * 16;
    st_rlx4(p, 0u, 0u, 0u, 0u);
    if (lane < 16) st_rlx4(p + 4096, 0u, 0u, 0u, 0u);
}

template <bool Q>
DEVI void aux_main(uint32_t sb, int warp, uint32_t rank, int head, const CUtensorMap* tmX, const bf16* xg, unsigned E, int delay, uint32_t zero) {
    const uint32_t lo = __shfl_sync(0xffffffffu, ((tid_now() >> 3) & 3) * 1024 + (tid_now() & 7) * 16, tid_now() & 31);
    if (!Q && warp == 3) x_send(sb, 0, rank, tmX);
    for (int s = 0; s < NSEG - 1; s++) {
        if (!Q && warp == 0 && elect_one()) mbar_expect_tx(sb + RB_O, 2048 + 32);
        __syncwarp();
        const uint32_t slot = (s & 3) * 128 + rank * 16384;
        mbar_wait(sb + RB_O, s & 1);
        EV(tid_now() == 256, s, 10);
        wo_phase<Q>(sb, s, g_acc + (uint32_t)(slot + warp * 4096 + opaque(lo)), sb + RS_INV + ((opaque(lo) >> 1) & 24), opaque(zero));
        SCHED_FENCE();
        const uint32_t t_o = clk32();
        EV(tid_now() == 256, s, 12);
        {
            const uint32_t l = opaque(lo);
            const uint8_t* src = g_acc + (uint32_t)(slot + warp * ACC_CH + (l & 0xC00) * 4 + (l & 0x70));
            const uint32_t col = sb + RS_MEM + (Q ? 0 : (rank == 1 ? 6 : 11)) * 1024 + ((l >> 2) & 0x300) + (l & 0x30) + ((l >> 3) & 8);
            if (Q || warp < 3) stage_sums<Q, true>(sb, s, rank, warp, src, col, t_o + delay);
            else               stage_sums<Q, false>(sb, s, rank, 3, src, col, t_o + delay);
        }
        EV(tid_now() == 256 + 64, s, 14);
        if (warp == 3) {
            if (Q) {
                mbar_wait(sb + RB_T, s & 1);
                if ((s & 7) == 7) wait_count_warp(&g_cnt_q[(s + 1) >> 3], 64 * E);
                if (elect_one()) {
                    if ((s & 7) == 7) asm volatile("fence.proxy.async;" ::: "memory"); else fence_proxy_async();
                    mbar_expect_tx(sb + RB_QX, 8192);
                    bulk_load(sb + RS_QX, g_qx + ((size_t)(s + 1) * NH + head) * 4096, 8192, sb + RB_QX);
                    signal_count(&g_prog[s >> 2]);
                    if (s + 4 < NSEG) l2_prefetch(xg + (size_t)((s + 4) * 32 + head) * DM, 2048);
                }
                __syncwarp();
            } else {
                x_send(sb, s + 1, rank, tmX);
                if (s + 2 < NSEG - 1) { acc_clear((s + 2) & 3, 2 * head + (int)rank - 1); __threadfence(); }
            }
        }
    }
}

DEVI void load_weights(uint32_t sb, const CUtensorMap* tmW, const CUtensorMap* tmWo, int head, uint32_t rank) {
    const uint32_t bW = sb + RB_W, bSF = sb + RB_SF, bSE = sb + RB_SE;
    const int ntile = rank == 0 ? 6 : 5, tile0 = rank == 0 ? 0 : (rank == 1 ? 6 : 11);
    mbar_expect_tx(bW, R_NSS * 16384 + ntile * 16384);
    if (rank == 0) tma_load_wo(sb + RS_WO5, tmWo, 5 * 64, head * 4, bW);
    for (int pos = 0; pos < 16; pos++) {
        const int k = (int)((R_TORD_PACK >> (4 * pos)) & 15ull) * 64;
        if (r_pos_ss(pos)) {
            const uint32_t dst = sb + RS_WSS + (pos / 3) * 16384;
            tma_load_2d(dst, tmW, head * DH, k, bW);
            tma_load_2d(dst + 8192, tmW, head * DH + 64, k, bW);
        } else {
            const int rd = pos - pos / 3, slot = rd % 5;
            if (rd >= 5) mbar_wait(bSE + 8 * slot, ((rd / 5) - 1) & 1);
            mbar_expect_tx(bSF + 8 * slot, 16384);
            const uint32_t dst = sb + RS_WO + slot * 16384;
            tma_load_2d(dst, tmW, head * DH, k, bSF + 8 * slot);
            tma_load_2d(dst + 8192, tmW, head * DH + 64, k, bSF + 8 * slot);
        }
    }
    for (int slot = 0; slot < 5; slot++) {
        const int last = slot + 10 < R_NRS ? slot + 10 : slot + 5;
        mbar_wait(bSE + 8 * slot, (last / 5) & 1);
        tma_load_wo(sb + RS_WO + slot * 16384, tmWo, (tile0 + slot) * 64, head * 4, bW);
    }
}
template <bool XP>
DEVI void big_prologue(uint32_t* w, uint32_t sb, int g, int warp, const bf16* __restrict__ mem0) {
    const int tid = tid_now(), lane = tid & 31;
#pragma unroll 1
    for (int j = 0; j < 4; j++) {
        const int c = tid + j * 256;
        sts128(sb + RS_MEM + c * 16, *(const uint4*)(mem0 + (c & 7) * DM + (c >> 3) * 8));
    }
    const uint32_t a0 = sb + RS_WO + g * (8192 + 4096) + a_frag_off(lane, warp), a1 = a0 + 8192 - g * 16384;
#pragma unroll
    for (int rd = 0; rd < R_NRS; rd++) {
        const int slot = rd % 5;
        mbar_wait(sb + RB_SF + 8 * slot, (rd / 5) & 1);
#pragma unroll
        for (int q = 0; q < 4; q++) {
            if (XP && rd == 0 && q == 3) {
                sts128(sb + RS_WX + g * 2048 + (tid & 127) * 16, lds128(sb + RS_WO + 8192 - g * 4096 + 2048 + (tid & 127) * 16));
                fence_proxy_async();
                nbar_sync(NB_WG + g, 128);
            } else ldsm4t(&w[rd * 16 + q * 4], ((q & 1) ? a1 : a0) + slot * 16384 + (q >> 1) * 2048);
        }
        mbar_arrive(sb + RB_SE + 8 * slot);
    }
    mbar_wait(sb + RB_W, 0);
}

__global__ void __cluster_dims__(3, 1, 1) __launch_bounds__(384, 1)
k_rec(const __grid_constant__ CUtensorMap tmWq, const __grid_constant__ CUtensorMap tmWk, const __grid_constant__ CUtensorMap tmWv,
      const __grid_constant__ CUtensorMap tmWo, const __grid_constant__ CUtensorMap tmX, const bf16* __restrict__ mem0, const bf16* __restrict__ xg,
      int hq0, int hqw, int hk0, int hkw, uint32_t zero) {
    extern __shared__ __align__(1024) uint8_t smem_raw[];
    const uint32_t sb = smem_u32(smem_raw);
    if ((sb & 0x3FFFFu) != SB0) __trap();
    const int tid = threadIdx.x;
    const int wg = __shfl_sync(0xffffffffu, tid >> 7, 0), warp = __shfl_sync(0xffffffffu, (tid >> 5) & 3, 0);
    uint32_t rank; asm("mov.u32 %0, %%cluster_ctarank;" : "=r"(rank));
    const int head = blockIdx.x / 3;
    if (tid == 0) {
        mbar_init(sb + RB_G, 2);
        mbar_init(sb + RB_G + 8, 2);
        mbar_init(sb + RB_G + 16, rank == 0 ? 4 : 3);
        mbar_init(sb + RB_T, 1);
        mbar_init(sb + RB_K, 1); mbar_init(sb + RB_V, 1); mbar_init(sb + RB_KV, 1); mbar_init(sb + RB_QX, 1);
        mbar_init(sb + RB_O, rank == 0 ? 4 : 1); mbar_init(sb + RB_ATT, 1); mbar_init(sb + RB_W, 1);
        for (int i = 0; i < 5; i++) { mbar_init(sb + RB_SF + 8 * i, 1); mbar_init(sb + RB_SE + 8 * i, 256); }
        for (int i = 0; i < 2 * X_SLOTS; i++) mbar_init(sb + RB_XF + 8 * i, 1);
        fence_mbar_init();
        if (rank == 0) { mbar_expect_tx(sb + RB_KV, 16384); mbar_expect_tx(sb + RB_K, 2048); mbar_expect_tx(sb + RB_V, 2048); }
        atomicAdd(&g_resident, 1u);
    }
    __syncthreads();
    cluster_sync();

    if (wg < 2) {
        reg_inc<REG_KB>();
        if (rank != 0) {
            uint32_t w[R_NRS * 16];
            if ((tid & 127) == 0) for (int j = 0; j < X_SLOTS; j++) x_load(sb, 0, j, wg, &tmX);
            __syncwarp();
            big_prologue<true>(w, sb, wg, warp, mem0);
            big_main<true>(w, sb, wg, warp, rank, head, &tmX, xg, 0u);
        } else {
            uint32_t w[R_NRS * 16];
            big_prologue<false>(w, sb, wg, warp, mem0);
            big_main<false>(w, sb, wg, warp, rank, head, &tmX, xg, *(volatile unsigned*)&g_epoch + 1);
        }
    } else {
        reg_dec<504 - 2 * REG_KB>();
        const unsigned E = __shfl_sync(0xffffffffu, *(volatile unsigned*)&g_epoch + 1, 0);
        if (warp == 3 && rank != 0) {
            acc_clear(0, 2 * head + (int)rank - 1); acc_clear(1, 2 * head + (int)rank - 1);
            __threadfence();
            __syncwarp();
            if (tid == 256 + 96) atomicAdd(&g_zero, 1u);
        }
        if (tid == 256) {
            if (rank == 0) for (int sg = 0; sg < 4; sg++) l2_prefetch(xg + (size_t)(sg * 32 + head) * DM, 2048);
            load_weights(sb, rank == 0 ? &tmWq : (rank == 1 ? &tmWk : &tmWv), &tmWo, head, rank);
            wait_count(&g_zero, E * 64u);
        }
        __syncwarp();
        mbar_wait(sb + RB_W, 0);
        wo_permute(sb + RS_WO + (tid & 127) * 16, 40);
        if (rank == 0) wo_permute(sb + RS_WO5 + (tid & 127) * 16, 8);
        fence_proxy_async();
        nbar_sync(NB_AUX, 128);
        if (rank == 0) aux_main<true>(sb, warp, rank, head, &tmX, xg, E, hq0 + warp * hqw, zero);
        else           aux_main<false>(sb, warp, rank, head, &tmX, xg, E, hk0 + warp * hkw, zero);
    }
    __syncthreads();
    cluster_sync();
}

__global__ void k_gate() {
    if (threadIdx.x == 0) {
        int n = 0;
        while (*(volatile unsigned*)&g_resident < 96u) { __nanosleep(200); if (++n > (1 << 22)) __trap(); }
        g_resident = 0;
    }
}

typedef CUresult (*EncodeFn)(CUtensorMap*, CUtensorMapDataType, cuuint32_t, void*, const cuuint64_t*, const cuuint64_t*,
                             const cuuint32_t*, const cuuint32_t*, CUtensorMapInterleave, CUtensorMapSwizzle,
                             CUtensorMapL2promotion, CUtensorMapFloatOOBfill);

static CUtensorMap make_map(EncodeFn fn, const void* ptr, uint64_t inner, uint64_t outer, uint32_t box_inner, uint32_t box_outer) {
    CUtensorMap m;
    cuuint64_t dims[2] = {inner, outer};
    cuuint64_t strides[1] = {inner * 2};
    cuuint32_t box[2] = {box_inner, box_outer};
    cuuint32_t es[2] = {1, 1};
    fn(&m, CU_TENSOR_MAP_DATA_TYPE_BFLOAT16, 2, const_cast<void*>(ptr), dims, strides, box, es,
       CU_TENSOR_MAP_INTERLEAVE_NONE, CU_TENSOR_MAP_SWIZZLE_128B, CU_TENSOR_MAP_L2_PROMOTION_L2_256B, CU_TENSOR_MAP_FLOAT_OOB_FILL_NONE);
    return m;
}

static CUtensorMap make_wo_map(EncodeFn fn, const void* ptr, uint32_t ngrp) {
    CUtensorMap m;
    cuuint64_t dims[5] = {DM, 2, 4, 4, HD / 32};
    cuuint64_t strides[4] = {DM * 2, 8 * DM * 2, 2 * DM * 2, 32 * DM * 2};
    cuuint32_t box[5] = {64, 2, 4, 4, ngrp};
    cuuint32_t es[5] = {1, 1, 1, 1, 1};
    fn(&m, CU_TENSOR_MAP_DATA_TYPE_BFLOAT16, 5, const_cast<void*>(ptr), dims, strides, box, es,
       CU_TENSOR_MAP_INTERLEAVE_NONE, CU_TENSOR_MAP_SWIZZLE_128B, CU_TENSOR_MAP_L2_PROMOTION_L2_256B, CU_TENSOR_MAP_FLOAT_OOB_FILL_NONE);
    return m;
}

struct Maps {
    PMaps post;
    CUtensorMap wq16, wk16, wv16, wo128, x32;
};

extern "C" void kernel_launch(void* const* d_in, const int* in_sizes, int n_in, void* d_out, int out_size) {
    const bf16* A_x   = (const bf16*)d_in[0];
    const bf16* A_mem = (const bf16*)d_in[1];
    const bf16* A_Wq  = (const bf16*)d_in[2];
    const bf16* A_Wk  = (const bf16*)d_in[3];
    const bf16* A_Wv  = (const bf16*)d_in[4];
    const bf16* A_Wo  = (const bf16*)d_in[5];
    const bf16* B_x   = (const bf16*)d_in[7];
    const bf16* B_w   = (const bf16*)d_in[8];
    const bf16* B_wo  = (const bf16*)d_in[9];

    static EncodeFn fn = nullptr;
    static Maps mp;
    static const void* cached[10];
    const void* cur[10] = {A_x, A_mem, A_Wq, A_Wk, A_Wv, A_Wo, B_x, B_w, B_wo, d_out};
    bool same = fn != nullptr;
    for (int i = 0; i < 10 && same; i++) same = cached[i] == cur[i];
    if (!same) {
        if (!fn) {
            void* p = nullptr; cudaDriverEntryPointQueryResult qr;
            cudaGetDriverEntryPoint("cuTensorMapEncodeTiled", &p, cudaEnableDefault, &qr);
            fn = (EncodeFn)p;
            cudaFuncSetAttribute(k_post, cudaFuncAttributeMaxDynamicSharedMemorySize, P_SMEM);
            cudaFuncSetAttribute(k_rec, cudaFuncAttributeMaxDynamicSharedMemorySize, R_SMEM);
            cudaFuncAttributes fa; cudaFuncGetAttributes(&fa, k_gate);
        }
        void *p_ox, *p_bqkv, *p_bo;
        cudaGetSymbolAddress(&p_ox, g_ox); cudaGetSymbolAddress(&p_bqkv, g_bqkv); cudaGetSymbolAddress(&p_bo, g_bo);
        mp.post.wq   = make_map(fn, A_Wq, HD, DM, 64, 64);
        mp.post.wo   = make_wo_map(fn, A_Wo, 2);
        mp.post.bw   = make_map(fn, B_w, 3 * DM, DM, 64, 64);
        mp.post.bwo  = make_map(fn, B_wo, DM, DM, 64, 64);
        mp.post.x    = make_map(fn, A_x, DM, S_TOK, 64, 256);
        mp.post.bx   = make_map(fn, B_x, DM, S_TOK, 64, 256);
        mp.post.bo   = make_map(fn, p_bo, DM, S_TOK, 64, 256);
        mp.post.ox   = make_map(fn, p_ox, HD, S_TOK, 64, 128);
        mp.post.cb   = make_map(fn, p_bqkv, 3 * DM, S_TOK, 64, 64);
        mp.post.cout = make_map(fn, d_out, 2 * DM, S_TOK, 64, 64);
        {
            cuuint64_t dims[4] = {DM, 3, 2, S_TOK / 2};
            cuuint64_t strides[3] = {DM * 2, 3 * DM * 2, 3 * DM * 4};
            cuuint32_t box[4] = {64, 3, 1, 40};
            cuuint32_t es[4] = {1, 1, 1, 1};
            fn(&mp.post.b40, CU_TENSOR_MAP_DATA_TYPE_BFLOAT16, 4, p_bqkv, dims, strides, box, es,
               CU_TENSOR_MAP_INTERLEAVE_NONE, CU_TENSOR_MAP_SWIZZLE_128B, CU_TENSOR_MAP_L2_PROMOTION_L2_256B, CU_TENSOR_MAP_FLOAT_OOB_FILL_NONE);
        }
        mp.wq16 = make_map(fn, A_Wq, HD, DM, 64, 64);
        mp.wk16 = make_map(fn, A_Wk, HD, DM, 64, 64);
        mp.wv16 = make_map(fn, A_Wv, HD, DM, 64, 64);
        mp.wo128 = make_wo_map(fn, A_Wo, 4);
        {
            cuuint64_t dims[3] = {64, S_TOK, DM / 64};
            cuuint64_t strides[2] = {DM * 2, 128};
            cuuint32_t box[3] = {32, 32, 2};
            cuuint32_t es[3] = {1, 1, 1};
            fn(&mp.x32, CU_TENSOR_MAP_DATA_TYPE_BFLOAT16, 3, const_cast<bf16*>(A_x), dims, strides, box, es,
               CU_TENSOR_MAP_INTERLEAVE_NONE, CU_TENSOR_MAP_SWIZZLE_64B, CU_TENSOR_MAP_L2_PROMOTION_L2_128B, CU_TENSOR_MAP_FLOAT_OOB_FILL_NONE);
        }
        for (int i = 0; i < 10; i++) cached[i] = cur[i];
    }

    cudaStream_t st = cudaStreamPerThread;
    static cudaStream_t side = nullptr;
    static cudaEvent_t evFork, evSide;
    if (!side) {
        cudaStreamCreateWithFlags(&side, cudaStreamNonBlocking);
        cudaEventCreateWithFlags(&evFork, cudaEventDisableTiming);
        cudaEventCreateWithFlags(&evSide, cudaEventDisableTiming);
    }
    cudaEventRecord(evFork, st);
    int hq0 = 500, hqw = 150, hk0 = 450, hkw = 150;
    k_rec<<<96, 384, R_SMEM, st>>>(mp.wq16, mp.wk16, mp.wv16, mp.wo128, mp.x32, A_mem, A_x, hq0, hqw, hk0, hkw, 0u);
    cudaStreamWaitEvent(side, evFork, 0);
    k_gate<<<1, 32, 0, side>>>();
    k_post<<<132, 384, P_SMEM, side>>>(mp.post);
    cudaEventRecord(evSide, side);
    cudaStreamWaitEvent(st, evSide, 0);
}
```

```cpp
#include <cuda_runtime.h>
#include <cuda_bf16.h>
#include <cuda.h>
#include <stdint.h>

typedef __nv_bfloat16 bf16;

constexpr int S_TOK = 2048;
constexpr int DM    = 1024;
constexpr int NH    = 32;
constexpr int DH    = 128;
constexpr int NSEG  = 64;
constexpr int HD    = NH * DH;

__device__ __align__(1024) bf16 g_qx[NSEG * NH * 4 * DH * 8];
__device__ __align__(1024) bf16 g_ox[S_TOK * HD];
__device__ __align__(1024) bf16 g_bqkv[S_TOK * 3 * DM];
__device__ __align__(1024) bf16 g_bo[S_TOK * DM];
__device__ __align__(1024) uint8_t g_acc[192 * 1024];

#define EV(cond, s, k) do {} while (0)
#define EVCAL(s) do {} while (0)

__device__ unsigned g_epoch, g_qctr, g_done, g_zero;
__device__ unsigned g_cnt_b1[8], g_cnt_b2[8], g_cnt_q[8], g_prog[16], g_cnt_sk[32];
__device__ __align__(1024) float g_skp[2 * 8 * 4 * 2 * 128 * 64];
__device__ __align__(128) unsigned long long g_tlast;
__device__ __align__(128) unsigned g_pred;
__device__ __forceinline__ unsigned long long gtime() { unsigned long long g; asm volatile("mov.u64 %0, %%globaltimer;" : "=l"(g)); return g; }
#define TLOG(i, k, v) do {} while (0)
__device__ unsigned g_resident;

#define DEVI __device__ __forceinline__

DEVI uint32_t opaque(uint32_t v) { uint32_t r; asm volatile("mov.u32 %0, %1;" : "=r"(r) : "r"(v)); return r; }
DEVI uint32_t smem_u32(const void* p) { return (uint32_t)__cvta_generic_to_shared(p); }

#define TRAP(code) __trap()
constexpr int SPIN_LIMIT = 1 << 22;
#define MBAR_HINT_NS 20000u
constexpr int SPIN_LIMIT_MBAR = 1 << 17;

DEVI void mbar_init(uint32_t bar, uint32_t cnt) { asm volatile("mbarrier.init.shared::cta.b64 [%0], %1;" :: "r"(bar), "r"(cnt)); }
DEVI void mbar_expect_tx(uint32_t bar, uint32_t bytes) {
    asm volatile("mbarrier.arrive.expect_tx.shared::cta.b64 _, [%0], %1;" :: "r"(bar), "r"(bytes) : "memory");
}
DEVI void mbar_arrive(uint32_t bar) { asm volatile("mbarrier.arrive.shared::cta.b64 _, [%0];" :: "r"(bar) : "memory"); }
DEVI bool mbar_try(uint32_t bar, uint32_t parity) {
    uint32_t ok;
    asm volatile("{.reg .pred p; mbarrier.try_wait.parity.shared::cta.b64 p, [%1], %2; selp.u32 %0, 1, 0, p;}"
                 : "=r"(ok) : "r"(bar), "r"(parity) : "memory");
    return ok;
}
DEVI bool mbar_try_cluster(uint32_t bar, uint32_t parity) {
    uint32_t ok;
    asm volatile("{.reg .pred p; mbarrier.try_wait.parity.acquire.cluster.shared::cta.b64 p, [%1], %2; selp.u32 %0, 1, 0, p;}"
                 : "=r"(ok) : "r"(bar), "r"(parity) : "memory");
    return ok;
}
DEVI bool mbar_try_hint(uint32_t bar, uint32_t parity) {
    uint32_t ok;
    asm volatile("{.reg .pred p; mbarrier.try_wait.parity.shared::cta.b64 p, [%1], %2, %3; selp.u32 %0, 1, 0, p;}"
                 : "=r"(ok) : "r"(bar), "r"(parity), "r"(MBAR_HINT_NS) : "memory");
    return ok;
}
DEVI void mbar_wait(uint32_t bar, uint32_t parity) {
    int n = 0;
    while (!mbar_try(bar, parity)) { if (++n > SPIN_LIMIT) TRAP(bar | (parity << 31)); }
}
DEVI void mbar_wait_sleepy(uint32_t bar, uint32_t parity) {
    int n = 0;
    while (!mbar_try_hint(bar, parity)) { if (++n > SPIN_LIMIT_MBAR) __trap(); }
}
DEVI void mbar_wait_cluster(uint32_t bar, uint32_t parity) {
    int n = 0;
    while (!mbar_try_cluster(bar, parity)) { if (++n > SPIN_LIMIT) __trap(); }
}
DEVI void mbar_spin(uint32_t bar, uint32_t parity) {
    uint32_t ok; int n = 0;
    do {
        asm volatile("{.reg .pred p; mbarrier.test_wait.parity.shared::cta.b64 p, [%1], %2; selp.u32 %0, 1, 0, p;}"
                     : "=r"(ok) : "r"(bar), "r"(parity) : "memory");
        if (++n > SPIN_LIMIT) __trap();
    } while (!ok);
}
DEVI void fence_mbar_init() { asm volatile("fence.mbarrier_init.release.cluster;" ::: "memory"); }
DEVI void fence_proxy_async() { asm volatile("fence.proxy.async.shared::cta;" ::: "memory"); }
DEVI void cluster_sync() {
    asm volatile("barrier.cluster.arrive.release.aligned;\n barrier.cluster.wait.acquire.aligned;" ::: "memory");
}
DEVI void nbar_sync(int id, int n) { asm volatile("bar.sync %0, %1;" :: "r"(id), "r"(n) : "memory"); }
DEVI void nbar_arrive(int id, int n) { asm volatile("bar.arrive %0, %1;" :: "r"(id), "r"(n) : "memory"); }

DEVI void tma_load_2d(uint32_t dst, const CUtensorMap* map, int x, int y, uint32_t bar) {
    asm volatile("cp.async.bulk.tensor.2d.shared::cluster.global.mbarrier::complete_tx::bytes [%0], [%1, {%3, %4}], [%2];"
                 :: "r"(dst), "l"(map), "r"(bar), "r"(x), "r"(y) : "memory");
}
DEVI void tma_load_3d(uint32_t dst, const CUtensorMap* map, int x, int y, int z, uint32_t bar) {
    asm volatile("cp.async.bulk.tensor.3d.shared::cluster.global.mbarrier::complete_tx::bytes [%0], [%1, {%3, %4, %5}], [%2];"
                 :: "r"(dst), "l"(map), "r"(bar), "r"(x), "r"(y), "r"(z) : "memory");
}
DEVI void tma_load_wo(uint32_t dst, const CUtensorMap* map, int col, int k32, uint32_t bar) {
    asm volatile("cp.async.bulk.tensor.5d.shared::cluster.global.mbarrier::complete_tx::bytes [%0], [%1, {%3, %5, %5, %5, %4}], [%2];"
                 :: "r"(dst), "l"(map), "r"(bar), "r"(col), "r"(k32), "r"(0) : "memory");
}
DEVI void tma_store_2d(const CUtensorMap* map, uint32_t src, int x, int y) {
    asm volatile("cp.async.bulk.tensor.2d.global.shared::cta.bulk_group [%0, {%2, %3}], [%1];"
                 :: "l"(map), "r"(src), "r"(x), "r"(y) : "memory");
}
DEVI void bulk_load(uint32_t dst, const void* src, uint32_t bytes, uint32_t bar) {
    asm volatile("cp.async.bulk.shared::cluster.global.mbarrier::complete_tx::bytes [%0], [%1], %2, [%3];"
                 :: "r"(dst), "l"(src), "r"(bytes), "r"(bar) : "memory");
}
DEVI void tma_load_2d_mc(uint32_t dst, const CUtensorMap* map, int x, int y, uint32_t bar, uint16_t mask) {
    asm volatile("cp.async.bulk.tensor.2d.shared::cluster.global.mbarrier::complete_tx::bytes.multicast::cluster [%0], [%1, {%3, %4}], [%2], %5;"
                 :: "r"(dst), "l"(map), "r"(bar), "r"(x), "r"(y), "h"(mask) : "memory");
}
DEVI void bulk_copy_s2c(uint32_t dst_cluster, uint32_t src, uint32_t bytes, uint32_t bar_cluster) {
    asm volatile("cp.async.bulk.shared::cluster.shared::cta.mbarrier::complete_tx::bytes [%0], [%1], %2, [%3];"
                 :: "r"(dst_cluster), "r"(src), "r"(bytes), "r"(bar_cluster) : "memory");
}
DEVI void bulk_store(void* dst, uint32_t src, uint32_t bytes) {
    asm volatile("cp.async.bulk.global.shared::cta.bulk_group [%0], [%1], %2;" :: "l"(dst), "r"(src), "r"(bytes) : "memory");
}
DEVI void bulk_wait_read() { asm volatile("cp.async.bulk.wait_group.read 0;" ::: "memory"); }
DEVI void mbar_arrive_remote(uint32_t bar_cluster) {
    asm volatile("mbarrier.arrive.shared::cluster.b64 _, [%0];" :: "r"(bar_cluster) : "memory");
}
DEVI void mbar_expect_tx_remote(uint32_t bar_cluster, uint32_t bytes) {
    asm volatile("mbarrier.arrive.expect_tx.shared::cluster.b64 _, [%0], %1;" :: "r"(bar_cluster), "r"(bytes) : "memory");
}
DEVI void l2_prefetch(const void* p, uint32_t bytes) {
    asm volatile("cp.async.bulk.prefetch.L2.global [%0], %1;" :: "l"(p), "r"(bytes) : "memory");
}
DEVI void bulk_commit() { asm volatile("cp.async.bulk.commit_group;" ::: "memory"); }
DEVI void bulk_wait_all() { asm volatile("cp.async.bulk.wait_group 0;" ::: "memory"); }

DEVI void wg_fence() { asm volatile("wgmma.fence.sync.aligned;" ::: "memory"); }
DEVI void wg_commit() { asm volatile("wgmma.commit_group.sync.aligned;" ::: "memory"); }
template <int N> DEVI void wg_wait() { asm volatile("wgmma.wait_group.sync.aligned %0;" :: "n"(N) : "memory"); }

template <int R> DEVI void reg_dec() { asm volatile("setmaxnreg.dec.sync.aligned.u32 %0;" :: "n"(R)); }
template <int R> DEVI void reg_inc() { asm volatile("setmaxnreg.inc.sync.aligned.u32 %0;" :: "n"(R)); }

DEVI uint64_t mk_desc(uint32_t addr, uint32_t lbo, uint32_t sbo, uint32_t sw) {
    return (uint64_t)((addr & 0x3FFFF) >> 4) | ((uint64_t)(lbo >> 4) << 16) | ((uint64_t)(sbo >> 4) << 32) | ((uint64_t)sw << 62);
}

DEVI uint32_t desc_lo(uint32_t addr, uint32_t lbo) { return ((addr & 0x3FFFF) >> 4) | ((lbo >> 4) << 16); }
constexpr uint32_t DHI_SW128 = (1024u >> 4) | (1u << 30);
constexpr uint32_t DHI_SW64  = (512u >> 4) | (2u << 30);
constexpr uint32_t DHI_NONE  = (128u >> 4);

template <int TB, int SCALE_D>
DEVI void wgmma_n8_ss(float* d, uint32_t alo, uint32_t blo) {
    asm volatile("{.reg .b64 da, db; mov.b64 da, {%4, %6}; mov.b64 db, {%5, %7};\n"
                 "wgmma.mma_async.sync.aligned.m64n8k16.f32.bf16.bf16 {%0,%1,%2,%3}, da, db, %8, 1, 1, 1, %9;}"
                 : "+f"(d[0]), "+f"(d[1]), "+f"(d[2]), "+f"(d[3])
                 : "r"(alo), "r"(blo), "n"(DHI_SW128), "n"(DHI_NONE), "n"(SCALE_D), "n"(TB));
}

template <int TB>
DEVI void wgmma_n8_ss_first(float* d, uint32_t alo, uint32_t blo) {
    asm volatile("{.reg .b64 da, db; mov.b64 da, {%4, %6}; mov.b64 db, {%5, %7};\n"
                 "wgmma.mma_async.sync.aligned.m64n8k16.f32.bf16.bf16 {%0,%1,%2,%3}, da, db, 0, 1, 1, 1, %8;}"
                 : "=f"(d[0]), "=f"(d[1]), "=f"(d[2]), "=f"(d[3])
                 : "r"(alo), "r"(blo), "n"(DHI_SW128), "n"(DHI_NONE), "n"(TB));
}
DEVI void wgmma_n32_rs_first(float* d, const uint32_t* a, uint32_t blo) {
    asm volatile("{.reg .b64 db; mov.b64 db, {%20, %21};\n"
                 "wgmma.mma_async.sync.aligned.m64n32k16.f32.bf16.bf16 {%0,%1,%2,%3,%4,%5,%6,%7,%8,%9,%10,%11,%12,%13,%14,%15}, "
                 "{%16,%17,%18,%19}, db, 0, 1, 1, 0;}"
                 : "=f"(d[0]), "=f"(d[1]), "=f"(d[2]), "=f"(d[3]), "=f"(d[4]), "=f"(d[5]), "=f"(d[6]), "=f"(d[7]),
                   "=f"(d[8]), "=f"(d[9]), "=f"(d[10]), "=f"(d[11]), "=f"(d[12]), "=f"(d[13]), "=f"(d[14]), "=f"(d[15])
                 : "r"(a[0]), "r"(a[1]), "r"(a[2]), "r"(a[3]), "r"(blo), "n"(DHI_SW64));
}
template <int N> DEVI void reg_fence(float* d) {
#pragma unroll
    for (int i = 0; i < N; i++) asm volatile("" : "+f"(d[i]) :: "memory");
}
DEVI void wgmma_n32_rs(float* d, const uint32_t* a, uint32_t blo) {
    asm volatile("{.reg .b64 db; mov.b64 db, {%20, %21};\n"
                 "wgmma.mma_async.sync.aligned.m64n32k16.f32.bf16.bf16 {%0,%1,%2,%3,%4,%5,%6,%7,%8,%9,%10,%11,%12,%13,%14,%15}, "
                 "{%16,%17,%18,%19}, db, 1, 1, 1, 0;}"
                 : "+f"(d[0]), "+f"(d[1]), "+f"(d[2]), "+f"(d[3]), "+f"(d[4]), "+f"(d[5]), "+f"(d[6]), "+f"(d[7]),
                   "+f"(d[8]), "+f"(d[9]), "+f"(d[10]), "+f"(d[11]), "+f"(d[12]), "+f"(d[13]), "+f"(d[14]), "+f"(d[15])
                 : "r"(a[0]), "r"(a[1]), "r"(a[2]), "r"(a[3]), "r"(blo), "n"(DHI_SW64));
}
DEVI void wgmma_n32_ss(float* d, uint32_t alo, uint32_t blo) {
    asm volatile("{.reg .b64 da, db; mov.b64 da, {%16, %18}; mov.b64 db, {%17, %19};\n"
                 "wgmma.mma_async.sync.aligned.m64n32k16.f32.bf16.bf16 {%0,%1,%2,%3,%4,%5,%6,%7,%8,%9,%10,%11,%12,%13,%14,%15}, "
                 "da, db, 1, 1, 1, 1, 0;}"
                 : "+f"(d[0]), "+f"(d[1]), "+f"(d[2]), "+f"(d[3]), "+f"(d[4]), "+f"(d[5]), "+f"(d[6]), "+f"(d[7]),
                   "+f"(d[8]), "+f"(d[9]), "+f"(d[10]), "+f"(d[11]), "+f"(d[12]), "+f"(d[13]), "+f"(d[14]), "+f"(d[15])
                 : "r"(alo), "r"(blo), "n"(DHI_SW128), "n"(DHI_SW64));
}

DEVI void wgmma_n256_ss(float* d, uint64_t a, uint64_t b, int scale_d) {
    asm volatile("{.reg .pred p; setp.ne.b32 p, %130, 0;\n"
        "wgmma.mma_async.sync.aligned.m64n256k16.f32.bf16.bf16 "
        "{%0,%1,%2,%3,%4,%5,%6,%7,%8,%9,%10,%11,%12,%13,%14,%15,"
        "%16,%17,%18,%19,%20,%21,%22,%23,%24,%25,%26,%27,%28,%29,%30,%31,"
        "%32,%33,%34,%35,%36,%37,%38,%39,%40,%41,%42,%43,%44,%45,%46,%47,"
        "%48,%49,%50,%51,%52,%53,%54,%55,%56,%57,%58,%59,%60,%61,%62,%63,"
        "%64,%65,%66,%67,%68,%69,%70,%71,%72,%73,%74,%75,%76,%77,%78,%79,"
        "%80,%81,%82,%83,%84,%85,%86,%87,%88,%89,%90,%91,%92,%93,%94,%95,"
        "%96,%97,%98,%99,%100,%101,%102,%103,%104,%105,%106,%107,%108,%109,%110,%111,"
        "%112,%113,%114,%115,%116,%117,%118,%119,%120,%121,%122,%123,%124,%125,%126,%127},"
        " %128, %129, p, 1, 1, 1, 0;}"
        : "+f"(d[0]), "+f"(d[1]), "+f"(d[2]), "+f"(d[3]), "+f"(d[4]), "+f"(d[5]), "+f"(d[6]), "+f"(d[7]),
          "+f"(d[8]), "+f"(d[9]), "+f"(d[10]), "+f"(d[11]), "+f"(d[12]), "+f"(d[13]), "+f"(d[14]), "+f"(d[15]),
          "+f"(d[16]), "+f"(d[17]), "+f"(d[18]), "+f"(d[19]), "+f"(d[20]), "+f"(d[21]), "+f"(d[22]), "+f"(d[23]),
          "+f"(d[24]), "+f"(d[25]), "+f"(d[26]), "+f"(d[27]), "+f"(d[28]), "+f"(d[29]), "+f"(d[30]), "+f"(d[31]),
          "+f"(d[32]), "+f"(d[33]), "+f"(d[34]), "+f"(d[35]), "+f"(d[36]), "+f"(d[37]), "+f"(d[38]), "+f"(d[39]),
          "+f"(d[40]), "+f"(d[41]), "+f"(d[42]), "+f"(d[43]), "+f"(d[44]), "+f"(d[45]), "+f"(d[46]), "+f"(d[47]),
          "+f"(d[48]), "+f"(d[49]), "+f"(d[50]), "+f"(d[51]), "+f"(d[52]), "+f"(d[53]), "+f"(d[54]), "+f"(d[55]),
          "+f"(d[56]), "+f"(d[57]), "+f"(d[58]), "+f"(d[59]), "+f"(d[60]), "+f"(d[61]), "+f"(d[62]), "+f"(d[63]),
          "+f"(d[64]), "+f"(d[65]), "+f"(d[66]), "+f"(d[67]), "+f"(d[68]), "+f"(d[69]), "+f"(d[70]), "+f"(d[71]),
          "+f"(d[72]), "+f"(d[73]), "+f"(d[74]), "+f"(d[75]), "+f"(d[76]), "+f"(d[77]), "+f"(d[78]), "+f"(d[79]),
          "+f"(d[80]), "+f"(d[81]), "+f"(d[82]), "+f"(d[83]), "+f"(d[84]), "+f"(d[85]), "+f"(d[86]), "+f"(d[87]),
          "+f"(d[88]), "+f"(d[89]), "+f"(d[90]), "+f"(d[91]), "+f"(d[92]), "+f"(d[93]), "+f"(d[94]), "+f"(d[95]),
          "+f"(d[96]), "+f"(d[97]), "+f"(d[98]), "+f"(d[99]), "+f"(d[100]), "+f"(d[101]), "+f"(d[102]), "+f"(d[103]),
          "+f"(d[104]), "+f"(d[105]), "+f"(d[106]), "+f"(d[107]), "+f"(d[108]), "+f"(d[109]), "+f"(d[110]), "+f"(d[111]),
          "+f"(d[112]), "+f"(d[113]), "+f"(d[114]), "+f"(d[115]), "+f"(d[116]), "+f"(d[117]), "+f"(d[118]), "+f"(d[119]),
          "+f"(d[120]), "+f"(d[121]), "+f"(d[122]), "+f"(d[123]), "+f"(d[124]), "+f"(d[125]), "+f"(d[126]), "+f"(d[127])
        : "l"(a), "l"(b), "r"(scale_d));
}

DEVI void wgmma_n128_ss(float* d, uint64_t a, uint64_t b, int scale_d) {
    asm volatile("{.reg .pred p; setp.ne.b32 p, %66, 0;\n"
        "wgmma.mma_async.sync.aligned.m64n128k16.f32.bf16.bf16 "
        "{%0,%1,%2,%3,%4,%5,%6,%7,%8,%9,%10,%11,%12,%13,%14,%15,"
        "%16,%17,%18,%19,%20,%21,%22,%23,%24,%25,%26,%27,%28,%29,%30,%31,"
        "%32,%33,%34,%35,%36,%37,%38,%39,%40,%41,%42,%43,%44,%45,%46,%47,"
        "%48,%49,%50,%51,%52,%53,%54,%55,%56,%57,%58,%59,%60,%61,%62,%63},"
        " %64, %65, p, 1, 1, 1, 0;}"
        : "+f"(d[0]), "+f"(d[1]), "+f"(d[2]), "+f"(d[3]), "+f"(d[4]), "+f"(d[5]), "+f"(d[6]), "+f"(d[7]),
          "+f"(d[8]), "+f"(d[9]), "+f"(d[10]), "+f"(d[11]), "+f"(d[12]), "+f"(d[13]), "+f"(d[14]), "+f"(d[15]),
          "+f"(d[16]), "+f"(d[17]), "+f"(d[18]), "+f"(d[19]), "+f"(d[20]), "+f"(d[21]), "+f"(d[22]), "+f"(d[23]),
          "+f"(d[24]), "+f"(d[25]), "+f"(d[26]), "+f"(d[27]), "+f"(d[28]), "+f"(d[29]), "+f"(d[30]), "+f"(d[31]),
          "+f"(d[32]), "+f"(d[33]), "+f"(d[34]), "+f"(d[35]), "+f"(d[36]), "+f"(d[37]), "+f"(d[38]), "+f"(d[39]),
          "+f"(d[40]), "+f"(d[41]), "+f"(d[42]), "+f"(d[43]), "+f"(d[44]), "+f"(d[45]), "+f"(d[46]), "+f"(d[47]),
          "+f"(d[48]), "+f"(d[49]), "+f"(d[50]), "+f"(d[51]), "+f"(d[52]), "+f"(d[53]), "+f"(d[54]), "+f"(d[55]),
          "+f"(d[56]), "+f"(d[57]), "+f"(d[58]), "+f"(d[59]), "+f"(d[60]), "+f"(d[61]), "+f"(d[62]), "+f"(d[63])
        : "l"(a), "l"(b), "r"(scale_d));
}

DEVI void mma16816(float* d, const uint32_t* a, uint32_t b0, uint32_t b1) {
    asm volatile("mma.sync.aligned.m16n8k16.row.col.f32.bf16.bf16.f32 {%0,%1,%2,%3}, {%4,%5,%6,%7}, {%8,%9}, {%0,%1,%2,%3};"
                 : "+f"(d[0]), "+f"(d[1]), "+f"(d[2]), "+f"(d[3])
                 : "r"(a[0]), "r"(a[1]), "r"(a[2]), "r"(a[3]), "r"(b0), "r"(b1));
}
DEVI void mma1688(float* d, uint32_t a0, uint32_t a1, uint32_t b0) {
    asm volatile("mma.sync.aligned.m16n8k8.row.col.f32.bf16.bf16.f32 {%0,%1,%2,%3}, {%4,%5}, {%6}, {%0,%1,%2,%3};"
                 : "+f"(d[0]), "+f"(d[1]), "+f"(d[2]), "+f"(d[3]) : "r"(a0), "r"(a1), "r"(b0));
}
DEVI void ldsm4(uint32_t* r, uint32_t addr) {
    asm volatile("ldmatrix.sync.aligned.m8n8.x4.shared.b16 {%0,%1,%2,%3}, [%4];"
                 : "=r"(r[0]), "=r"(r[1]), "=r"(r[2]), "=r"(r[3]) : "r"(addr) : "memory");
}
DEVI void ldsm4t(uint32_t* r, uint32_t addr) {
    asm volatile("ldmatrix.sync.aligned.m8n8.x4.trans.shared.b16 {%0,%1,%2,%3}, [%4];"
                 : "=r"(r[0]), "=r"(r[1]), "=r"(r[2]), "=r"(r[3]) : "r"(addr) : "memory");
}
DEVI void ldsm2(uint32_t* r, uint32_t addr) {
    asm volatile("ldmatrix.sync.aligned.m8n8.x2.shared.b16 {%0,%1}, [%2];" : "=r"(r[0]), "=r"(r[1]) : "r"(addr) : "memory");
}
DEVI void ldsm1t(uint32_t& r, uint32_t addr) {
    asm volatile("ldmatrix.sync.aligned.m8n8.x1.trans.shared.b16 {%0}, [%1];" : "=r"(r) : "r"(addr) : "memory");
}
DEVI void stsm4(uint32_t addr, uint32_t r0, uint32_t r1, uint32_t r2, uint32_t r3) {
    asm volatile("stmatrix.sync.aligned.m8n8.x4.shared.b16 [%0], {%1,%2,%3,%4};" :: "r"(addr), "r"(r0), "r"(r1), "r"(r2), "r"(r3) : "memory");
}
DEVI void stsm4t(uint32_t addr, uint32_t r0, uint32_t r1, uint32_t r2, uint32_t r3) {
    asm volatile("stmatrix.sync.aligned.m8n8.x4.trans.shared.b16 [%0], {%1,%2,%3,%4};" :: "r"(addr), "r"(r0), "r"(r1), "r"(r2), "r"(r3) : "memory");
}
DEVI uint32_t movm_t(uint32_t a) {
    uint32_t d; asm volatile("movmatrix.sync.aligned.m8n8.trans.b16 %0, %1;" : "=r"(d) : "r"(a)); return d;
}
DEVI uint32_t pack_bf16(float lo, float hi) {
    uint32_t r; asm("cvt.rn.bf16x2.f32 %0, %1, %2;" : "=r"(r) : "f"(hi), "f"(lo)); return r;
}
DEVI float ex2(float x) { float y; asm("ex2.approx.ftz.f32 %0, %1;" : "=f"(y) : "f"(x)); return y; }

DEVI uint4 ld_rlx4(const void* p) {
    uint4 v;
    asm volatile("ld.relaxed.gpu.global.v4.u32 {%0,%1,%2,%3}, [%4];" : "=r"(v.x), "=r"(v.y), "=r"(v.z), "=r"(v.w) : "l"(p) : "memory");
    return v;
}
DEVI void ld_rlx4f(float* d, const void* p) {
    asm volatile("ld.relaxed.gpu.global.v4.f32 {%0,%1,%2,%3}, [%4];" : "=f"(d[0]), "=f"(d[1]), "=f"(d[2]), "=f"(d[3]) : "l"(p) : "memory");
}
DEVI bool all_nzf(const float* d) { return __float_as_uint(d[0]) && __float_as_uint(d[1]) && __float_as_uint(d[2]) && __float_as_uint(d[3]); }
DEVI void sts128f(uint32_t addr, const float* d) {
    asm volatile("st.shared.v4.f32 [%0], {%1,%2,%3,%4};" :: "r"(addr), "f"(d[0]), "f"(d[1]), "f"(d[2]), "f"(d[3]) : "memory");
}
DEVI void st_rlx4(void* p, uint32_t a, uint32_t b, uint32_t c, uint32_t d) {
    asm volatile("st.relaxed.gpu.global.v4.u32 [%0], {%1,%2,%3,%4};" :: "l"(p), "r"(a), "r"(b), "r"(c), "r"(d) : "memory");
}
DEVI void st_rlx(void* p, uint32_t v) { asm volatile("st.relaxed.gpu.global.u32 [%0], %1;" :: "l"(p), "r"(v) : "memory"); }
DEVI void sts128(uint32_t addr, uint4 v) {
    asm volatile("st.shared.v4.u32 [%0], {%1,%2,%3,%4};" :: "r"(addr), "r"(v.x), "r"(v.y), "r"(v.z), "r"(v.w) : "memory");
}
DEVI void sts64(uint32_t addr, uint32_t a, uint32_t b) { asm volatile("st.shared.v2.u32 [%0], {%1,%2};" :: "r"(addr), "r"(a), "r"(b) : "memory"); }
DEVI void sts32(uint32_t addr, uint32_t v) { asm volatile("st.shared.u32 [%0], %1;" :: "r"(addr), "r"(v) : "memory"); }
DEVI uint4 lds128(uint32_t addr) {
    uint4 v; asm volatile("ld.shared.v4.u32 {%0,%1,%2,%3}, [%4];" : "=r"(v.x), "=r"(v.y), "=r"(v.z), "=r"(v.w) : "r"(addr) : "memory"); return v;
}
DEVI float2 lds64f(uint32_t addr) {
    float2 v; asm volatile("ld.shared.v2.f32 {%0,%1}, [%2];" : "=f"(v.x), "=f"(v.y) : "r"(addr) : "memory"); return v;
}
DEVI void cp_async16(uint32_t dst, const void* src) {
    asm volatile("cp.async.cg.shared.global [%0], [%1], 16;" :: "r"(dst), "l"(src) : "memory");
}
DEVI void cp_async_commit() { asm volatile("cp.async.commit_group;" ::: "memory"); }
DEVI void cp_async_wait0() { asm volatile("cp.async.wait_group 0;" ::: "memory"); }
DEVI uint32_t lds32(uint32_t addr) { uint32_t v; asm volatile("ld.shared.u32 %0, [%1];" : "=r"(v) : "r"(addr) : "memory"); return v; }
DEVI float rcp_fast(float x) { float y; asm("rcp.approx.ftz.f32 %0, %1;" : "=f"(y) : "f"(x)); return y; }
DEVI bool all_nz(const uint4& v) { return v.x && v.y && v.z && v.w; }
DEVI uint32_t mapa(uint32_t addr, uint32_t rank) {
    uint32_t r; asm("mapa.shared::cluster.u32 %0, %1, %2;" : "=r"(r) : "r"(addr), "r"(rank)); return r;
}
DEVI void st_async64(uint32_t dst, uint32_t a, uint32_t b, uint32_t bar) {
    asm volatile("st.async.weak.shared::cluster.mbarrier::complete_tx::bytes.v2.b32 [%0], {%1,%2}, [%3];"
                 :: "r"(dst), "r"(a), "r"(b), "r"(bar) : "memory");
}

DEVI void st_async128(uint32_t dst, uint32_t a, uint32_t b, uint32_t c, uint32_t d, uint32_t bar) {
    asm volatile("st.async.weak.shared::cluster.mbarrier::complete_tx::bytes.v4.b32 [%0], {%1,%2,%3,%4}, [%5];"
                 :: "r"(dst), "r"(a), "r"(b), "r"(c), "r"(d), "r"(bar) : "memory");
}

DEVI uint32_t b_addr(uint32_t sb, int row, int which, int chunk) { const int l = 3 * row + which; return sb + l * 128 + ((chunk ^ (l & 7)) * 16); }
DEVI void battn_warp(uint32_t st, uint32_t so, int i0, int par, int head, int hh, int mt, int lane) {
    const int gq = lane >> 2, t = lane & 3;
    float s[3][4];
#pragma unroll
    for (int n = 0; n < 3; n++) { s[n][0] = s[n][1] = s[n][2] = s[n][3] = 0.f; }
    const int arow = 16 * mt + (lane & 7) + ((lane >> 3) & 1) * 8;
#pragma unroll
    for (int ks = 0; ks < 2; ks++) {
        uint32_t a[4], b[4], b2[2];
        ldsm4(a, b_addr(st, 8 + arow, 0, hh * 4 + ks * 2 + (lane >> 4)));
        const int brow = 16 * mt + (lane >> 4) * 8 + (lane & 7);
        ldsm4(b, b_addr(st, brow, 1, hh * 4 + ks * 2 + ((lane >> 3) & 1)));
        const int crow = 16 * mt + 16 + (lane & 7);
        ldsm2(b2, b_addr(st, crow, 1, hh * 4 + ks * 2 + ((lane >> 3) & 1)));
        mma16816(s[0], a, b[0], b[1]);
        mma16816(s[1], a, b[2], b[3]);
        mma16816(s[2], a, b2[0], b2[1]);
    }
    float m0 = -INFINITY, m1 = -INFINITY;
#pragma unroll
    for (int n = 0; n < 3; n++) {
#pragma unroll
        for (int c = 0; c < 2; c++) {
            const int dj = 8 * n - 8 + 2 * t + c;
            const bool ex = i0 + 16 * mt + dj >= 0;
            if (!(ex && gq - dj >= 0 && gq - dj <= 7)) s[n][c] = -INFINITY;
            if (!(ex && gq + 8 - dj >= 0 && gq + 8 - dj <= 7)) s[n][2 + c] = -INFINITY;
            m0 = fmaxf(m0, s[n][c]); m1 = fmaxf(m1, s[n][2 + c]);
        }
    }
    m0 = fmaxf(m0, __shfl_xor_sync(0xffffffffu, m0, 1)); m0 = fmaxf(m0, __shfl_xor_sync(0xffffffffu, m0, 2));
    m1 = fmaxf(m1, __shfl_xor_sync(0xffffffffu, m1, 1)); m1 = fmaxf(m1, __shfl_xor_sync(0xffffffffu, m1, 2));
    constexpr float C = 0.17677669529663687f * 1.4426950408889634f;
    float l0 = 0.f, l1 = 0.f;
    uint32_t p[3][2];
#pragma unroll
    for (int n = 0; n < 3; n++) {
        const float e0 = ex2((s[n][0] - m0) * C), e1 = ex2((s[n][1] - m0) * C), e2 = ex2((s[n][2] - m1) * C), e3 = ex2((s[n][3] - m1) * C);
        l0 += e0 + e1; l1 += e2 + e3;
        p[n][0] = pack_bf16(e0, e1); p[n][1] = pack_bf16(e2, e3);
    }
    l0 += __shfl_xor_sync(0xffffffffu, l0, 1); l0 += __shfl_xor_sync(0xffffffffu, l0, 2);
    l1 += __shfl_xor_sync(0xffffffffu, l1, 1); l1 += __shfl_xor_sync(0xffffffffu, l1, 2);
    const float i0f = rcp_fast(l0), i1f = rcp_fast(l1);
    float o[4][4];
#pragma unroll
    for (int n = 0; n < 4; n++) { o[n][0] = o[n][1] = o[n][2] = o[n][3] = 0.f; }
    {
        const uint32_t a0[4] = {p[0][0], p[0][1], p[1][0], p[1][1]}, a1[4] = {p[2][0], p[2][1], 0u, 0u};
#pragma unroll
        for (int n = 0; n < 4; n += 2) {
            uint32_t b[4], b2[4];
            const int vrow = 16 * mt + ((lane >> 3) & 1) * 8 + (lane & 7);
            ldsm4t(b, b_addr(st, vrow, 2, hh * 4 + n + (lane >> 4)));
            const int wrow = 16 * mt + 16 + (lane & 7);
            ldsm4t(b2, b_addr(st, wrow, 2, hh * 4 + n + (lane >> 4)));
            mma16816(o[n], a0, b[0], b[1]);
            mma16816(o[n + 1], a0, b[2], b[3]);
            mma16816(o[n], a1, b2[0], 0u);
            mma16816(o[n + 1], a1, b2[2], 0u);
        }
    }
    {
        const int row = (lane & 7) + ((lane >> 3) & 1) * 8;
#pragma unroll
        for (int n = 0; n < 4; n += 2)
            stsm4(so + row * 64 + (((n + (lane >> 4)) ^ ((row >> 1) & 3)) * 16),
                  pack_bf16(o[n][0] * i0f, o[n][1] * i0f), pack_bf16(o[n][2] * i1f, o[n][3] * i1f),
                  pack_bf16(o[n + 1][0] * i0f, o[n + 1][1] * i0f), pack_bf16(o[n + 1][2] * i1f, o[n + 1][3] * i1f));
    }
    __syncwarp();
#pragma unroll
    for (int i = 0; i < 2; i++) {
        const int idx = lane + i * 32, row = idx >> 2, ch = idx & 3;
        const uint4 v = lds128(so + row * 64 + ((ch ^ ((row >> 1) & 3)) * 16));
        *(uint4*)(g_bo + (size_t)(2 * (i0 + 16 * mt + row) + par) * 1024 + head * 32 + ch * 8) = v;
    }
    __syncwarp();
}

constexpr float SCALE_LOG2E = 0.08838834764831845f * 1.4426950408889634f;

constexpr int P_STAGES = 4, P_STAGE = 16384 + 32768;
constexpr int PS_STG = P_STAGES * P_STAGE;
constexpr int PS_BAR = PS_STG + 32768;
constexpr int P_SMEM = PS_BAR + 256;
static_assert(P_SMEM <= 232448, "smem");
constexpr int PT_B1 = 256, PT_A0 = PT_B1 + 192, PT_B2 = PT_A0 + 32, PT_A1 = PT_B2 + 32, PT_B3 = PT_A1 + 32, PT_A2 = PT_B3 + 64;
constexpr int PT_SK = PT_A2 + 48, P_NTASK = PT_SK + 64;
enum { K_B1, K_Q, K_B2, K_B3, K_A3, K_SK, K_END };
struct PTask { int kind, a, b, c; };
DEVI PTask p_decode(int id) {
    if (id < PT_B1) return {K_Q, id % 32, id / 32, 0};
    if (id < PT_A0) return {K_B1, (id - PT_B1) % 24, (id - PT_B1) / 24, 0};
    if (id < PT_B2) return {K_A3, (id - PT_A0) & 7, (id - PT_A0) >> 3, 0};
    if (id < PT_A1) return {K_B2, id - PT_B2, 0, 0};
    if (id < PT_B3) return {K_A3, (id - PT_A1) & 7, 4 + ((id - PT_A1) >> 3), 0};
    if (id < PT_A2) return {K_B3, (id - PT_B3) % 8, (id - PT_B3) / 8, 0};
    if (id < PT_SK) return {K_A3, (id - PT_A2) & 7, 8 + ((id - PT_A2) >> 3), 0};
    if (id >= P_NTASK) return {K_END, 0, 0, 0};
    const int j = id - PT_SK;
    return {K_SK, (j >> 2) & 7, 14 + (j >> 5), j & 3};
}
DEVI void wait_count(const unsigned* p, unsigned target) {
    int n = 0;
    while (true) {
        unsigned v; asm volatile("ld.acquire.gpu.global.u32 %0, [%1];" : "=r"(v) : "l"(p) : "memory");
        if ((int)(v - target) >= 0) break;
        __nanosleep(100);
        if (++n > SPIN_LIMIT) TRAP(0x10000000u | ((unsigned)(size_t)p & 0xFFFFu));
    }
}
DEVI void wait_count_warp(const unsigned* p, unsigned target) {
    int n = 0;
    while (true) {
        unsigned v; asm volatile("ld.acquire.gpu.global.u32 %0, [%1];" : "=r"(v) : "l"(p) : "memory");
        if (__all_sync(0xffffffffu, (int)(v - target) >= 0)) break;
        __nanosleep(100);
        if (++n > SPIN_LIMIT) TRAP(0x10000000u | ((unsigned)(size_t)p & 0xFFFFu));
    }
}
DEVI void signal_count(unsigned* p) { __threadfence(); atomicAdd(p, 1u); }

struct PMaps { CUtensorMap wq, bw, bwo, wo, x, bx, bo, ox, cb, cout, b40; };

template <int BN>
DEVI void p_mainloop(float* d, uint32_t sb, int g, int nk, int& it, bool elected) {
#pragma unroll
    for (int i = 0; i < BN / 2; i++) d[i] = 0.f;
    for (int kb = 0; kb < nk; kb++, it++) {
        const int st = it % P_STAGES;
        mbar_wait(sb + PS_BAR + st * 8, (it / P_STAGES) & 1);
        const uint32_t a = sb + st * P_STAGE;
        const uint64_t da = mk_desc(a + g * 8192, 16, 1024, 1), db = mk_desc(a + 16384, 16, 1024, 1);
        wg_fence();
#pragma unroll
        for (int kk = 0; kk < 4; kk++) {
            if (BN == 256) wgmma_n256_ss(d, da + (uint64_t)(kk * 128), db + (uint64_t)(kk * 2), (kb | kk) != 0);
            else           wgmma_n128_ss(d, da + (uint64_t)(kk * 128), db + (uint64_t)(kk * 2), (kb | kk) != 0);
        }
        wg_commit();
        if (kb > 0) {
            wg_wait<1>();
            if (elected) mbar_arrive(sb + PS_BAR + 32 + ((it - 1) % P_STAGES) * 8);
        }
    }
    wg_wait<0>();
    if (elected) mbar_arrive(sb + PS_BAR + 32 + ((it - 1) % P_STAGES) * 8);
}
template <int BN>
DEVI void p_epi_row(const float* d, uint32_t stg, const CUtensorMap* tmC, int col, int tok0, int warp, int lane_, int barid, bool elected, int& nstore) {
    const int lane = (int)opaque((uint32_t)lane_);
    const int mi = lane >> 3, r = lane & 7;
#pragma unroll
    for (int c = 0; c < BN / 64; c++, nstore++) {
        const uint32_t buf = stg + (nstore & 1) * 8192;
        if (elected) asm volatile("cp.async.bulk.wait_group.read 1;" ::: "memory");
        nbar_sync(barid, 128);
#pragma unroll
        for (int j = 0; j < 8; j += 2) {
            const int jj = c * 8 + j;
            const int tok = 8 * (j + (mi >> 1)) + r;
            const int chunk = (2 * warp + (mi & 1)) ^ r;
            stsm4t(buf + tok * 128 + chunk * 16,
                   pack_bf16(d[4 * jj], d[4 * jj + 1]), pack_bf16(d[4 * jj + 2], d[4 * jj + 3]),
                   pack_bf16(d[4 * jj + 4], d[4 * jj + 5]), pack_bf16(d[4 * jj + 6], d[4 * jj + 7]));
        }
        fence_proxy_async();
        nbar_sync(barid, 128);
        if (elected) { tma_store_2d(tmC, buf, col, tok0 + c * 64); bulk_commit(); }
    }
}

__global__ void __launch_bounds__(384, 1) k_post(const __grid_constant__ PMaps mp) {
    extern __shared__ __align__(1024) uint8_t smem_raw[];
    const uint32_t sb = smem_u32(smem_raw);
    if (sb & 1023u) __trap();
    const int tid = threadIdx.x, lane = tid & 31;
    const int wg = __shfl_sync(0xffffffffu, tid >> 7, 0), warp = __shfl_sync(0xffffffffu, (tid >> 5) & 3, 0);
    const uint32_t bF = sb + PS_BAR, bE = bF + 32, bTF = bF + 64, bTE = bF + 80, sT = bF + 96;
    if (tid == 0) {
        for (int i = 0; i < P_STAGES; i++) { mbar_init(bF + i * 8, 1); mbar_init(bE + i * 8, 2); }
        for (int i = 0; i < 2; i++) { mbar_init(bTF + i * 8, 1); mbar_init(bTE + i * 8, 256); }
        fence_mbar_init();
    }
    __syncthreads();
    if (wg == 2) {
        reg_dec<40>();
        if (tid == 256) {
            const unsigned E = *(volatile unsigned*)&g_epoch + 1;
            const unsigned qbase = (E - 1) * (unsigned)(P_NTASK + gridDim.x);
            int it = 0;
            for (int i = 0;; i++) {
                mbar_wait(bTE + (i & 1) * 8, ((i >> 1) & 1) ^ 1);
                const int id = (int)(atomicAdd(&g_qctr, 1u) - qbase);
                const PTask tk = p_decode(id);
                if (tk.kind == K_B2) {
                    wait_count(&g_cnt_b1[tk.a >> 2], 48 * E);
                    if ((tk.a & 3) == 0 && tk.a > 0) wait_count(&g_cnt_b1[(tk.a >> 2) - 1], 48 * E);
                } else if (tk.kind == K_B3) wait_count(&g_cnt_b2[tk.b], 4 * E);
                else if (tk.kind == K_A3 || tk.kind == K_SK) wait_count(&g_prog[tk.b], 128 * E);
                asm volatile("fence.proxy.async;" ::: "memory");
                sts32(sT + (i & 1) * 4, (uint32_t)id);
                mbar_arrive(bTF + (i & 1) * 8);
                if (tk.kind == K_END) break;
                if (tk.kind == K_B2) {
                    const int i0 = tk.a * 32;
                    for (int j = 0; j < 16; j++, it++) {
                        const int st = it % P_STAGES;
                        mbar_wait(bE + st * 8, ((it / P_STAGES) & 1) ^ 1);
                        const uint32_t a = sb + st * P_STAGE, bar = bF + st * 8;
                        mbar_expect_tx(bar, 2 * 15360);
                        for (int u = 0; u < 2; u++)
                            asm volatile("cp.async.bulk.tensor.4d.shared::cluster.global.mbarrier::complete_tx::bytes [%0], [%1, {%3, %4, %5, %6}], [%2];"
                                         :: "r"(a + u * 15360), "l"(&mp.b40), "r"(bar), "r"(j * 64), "r"(0), "r"(u), "r"(i0 - 8) : "memory");
                    }
                    continue;
                }
                const CUtensorMap* tw = tk.kind == K_B1 ? &mp.bw : (tk.kind == K_Q ? &mp.wq : (tk.kind == K_B3 ? &mp.bwo : &mp.wo));
                const CUtensorMap* tx = tk.kind == K_B1 ? &mp.bx : (tk.kind == K_Q ? &mp.x : (tk.kind == K_B3 ? &mp.bo : &mp.ox));
                const bool a3 = tk.kind == K_A3 || tk.kind == K_SK;
                const int nk = tk.kind == K_A3 ? HD / 64 : DM / 64, kb0 = tk.kind == K_SK ? tk.c * 16 : 0;
                for (int kb = kb0; kb < kb0 + nk; kb++, it++) {
                    const int st = it % P_STAGES;
                    mbar_wait(bE + st * 8, ((it / P_STAGES) & 1) ^ 1);
                    const uint32_t a = sb + st * P_STAGE, bar = bF + st * 8;
                    mbar_expect_tx(bar, a3 ? 32768 : P_STAGE);
                    if (a3) {
                        tma_load_wo(a, tw, tk.a * 128, kb * 2, bar);
                        tma_load_wo(a + 8192, tw, tk.a * 128 + 64, kb * 2, bar);
                    } else {
                        tma_load_2d(a, tw, tk.a * 128, kb * 64, bar);
                        tma_load_2d(a + 8192, tw, tk.a * 128 + 64, kb * 64, bar);
                    }
                    tma_load_2d(a + 16384, tx, kb * 64, tk.b * (a3 ? 128 : 256), bar);
                }
            }
            __threadfence();
            if (atomicAdd(&g_done, 1u) == E * gridDim.x - 1) { __threadfence(); *(volatile unsigned*)&g_epoch = E; }
        }
    } else {
        reg_inc<232>();
        const int g = wg, ct = tid, barid = 1 + g;
        const bool elected = (tid & 127) == 0;
        const uint32_t stg = sb + PS_STG + g * 16384;
        int it = 0, nstore = 0;
        unsigned* pending = nullptr;
        for (int i = 0;; i++) {
            if (elected && pending && !mbar_try(bTF + (i & 1) * 8, (i >> 1) & 1)) { bulk_wait_all(); signal_count(pending); pending = nullptr; }
            mbar_wait(bTF + (i & 1) * 8, (i >> 1) & 1);
            const int id = (int)lds32(sT + (i & 1) * 4);
            mbar_arrive(bTE + (i & 1) * 8);
            const PTask tk = p_decode(id);
            if (tk.kind == K_END) break;
            if (tk.kind == K_B2) {
                if (elected && pending) { bulk_wait_all(); signal_count(pending); }
                pending = nullptr;
                if (elected) bulk_wait_all();
                nbar_sync(barid, 128);
#pragma unroll 1
                for (int j = 0; j < 16; j++, it++) {
                    const int st = it % P_STAGES;
                    mbar_wait(bF + st * 8, (it / P_STAGES) & 1);
                    const uint32_t a = sb + st * P_STAGE + g * 15360;
                    battn_warp(a, stg + warp * 1024, tk.a * 32, g, j * 2 + (warp >> 1), warp >> 1, warp & 1, (int)opaque((uint32_t)lane));
                    nbar_sync(barid, 128);
                    if (elected) mbar_arrive(bE + st * 8);
                }
                nbar_sync(3, 256);
                if (ct == 0) signal_count(&g_cnt_b2[tk.a >> 2]);
            } else if (tk.kind == K_A3 || tk.kind == K_SK) {
                float d[64];
                p_mainloop<128>(d, sb, g, tk.kind == K_A3 ? HD / 64 : DM / 64, it, elected);
                if (elected && pending) { bulk_wait_all(); signal_count(pending); }
                pending = nullptr;
                bool finish = true;
                if (tk.kind == K_SK) {
                    const int tile = ((tk.b - 14) * 8 + tk.a);
                    float4* mine = (float4*)(g_skp + ((size_t)(tile * 4 + tk.c) * 2 + g) * 8192) + (tid & 127);
#pragma unroll
                    for (int j = 0; j < 16; j++) mine[j * 128] = make_float4(d[4 * j], d[4 * j + 1], d[4 * j + 2], d[4 * j + 3]);
                    nbar_sync(barid, 128);
                    if (elected) { __threadfence(); const unsigned old = atomicAdd(&g_cnt_sk[tile * 2 + g], 1u); __threadfence(); sts32(sT + 16 + g * 4, old & 3u); }
                    nbar_sync(barid, 128);
                    finish = lds32(sT + 16 + g * 4) == 3u;
                    if (finish) {
#pragma unroll 1
                        for (int q = 1; q < 4; q++) {
                            const float4* o = (const float4*)(g_skp + ((size_t)(tile * 4 + ((tk.c + q) & 3)) * 2 + g) * 8192) + (tid & 127);
#pragma unroll
                            for (int j = 0; j < 16; j++) {
                                const float4 v = __ldcg(o + j * 128);
                                d[4 * j] += v.x; d[4 * j + 1] += v.y; d[4 * j + 2] += v.z; d[4 * j + 3] += v.w;
                            }
                        }
                    }
                    nbar_sync(barid, 128);
                }
                if (finish) p_epi_row<128>(d, stg, &mp.cout, tk.a * 128 + g * 64, tk.b * 128, warp, lane, barid, elected, nstore);
            } else {
                float d[128];
                p_mainloop<256>(d, sb, g, DM / 64, it, elected);
                if (elected && pending) { bulk_wait_all(); signal_count(pending); }
                pending = nullptr;
                if (tk.kind == K_Q) {
                    const int ln = (int)opaque((uint32_t)lane), gq = ln >> 2, t = ln & 3, dim = g * 64 + warp * 16 + gq;
#pragma unroll
                    for (int j = 0; j < 32; j++) {
                        const int seg = tk.b * 8 + (j >> 2), blk = j & 3;
                        uint32_t* p = (uint32_t*)(g_qx + ((((size_t)seg * NH + tk.a) * 4 + blk) * DH + dim) * 8 + 2 * t);
                        p[0]  = pack_bf16(d[4 * j], d[4 * j + 1]);
                        p[32] = pack_bf16(d[4 * j + 2], d[4 * j + 3]);
                    }
                    nbar_sync(barid, 128);
                    if (elected) signal_count(&g_cnt_q[tk.b]);
                } else if (tk.kind == K_B1) {
                    p_epi_row<256>(d, stg, &mp.cb, tk.a * 128 + g * 64, tk.b * 256, warp, lane, barid, elected, nstore);
                    pending = &g_cnt_b1[tk.b];
                } else {
                    p_epi_row<256>(d, stg, &mp.cout, DM + tk.a * 128 + g * 64, tk.b * 256, warp, lane, barid, elected, nstore);
                }
            }
        }
        if (elected) { bulk_wait_all(); if (pending) signal_count(pending); }
    }
    __syncthreads();
}

constexpr unsigned long long R_TORD_PACK = 0xf4a53e92dc7816b0ull;
__host__ __device__ constexpr int r_tord(int pos) { return (int)((R_TORD_PACK >> (4 * pos)) & 15ull); }
__host__ __device__ constexpr int r_tinv(int T) { for (int p = 0; p < 16; p++) if (r_tord(p) == T) return p; return 0; }
__host__ __device__ constexpr bool r_pos_ss(int pos) { return pos % 3 == 2; }
__host__ __device__ constexpr int r_ss(int pos) { return pos / 3; }
__host__ __device__ constexpr int r_rs(int pos) { return pos - pos / 3; }
constexpr int R_NRS = 11, R_NSS = 5;
constexpr int R_G1 = 9;
#define REG_KB 232
#define X_NA_DEF 4
constexpr int X_SLOTS = 4;
constexpr int X_NST = 8;
constexpr int X_NA = X_NA_DEF;

constexpr int RS_WSS  = 0;
constexpr int RS_WO   = RS_WSS + R_NSS * 16384;
constexpr int RS_MEM  = RS_WO + 5 * 16384;
constexpr int RS_O    = RS_MEM + 16384;
constexpr int RS_SX   = RS_O + 2048;
constexpr int RS_BAR  = RS_SX + 2048;
constexpr int RS_TAIL = RS_BAR + 1024;
constexpr int RS_WO5  = RS_TAIL;
constexpr int RS_K    = RS_WO5 + 16384;
constexpr int RS_V    = RS_K + 10240;
constexpr int RS_Q    = RS_V + 10240;
constexpr int RS_QX   = RS_Q + 2048;
constexpr int RS_QEND = RS_QX + 8192;
constexpr int RS_X    = RS_TAIL;
constexpr int X_PITCH = X_SLOTS * 4096;
constexpr int RS_XD   = RS_X + 2 * X_PITCH;
constexpr int RS_WX   = RS_XD + 8192;
constexpr int RS_KEND = RS_WX + 4096;
constexpr int RS_EV   = RS_BAR + 256;
constexpr int R_SMEM  = RS_KEND > RS_QEND ? RS_KEND : RS_QEND;
static_assert(R_SMEM <= 232448, "smem");
static_assert(RS_TAIL % 1024 == 0 && RS_MEM % 1024 == 0, "alignment");

constexpr int RB_G = RS_BAR, RB_K = RS_BAR + 24, RB_V = RS_BAR + 32, RB_KV = RS_BAR + 40, RB_QX = RS_BAR + 48, RB_O = RS_BAR + 56;
constexpr int RB_ATT = RS_BAR + 64, RB_W = RS_BAR + 72, RB_SF = RS_BAR + 80, RB_SE = RB_SF + 40, RB_XF = RB_SE + 40;
constexpr int RB_T = RB_XF + 64, RS_INV = RB_SF;
static_assert(RB_T + 8 <= RS_EV, "barriers");
constexpr uint32_t SB0 = 1024;
__host__ __device__ constexpr uint32_t cdesc(uint32_t off, uint32_t lbo) { return ((SB0 + off) >> 4) | ((lbo >> 4) << 16); }
#define SCHED_FENCE() __syncwarp()
constexpr int NB_BIG = 1, NB_Q = 2, NB_AUX = 3, NB_WO = 4, NB_XS = 5, NB_WG = 6, NB_PAIR = 8;

DEVI int tid_now() { int t; asm volatile("mov.u32 %0, %%tid.x;" : "=r"(t)); return t; }
DEVI uint32_t a_frag_off(int lane, int warp) { return (uint32_t)((((lane >> 4) * 8 + (lane & 7)) * 128) + (((2 * warp + ((lane >> 3) & 1)) ^ (lane & 7)) * 16)); }
DEVI uint32_t b_frag_off(int lane) { return (uint32_t)((lane & 3) * 64 + (((lane >> 2) * 8) ^ ((lane & 2) * 16))); }
DEVI void lds_b(uint32_t* b, uint32_t a) {
    asm volatile("ld.shared.v2.u32 {%0,%1}, [%2];" : "=r"(b[0]), "=r"(b[1]) : "r"(a) : "memory");
    asm volatile("ld.shared.v2.u32 {%0,%1}, [%2];" : "=r"(b[2]), "=r"(b[3]) : "r"(a + 256) : "memory");
}
DEVI uint32_t clk32() { unsigned long long c; asm volatile("mov.u64 %0, %%clock64;" : "=l"(c)); return (uint32_t)c; }
DEVI bool elect_one() {
    uint32_t e; asm volatile("{.reg .pred p; elect.sync _|p, 0xffffffff; selp.u32 %0, 1, 0, p;}" : "=r"(e)); return e;
}
DEVI void spin_until(uint32_t t) { while ((int)((uint32_t)gtime() - t) < 0) { } }

DEVI void x_load(uint32_t sb, int seg, int j, int g, const CUtensorMap* tmX) {
    const uint32_t bar = sb + RB_XF + g * (8 * X_SLOTS) + 8 * (j % X_SLOTS);
    mbar_expect_tx(bar, 4096);
    tma_load_3d(sb + RS_X + g * X_PITCH + (j % X_SLOTS) * 4096, tmX, g * 32, seg * 32, j * 2, bar);
}
DEVI void x_refill(uint32_t sb, int seg, int j, int g, int warp, const CUtensorMap* tmX) {
    const int sn = j + X_SLOTS < X_NST ? seg : seg + 1;
    if (warp == (j & 3) && sn < NSEG) {
        if (elect_one()) x_load(sb, sn, (j + X_SLOTS) % X_NST, g, tmX);
    }
}
template <int J0, int J1>
DEVI void x_stages(float* xa, const uint32_t* w, uint32_t sb, int seg, int g0, int warp, const CUtensorMap* tmX) {
#pragma unroll
    for (int j = J0; j < J1; j++) {
        const int g = (int)opaque((uint32_t)g0);
        const uint32_t dW0 = cdesc(RS_WSS, 16) + g * 768, dW1 = cdesc(RS_WSS + 8192, 16) - g * 256;
        const uint32_t dX = cdesc(RS_X + (j % X_SLOTS) * 4096, 16) + g * (X_PITCH >> 4);
        mbar_wait(sb + RB_XF + g * (8 * X_SLOTS) + 8 * (j % X_SLOTS), (j / X_SLOTS) & 1);
        wg_fence();
#pragma unroll
        for (int q = 0; q < 8; q++) {
            const int pos = r_tinv(2 * j + (q >> 2)), kk = (q >> 1) & 1, mt = q & 1;
            const uint32_t db = dX + (q >> 2) * 128 + kk * 2;
            if (j == 0 && q < 2)   wgmma_n32_rs_first(xa + 16 * mt, &w[((r_rs(pos) * 2 + kk) * 2 + mt) * 4], db);
            else if (j == 0 && q == 3) wgmma_n32_ss(xa + 16, cdesc(RS_WX, 16) + g * 128, db);
            else if (r_pos_ss(pos)) wgmma_n32_ss(xa + 16 * mt, (mt ? dW1 : dW0) + r_ss(pos) * 1024 + kk * 128, db);
            else                   wgmma_n32_rs(xa + 16 * mt, &w[((r_rs(pos) * 2 + kk) * 2 + mt) * 4], db);
        }
        wg_commit();
        if (j > J0) { wg_wait<1>(); x_refill(sb, seg, j - 1, g, warp, tmX); }
    }
    wg_wait<0>();
    reg_fence<32>(xa);
    if (J1 < X_NST) x_refill(sb, seg, J1 - 1, (int)opaque((uint32_t)g0), warp, tmX);
}
DEVI void x_finish(float* xa, uint32_t sb, int g, int warp, int lane) {
    const uint32_t ring = sb + RS_X + (X_SLOTS - 1) * 4096 + warp * 512 + lane * 16;
    const uint32_t d = sb + RS_XD + (lane >> 4) * 2048 + warp * 256 + (lane & 15) * 16;
    sts128f(d + (g ^ 1) * 1024, xa + 24); sts128f(d + (g ^ 1) * 1024 + 4096, xa + 28);
    nbar_sync(NB_WG + g, 128);
    sts128f(ring + g * X_PITCH, xa + 16); sts128f(ring + g * X_PITCH + 2048, xa + 20);
    nbar_sync(NB_PAIR + warp, 64);
    uint32_t p[8];
#pragma unroll
    for (int i = 0; i < 4; i++) {
        const uint4 v = lds128(i < 2 ? ring + (g ^ 1) * X_PITCH + i * 2048 : d + g * 1024 + (i - 2) * 4096);
        p[2 * i]     = pack_bf16(xa[4 * i] + __uint_as_float(v.x), xa[4 * i + 1] + __uint_as_float(v.y));
        p[2 * i + 1] = pack_bf16(xa[4 * i + 2] + __uint_as_float(v.z), xa[4 * i + 3] + __uint_as_float(v.w));
    }
    __syncwarp();
    stsm4(d + g * 1024, p[0], p[1], p[2], p[3]);
    stsm4(d + g * 1024 + 4096, p[4], p[5], p[6], p[7]);
    nbar_arrive(NB_XS, 256 + 32);
}
DEVI void x_send(uint32_t sb, int seg, uint32_t rank, const CUtensorMap* tmX) {
    mbar_wait(sb + RB_ATT, (seg - 1) & 1);
    nbar_sync(NB_XS, 256 + 32);
    if (elect_one()) {
        fence_proxy_async();
        bulk_copy_s2c(mapa(sb + (rank == 1 ? RS_K : RS_V) + 2048, 0), sb + RS_XD, 8192, mapa(sb + RB_KV, 0));
        if (seg + 1 < NSEG) { x_load(sb, seg + 1, X_SLOTS - 1, 0, tmX); x_load(sb, seg + 1, X_SLOTS - 1, 1, tmX); }
    }
    __syncwarp();
}

template <bool XP>
DEVI void mem_pass(float* c0, float* c1, const uint32_t* w, uint32_t sb, uint32_t aA0, uint32_t aB, int g, int s) {
    const uint32_t aA1 = aA0 + 8192 - g * 16384, par = (s - 1) & 1;
    uint32_t a[16], b[2][4], e[4];
    float d0[4], d1[4];
    if (XP) ldsm4t(e, aA0 + (RS_WX - RS_WSS) - g * (8192 + 2048));
#pragma unroll
    for (int q = 0; q < 4; q++) ldsm4t(a + 4 * q, ((q & 1) ? aA1 : aA0) + (q >> 1) * 2048);
#pragma unroll
    for (int i = 0; i < 4; i++) { c0[i] = 0.f; c1[i] = 0.f; d0[i] = 0.f; d1[i] = 0.f; }
    EV(tid_now() == 0, s, 0);
    mbar_wait(sb + RB_G, par);
    EV(tid_now() == 0, s, 1);
    lds_b(b[0], aB + r_tord(0) * 1024);
    bool in = false;
#pragma unroll
    for (int pos = 0; pos < 16; pos++) {
        if (pos + 1 < 16) {
            if (pos + 1 == R_G1) { if (!in) mbar_wait(sb + RB_G + 8, par); EV(tid_now() == 0, s, 2); }
            lds_b(b[(pos + 1) & 1], aB + r_tord(pos + 1) * 1024);
        }
        if (pos + 2 == R_G1) in = mbar_try(sb + RB_G + 8, par);
        if (XP && pos == 14) in = mbar_try(sb + RB_ATT, par);
        const uint32_t* bb = b[pos & 1];
        const uint32_t* aa = r_pos_ss(pos) ? a : &w[r_rs(pos) * 16];
        mma16816(c1, aa + 4, bb[0], bb[1]);
        mma16816(d1, XP && pos == 0 ? e : aa + 12, bb[2], bb[3]);
        mma16816(c0, aa, bb[0], bb[1]);
        mma16816(d0, aa + 8, bb[2], bb[3]);
        if (r_pos_ss(pos) && pos + 3 < 16) {
#pragma unroll
            for (int q = 0; q < 4; q++) ldsm4t(a + 4 * q, ((q & 1) ? aA1 : aA0) + (r_ss(pos) + 1) * 16384 + (q >> 1) * 2048);
        }
        SCHED_FENCE();
    }
    if (XP && !in) mbar_wait(sb + RB_ATT, par);
#pragma unroll
    for (int i = 0; i < 4; i++) { c1[i] += d1[i]; c0[i] += d0[i]; }
}

DEVI uint32_t k_frag_off(int lane) { return (uint32_t)((((lane >> 3) & 1) * 16 + (lane >> 4) * 8 + (lane & 7)) * 16); }
DEVI uint32_t v_frag_off(int lane) { return (uint32_t)(((lane >> 3) & 1) * 2048 + ((lane >> 4) * 8 + (lane & 7)) * 16); }
DEVI void pv_pair(float (*o)[4], const uint32_t* p, const uint32_t* v) {
#pragma unroll
    for (int n = 0; n < 4; n++) mma16816(o[n], p, v[2 * n], v[2 * n + 1]);
}
DEVI void pv_single(float (*o)[4], const uint32_t* p, const uint32_t* v) {
#pragma unroll
    for (int n = 0; n < 4; n++) mma1688(o[n], p[0], p[1], v[n]);
}
DEVI float inv_sum4(float l) {
    l += __shfl_xor_sync(0xffffffffu, l, 1);
    l += __shfl_xor_sync(0xffffffffu, l, 2);
    return rcp_fast(l);
}

DEVI void mem_attn(uint32_t sb, int s, int warp, int lane) {
    const uint32_t ka = sb + RS_K + k_frag_off(lane), va = sb + RS_V + warp * 512;
    uint32_t qa[16], vx[16];
    float sc[10];
    mbar_wait(sb + RB_KV, s & 1);
    {
        uint32_t kx[16];
#pragma unroll
        for (int q = 0; q < 4; q++) ldsm4t(kx + 4 * q, ka + (1 + warp) * 2048 + q * 512);
        nbar_sync(NB_Q, 256);
        EV(tid_now() == 0 && lds32(sb + RS_Q) != 0x12345678u, s, 8);
#pragma unroll
        for (int q = 0; q < 4; q++) ldsm4t(qa + 4 * q, sb + RS_Q + q * 512 + lane * 16);
        float c[4] = {0.f, 0.f, 0.f, 0.f}, d[4] = {0.f, 0.f, 0.f, 0.f};
#pragma unroll
        for (int q = 0; q < 4; q++) { mma16816(c, qa + 4 * q, kx[4 * q], kx[4 * q + 1]); mma16816(d, qa + 4 * q, kx[4 * q + 2], kx[4 * q + 3]); }
        asm volatile("st.shared.v2.f32 [%0], {%1,%2};" :: "r"(sb + RS_SX + warp * 256 + lane * 8), "f"(c[0] + d[2]), "f"(c[1] + d[3]) : "memory");
    }
    nbar_sync(NB_WG, 128);
#pragma unroll
    for (int n = 0; n < 4; n++) { const float2 v = lds64f(sb + RS_SX + n * 256 + lane * 8); sc[2 + 2 * n] = v.x; sc[3 + 2 * n] = v.y; }
    const uint32_t dst = sb + RS_O + warp * 512 + (lane & 3) * 128 + (lane >> 2) * 16;
    float m = fmaxf(fmaxf(fmaxf(sc[2], sc[3]), fmaxf(sc[4], sc[5])), fmaxf(fmaxf(sc[6], sc[7]), fmaxf(sc[8], sc[9])));
    mbar_wait(sb + RB_K, s & 1);
    EV(tid_now() == 0, s, 9);
    {
        float c[4][4];
#pragma unroll
        for (int q = 0; q < 4; q++) { c[q][0] = c[q][1] = c[q][2] = c[q][3] = 0.f; }
        uint32_t km[16];
#pragma unroll
        for (int q = 0; q < 4; q++) ldsm4t(km + 4 * q, ka + q * 512);
        SCHED_FENCE();
#pragma unroll
        for (int q = 0; q < 4; q++) {
            mma16816(c[2 * (q & 1)], qa + 4 * q, km[4 * q], km[4 * q + 1]);
            mma16816(c[2 * (q & 1) + 1], qa + 4 * q, km[4 * q + 2], km[4 * q + 3]);
        }
        sc[0] = (c[0][0] + c[1][2]) + (c[2][0] + c[3][2]);
        sc[1] = (c[0][1] + c[1][3]) + (c[2][1] + c[3][3]);
    }
    const bool v_in = mbar_try(sb + RB_V, s & 1);
#pragma unroll
    for (int q = 0; q < 4; q++) ldsm4(vx + 4 * q, va + 2048 + (q >> 1) * 4096 + (q & 1) * 256 + v_frag_off(lane));
    m = fmaxf(m, fmaxf(sc[0], sc[1]));
    m = fmaxf(fmaxf(m, __shfl_xor_sync(0xffffffffu, m, 1)), fmaxf(__shfl_xor_sync(0xffffffffu, m, 2), __shfl_xor_sync(0xffffffffu, m, 3)));
    if (!v_in) mbar_wait(sb + RB_V, s & 1);
    uint32_t vm[4], p[10];
    ldsm4(vm, va + lane * 16);
    const float nm = -m * SCALE_LOG2E;
    float l = 0.f;
#pragma unroll
    for (int n = 4; n >= 0; n--) {
        const float e0 = ex2(fmaf(sc[2 * n], SCALE_LOG2E, nm)), e1 = ex2(fmaf(sc[2 * n + 1], SCALE_LOG2E, nm));
        l += e0 + e1;
        p[2 * n] = pack_bf16(e0, e1); p[2 * n + 1] = __float_as_uint(e0);
    }
    float o[4][4];
#pragma unroll
    for (int n = 0; n < 4; n++) { o[n][0] = o[n][1] = o[n][2] = o[n][3] = 0.f; }
    pv_pair(o, p + 6, vx + 8);
    pv_pair(o, p + 2, vx);
    pv_single(o, p, vm);
    l = (l + __shfl_xor_sync(0xffffffffu, l, 1)) + (__shfl_xor_sync(0xffffffffu, l, 2) + __shfl_xor_sync(0xffffffffu, l, 3));
    if ((lane & 3) == 0) {
        if (warp == 0) sts32(sb + RS_INV + lane, __float_as_uint(l));
        else if (warp < 3)
            asm volatile("st.async.weak.shared::cluster.mbarrier::complete_tx::bytes.b32 [%0], %1, [%2];"
                         :: "r"(mapa(sb + RS_INV + lane, warp)), "r"(__float_as_uint(l)), "r"(mapa(sb + RB_O, warp)) : "memory");
    }
    const uint4 u = make_uint4(pack_bf16(o[0][0], o[0][1]), pack_bf16(o[1][0], o[1][1]), pack_bf16(o[2][0], o[2][1]), pack_bf16(o[3][0], o[3][1]));
    st_async128(mapa(dst, 1), u.x, u.y, u.z, u.w, mapa(sb + RB_O, 1));
    st_async128(mapa(dst, 2), u.x, u.y, u.z, u.w, mapa(sb + RB_O, 2));
    sts128(dst, u);
    __syncwarp();
    if (elect_one()) mbar_arrive(sb + RB_O);
}

DEVI void ta_scores(float* c, uint32_t sb, int seg, int cw, int lane) {
    const int mt = cw >= 3, n = cw - 3 * mt;
    const uint32_t qa = sb + RS_QX + (2 * mt + ((lane >> 3) & 1)) * 2048 + ((lane >> 4) * 8 + (lane & 7)) * 16;
    const uint32_t ka = sb + RS_K + n * 2048 + lane * 16;
    float d[4] = {0.f, 0.f, 0.f, 0.f};
    c[0] = c[1] = c[2] = c[3] = 0.f;
    mbar_wait(sb + RB_QX, seg & 1);
    mbar_wait(sb + (n == 0 ? RB_K : RB_KV), seg & 1);
#pragma unroll
    for (int j = 0; j < 4; j++) {
        uint32_t a0[4], a1[4], b[4];
        ldsm4t(a0, qa + j * 512);
        ldsm4t(b, ka + j * 512);
        ldsm4t(a1, qa + j * 512 + 256);
        mma16816(c, a0, b[0], b[1]);
        mma16816(d, a1, b[2], b[3]);
    }
    const int over = 8 * (n - 1) + 2 * (lane & 3) - 16 * mt - (lane >> 2);
    c[0] = over > 0 ? -INFINITY : c[0] + d[0];
    c[1] = over >= 0 ? -INFINITY : c[1] + d[1];
    c[2] = over > 8 ? -INFINITY : c[2] + d[2];
    c[3] = over >= 8 ? -INFINITY : c[3] + d[3];
}
DEVI void ta_output(uint32_t sb, int seg, int head, int mt, int j, int lane) {
    const uint32_t sa = sb + RS_QX + mt * 1536 + lane * 16;
    float sc[5][4];
#pragma unroll
    for (int n = 0; n < 5; n++) {
        uint4 v = make_uint4(0xFF800000u, 0xFF800000u, 0xFF800000u, 0xFF800000u);
        if (n < 2 || n == 4 || mt) v = lds128(sa + (n == 4 ? 1024 + mt * 1024 : n * 512));
        sc[n][0] = __uint_as_float(v.x); sc[n][1] = __uint_as_float(v.y); sc[n][2] = __uint_as_float(v.z); sc[n][3] = __uint_as_float(v.w);
    }
    float m0 = -INFINITY, m1 = -INFINITY;
#pragma unroll
    for (int n = 0; n < 5; n++) { m0 = fmaxf(m0, fmaxf(sc[n][0], sc[n][1])); m1 = fmaxf(m1, fmaxf(sc[n][2], sc[n][3])); }
    m0 = fmaxf(m0, __shfl_xor_sync(0xffffffffu, m0, 1)); m1 = fmaxf(m1, __shfl_xor_sync(0xffffffffu, m1, 1));
    m0 = fmaxf(m0, __shfl_xor_sync(0xffffffffu, m0, 2)); m1 = fmaxf(m1, __shfl_xor_sync(0xffffffffu, m1, 2));
    m0 *= -SCALE_LOG2E; m1 *= -SCALE_LOG2E;
    float l0 = 0.f, l1 = 0.f;
    uint32_t p[10];
#pragma unroll
    for (int n = 0; n < 5; n++) {
        const float e0 = ex2(fmaf(sc[n][0], SCALE_LOG2E, m0)), e1 = ex2(fmaf(sc[n][1], SCALE_LOG2E, m0));
        const float e2 = ex2(fmaf(sc[n][2], SCALE_LOG2E, m1)), e3 = ex2(fmaf(sc[n][3], SCALE_LOG2E, m1));
        l0 += e0 + e1; l1 += e2 + e3;
        p[2 * n] = pack_bf16(e0, e1); p[2 * n + 1] = pack_bf16(e2, e3);
    }
    const float i0 = inv_sum4(l0), i1 = inv_sum4(l1);
    mbar_wait(sb + RB_V, seg & 1);
    mbar_wait(sb + RB_KV, seg & 1);
    const uint32_t vb = sb + RS_V + j * 512;
    float o[4][4];
#pragma unroll
    for (int n = 0; n < 4; n++) { o[n][0] = o[n][1] = o[n][2] = o[n][3] = 0.f; }
    uint32_t v[8];
    ldsm4(v, vb + v_frag_off(lane)); ldsm4(v + 4, vb + v_frag_off(lane) + 256);
    pv_pair(o, p, v);
    SCHED_FENCE();
    ldsm4(v, vb + 4096 + v_frag_off(lane)); ldsm4(v + 4, vb + 4096 + v_frag_off(lane) + 256);
    pv_pair(o, p + 4, v);
    SCHED_FENCE();
    ldsm4(v, vb + 4096 + mt * 4096 + lane * 16);
    pv_single(o, p + 8, v);
    bf16* dst = g_ox + (uint32_t)((seg * 32 + mt * 16 + (lane >> 2)) * HD + head * DH + j * 32 + (lane & 3) * 8);
    asm volatile("st.global.v4.u32 [%0], {%1,%2,%3,%4};" :: "l"(dst), "r"(pack_bf16(o[0][0] * i0, o[0][1] * i0)), "r"(pack_bf16(o[1][0] * i0, o[1][1] * i0)),
                 "r"(pack_bf16(o[2][0] * i0, o[2][1] * i0)), "r"(pack_bf16(o[3][0] * i0, o[3][1] * i0)) : "memory");
    asm volatile("st.global.v4.u32 [%0], {%1,%2,%3,%4};" :: "l"(dst + 8 * HD), "r"(pack_bf16(o[0][2] * i1, o[0][3] * i1)), "r"(pack_bf16(o[1][2] * i1, o[1][3] * i1)),
                 "r"(pack_bf16(o[2][2] * i1, o[2][3] * i1)), "r"(pack_bf16(o[3][2] * i1, o[3][3] * i1)) : "memory");
}

template <bool XP>
DEVI void big_main(const uint32_t* w, const uint32_t sb, const int g, const int warp, const uint32_t rank, const int head,
                   const CUtensorMap* tmX, const bf16* xg, const unsigned E) {
    float xa[32];
    const uint32_t aB = __shfl_sync(0xffffffffu, sb + RS_MEM + (g * 32 + (tid_now() & 31)) * 16, tid_now() & 31);
#define lane0 ((int)(opaque(aB) >> 4) & 31)
    const uint32_t aA0 = sb + RS_WSS + g * (8192 + 4096) + a_frag_off(lane0, warp);
    if constexpr (XP) {
        x_stages<0, X_NST>(xa, w, sb, 0, g, warp, tmX);
        x_finish(xa, sb, g, warp, lane0);
    }
    nbar_sync(NB_BIG, 256);
    for (int s = 0; s < NSEG; s++) {
        {
            float c0[4], c1[4];
            mem_pass<XP>(c0, c1, w, sb, aA0, sb + RS_MEM + g * 512 + b_frag_off(lane0), g, s);
            const int lane = lane0, t = lane & 3;
            const uint32_t xs = aB + (RS_O - RS_MEM) + (warp - g) * 512;
            const int dim = g * 64 + warp * 16 + (lane >> 2) + ((t & 1) ? 8 : 0);
            const uint32_t off = (uint32_t)((XP ? (rank == 1 ? RS_K : RS_V) : RS_Q) + dim * 16 + (t & 2) * 4);
            const uint32_t dst = XP ? mapa(sb + off, 0) : sb + off;
            const uint32_t rbar = XP ? mapa(sb + (rank == 1 ? RB_K : RB_V), 0) : 0u;
            EV(tid_now() == 0 && c0[0] != 1.2345e30f, s, 3);
            sts128f(xs + g * 2048, c1);
            nbar_sync(NB_PAIR + warp, 64);
            const uint4 v = lds128(xs + (g ^ 1) * 2048);
            const uint32_t p0 = pack_bf16(c0[0] + __uint_as_float(v.x), c0[1] + __uint_as_float(v.y));
            const uint32_t p1 = pack_bf16(c0[2] + __uint_as_float(v.z), c0[3] + __uint_as_float(v.w));
            const uint32_t rcv = __shfl_xor_sync(0xffffffffu, (t & 1) ? p0 : p1, 1);
            const uint32_t lo = (t & 1) ? rcv : p0, hi = (t & 1) ? p1 : rcv;
            if constexpr (XP) st_async64(dst, lo, hi, rbar);
            else if (s < NSEG - 1) {
                asm volatile("st.shared.v2.u32 [%0], {%1,%2};" :: "r"(dst), "r"(lo), "r"(hi) : "memory");
                if (g == 1) nbar_arrive(NB_Q, 256);
            }
            EV(tid_now() == 0, s, 4);
        }
        if constexpr (XP) {
            if (s == NSEG - 1) break;
            x_stages<0, X_NA>(xa, w, sb, s + 1, g, warp, tmX);
            EV(tid_now() == 0, s, 5);
            EVCAL(s);
            nbar_sync(NB_WO, 384);
            EV(tid_now() == 0 && lds32(sb + RS_O) != 0x12345678u, s, 6);
            x_stages<X_NA, X_NST>(xa, w, sb, s + 1, g, warp, tmX);
            EV(tid_now() == 0, s, 7);
            x_finish(xa, sb, g, warp, lane0);
        } else {
            if (g == 0) {
                if (s < NSEG - 1) mem_attn(sb, s, warp, lane0);
            } else {
                if (s == 0 && warp == 0) {
                    wait_count_warp(&g_cnt_q[0], 64 * E);
                    if (elect_one()) {
                        asm volatile("fence.proxy.async;" ::: "memory");
                        mbar_expect_tx(sb + RB_QX, 8192);
                        bulk_load(sb + RS_QX, g_qx + (size_t)head * 4096, 8192, sb + RB_QX);
                    }
                    __syncwarp();
                }
                float sc[8];
                const int t2 = warp == 3 ? 3 : (warp + 1) % 3;
                ta_scores(sc, sb, s, 4 + warp, lane0);
                ta_scores(sc + 4, sb, s, t2, lane0);
                nbar_sync(NB_WG + 1, 128);
                sts128f(aB + (RS_QX - RS_MEM) + (3 + warp) * 512, sc);
                sts128f(aB + (RS_QX - RS_MEM) + (t2 - 1) * 512, sc + 4);
            }
            EVCAL(s);
            if (s < NSEG - 1) nbar_sync(NB_WO, 384); else nbar_sync(NB_BIG, 256);
            EV(tid_now() == 0 && lds32(sb + RS_O) != 0x12345678u, s, 6);
            ta_output(sb, s, head, g, warp, lane0);
            nbar_sync(NB_BIG, 256);
            EV(tid_now() == 0 && lds32(sb + RS_O) != 0x12345678u, s, 7);
            if (g == 0 && warp == 0 && s + 1 < NSEG) {
                if (elect_one()) {
                    mbar_arrive_remote(mapa(sb + RB_ATT, 1));
                    mbar_arrive_remote(mapa(sb + RB_ATT, 2));
                    mbar_expect_tx(sb + RB_KV, 16384);
                    mbar_expect_tx(sb + RB_K, 2048);
                    mbar_expect_tx(sb + RB_V, 2048);
                    mbar_arrive(sb + RB_T);
                }
                __syncwarp();
            }
        }
    }
    if constexpr (!XP) { if (tid_now() == 0) signal_count(&g_prog[(NSEG - 1) >> 2]); }
#undef lane0
}

template <int T, int K0, int K1>
DEVI void wo_part(float* acc) {
    constexpr uint32_t dWo = cdesc(T < 5 ? RS_WO + T * 16384 : RS_WO5, 16), dO = cdesc(RS_O, 128);
#pragma unroll
    for (int kk = K0; kk < K1; kk++) {
        if (kk == 0) { if (T < 3) wgmma_n8_ss_first<0>(acc, dWo, dO); else wgmma_n8_ss<0, 0>(acc, dWo, dO); }
        else wgmma_n8_ss<0, 1>(acc, dWo + kk * 128, dO + kk * 16);
    }
    wg_commit();
}
DEVI void red3(uint8_t* p, uint32_t a, uint32_t b, uint32_t c, uint32_t one) {
    asm volatile("red.relaxed.gpu.global.add.noftz.v4.bf16x2 [%0], {%1,%2,%3,%4};" :: "l"(p), "r"(a), "r"(b), "r"(c), "r"(one) : "memory");
}
constexpr int ACC_CH = 3 * 16 * 1024;
template <bool Q>
DEVI void wo_phase(uint32_t sb, int s, uint8_t* p, uint32_t ainv) {
    float a0[4], a1[4], a2[4];
    const float2 iv = lds64f(ainv);
    fence_proxy_async();
    const float i0 = rcp_fast(iv.x), i1 = rcp_fast(iv.y);
#define WORD(a, h) pack_bf16(a[2 * h] * i0, a[2 * h + 1] * i1)
    wg_fence();
    wo_part<0, 0, 8>(a0); wo_part<1, 0, 8>(a1); wo_part<2, 0, 8>(a2);
    wg_wait<1>(); reg_fence<4>(a0); reg_fence<4>(a1);
    red3(p, WORD(a0, 0), WORD(a0, 1), WORD(a1, 0), 0x3F80u);
    SCHED_FENCE();
    EV(tid_now() == 256, s, 11);
    wg_wait<0>(); reg_fence<4>(a2);
    red3(p + ACC_CH, WORD(a2, 0), WORD(a2, 1), WORD(a1, 1), 0x3F80u);
    if (lds32(sb + RB_W) == 0x5EEDF00Du) __trap();
    wg_fence();
    wo_part<3, 0, 8>(a0); wo_part<4, 0, 8>(a1);
    if (Q) {
        wo_part<5, 0, 8>(a2);
        wg_wait<1>(); reg_fence<4>(a0); reg_fence<4>(a1);
        red3(p + 2 * ACC_CH, WORD(a0, 0), WORD(a0, 1), WORD(a1, 0), 0x3F80u);
        SCHED_FENCE();
        wg_wait<0>(); reg_fence<4>(a2);
        red3(p + 3 * ACC_CH, WORD(a2, 0), WORD(a2, 1), WORD(a1, 1), 0x3F80u);
        nbar_arrive(NB_WO, 384);
    } else {
        wg_wait<1>();
        nbar_arrive(NB_WO, 384);
        wg_wait<0>(); reg_fence<4>(a0); reg_fence<4>(a1);
        red3(p + 2 * ACC_CH, WORD(a0, 0), WORD(a0, 1), WORD(a1, 0), 0x3F80u);
        red3(p + 3 * ACC_CH, 0u, 0u, WORD(a1, 1), 0x3F80u);
    }
#undef WORD
}
DEVI void unit_send(uint32_t d, uint32_t x0, uint32_t x1, uint32_t x2, uint32_t x3, uint32_t bar, uint32_t r1, uint32_t r2) {
    const uint32_t u0 = __byte_perm(x0, x1, 0x5410), u1 = __byte_perm(x2, x3, 0x5410), u2 = __byte_perm(x0, x1, 0x7632), u3 = __byte_perm(x2, x3, 0x7632);
    st_async128(mapa(d, r1), u0, u1, u2, u3, mapa(bar, r1));
    st_async128(mapa(d, r2), u0, u1, u2, u3, mapa(bar, r2));
    sts128(d, make_uint4(u0, u1, u2, u3));
}
template <bool Q>
DEVI void stage_sums(uint32_t sb, int s, uint32_t rank, int warp, const uint8_t* src, uint32_t l, uint32_t gate) {
    uint4 v[4];
    spin_until(gate);
    EV(elect_one(), s, 16 + warp);
#pragma unroll
    for (int j = 0; j < 4; j++) v[j] = ld_rlx4(src + j * 1024);
    const uint32_t col = sb + RS_MEM + ((Q ? 0 : (rank == 1 ? 6 : 11)) + 3 * (warp >> 1)) * 1024 + ((l >> 2) & 0x300) + (l & 0x70);
    const uint32_t r1 = Q ? 1 : 0, r2 = Q ? 2 : 3 - rank, bar = sb + RB_G + 8 * (warp >> 1);
    int n = 0;
    while (!__all_sync(0xffffffffu, v[0].w == 0x4200u && v[1].w == 0x4200u && v[2].w == 0x4200u && v[3].w == 0x4200u)) {
#pragma unroll
        for (int j = 0; j < 4; j++) v[j] = ld_rlx4(src + j * 1024);
        if (++n > SPIN_LIMIT) TRAP(0x20000000u | (s << 8) | warp);
    }
    EV(elect_one(), s, 24 + warp);
    if (Q || warp < 3) {
        unit_send(col + (warp & 1) * 2048, v[0].x, v[1].x, v[2].x, v[3].x, bar, r1, r2);
        unit_send((col ^ 160) + (warp & 1) * 2048, v[0].y, v[1].y, v[2].y, v[3].y, bar, r1, r2);
    }
    unit_send((col ^ ((warp & 1) * 160)) + 1024, v[0].z, v[1].z, v[2].z, v[3].z, bar, r1, r2);
    __syncwarp();
    if (elect_one()) mbar_expect_tx(bar, warp < 2 ? 3072u : (warp == 3 ? 0u : (Q ? 4096u : 5120u)));
    EV(elect_one(), s, 20 + warp);
}
DEVI void wo_permute(uint32_t a, int n) {
    const uint32_t flip = (a >> 3) & 16;
#pragma unroll 2
    for (int i = 0; i < n; i++, a += 4096) {
        const uint4 v = lds128(a ^ flip), u = lds128(a ^ flip ^ 16);
        sts128(a ^ flip, make_uint4(__byte_perm(v.x, v.y, 0x5410), __byte_perm(v.x, v.y, 0x7632), __byte_perm(u.x, u.y, 0x5410), __byte_perm(u.x, u.y, 0x7632)));
        sts128(a ^ flip ^ 16, make_uint4(__byte_perm(v.z, v.w, 0x5410), __byte_perm(v.z, v.w, 0x7632), __byte_perm(u.z, u.w, 0x5410), __byte_perm(u.z, u.w, 0x7632)));
    }
}
DEVI void acc_clear(int slot, int idx) {
    const int lane = tid_now() & 31;
    if (lane < 24) st_rlx4(g_acc + slot * 128 + (idx * 3 + (lane >> 3)) * 1024 + (lane & 7) * 16, 0u, 0u, 0u, 0u);
}

template <bool Q>
DEVI void aux_main(uint32_t sb, int warp, uint32_t rank, int head, const CUtensorMap* tmX, const bf16* xg, unsigned E, int delay, int period, const int4 tune) {
    const uint32_t lo = __shfl_sync(0xffffffffu, ((tid_now() >> 3) & 3) * 1024 + (tid_now() & 7) * 16, tid_now() & 31);
    if (!Q && warp == 3) x_send(sb, 0, rank, tmX);
    for (int s = 0; s < NSEG - 1; s++) {
        if (!Q && warp == 0 && elect_one()) mbar_expect_tx(sb + RB_O, 2048 + 32);
        __syncwarp();
        const uint32_t slot = (s & 3) * 128 + rank * 16384;
        mbar_wait(sb + RB_O, s & 1);
        uint32_t pred; asm volatile("ld.relaxed.gpu.global.u32 %0, [%1];" : "=r"(pred) : "l"(&g_pred) : "memory");
        EV(tid_now() == 256, s, 10);
        wo_phase<Q>(sb, s, g_acc + (uint32_t)(slot + warp * 4096 + opaque(lo)), sb + RS_INV + ((opaque(lo) >> 1) & 24));
        SCHED_FENCE();
        const unsigned long long now = gtime();
        if (warp == 0 && elect_one()) asm volatile("red.relaxed.gpu.global.max.u64 [%0], %1;" :: "l"(&g_tlast), "l"(now) : "memory");
        const uint32_t t_o = ((pred ^ s) & 31) == 0 && (pred - (uint32_t)now) < 4096u && s > 0 ? pred : (uint32_t)now;
        EV(tid_now() == 256, s, 12);
        {
            const uint32_t l = opaque(lo);
            const uint8_t* src = g_acc + (uint32_t)(slot + warp * ACC_CH + (l & 0xC00) * 4 + (l & 0x70));
            stage_sums<Q>(sb, s, rank, warp, src, l, t_o + delay);
        }
        EV(tid_now() == 256 + 64, s, 14);
        mbar_wait(sb + RB_G + 8, s & 1);
        if (warp == 3) {
            if (Q) {
                mbar_wait(sb + RB_T, s & 1);
                if ((s & 7) == 7) wait_count_warp(&g_cnt_q[(s + 1) >> 3], 64 * E);
                if (elect_one()) {
                    if ((s & 7) == 7) asm volatile("fence.proxy.async;" ::: "memory"); else fence_proxy_async();
                    mbar_expect_tx(sb + RB_QX, 8192);
                    bulk_load(sb + RS_QX, g_qx + ((size_t)(s + 1) * NH + head) * 4096, 8192, sb + RB_QX);
                    signal_count(&g_prog[s >> 2]);
                    if (s + 4 < NSEG) l2_prefetch(xg + (size_t)((s + 4) * 32 + head) * DM, 2048);
                }
                __syncwarp();
            } else {
                x_send(sb, s + 1, rank, tmX);
                if (s + 2 < NSEG - 1) { acc_clear((s + 2) & 3, 2 * head + (int)rank - 1); __threadfence(); }
            }
        }
        if (Q && head == 0 && warp == 0) {
            if (elect_one()) {
                uint32_t tl; asm volatile("ld.relaxed.gpu.global.u32 %0, [%1];" : "=r"(tl) : "l"(&g_tlast) : "memory");
                const uint32_t st = sb + RS_INV + 32;
                uint32_t pr = s == 0 ? tl : lds32(st);
                int per = s == 0 ? period : (int)lds32(st + 4);
                const bool clean = s > 0 && lds32(st + 8);
                const int err = (int)(tl - pr);
                const bool miss = err > tune.x || s == 0;
                if (clean) per += miss ? min(err, 256) >> 1 : (err + tune.y) >> tune.w;
                pr += per + (miss ? err + tune.z : 0);
                st_rlx(&g_pred, (pr & ~31u) | ((s + 1) & 31));
                sts32(st, pr); sts32(st + 4, (uint32_t)per); sts32(st + 8, !miss);
            }
            __syncwarp();
        }
    }
}

DEVI void load_weights(uint32_t sb, const CUtensorMap* tmW, const CUtensorMap* tmWo, int head, uint32_t rank) {
    const uint32_t bW = sb + RB_W, bSF = sb + RB_SF, bSE = sb + RB_SE;
    const int ntile = rank == 0 ? 6 : 5, tile0 = rank == 0 ? 0 : (rank == 1 ? 6 : 11);
    mbar_expect_tx(bW, R_NSS * 16384 + ntile * 16384);
    if (rank == 0) tma_load_wo(sb + RS_WO5, tmWo, 5 * 64, head * 4, bW);
    for (int pos = 0; pos < 16; pos++) {
        const int k = (int)((R_TORD_PACK >> (4 * pos)) & 15ull) * 64;
        if (r_pos_ss(pos)) {
            const uint32_t dst = sb + RS_WSS + (pos / 3) * 16384;
            tma_load_2d(dst, tmW, head * DH, k, bW);
            tma_load_2d(dst + 8192, tmW, head * DH + 64, k, bW);
        } else {
            const int rd = pos - pos / 3, slot = rd % 5;
            if (rd >= 5) mbar_wait(bSE + 8 * slot, ((rd / 5) - 1) & 1);
            mbar_expect_tx(bSF + 8 * slot, 16384);
            const uint32_t dst = sb + RS_WO + slot * 16384;
            tma_load_2d(dst, tmW, head * DH, k, bSF + 8 * slot);
            tma_load_2d(dst + 8192, tmW, head * DH + 64, k, bSF + 8 * slot);
        }
    }
    for (int slot = 0; slot < 5; slot++) {
        const int last = slot + 10 < R_NRS ? slot + 10 : slot + 5;
        mbar_wait(bSE + 8 * slot, (last / 5) & 1);
        tma_load_wo(sb + RS_WO + slot * 16384, tmWo, (tile0 + slot) * 64, head * 4, bW);
    }
}
template <bool XP>
DEVI void big_prologue(uint32_t* w, uint32_t sb, int g, int warp, const bf16* __restrict__ mem0) {
    const int tid = tid_now(), lane = tid & 31;
#pragma unroll 1
    for (int ks = tid >> 5; ks < 64; ks += 8) {
        const uint32_t* m = (const uint32_t*)(mem0 + (lane >> 2) * DM + ks * 16) + (lane & 3);
        sts64(sb + RS_MEM + ks * 256 + b_frag_off(lane), m[0], m[4]);
    }
    const uint32_t a0 = sb + RS_WO + g * (8192 + 4096) + a_frag_off(lane, warp), a1 = a0 + 8192 - g * 16384;
#pragma unroll
    for (int rd = 0; rd < R_NRS; rd++) {
        const int slot = rd % 5;
        mbar_wait(sb + RB_SF + 8 * slot, (rd / 5) & 1);
#pragma unroll
        for (int q = 0; q < 4; q++) {
            if (XP && rd == 0 && q == 3) {
                sts128(sb + RS_WX + g * 2048 + (tid & 127) * 16, lds128(sb + RS_WO + 8192 - g * 4096 + 2048 + (tid & 127) * 16));
                fence_proxy_async();
                nbar_sync(NB_WG + g, 128);
            } else ldsm4t(&w[rd * 16 + q * 4], ((q & 1) ? a1 : a0) + slot * 16384 + (q >> 1) * 2048);
        }
        mbar_arrive(sb + RB_SE + 8 * slot);
    }
    mbar_wait(sb + RB_W, 0);
}

__global__ void __cluster_dims__(3, 1, 1) __launch_bounds__(384, 1)
k_rec(const __grid_constant__ CUtensorMap tmWq, const __grid_constant__ CUtensorMap tmWk, const __grid_constant__ CUtensorMap tmWv,
      const __grid_constant__ CUtensorMap tmWo, const __grid_constant__ CUtensorMap tmX, const bf16* __restrict__ mem0, const bf16* __restrict__ xg,
      int hq0, int hqw, int hq2, int hk0, int hkw, int hk2, int period, int4 tune) {
    extern __shared__ __align__(1024) uint8_t smem_raw[];
    const uint32_t sb = smem_u32(smem_raw);
    if ((sb & 0x3FFFFu) != SB0) __trap();
    const int tid = threadIdx.x;
    const int wg = __shfl_sync(0xffffffffu, tid >> 7, 0), warp = __shfl_sync(0xffffffffu, (tid >> 5) & 3, 0);
    uint32_t rank; asm("mov.u32 %0, %%cluster_ctarank;" : "=r"(rank));
    const int head = blockIdx.x / 3;
    if (tid == 0) {
        mbar_init(sb + RB_G, 2);
        mbar_init(sb + RB_G + 8, 2);
        mbar_init(sb + RB_T, 1);
        mbar_init(sb + RB_K, 1); mbar_init(sb + RB_V, 1); mbar_init(sb + RB_KV, 1); mbar_init(sb + RB_QX, 1);
        mbar_init(sb + RB_O, rank == 0 ? 4 : 1); mbar_init(sb + RB_ATT, 1); mbar_init(sb + RB_W, 1);
        for (int i = 0; i < 5; i++) { mbar_init(sb + RB_SF + 8 * i, 1); mbar_init(sb + RB_SE + 8 * i, 256); }
        for (int i = 0; i < 2 * X_SLOTS; i++) mbar_init(sb + RB_XF + 8 * i, 1);
        fence_mbar_init();
        if (rank == 0) { mbar_expect_tx(sb + RB_KV, 16384); mbar_expect_tx(sb + RB_K, 2048); mbar_expect_tx(sb + RB_V, 2048); }
        atomicAdd(&g_resident, 1u);
    }
    __syncthreads();
    cluster_sync();

    if (wg < 2) {
        reg_inc<REG_KB>();
        if (rank != 0) {
            uint32_t w[R_NRS * 16];
            if ((tid & 127) == 0) for (int j = 0; j < X_SLOTS; j++) x_load(sb, 0, j, wg, &tmX);
            __syncwarp();
            big_prologue<true>(w, sb, wg, warp, mem0);
            big_main<true>(w, sb, wg, warp, rank, head, &tmX, xg, 0u);
        } else {
            uint32_t w[R_NRS * 16];
            big_prologue<false>(w, sb, wg, warp, mem0);
            big_main<false>(w, sb, wg, warp, rank, head, &tmX, xg, *(volatile unsigned*)&g_epoch + 1);
        }
    } else {
        reg_dec<504 - 2 * REG_KB>();
        const unsigned E = __shfl_sync(0xffffffffu, *(volatile unsigned*)&g_epoch + 1, 0);
        if (warp == 3 && rank != 0) {
            acc_clear(0, 2 * head + (int)rank - 1); acc_clear(1, 2 * head + (int)rank - 1);
            __threadfence();
            __syncwarp();
            if (tid == 256 + 96) atomicAdd(&g_zero, 1u);
        }
        if (tid == 256) {
            if (rank == 0) for (int sg = 0; sg < 4; sg++) l2_prefetch(xg + (size_t)(sg * 32 + head) * DM, 2048);
            load_weights(sb, rank == 0 ? &tmWq : (rank == 1 ? &tmWk : &tmWv), &tmWo, head, rank);
            wait_count(&g_zero, E * 64u);
        }
        __syncwarp();
        mbar_wait(sb + RB_W, 0);
        wo_permute(sb + RS_WO + (tid & 127) * 32, 20);
        if (rank == 0) wo_permute(sb + RS_WO5 + (tid & 127) * 32, 4);
        fence_proxy_async();
        nbar_sync(NB_AUX, 128);
        if (rank == 0) aux_main<true>(sb, warp, rank, head, &tmX, xg, E, hq0 + (warp & 1) * hqw + (warp >> 1) * hq2, period, tune);
        else           aux_main<false>(sb, warp, rank, head, &tmX, xg, E, hk0 + (warp == 1) * hkw + (warp >> 1) * hk2, period, tune);
    }
    __syncthreads();
    cluster_sync();
}

__global__ void k_gate() {
    if (threadIdx.x == 0) {
        int n = 0;
        while (*(volatile unsigned*)&g_resident < 96u) { __nanosleep(200); if (++n > (1 << 22)) __trap(); }
        g_resident = 0;
    }
}

typedef CUresult (*EncodeFn)(CUtensorMap*, CUtensorMapDataType, cuuint32_t, void*, const cuuint64_t*, const cuuint64_t*,
                             const cuuint32_t*, const cuuint32_t*, CUtensorMapInterleave, CUtensorMapSwizzle,
                             CUtensorMapL2promotion, CUtensorMapFloatOOBfill);

static CUtensorMap make_map(EncodeFn fn, const void* ptr, uint64_t inner, uint64_t outer, uint32_t box_inner, uint32_t box_outer) {
    CUtensorMap m;
    cuuint64_t dims[2] = {inner, outer};
    cuuint64_t strides[1] = {inner * 2};
    cuuint32_t box[2] = {box_inner, box_outer};
    cuuint32_t es[2] = {1, 1};
    fn(&m, CU_TENSOR_MAP_DATA_TYPE_BFLOAT16, 2, const_cast<void*>(ptr), dims, strides, box, es,
       CU_TENSOR_MAP_INTERLEAVE_NONE, CU_TENSOR_MAP_SWIZZLE_128B, CU_TENSOR_MAP_L2_PROMOTION_L2_256B, CU_TENSOR_MAP_FLOAT_OOB_FILL_NONE);
    return m;
}

static CUtensorMap make_wo_map(EncodeFn fn, const void* ptr, uint32_t ngrp) {
    CUtensorMap m;
    cuuint64_t dims[5] = {DM, 2, 4, 4, HD / 32};
    cuuint64_t strides[4] = {DM * 2, 8 * DM * 2, 2 * DM * 2, 32 * DM * 2};
    cuuint32_t box[5] = {64, 2, 4, 4, ngrp};
    cuuint32_t es[5] = {1, 1, 1, 1, 1};
    fn(&m, CU_TENSOR_MAP_DATA_TYPE_BFLOAT16, 5, const_cast<void*>(ptr), dims, strides, box, es,
       CU_TENSOR_MAP_INTERLEAVE_NONE, CU_TENSOR_MAP_SWIZZLE_128B, CU_TENSOR_MAP_L2_PROMOTION_L2_256B, CU_TENSOR_MAP_FLOAT_OOB_FILL_NONE);
    return m;
}

struct Maps {
    PMaps post;
    CUtensorMap wq16, wk16, wv16, wo128, x32;
};

extern "C" void kernel_launch(void* const* d_in, const int* in_sizes, int n_in, void* d_out, int out_size) {
    const bf16* A_x   = (const bf16*)d_in[0];
    const bf16* A_mem = (const bf16*)d_in[1];
    const bf16* A_Wq  = (const bf16*)d_in[2];
    const bf16* A_Wk  = (const bf16*)d_in[3];
    const bf16* A_Wv  = (const bf16*)d_in[4];
    const bf16* A_Wo  = (const bf16*)d_in[5];
    const bf16* B_x   = (const bf16*)d_in[7];
    const bf16* B_w   = (const bf16*)d_in[8];
    const bf16* B_wo  = (const bf16*)d_in[9];

    static EncodeFn fn = nullptr;
    static Maps mp;
    static const void* cached[10];
    const void* cur[10] = {A_x, A_mem, A_Wq, A_Wk, A_Wv, A_Wo, B_x, B_w, B_wo, d_out};
    bool same = fn != nullptr;
    for (int i = 0; i < 10 && same; i++) same = cached[i] == cur[i];
    if (!same) {
        if (!fn) {
            void* p = nullptr; cudaDriverEntryPointQueryResult qr;
            cudaGetDriverEntryPoint("cuTensorMapEncodeTiled", &p, cudaEnableDefault, &qr);
            fn = (EncodeFn)p;
            cudaFuncSetAttribute(k_post, cudaFuncAttributeMaxDynamicSharedMemorySize, P_SMEM);
            cudaFuncSetAttribute(k_rec, cudaFuncAttributeMaxDynamicSharedMemorySize, R_SMEM);
            cudaFuncAttributes fa; cudaFuncGetAttributes(&fa, k_gate);
        }
        void *p_ox, *p_bqkv, *p_bo;
        cudaGetSymbolAddress(&p_ox, g_ox); cudaGetSymbolAddress(&p_bqkv, g_bqkv); cudaGetSymbolAddress(&p_bo, g_bo);
        mp.post.wq   = make_map(fn, A_Wq, HD, DM, 64, 64);
        mp.post.wo   = make_wo_map(fn, A_Wo, 2);
        mp.post.bw   = make_map(fn, B_w, 3 * DM, DM, 64, 64);
        mp.post.bwo  = make_map(fn, B_wo, DM, DM, 64, 64);
        mp.post.x    = make_map(fn, A_x, DM, S_TOK, 64, 256);
        mp.post.bx   = make_map(fn, B_x, DM, S_TOK, 64, 256);
        mp.post.bo   = make_map(fn, p_bo, DM, S_TOK, 64, 256);
        mp.post.ox   = make_map(fn, p_ox, HD, S_TOK, 64, 128);
        mp.post.cb   = make_map(fn, p_bqkv, 3 * DM, S_TOK, 64, 64);
        mp.post.cout = make_map(fn, d_out, 2 * DM, S_TOK, 64, 64);
        {
            cuuint64_t dims[4] = {DM, 3, 2, S_TOK / 2};
            cuuint64_t strides[3] = {DM * 2, 3 * DM * 2, 3 * DM * 4};
            cuuint32_t box[4] = {64, 3, 1, 40};
            cuuint32_t es[4] = {1, 1, 1, 1};
            fn(&mp.post.b40, CU_TENSOR_MAP_DATA_TYPE_BFLOAT16, 4, p_bqkv, dims, strides, box, es,
               CU_TENSOR_MAP_INTERLEAVE_NONE, CU_TENSOR_MAP_SWIZZLE_128B, CU_TENSOR_MAP_L2_PROMOTION_L2_256B, CU_TENSOR_MAP_FLOAT_OOB_FILL_NONE);
        }
        mp.wq16 = make_map(fn, A_Wq, HD, DM, 64, 64);
        mp.wk16 = make_map(fn, A_Wk, HD, DM, 64, 64);
        mp.wv16 = make_map(fn, A_Wv, HD, DM, 64, 64);
        mp.wo128 = make_wo_map(fn, A_Wo, 4);
        {
            cuuint64_t dims[3] = {64, S_TOK, DM / 64};
            cuuint64_t strides[2] = {DM * 2, 128};
            cuuint32_t box[3] = {32, 32, 2};
            cuuint32_t es[3] = {1, 1, 1};
            fn(&mp.x32, CU_TENSOR_MAP_DATA_TYPE_BFLOAT16, 3, const_cast<bf16*>(A_x), dims, strides, box, es,
               CU_TENSOR_MAP_INTERLEAVE_NONE, CU_TENSOR_MAP_SWIZZLE_64B, CU_TENSOR_MAP_L2_PROMOTION_L2_128B, CU_TENSOR_MAP_FLOAT_OOB_FILL_NONE);
        }
        for (int i = 0; i < 10; i++) cached[i] = cur[i];
    }

    cudaStream_t st = cudaStreamPerThread;
    static cudaStream_t side = nullptr;
    static cudaEvent_t evFork, evSide;
    if (!side) {
        cudaStreamCreateWithFlags(&side, cudaStreamNonBlocking);
        cudaEventCreateWithFlags(&evFork, cudaEventDisableTiming);
        cudaEventCreateWithFlags(&evSide, cudaEventDisableTiming);
    }
    cudaEventRecord(evFork, st);
    int hq0 = 0, hqw = 0, hq2 = 256, hk0 = 0, hkw = 0, hk2 = 256, period = 3300;
    int4 tune = make_int4(32, 32, 400, 2);
    k_rec<<<96, 384, R_SMEM, st>>>(mp.wq16, mp.wk16, mp.wv16, mp.wo128, mp.x32, A_mem, A_x, hq0, hqw, hq2, hk0, hkw, hk2, period, tune);
    cudaStreamWaitEvent(side, evFork, 0);
    k_gate<<<1, 32, 0, side>>>();
    k_post<<<132, 384, P_SMEM, side>>>(mp.post);
    cudaEventRecord(evSide, side);
    cudaStreamWaitEvent(st, evSide, 0);
}
```

```cpp
#include <cuda_runtime.h>
#include <cuda_bf16.h>
#include <cuda.h>
#include <stdint.h>

typedef __nv_bfloat16 bf16;

constexpr int S_TOK = 2048;
constexpr int DM    = 1024;
constexpr int NH    = 32;
constexpr int DH    = 128;
constexpr int NSEG  = 64;
constexpr int HD    = NH * DH;

__device__ __align__(1024) bf16 g_qx[NSEG * NH * 4 * DH * 8];
__device__ __align__(1024) bf16 g_ox[S_TOK * HD];
__device__ __align__(1024) bf16 g_bqkv[S_TOK * 3 * DM];
__device__ __align__(1024) bf16 g_bo[S_TOK * DM];
__device__ __align__(1024) uint8_t g_acc[192 * 1024];

#define EV(cond, s, k) do {} while (0)
#define EVCAL(s) do {} while (0)

constexpr int P_NSK = 4;
__device__ unsigned g_epoch, g_qctr, g_done, g_zero;
enum { C_B1 = 0, C_B2 = 8, C_Q = 16, C_QH = 24, C_NONE = 31 };
__device__ unsigned g_cnt[32], g_prog[16], g_cnt_sk[P_NSK * 16];
__device__ __align__(1024) float g_skp[P_NSK * 8 * 4 * 2 * 128 * 64];
__device__ __align__(128) unsigned long long g_tlast;
__device__ __align__(128) unsigned g_pred;
__device__ __forceinline__ unsigned long long gtime() { unsigned long long g; asm volatile("mov.u64 %0, %%globaltimer;" : "=l"(g)); return g; }
#define TLOG(i, k, v) do {} while (0)

#define DEVI __device__ __forceinline__

DEVI uint32_t opaque(uint32_t v) { uint32_t r; asm volatile("mov.u32 %0, %1;" : "=r"(r) : "r"(v)); return r; }
DEVI uint32_t smem_u32(const void* p) { return (uint32_t)__cvta_generic_to_shared(p); }

#define TRAP(code) __trap()
constexpr int SPIN_LIMIT = 1 << 22;
#define MBAR_HINT_NS 20000u
constexpr int SPIN_LIMIT_MBAR = 1 << 17;

DEVI void mbar_init(uint32_t bar, uint32_t cnt) { asm volatile("mbarrier.init.shared::cta.b64 [%0], %1;" :: "r"(bar), "r"(cnt)); }
DEVI void mbar_expect_tx(uint32_t bar, uint32_t bytes) {
    asm volatile("mbarrier.arrive.expect_tx.shared::cta.b64 _, [%0], %1;" :: "r"(bar), "r"(bytes) : "memory");
}
DEVI void mbar_arrive(uint32_t bar) { asm volatile("mbarrier.arrive.shared::cta.b64 _, [%0];" :: "r"(bar) : "memory"); }
DEVI bool mbar_try(uint32_t bar, uint32_t parity) {
    uint32_t ok;
    asm volatile("{.reg .pred p; mbarrier.try_wait.parity.shared::cta.b64 p, [%1], %2; selp.u32 %0, 1, 0, p;}"
                 : "=r"(ok) : "r"(bar), "r"(parity) : "memory");
    return ok;
}
DEVI bool mbar_try_cluster(uint32_t bar, uint32_t parity) {
    uint32_t ok;
    asm volatile("{.reg .pred p; mbarrier.try_wait.parity.acquire.cluster.shared::cta.b64 p, [%1], %2; selp.u32 %0, 1, 0, p;}"
                 : "=r"(ok) : "r"(bar), "r"(parity) : "memory");
    return ok;
}
DEVI bool mbar_try_hint(uint32_t bar, uint32_t parity) {
    uint32_t ok;
    asm volatile("{.reg .pred p; mbarrier.try_wait.parity.shared::cta.b64 p, [%1], %2, %3; selp.u32 %0, 1, 0, p;}"
                 : "=r"(ok) : "r"(bar), "r"(parity), "r"(MBAR_HINT_NS) : "memory");
    return ok;
}
DEVI void mbar_wait(uint32_t bar, uint32_t parity) {
    int n = 0;
    while (!mbar_try(bar, parity)) { if (++n > SPIN_LIMIT) TRAP(bar | (parity << 31)); }
}
DEVI void mbar_wait_sleepy(uint32_t bar, uint32_t parity) {
    int n = 0;
    while (!mbar_try_hint(bar, parity)) { if (++n > SPIN_LIMIT_MBAR) __trap(); }
}
DEVI void mbar_wait_cluster(uint32_t bar, uint32_t parity) {
    int n = 0;
    while (!mbar_try_cluster(bar, parity)) { if (++n > SPIN_LIMIT) __trap(); }
}
DEVI void mbar_spin(uint32_t bar, uint32_t parity) {
    uint32_t ok; int n = 0;
    do {
        asm volatile("{.reg .pred p; mbarrier.test_wait.parity.shared::cta.b64 p, [%1], %2; selp.u32 %0, 1, 0, p;}"
                     : "=r"(ok) : "r"(bar), "r"(parity) : "memory");
        if (++n > SPIN_LIMIT) __trap();
    } while (!ok);
}
DEVI void fence_mbar_init() { asm volatile("fence.mbarrier_init.release.cluster;" ::: "memory"); }
DEVI void fence_proxy_async() { asm volatile("fence.proxy.async.shared::cta;" ::: "memory"); }
DEVI void cluster_sync() {
    asm volatile("barrier.cluster.arrive.release.aligned;\n barrier.cluster.wait.acquire.aligned;" ::: "memory");
}
DEVI void nbar_sync(int id, int n) { asm volatile("bar.sync %0, %1;" :: "r"(id), "r"(n) : "memory"); }
DEVI void nbar_arrive(int id, int n) { asm volatile("bar.arrive %0, %1;" :: "r"(id), "r"(n) : "memory"); }

DEVI void tma_load_2d(uint32_t dst, const CUtensorMap* map, int x, int y, uint32_t bar) {
    asm volatile("cp.async.bulk.tensor.2d.shared::cluster.global.mbarrier::complete_tx::bytes [%0], [%1, {%3, %4}], [%2];"
                 :: "r"(dst), "l"(map), "r"(bar), "r"(x), "r"(y) : "memory");
}
DEVI void tma_load_3d(uint32_t dst, const CUtensorMap* map, int x, int y, int z, uint32_t bar) {
    asm volatile("cp.async.bulk.tensor.3d.shared::cluster.global.mbarrier::complete_tx::bytes [%0], [%1, {%3, %4, %5}], [%2];"
                 :: "r"(dst), "l"(map), "r"(bar), "r"(x), "r"(y), "r"(z) : "memory");
}
DEVI void tma_load_wo(uint32_t dst, const CUtensorMap* map, int col, int k32, uint32_t bar) {
    asm volatile("cp.async.bulk.tensor.5d.shared::cluster.global.mbarrier::complete_tx::bytes [%0], [%1, {%3, %5, %5, %5, %4}], [%2];"
                 :: "r"(dst), "l"(map), "r"(bar), "r"(col), "r"(k32), "r"(0) : "memory");
}
DEVI void tma_store_2d(const CUtensorMap* map, uint32_t src, int x, int y) {
    asm volatile("cp.async.bulk.tensor.2d.global.shared::cta.bulk_group [%0, {%2, %3}], [%1];"
                 :: "l"(map), "r"(src), "r"(x), "r"(y) : "memory");
}
DEVI void bulk_load(uint32_t dst, const void* src, uint32_t bytes, uint32_t bar) {
    asm volatile("cp.async.bulk.shared::cluster.global.mbarrier::complete_tx::bytes [%0], [%1], %2, [%3];"
                 :: "r"(dst), "l"(src), "r"(bytes), "r"(bar) : "memory");
}
DEVI void tma_load_2d_mc(uint32_t dst, const CUtensorMap* map, int x, int y, uint32_t bar, uint16_t mask) {
    asm volatile("cp.async.bulk.tensor.2d.shared::cluster.global.mbarrier::complete_tx::bytes.multicast::cluster [%0], [%1, {%3, %4}], [%2], %5;"
                 :: "r"(dst), "l"(map), "r"(bar), "r"(x), "r"(y), "h"(mask) : "memory");
}
DEVI void bulk_copy_s2c(uint32_t dst_cluster, uint32_t src, uint32_t bytes, uint32_t bar_cluster) {
    asm volatile("cp.async.bulk.shared::cluster.shared::cta.mbarrier::complete_tx::bytes [%0], [%1], %2, [%3];"
                 :: "r"(dst_cluster), "r"(src), "r"(bytes), "r"(bar_cluster) : "memory");
}
DEVI void bulk_store(void* dst, uint32_t src, uint32_t bytes) {
    asm volatile("cp.async.bulk.global.shared::cta.bulk_group [%0], [%1], %2;" :: "l"(dst), "r"(src), "r"(bytes) : "memory");
}
DEVI void bulk_wait_read() { asm volatile("cp.async.bulk.wait_group.read 0;" ::: "memory"); }
DEVI void mbar_arrive_remote(uint32_t bar_cluster) {
    asm volatile("mbarrier.arrive.shared::cluster.b64 _, [%0];" :: "r"(bar_cluster) : "memory");
}
DEVI void mbar_expect_tx_remote(uint32_t bar_cluster, uint32_t bytes) {
    asm volatile("mbarrier.arrive.expect_tx.shared::cluster.b64 _, [%0], %1;" :: "r"(bar_cluster), "r"(bytes) : "memory");
}
DEVI void l2_prefetch(const void* p, uint32_t bytes) {
    asm volatile("cp.async.bulk.prefetch.L2.global [%0], %1;" :: "l"(p), "r"(bytes) : "memory");
}
DEVI void bulk_commit() { asm volatile("cp.async.bulk.commit_group;" ::: "memory"); }
DEVI void bulk_wait_all() { asm volatile("cp.async.bulk.wait_group 0;" ::: "memory"); }

DEVI void wg_fence() { asm volatile("wgmma.fence.sync.aligned;" ::: "memory"); }
DEVI void wg_commit() { asm volatile("wgmma.commit_group.sync.aligned;" ::: "memory"); }
template <int N> DEVI void wg_wait() { asm volatile("wgmma.wait_group.sync.aligned %0;" :: "n"(N) : "memory"); }

template <int R> DEVI void reg_dec() { asm volatile("setmaxnreg.dec.sync.aligned.u32 %0;" :: "n"(R)); }
template <int R> DEVI void reg_inc() { asm volatile("setmaxnreg.inc.sync.aligned.u32 %0;" :: "n"(R)); }

DEVI uint64_t mk_desc(uint32_t addr, uint32_t lbo, uint32_t sbo, uint32_t sw) {
    return (uint64_t)((addr & 0x3FFFF) >> 4) | ((uint64_t)(lbo >> 4) << 16) | ((uint64_t)(sbo >> 4) << 32) | ((uint64_t)sw << 62);
}

DEVI uint32_t desc_lo(uint32_t addr, uint32_t lbo) { return ((addr & 0x3FFFF) >> 4) | ((lbo >> 4) << 16); }
constexpr uint32_t DHI_SW128 = (1024u >> 4) | (1u << 30);
constexpr uint32_t DHI_SW64  = (512u >> 4) | (2u << 30);
constexpr uint32_t DHI_NONE  = (128u >> 4);

template <int TB, int SCALE_D>
DEVI void wgmma_n8_ss(float* d, uint32_t alo, uint32_t blo) {
    asm volatile("{.reg .b64 da, db; mov.b64 da, {%4, %6}; mov.b64 db, {%5, %7};\n"
                 "wgmma.mma_async.sync.aligned.m64n8k16.f32.bf16.bf16 {%0,%1,%2,%3}, da, db, %8, 1, 1, 1, %9;}"
                 : "+f"(d[0]), "+f"(d[1]), "+f"(d[2]), "+f"(d[3])
                 : "r"(alo), "r"(blo), "n"(DHI_SW128), "n"(DHI_NONE), "n"(SCALE_D), "n"(TB));
}

template <int TB>
DEVI void wgmma_n8_ss_first(float* d, uint32_t alo, uint32_t blo) {
    asm volatile("{.reg .b64 da, db; mov.b64 da, {%4, %6}; mov.b64 db, {%5, %7};\n"
                 "wgmma.mma_async.sync.aligned.m64n8k16.f32.bf16.bf16 {%0,%1,%2,%3}, da, db, 0, 1, 1, 1, %8;}"
                 : "=f"(d[0]), "=f"(d[1]), "=f"(d[2]), "=f"(d[3])
                 : "r"(alo), "r"(blo), "n"(DHI_SW128), "n"(DHI_NONE), "n"(TB));
}
DEVI void wgmma_n32_rs_first(float* d, const uint32_t* a, uint32_t blo) {
    asm volatile("{.reg .b64 db; mov.b64 db, {%20, %21};\n"
                 "wgmma.mma_async.sync.aligned.m64n32k16.f32.bf16.bf16 {%0,%1,%2,%3,%4,%5,%6,%7,%8,%9,%10,%11,%12,%13,%14,%15}, "
                 "{%16,%17,%18,%19}, db, 0, 1, 1, 0;}"
                 : "=f"(d[0]), "=f"(d[1]), "=f"(d[2]), "=f"(d[3]), "=f"(d[4]), "=f"(d[5]), "=f"(d[6]), "=f"(d[7]),
                   "=f"(d[8]), "=f"(d[9]), "=f"(d[10]), "=f"(d[11]), "=f"(d[12]), "=f"(d[13]), "=f"(d[14]), "=f"(d[15])
                 : "r"(a[0]), "r"(a[1]), "r"(a[2]), "r"(a[3]), "r"(blo), "n"(DHI_SW64));
}
template <int N> DEVI void reg_fence(float* d) {
#pragma unroll
    for (int i = 0; i < N; i++) asm volatile("" : "+f"(d[i]) :: "memory");
}
DEVI void wgmma_n32_rs(float* d, const uint32_t* a, uint32_t blo) {
    asm volatile("{.reg .b64 db; mov.b64 db, {%20, %21};\n"
                 "wgmma.mma_async.sync.aligned.m64n32k16.f32.bf16.bf16 {%0,%1,%2,%3,%4,%5,%6,%7,%8,%9,%10,%11,%12,%13,%14,%15}, "
                 "{%16,%17,%18,%19}, db, 1, 1, 1, 0;}"
                 : "+f"(d[0]), "+f"(d[1]), "+f"(d[2]), "+f"(d[3]), "+f"(d[4]), "+f"(d[5]), "+f"(d[6]), "+f"(d[7]),
                   "+f"(d[8]), "+f"(d[9]), "+f"(d[10]), "+f"(d[11]), "+f"(d[12]), "+f"(d[13]), "+f"(d[14]), "+f"(d[15])
                 : "r"(a[0]), "r"(a[1]), "r"(a[2]), "r"(a[3]), "r"(blo), "n"(DHI_SW64));
}
DEVI void wgmma_n32_ss(float* d, uint32_t alo, uint32_t blo) {
    asm volatile("{.reg .b64 da, db; mov.b64 da, {%16, %18}; mov.b64 db, {%17, %19};\n"
                 "wgmma.mma_async.sync.aligned.m64n32k16.f32.bf16.bf16 {%0,%1,%2,%3,%4,%5,%6,%7,%8,%9,%10,%11,%12,%13,%14,%15}, "
                 "da, db, 1, 1, 1, 1, 0;}"
                 : "+f"(d[0]), "+f"(d[1]), "+f"(d[2]), "+f"(d[3]), "+f"(d[4]), "+f"(d[5]), "+f"(d[6]), "+f"(d[7]),
                   "+f"(d[8]), "+f"(d[9]), "+f"(d[10]), "+f"(d[11]), "+f"(d[12]), "+f"(d[13]), "+f"(d[14]), "+f"(d[15])
                 : "r"(alo), "r"(blo), "n"(DHI_SW128), "n"(DHI_SW64));
}

template <bool FIRST>
DEVI void wgmma_n256_ss(float* d, uint64_t a, uint64_t b) {
    if (FIRST)
        asm volatile("wgmma.mma_async.sync.aligned.m64n256k16.f32.bf16.bf16 {%0,%1,%2,%3,%4,%5,%6,%7,%8,%9,%10,%11,%12,%13,%14,%15,%16,%17,%18,%19,%20,%21,%22,%23,%24,%25,%26,%27,%28,%29,%30,%31,%32,%33,%34,%35,%36,%37,%38,%39,%40,%41,%42,%43,%44,%45,%46,%47,%48,%49,%50,%51,%52,%53,%54,%55,%56,%57,%58,%59,%60,%61,%62,%63,%64,%65,%66,%67,%68,%69,%70,%71,%72,%73,%74,%75,%76,%77,%78,%79,%80,%81,%82,%83,%84,%85,%86,%87,%88,%89,%90,%91,%92,%93,%94,%95,%96,%97,%98,%99,%100,%101,%102,%103,%104,%105,%106,%107,%108,%109,%110,%111,%112,%113,%114,%115,%116,%117,%118,%119,%120,%121,%122,%123,%124,%125,%126,%127}, %128, %129, 0, 1, 1, 1, 0;"
            : "=f"(d[0]), "=f"(d[1]), "=f"(d[2]), "=f"(d[3]), "=f"(d[4]), "=f"(d[5]), "=f"(d[6]), "=f"(d[7]), "=f"(d[8]), "=f"(d[9]), "=f"(d[10]), "=f"(d[11]), "=f"(d[12]), "=f"(d[13]), "=f"(d[14]), "=f"(d[15]), "=f"(d[16]), "=f"(d[17]), "=f"(d[18]), "=f"(d[19]), "=f"(d[20]), "=f"(d[21]), "=f"(d[22]), "=f"(d[23]), "=f"(d[24]), "=f"(d[25]), "=f"(d[26]), "=f"(d[27]), "=f"(d[28]), "=f"(d[29]), "=f"(d[30]), "=f"(d[31]), "=f"(d[32]), "=f"(d[33]), "=f"(d[34]), "=f"(d[35]), "=f"(d[36]), "=f"(d[37]), "=f"(d[38]), "=f"(d[39]), "=f"(d[40]), "=f"(d[41]), "=f"(d[42]), "=f"(d[43]), "=f"(d[44]), "=f"(d[45]), "=f"(d[46]), "=f"(d[47]), "=f"(d[48]), "=f"(d[49]), "=f"(d[50]), "=f"(d[51]), "=f"(d[52]), "=f"(d[53]), "=f"(d[54]), "=f"(d[55]), "=f"(d[56]), "=f"(d[57]), "=f"(d[58]), "=f"(d[59]), "=f"(d[60]), "=f"(d[61]), "=f"(d[62]), "=f"(d[63]), "=f"(d[64]), "=f"(d[65]), "=f"(d[66]), "=f"(d[67]), "=f"(d[68]), "=f"(d[69]), "=f"(d[70]), "=f"(d[71]), "=f"(d[72]), "=f"(d[73]), "=f"(d[74]), "=f"(d[75]), "=f"(d[76]), "=f"(d[77]), "=f"(d[78]), "=f"(d[79]), "=f"(d[80]), "=f"(d[81]), "=f"(d[82]), "=f"(d[83]), "=f"(d[84]), "=f"(d[85]), "=f"(d[86]), "=f"(d[87]), "=f"(d[88]), "=f"(d[89]), "=f"(d[90]), "=f"(d[91]), "=f"(d[92]), "=f"(d[93]), "=f"(d[94]), "=f"(d[95]), "=f"(d[96]), "=f"(d[97]), "=f"(d[98]), "=f"(d[99]), "=f"(d[100]), "=f"(d[101]), "=f"(d[102]), "=f"(d[103]), "=f"(d[104]), "=f"(d[105]), "=f"(d[106]), "=f"(d[107]), "=f"(d[108]), "=f"(d[109]), "=f"(d[110]), "=f"(d[111]), "=f"(d[112]), "=f"(d[113]), "=f"(d[114]), "=f"(d[115]), "=f"(d[116]), "=f"(d[117]), "=f"(d[118]), "=f"(d[119]), "=f"(d[120]), "=f"(d[121]), "=f"(d[122]), "=f"(d[123]), "=f"(d[124]), "=f"(d[125]), "=f"(d[126]), "=f"(d[127]) : "l"(a), "l"(b));
    else
        asm volatile("wgmma.mma_async.sync.aligned.m64n256k16.f32.bf16.bf16 {%0,%1,%2,%3,%4,%5,%6,%7,%8,%9,%10,%11,%12,%13,%14,%15,%16,%17,%18,%19,%20,%21,%22,%23,%24,%25,%26,%27,%28,%29,%30,%31,%32,%33,%34,%35,%36,%37,%38,%39,%40,%41,%42,%43,%44,%45,%46,%47,%48,%49,%50,%51,%52,%53,%54,%55,%56,%57,%58,%59,%60,%61,%62,%63,%64,%65,%66,%67,%68,%69,%70,%71,%72,%73,%74,%75,%76,%77,%78,%79,%80,%81,%82,%83,%84,%85,%86,%87,%88,%89,%90,%91,%92,%93,%94,%95,%96,%97,%98,%99,%100,%101,%102,%103,%104,%105,%106,%107,%108,%109,%110,%111,%112,%113,%114,%115,%116,%117,%118,%119,%120,%121,%122,%123,%124,%125,%126,%127}, %128, %129, 1, 1, 1, 1, 0;"
            : "+f"(d[0]), "+f"(d[1]), "+f"(d[2]), "+f"(d[3]), "+f"(d[4]), "+f"(d[5]), "+f"(d[6]), "+f"(d[7]), "+f"(d[8]), "+f"(d[9]), "+f"(d[10]), "+f"(d[11]), "+f"(d[12]), "+f"(d[13]), "+f"(d[14]), "+f"(d[15]), "+f"(d[16]), "+f"(d[17]), "+f"(d[18]), "+f"(d[19]), "+f"(d[20]), "+f"(d[21]), "+f"(d[22]), "+f"(d[23]), "+f"(d[24]), "+f"(d[25]), "+f"(d[26]), "+f"(d[27]), "+f"(d[28]), "+f"(d[29]), "+f"(d[30]), "+f"(d[31]), "+f"(d[32]), "+f"(d[33]), "+f"(d[34]), "+f"(d[35]), "+f"(d[36]), "+f"(d[37]), "+f"(d[38]), "+f"(d[39]), "+f"(d[40]), "+f"(d[41]), "+f"(d[42]), "+f"(d[43]), "+f"(d[44]), "+f"(d[45]), "+f"(d[46]), "+f"(d[47]), "+f"(d[48]), "+f"(d[49]), "+f"(d[50]), "+f"(d[51]), "+f"(d[52]), "+f"(d[53]), "+f"(d[54]), "+f"(d[55]), "+f"(d[56]), "+f"(d[57]), "+f"(d[58]), "+f"(d[59]), "+f"(d[60]), "+f"(d[61]), "+f"(d[62]), "+f"(d[63]), "+f"(d[64]), "+f"(d[65]), "+f"(d[66]), "+f"(d[67]), "+f"(d[68]), "+f"(d[69]), "+f"(d[70]), "+f"(d[71]), "+f"(d[72]), "+f"(d[73]), "+f"(d[74]), "+f"(d[75]), "+f"(d[76]), "+f"(d[77]), "+f"(d[78]), "+f"(d[79]), "+f"(d[80]), "+f"(d[81]), "+f"(d[82]), "+f"(d[83]), "+f"(d[84]), "+f"(d[85]), "+f"(d[86]), "+f"(d[87]), "+f"(d[88]), "+f"(d[89]), "+f"(d[90]), "+f"(d[91]), "+f"(d[92]), "+f"(d[93]), "+f"(d[94]), "+f"(d[95]), "+f"(d[96]), "+f"(d[97]), "+f"(d[98]), "+f"(d[99]), "+f"(d[100]), "+f"(d[101]), "+f"(d[102]), "+f"(d[103]), "+f"(d[104]), "+f"(d[105]), "+f"(d[106]), "+f"(d[107]), "+f"(d[108]), "+f"(d[109]), "+f"(d[110]), "+f"(d[111]), "+f"(d[112]), "+f"(d[113]), "+f"(d[114]), "+f"(d[115]), "+f"(d[116]), "+f"(d[117]), "+f"(d[118]), "+f"(d[119]), "+f"(d[120]), "+f"(d[121]), "+f"(d[122]), "+f"(d[123]), "+f"(d[124]), "+f"(d[125]), "+f"(d[126]), "+f"(d[127]) : "l"(a), "l"(b));
}
template <bool FIRST>
DEVI void wgmma_n128_ss(float* d, uint64_t a, uint64_t b) {
    if (FIRST)
        asm volatile("wgmma.mma_async.sync.aligned.m64n128k16.f32.bf16.bf16 {%0,%1,%2,%3,%4,%5,%6,%7,%8,%9,%10,%11,%12,%13,%14,%15,%16,%17,%18,%19,%20,%21,%22,%23,%24,%25,%26,%27,%28,%29,%30,%31,%32,%33,%34,%35,%36,%37,%38,%39,%40,%41,%42,%43,%44,%45,%46,%47,%48,%49,%50,%51,%52,%53,%54,%55,%56,%57,%58,%59,%60,%61,%62,%63}, %64, %65, 0, 1, 1, 1, 0;"
            : "=f"(d[0]), "=f"(d[1]), "=f"(d[2]), "=f"(d[3]), "=f"(d[4]), "=f"(d[5]), "=f"(d[6]), "=f"(d[7]), "=f"(d[8]), "=f"(d[9]), "=f"(d[10]), "=f"(d[11]), "=f"(d[12]), "=f"(d[13]), "=f"(d[14]), "=f"(d[15]), "=f"(d[16]), "=f"(d[17]), "=f"(d[18]), "=f"(d[19]), "=f"(d[20]), "=f"(d[21]), "=f"(d[22]), "=f"(d[23]), "=f"(d[24]), "=f"(d[25]), "=f"(d[26]), "=f"(d[27]), "=f"(d[28]), "=f"(d[29]), "=f"(d[30]), "=f"(d[31]), "=f"(d[32]), "=f"(d[33]), "=f"(d[34]), "=f"(d[35]), "=f"(d[36]), "=f"(d[37]), "=f"(d[38]), "=f"(d[39]), "=f"(d[40]), "=f"(d[41]), "=f"(d[42]), "=f"(d[43]), "=f"(d[44]), "=f"(d[45]), "=f"(d[46]), "=f"(d[47]), "=f"(d[48]), "=f"(d[49]), "=f"(d[50]), "=f"(d[51]), "=f"(d[52]), "=f"(d[53]), "=f"(d[54]), "=f"(d[55]), "=f"(d[56]), "=f"(d[57]), "=f"(d[58]), "=f"(d[59]), "=f"(d[60]), "=f"(d[61]), "=f"(d[62]), "=f"(d[63]) : "l"(a), "l"(b));
    else
        asm volatile("wgmma.mma_async.sync.aligned.m64n128k16.f32.bf16.bf16 {%0,%1,%2,%3,%4,%5,%6,%7,%8,%9,%10,%11,%12,%13,%14,%15,%16,%17,%18,%19,%20,%21,%22,%23,%24,%25,%26,%27,%28,%29,%30,%31,%32,%33,%34,%35,%36,%37,%38,%39,%40,%41,%42,%43,%44,%45,%46,%47,%48,%49,%50,%51,%52,%53,%54,%55,%56,%57,%58,%59,%60,%61,%62,%63}, %64, %65, 1, 1, 1, 1, 0;"
            : "+f"(d[0]), "+f"(d[1]), "+f"(d[2]), "+f"(d[3]), "+f"(d[4]), "+f"(d[5]), "+f"(d[6]), "+f"(d[7]), "+f"(d[8]), "+f"(d[9]), "+f"(d[10]), "+f"(d[11]), "+f"(d[12]), "+f"(d[13]), "+f"(d[14]), "+f"(d[15]), "+f"(d[16]), "+f"(d[17]), "+f"(d[18]), "+f"(d[19]), "+f"(d[20]), "+f"(d[21]), "+f"(d[22]), "+f"(d[23]), "+f"(d[24]), "+f"(d[25]), "+f"(d[26]), "+f"(d[27]), "+f"(d[28]), "+f"(d[29]), "+f"(d[30]), "+f"(d[31]), "+f"(d[32]), "+f"(d[33]), "+f"(d[34]), "+f"(d[35]), "+f"(d[36]), "+f"(d[37]), "+f"(d[38]), "+f"(d[39]), "+f"(d[40]), "+f"(d[41]), "+f"(d[42]), "+f"(d[43]), "+f"(d[44]), "+f"(d[45]), "+f"(d[46]), "+f"(d[47]), "+f"(d[48]), "+f"(d[49]), "+f"(d[50]), "+f"(d[51]), "+f"(d[52]), "+f"(d[53]), "+f"(d[54]), "+f"(d[55]), "+f"(d[56]), "+f"(d[57]), "+f"(d[58]), "+f"(d[59]), "+f"(d[60]), "+f"(d[61]), "+f"(d[62]), "+f"(d[63]) : "l"(a), "l"(b));
}

DEVI void mma16816(float* d, const uint32_t* a, uint32_t b0, uint32_t b1) {
    asm volatile("mma.sync.aligned.m16n8k16.row.col.f32.bf16.bf16.f32 {%0,%1,%2,%3}, {%4,%5,%6,%7}, {%8,%9}, {%0,%1,%2,%3};"
                 : "+f"(d[0]), "+f"(d[1]), "+f"(d[2]), "+f"(d[3])
                 : "r"(a[0]), "r"(a[1]), "r"(a[2]), "r"(a[3]), "r"(b0), "r"(b1));
}
DEVI void mma1688(float* d, uint32_t a0, uint32_t a1, uint32_t b0) {
    asm volatile("mma.sync.aligned.m16n8k8.row.col.f32.bf16.bf16.f32 {%0,%1,%2,%3}, {%4,%5}, {%6}, {%0,%1,%2,%3};"
                 : "+f"(d[0]), "+f"(d[1]), "+f"(d[2]), "+f"(d[3]) : "r"(a0), "r"(a1), "r"(b0));
}
DEVI void ldsm4(uint32_t* r, uint32_t addr) {
    asm volatile("ldmatrix.sync.aligned.m8n8.x4.shared.b16 {%0,%1,%2,%3}, [%4];"
                 : "=r"(r[0]), "=r"(r[1]), "=r"(r[2]), "=r"(r[3]) : "r"(addr) : "memory");
}
DEVI void ldsm4t(uint32_t* r, uint32_t addr) {
    asm volatile("ldmatrix.sync.aligned.m8n8.x4.trans.shared.b16 {%0,%1,%2,%3}, [%4];"
                 : "=r"(r[0]), "=r"(r[1]), "=r"(r[2]), "=r"(r[3]) : "r"(addr) : "memory");
}
DEVI void ldsm2(uint32_t* r, uint32_t addr) {
    asm volatile("ldmatrix.sync.aligned.m8n8.x2.shared.b16 {%0,%1}, [%2];" : "=r"(r[0]), "=r"(r[1]) : "r"(addr) : "memory");
}
DEVI void ldsm1t(uint32_t& r, uint32_t addr) {
    asm volatile("ldmatrix.sync.aligned.m8n8.x1.trans.shared.b16 {%0}, [%1];" : "=r"(r) : "r"(addr) : "memory");
}
DEVI void stsm4(uint32_t addr, uint32_t r0, uint32_t r1, uint32_t r2, uint32_t r3) {
    asm volatile("stmatrix.sync.aligned.m8n8.x4.shared.b16 [%0], {%1,%2,%3,%4};" :: "r"(addr), "r"(r0), "r"(r1), "r"(r2), "r"(r3) : "memory");
}
DEVI void stsm4t(uint32_t addr, uint32_t r0, uint32_t r1, uint32_t r2, uint32_t r3) {
    asm volatile("stmatrix.sync.aligned.m8n8.x4.trans.shared.b16 [%0], {%1,%2,%3,%4};" :: "r"(addr), "r"(r0), "r"(r1), "r"(r2), "r"(r3) : "memory");
}
DEVI uint32_t movm_t(uint32_t a) {
    uint32_t d; asm volatile("movmatrix.sync.aligned.m8n8.trans.b16 %0, %1;" : "=r"(d) : "r"(a)); return d;
}
DEVI uint32_t pack_bf16(float lo, float hi) {
    uint32_t r; asm("cvt.rn.bf16x2.f32 %0, %1, %2;" : "=r"(r) : "f"(hi), "f"(lo)); return r;
}
DEVI float ex2(float x) { float y; asm("ex2.approx.ftz.f32 %0, %1;" : "=f"(y) : "f"(x)); return y; }

DEVI uint4 ld_rlx4(const void* p) {
    uint4 v;
    asm volatile("ld.relaxed.gpu.global.v4.u32 {%0,%1,%2,%3}, [%4];" : "=r"(v.x), "=r"(v.y), "=r"(v.z), "=r"(v.w) : "l"(p) : "memory");
    return v;
}
DEVI void ld_rlx4f(float* d, const void* p) {
    asm volatile("ld.relaxed.gpu.global.v4.f32 {%0,%1,%2,%3}, [%4];" : "=f"(d[0]), "=f"(d[1]), "=f"(d[2]), "=f"(d[3]) : "l"(p) : "memory");
}
DEVI bool all_nzf(const float* d) { return __float_as_uint(d[0]) && __float_as_uint(d[1]) && __float_as_uint(d[2]) && __float_as_uint(d[3]); }
DEVI void sts128f(uint32_t addr, const float* d) {
    asm volatile("st.shared.v4.f32 [%0], {%1,%2,%3,%4};" :: "r"(addr), "f"(d[0]), "f"(d[1]), "f"(d[2]), "f"(d[3]) : "memory");
}
DEVI void st_rlx4(void* p, uint32_t a, uint32_t b, uint32_t c, uint32_t d) {
    asm volatile("st.relaxed.gpu.global.v4.u32 [%0], {%1,%2,%3,%4};" :: "l"(p), "r"(a), "r"(b), "r"(c), "r"(d) : "memory");
}
DEVI void st_rlx(void* p, uint32_t v) { asm volatile("st.relaxed.gpu.global.u32 [%0], %1;" :: "l"(p), "r"(v) : "memory"); }
DEVI void sts128(uint32_t addr, uint4 v) {
    asm volatile("st.shared.v4.u32 [%0], {%1,%2,%3,%4};" :: "r"(addr), "r"(v.x), "r"(v.y), "r"(v.z), "r"(v.w) : "memory");
}
DEVI void sts64(uint32_t addr, uint32_t a, uint32_t b) { asm volatile("st.shared.v2.u32 [%0], {%1,%2};" :: "r"(addr), "r"(a), "r"(b) : "memory"); }
DEVI void sts32(uint32_t addr, uint32_t v) { asm volatile("st.shared.u32 [%0], %1;" :: "r"(addr), "r"(v) : "memory"); }
DEVI uint4 lds128(uint32_t addr) {
    uint4 v; asm volatile("ld.shared.v4.u32 {%0,%1,%2,%3}, [%4];" : "=r"(v.x), "=r"(v.y), "=r"(v.z), "=r"(v.w) : "r"(addr) : "memory"); return v;
}
DEVI float2 lds64f(uint32_t addr) {
    float2 v; asm volatile("ld.shared.v2.f32 {%0,%1}, [%2];" : "=f"(v.x), "=f"(v.y) : "r"(addr) : "memory"); return v;
}
DEVI void cp_async16(uint32_t dst, const void* src) {
    asm volatile("cp.async.cg.shared.global [%0], [%1], 16;" :: "r"(dst), "l"(src) : "memory");
}
DEVI void cp_async_commit() { asm volatile("cp.async.commit_group;" ::: "memory"); }
DEVI void cp_async_wait0() { asm volatile("cp.async.wait_group 0;" ::: "memory"); }
DEVI uint32_t lds32(uint32_t addr) { uint32_t v; asm volatile("ld.shared.u32 %0, [%1];" : "=r"(v) : "r"(addr) : "memory"); return v; }
DEVI float rcp_fast(float x) { float y; asm("rcp.approx.ftz.f32 %0, %1;" : "=f"(y) : "f"(x)); return y; }
DEVI bool all_nz(const uint4& v) { return v.x && v.y && v.z && v.w; }
DEVI uint32_t mapa(uint32_t addr, uint32_t rank) {
    uint32_t r; asm("mapa.shared::cluster.u32 %0, %1, %2;" : "=r"(r) : "r"(addr), "r"(rank)); return r;
}
DEVI void st_async64(uint32_t dst, uint32_t a, uint32_t b, uint32_t bar) {
    asm volatile("st.async.weak.shared::cluster.mbarrier::complete_tx::bytes.v2.b32 [%0], {%1,%2}, [%3];"
                 :: "r"(dst), "r"(a), "r"(b), "r"(bar) : "memory");
}

DEVI void st_async128(uint32_t dst, uint32_t a, uint32_t b, uint32_t c, uint32_t d, uint32_t bar) {
    asm volatile("st.async.weak.shared::cluster.mbarrier::complete_tx::bytes.v4.b32 [%0], {%1,%2,%3,%4}, [%5];"
                 :: "r"(dst), "r"(a), "r"(b), "r"(c), "r"(d), "r"(bar) : "memory");
}

DEVI uint32_t b_addr(uint32_t sb, int row, int which, int chunk) { const int l = 3 * row + which; return sb + l * 128 + ((chunk ^ (l & 7)) * 16); }
DEVI void battn_warp(uint32_t st, uint32_t so, int i0, int par, int head, int hh, int mt, int lane) {
    const int gq = lane >> 2, t = lane & 3;
    float s[3][4];
#pragma unroll
    for (int n = 0; n < 3; n++) { s[n][0] = s[n][1] = s[n][2] = s[n][3] = 0.f; }
    const int arow = 16 * mt + (lane & 7) + ((lane >> 3) & 1) * 8;
#pragma unroll
    for (int ks = 0; ks < 2; ks++) {
        uint32_t a[4], b[4], b2[2];
        ldsm4(a, b_addr(st, 8 + arow, 0, hh * 4 + ks * 2 + (lane >> 4)));
        const int brow = 16 * mt + (lane >> 4) * 8 + (lane & 7);
        ldsm4(b, b_addr(st, brow, 1, hh * 4 + ks * 2 + ((lane >> 3) & 1)));
        const int crow = 16 * mt + 16 + (lane & 7);
        ldsm2(b2, b_addr(st, crow, 1, hh * 4 + ks * 2 + ((lane >> 3) & 1)));
        mma16816(s[0], a, b[0], b[1]);
        mma16816(s[1], a, b[2], b[3]);
        mma16816(s[2], a, b2[0], b2[1]);
    }
    float m0 = -INFINITY, m1 = -INFINITY;
#pragma unroll
    for (int n = 0; n < 3; n++) {
#pragma unroll
        for (int c = 0; c < 2; c++) {
            const int dj = 8 * n - 8 + 2 * t + c;
            const bool ex = i0 + 16 * mt + dj >= 0;
            if (!(ex && gq - dj >= 0 && gq - dj <= 7)) s[n][c] = -INFINITY;
            if (!(ex && gq + 8 - dj >= 0 && gq + 8 - dj <= 7)) s[n][2 + c] = -INFINITY;
            m0 = fmaxf(m0, s[n][c]); m1 = fmaxf(m1, s[n][2 + c]);
        }
    }
    m0 = fmaxf(m0, __shfl_xor_sync(0xffffffffu, m0, 1)); m0 = fmaxf(m0, __shfl_xor_sync(0xffffffffu, m0, 2));
    m1 = fmaxf(m1, __shfl_xor_sync(0xffffffffu, m1, 1)); m1 = fmaxf(m1, __shfl_xor_sync(0xffffffffu, m1, 2));
    constexpr float C = 0.17677669529663687f * 1.4426950408889634f;
    float l0 = 0.f, l1 = 0.f;
    uint32_t p[3][2];
#pragma unroll
    for (int n = 0; n < 3; n++) {
        const float e0 = ex2((s[n][0] - m0) * C), e1 = ex2((s[n][1] - m0) * C), e2 = ex2((s[n][2] - m1) * C), e3 = ex2((s[n][3] - m1) * C);
        l0 += e0 + e1; l1 += e2 + e3;
        p[n][0] = pack_bf16(e0, e1); p[n][1] = pack_bf16(e2, e3);
    }
    l0 += __shfl_xor_sync(0xffffffffu, l0, 1); l0 += __shfl_xor_sync(0xffffffffu, l0, 2);
    l1 += __shfl_xor_sync(0xffffffffu, l1, 1); l1 += __shfl_xor_sync(0xffffffffu, l1, 2);
    const float i0f = rcp_fast(l0), i1f = rcp_fast(l1);
    float o[4][4];
#pragma unroll
    for (int n = 0; n < 4; n++) { o[n][0] = o[n][1] = o[n][2] = o[n][3] = 0.f; }
    {
        const uint32_t a0[4] = {p[0][0], p[0][1], p[1][0], p[1][1]}, a1[4] = {p[2][0], p[2][1], 0u, 0u};
#pragma unroll
        for (int n = 0; n < 4; n += 2) {
            uint32_t b[4], b2[4];
            const int vrow = 16 * mt + ((lane >> 3) & 1) * 8 + (lane & 7);
            ldsm4t(b, b_addr(st, vrow, 2, hh * 4 + n + (lane >> 4)));
            const int wrow = 16 * mt + 16 + (lane & 7);
            ldsm4t(b2, b_addr(st, wrow, 2, hh * 4 + n + (lane >> 4)));
            mma16816(o[n], a0, b[0], b[1]);
            mma16816(o[n + 1], a0, b[2], b[3]);
            mma16816(o[n], a1, b2[0], 0u);
            mma16816(o[n + 1], a1, b2[2], 0u);
        }
    }
    {
        const int row = (lane & 7) + ((lane >> 3) & 1) * 8;
#pragma unroll
        for (int n = 0; n < 4; n += 2)
            stsm4(so + row * 64 + (((n + (lane >> 4)) ^ ((row >> 1) & 3)) * 16),
                  pack_bf16(o[n][0] * i0f, o[n][1] * i0f), pack_bf16(o[n][2] * i1f, o[n][3] * i1f),
                  pack_bf16(o[n + 1][0] * i0f, o[n + 1][1] * i0f), pack_bf16(o[n + 1][2] * i1f, o[n + 1][3] * i1f));
    }
    __syncwarp();
#pragma unroll
    for (int i = 0; i < 2; i++) {
        const int idx = lane + i * 32, row = idx >> 2, ch = idx & 3;
        const uint4 v = lds128(so + row * 64 + ((ch ^ ((row >> 1) & 3)) * 16));
        *(uint4*)(g_bo + (size_t)(2 * (i0 + 16 * mt + row) + par) * 1024 + head * 32 + ch * 8) = v;
    }
    __syncwarp();
}

constexpr float SCALE_LOG2E = 0.08838834764831845f * 1.4426950408889634f;

constexpr int P_STAGES = 4, P_STAGE = 16384 + 32768;
constexpr int PS_STG = P_STAGES * P_STAGE;
constexpr int PS_BAR = PS_STG + 32768;
constexpr int P_SMEM = PS_BAR + 256;
static_assert(P_SMEM <= 232448, "smem");
enum { K_Q, K_B1, K_B3, K_A4, K_QH, K_A3, K_SK, K_B2, K_END };
struct PList { int n; int4 run[16]; };
struct PTask { int kind, a, b, c; };
DEVI PTask p_decode(const PList& pl, int id) {
    for (int i = 0; i < pl.n; i++) {
        const int4 r = pl.run[i];
        if (id < r.w) {
            const int j = id - r.z;
            if (r.x == K_Q || r.x == K_QH) return {r.x, j & 31, r.y + (j >> 5), 0};
            if (r.x == K_B1) return {r.x, j % 24, r.y + j / 24, 0};
            if (r.x == K_B2) return {r.x, 0, r.y + j, 0};
            if (r.x == K_SK) return {r.x, (j >> 2) & 7, r.y + (j >> 5), j & 3};
            return {r.x, j & 7, r.y + (j >> 3), 0};
        }
    }
    return {K_END, 0, 0, 0};
}
DEVI void wait_count(const unsigned* p, unsigned target) {
    int n = 0;
    while (true) {
        unsigned v; asm volatile("ld.acquire.gpu.global.u32 %0, [%1];" : "=r"(v) : "l"(p) : "memory");
        if ((int)(v - target) >= 0) break;
        __nanosleep(100);
        if (++n > SPIN_LIMIT) TRAP(0x10000000u | ((unsigned)(size_t)p & 0xFFFFu));
    }
}
DEVI void wait_count_warp(const unsigned* p, unsigned target) {
    int n = 0;
    while (true) {
        unsigned v; asm volatile("ld.acquire.gpu.global.u32 %0, [%1];" : "=r"(v) : "l"(p) : "memory");
        if (__all_sync(0xffffffffu, (int)(v - target) >= 0)) break;
        __nanosleep(100);
        if (++n > SPIN_LIMIT) TRAP(0x10000000u | ((unsigned)(size_t)p & 0xFFFFu));
    }
}
DEVI void signal_count(unsigned* p) { __threadfence(); atomicAdd(p, 1u); }

struct PMaps { CUtensorMap wq, bw, bwo, wo, x, bx, bo, ox, cb, cout, cq, b40; PList list; };
constexpr int PB_F = PS_BAR, PB_E = PB_F + 32, PB_TF = PB_F + 64, PB_TE = PB_F + 80, PB_S = PB_F + 96;
constexpr int PS_T = PB_F + 112, PS_SIG = PS_T + 32, PS_SK = PS_SIG + 16;

struct POut { const CUtensorMap* map; int col, tok, cnt; bool blocked; };
DEVI void p_store(const uint32_t* pk, const POut& o, int c, uint32_t stg, int warp, int lane_, int barid, bool elected) {
    const int lane = (int)opaque((uint32_t)lane_);
    const int mi = lane >> 3, r = lane & 7;
    const uint32_t buf = stg + (c & 1) * 8192;
    if (elected) asm volatile("cp.async.bulk.wait_group.read 1;" ::: "memory");
    nbar_sync(barid, 128);
    if (o.blocked) {
#pragma unroll
        for (int j = 0; j < 8; j += 2)
            stsm4(buf + (j + (mi >> 1)) * 1024 + (warp * 16 + (mi & 1) * 8 + r) * 16, pk[2 * j], pk[2 * j + 1], pk[2 * j + 2], pk[2 * j + 3]);
    } else {
#pragma unroll
        for (int j = 0; j < 8; j += 2)
            stsm4t(buf + (8 * (j + (mi >> 1)) + r) * 128 + ((2 * warp + (mi & 1)) ^ r) * 16, pk[2 * j], pk[2 * j + 1], pk[2 * j + 2], pk[2 * j + 3]);
    }
    fence_proxy_async();
    nbar_sync(barid, 128);
    if (elected) {
        if (o.blocked)
            asm volatile("cp.async.bulk.tensor.4d.global.shared::cta.bulk_group [%0, {%2, %3, %4, %5}], [%1];"
                         :: "l"(o.map), "r"(buf), "r"(0), "r"((o.col >> 5) & 2), "r"((o.col >> 7) * 4), "r"((o.tok >> 5) + 2 * c) : "memory");
        else tma_store_2d(o.map, buf, o.col, o.tok + c * 64);
        bulk_commit();
    }
}
DEVI void p_signal(uint32_t sb, int g, int cnt, int& nsig) {
    sts32(sb + PS_SIG + g * 8 + (nsig & 1) * 4, (uint32_t)cnt);
    mbar_arrive(sb + PB_S + g * 8);
    nsig++;
}
template <int BN, bool FIRST>
DEVI void p_kblock(float* d, uint32_t sb, int g, int it, bool elected) {
    const int st = it % P_STAGES;
    mbar_wait(sb + PB_F + st * 8, (it / P_STAGES) & 1);
    const uint32_t a = sb + st * P_STAGE;
    const uint64_t da = mk_desc(a + g * 8192, 16, 1024, 1), db = mk_desc(a + 16384, 16, 1024, 1);
    wg_fence();
#pragma unroll
    for (int kk = 0; kk < 4; kk++) {
        if (BN == 256) { if (FIRST && kk == 0) wgmma_n256_ss<true>(d, da, db); else wgmma_n256_ss<false>(d, da + (uint64_t)(kk * 128), db + (uint64_t)(kk * 2)); }
        else           { if (FIRST && kk == 0) wgmma_n128_ss<true>(d, da, db); else wgmma_n128_ss<false>(d, da + (uint64_t)(kk * 128), db + (uint64_t)(kk * 2)); }
    }
    wg_commit();
    if (!FIRST) {
        wg_wait<1>();
        if (elected) mbar_arrive(sb + PB_E + ((it - 1) % P_STAGES) * 8);
    }
}

DEVI void post_producer(const PMaps& mp, uint32_t sb, int nworker) {
    const uint32_t bF = sb + PB_F, bE = sb + PB_E;
    const unsigned E = *(volatile unsigned*)&g_epoch + 1;
    const unsigned qbase = (E - 1) * (unsigned)(mp.list.run[mp.list.n - 1].w + nworker);
    int it = 0;
    for (int i = 0;; i++) {
        mbar_wait(sb + PB_TE + (i & 1) * 8, ((i >> 1) & 1) ^ 1);
        const int id = (int)(atomicAdd(&g_qctr, 1u) - qbase);
        const PTask tk = p_decode(mp.list, id);
        if (tk.kind == K_B2) {
            wait_count(&g_cnt[C_B1 + (tk.b >> 2)], 48 * E);
            if ((tk.b & 3) == 0 && tk.b > 0) wait_count(&g_cnt[C_B1 + (tk.b >> 2) - 1], 48 * E);
        } else if (tk.kind == K_B3) wait_count(&g_cnt[C_B2 + tk.b], 8 * E);
        else if (tk.kind == K_A4) wait_count(&g_prog[2 * tk.b + 1], 128 * E);
        else if (tk.kind == K_A3 || tk.kind == K_SK) wait_count(&g_prog[tk.b], 128 * E);
        if (tk.kind != K_Q && tk.kind != K_QH && tk.kind != K_B1) asm volatile("fence.proxy.async;" ::: "memory");
        sts128(sb + PS_T + (i & 1) * 16, make_uint4((uint32_t)tk.kind | ((uint32_t)id << 8), (uint32_t)tk.a, (uint32_t)tk.b, (uint32_t)tk.c));
        mbar_arrive(sb + PB_TF + (i & 1) * 8);
        if (tk.kind == K_END) break;
        if (tk.kind == K_B2) {
            const int i0 = tk.b * 32;
            for (int j = 0; j < 16; j++, it++) {
                const int st = it % P_STAGES;
                mbar_wait(bE + st * 8, ((it / P_STAGES) & 1) ^ 1);
                const uint32_t a = sb + st * P_STAGE, bar = bF + st * 8;
                mbar_expect_tx(bar, 2 * 15360);
                for (int u = 0; u < 2; u++)
                    asm volatile("cp.async.bulk.tensor.4d.shared::cluster.global.mbarrier::complete_tx::bytes [%0], [%1, {%3, %4, %5, %6}], [%2];"
                                 :: "r"(a + u * 15360), "l"(&mp.b40), "r"(bar), "r"(j * 64), "r"(0), "r"(u), "r"(i0 - 8) : "memory");
            }
            continue;
        }
        const bool qk = tk.kind == K_Q || tk.kind == K_QH, ak = tk.kind == K_A4 || tk.kind == K_A3 || tk.kind == K_SK, wide = tk.kind <= K_A4;
        const CUtensorMap* tw = tk.kind == K_B1 ? &mp.bw : (qk ? &mp.wq : &mp.bwo);
        const CUtensorMap* tx = tk.kind == K_B1 ? &mp.bx : (qk ? &mp.x : (ak ? &mp.ox : &mp.bo));
        const int nk = tk.kind == K_A3 || tk.kind == K_A4 ? HD / 64 : DM / 64, kb0 = tk.c * 16;
        for (int kb = kb0; kb < kb0 + nk; kb++, it++) {
            const int st = it % P_STAGES;
            mbar_wait(bE + st * 8, ((it / P_STAGES) & 1) ^ 1);
            const uint32_t a = sb + st * P_STAGE, bar = bF + st * 8;
            mbar_expect_tx(bar, wide ? P_STAGE : 32768);
            if (ak) {
                tma_load_wo(a, &mp.wo, tk.a * 128, kb * 2, bar);
                tma_load_wo(a + 8192, &mp.wo, tk.a * 128 + 64, kb * 2, bar);
            } else {
                tma_load_2d(a, tw, tk.a * 128, kb * 64, bar);
                tma_load_2d(a + 8192, tw, tk.a * 128 + 64, kb * 64, bar);
            }
            tma_load_2d(a + 16384, tx, kb * 64, tk.b * (wide ? 256 : 128), bar);
            if (wide) tma_load_2d(a + 32768, tx, kb * 64, tk.b * 256 + 128, bar);
        }
    }
    __threadfence();
    if (atomicAdd(&g_done, 1u) == E * nworker - 1) { __threadfence(); *(volatile unsigned*)&g_epoch = E; }
}
DEVI void post_helper(uint32_t sb, int g) {
    for (int n = 0;; n++) {
        mbar_wait_sleepy(sb + PB_S + g * 8, n & 1);
        const int cnt = (int)lds32(sb + PS_SIG + g * 8 + (n & 1) * 4);
        if (cnt < 0) break;
        signal_count(&g_cnt[cnt]);
    }
}
DEVI void post_consumer(const PMaps& mp, uint32_t sb, int g, int warp) {
    const int barid = 1 + g, tid = threadIdx.x, lane = tid & 31;
    const bool elected = (tid & 127) == 0;
    const uint32_t stg = sb + PS_STG + g * 16384;
    int it = 0, nsig = 0;
    uint32_t pk[64];
    POut out;
    bool pend = false;
#pragma unroll
    for (int i = 0; i < 64; i++) pk[i] = 0u;
    for (int i = 0;; i++) {
        const uint32_t bTF = sb + PB_TF + (i & 1) * 8;
        if (pend) {
            uint32_t now;
            asm volatile("{.reg .pred p, q; mbarrier.test_wait.parity.shared::cta.b64 p, [%1], %2; bar.red.and.pred q, %3, 128, p; selp.u32 %0, 1, 0, q;}"
                         : "=r"(now) : "r"(bTF), "r"((i >> 1) & 1), "r"(barid) : "memory");
            if (!now || (lds32(sb + PS_T + (i & 1) * 16) & 255u) > K_A4) {
#pragma unroll
                for (int c = 0; c < 4; c++) p_store(pk + 16 * c, out, c, stg, warp, lane, barid, elected);
                if (elected && out.cnt != C_NONE) { bulk_wait_all(); p_signal(sb, g, out.cnt, nsig); }
                pend = false;
            }
        }
        mbar_wait(bTF, (i >> 1) & 1);
        const uint4 tw = lds128(sb + PS_T + (i & 1) * 16);
        mbar_arrive(sb + PB_TE + (i & 1) * 8);
        const PTask tk = {(int)(tw.x & 255u), (int)tw.y, (int)tw.z, (int)tw.w};
        if (tk.kind == K_END) break;
        if (tk.kind <= K_A4) {
            float d[128];
            const int nk = tk.kind == K_A4 ? HD / 64 : DM / 64;
            p_kblock<256, true>(d, sb, g, it, elected);
            if (pend) p_store(pk, out, 0, stg, warp, lane, barid, elected);
#pragma unroll
            for (int c = 1; c < 4; c++) {
                p_kblock<256, false>(d, sb, g, it + c, elected);
                if (pend) p_store(pk + 16 * c, out, c, stg, warp, lane, barid, elected);
            }
#pragma unroll 1
            for (int kb = 4; kb < nk; kb++) {
                p_kblock<256, false>(d, sb, g, it + kb, elected);
                if (kb == 6 && pend && elected && out.cnt != C_NONE) { bulk_wait_all(); p_signal(sb, g, out.cnt, nsig); }
            }
            it += nk;
            wg_wait<0>();
            reg_fence<128>(d);
            if (elected) mbar_arrive(sb + PB_E + ((it - 1) % P_STAGES) * 8);
#pragma unroll
            for (int j = 0; j < 64; j++) pk[j] = pack_bf16(d[2 * j], d[2 * j + 1]);
            out.map = tk.kind == K_Q ? &mp.cq : (tk.kind == K_B1 ? &mp.cb : &mp.cout);
            out.col = tk.a * 128 + g * 64 + (tk.kind == K_B3 ? DM : 0);
            out.tok = tk.b * 256;
            out.cnt = tk.kind == K_Q ? C_Q + tk.b : (tk.kind == K_B1 ? C_B1 + tk.b : C_NONE);
            out.blocked = tk.kind == K_Q;
            pend = true;
        } else if (tk.kind == K_B2) {
            if (elected) bulk_wait_all();
            nbar_sync(barid, 128);
#pragma unroll 1
            for (int j = 0; j < 16; j++, it++) {
                const int st = it % P_STAGES;
                mbar_wait(sb + PB_F + st * 8, (it / P_STAGES) & 1);
                const uint32_t a = sb + st * P_STAGE + g * 15360;
                battn_warp(a, stg + warp * 1024, tk.b * 32, g, j * 2 + (warp >> 1), warp >> 1, warp & 1, (int)opaque((uint32_t)lane));
                nbar_sync(barid, 128);
                if (elected) mbar_arrive(sb + PB_E + st * 8);
            }
            if (elected) p_signal(sb, g, C_B2 + (tk.b >> 2), nsig);
#pragma unroll
            for (int j = 0; j < 64; j++) pk[j] = 0u;
        } else {
            float d[64];
            const int nk = tk.kind == K_A3 ? HD / 64 : DM / 64;
            p_kblock<128, true>(d, sb, g, it, elected);
#pragma unroll 1
            for (int kb = 1; kb < nk; kb++) p_kblock<128, false>(d, sb, g, it + kb, elected);
            it += nk;
            wg_wait<0>();
            reg_fence<64>(d);
            if (elected) mbar_arrive(sb + PB_E + ((it - 1) % P_STAGES) * 8);
            bool finish = true;
            if (tk.kind == K_SK) {
                const int tile = ((tk.b - (16 - P_NSK)) * 8 + tk.a);
                float4* mine = (float4*)(g_skp + ((size_t)(tile * 4 + tk.c) * 2 + g) * 8192) + (tid & 127);
#pragma unroll
                for (int j = 0; j < 16; j++) mine[j * 128] = make_float4(d[4 * j], d[4 * j + 1], d[4 * j + 2], d[4 * j + 3]);
                nbar_sync(barid, 128);
                if (elected) { __threadfence(); const unsigned old = atomicAdd(&g_cnt_sk[tile * 2 + g], 1u); __threadfence(); sts32(sb + PS_SK + g * 4, old & 3u); }
                nbar_sync(barid, 128);
                finish = lds32(sb + PS_SK + g * 4) == 3u;
                if (finish) {
#pragma unroll 1
                    for (int q = 1; q < 4; q++) {
                        const float4* o = (const float4*)(g_skp + ((size_t)(tile * 4 + ((tk.c + q) & 3)) * 2 + g) * 8192) + (tid & 127);
#pragma unroll
                        for (int j = 0; j < 16; j++) {
                            const float4 v = __ldcg(o + j * 128);
                            d[4 * j] += v.x; d[4 * j + 1] += v.y; d[4 * j + 2] += v.z; d[4 * j + 3] += v.w;
                        }
                    }
                }
                nbar_sync(barid, 128);
            }
            if (finish) {
                const POut o = {tk.kind == K_QH ? &mp.cq : &mp.cout, tk.a * 128 + g * 64, tk.b * 128, 0, tk.kind == K_QH};
                uint32_t q[32];
#pragma unroll
                for (int j = 0; j < 32; j++) q[j] = pack_bf16(d[2 * j], d[2 * j + 1]);
                p_store(q, o, 0, stg, warp, lane, barid, elected);
                p_store(q + 16, o, 1, stg, warp, lane, barid, elected);
                if (elected && tk.kind == K_QH) { bulk_wait_all(); p_signal(sb, g, tk.b == 0 ? C_QH : C_Q, nsig); }
            }
#pragma unroll
            for (int j = 0; j < 64; j++) pk[j] = 0u;
        }
    }
    if (elected) { bulk_wait_all(); p_signal(sb, g, -1, nsig); }
}
DEVI void post_init(uint32_t sb) {
    for (int i = 0; i < P_STAGES; i++) { mbar_init(sb + PB_F + i * 8, 1); mbar_init(sb + PB_E + i * 8, 2); }
    for (int i = 0; i < 2; i++) { mbar_init(sb + PB_TF + i * 8, 1); mbar_init(sb + PB_TE + i * 8, 256); mbar_init(sb + PB_S + i * 8, 1); }
    fence_mbar_init();
}

__global__ void __launch_bounds__(384, 1) k_post(const __grid_constant__ PMaps mp) {
    extern __shared__ __align__(1024) uint8_t smem_raw[];
    const uint32_t sb = smem_u32(smem_raw);
    if (sb & 1023u) __trap();
    const int tid = threadIdx.x;
    const int wg = __shfl_sync(0xffffffffu, tid >> 7, 0), warp = __shfl_sync(0xffffffffu, (tid >> 5) & 3, 0);
    if (tid == 0) post_init(sb);
    __syncthreads();
    if (wg < 2) {
        reg_inc<232>();
        post_consumer(mp, sb, wg, warp);
    } else {
        reg_dec<40>();
        if (tid == 256) post_producer(mp, sb, gridDim.x);
        else if (tid == 288 || tid == 320) post_helper(sb, warp - 1);
    }
    __syncthreads();
    asm volatile("griddepcontrol.wait;" ::: "memory");
}

constexpr unsigned long long R_TORD_PACK = 0xf4a53e92dc7816b0ull;
__host__ __device__ constexpr int r_tord(int pos) { return (int)((R_TORD_PACK >> (4 * pos)) & 15ull); }
__host__ __device__ constexpr int r_tinv(int T) { for (int p = 0; p < 16; p++) if (r_tord(p) == T) return p; return 0; }
__host__ __device__ constexpr bool r_pos_ss(int pos) { return pos % 3 == 2; }
__host__ __device__ constexpr int r_ss(int pos) { return pos / 3; }
__host__ __device__ constexpr int r_rs(int pos) { return pos - pos / 3; }
constexpr int R_NRS = 11, R_NSS = 5;
constexpr int R_G1 = 9;
#define REG_KB 232
#define X_NA_DEF 4
constexpr int X_SLOTS = 4;
constexpr int X_NST = 8;
constexpr int X_NA = X_NA_DEF;

constexpr int RS_WSS  = 0;
constexpr int RS_WO   = RS_WSS + R_NSS * 16384;
constexpr int RS_MEM  = RS_WO + 5 * 16384;
constexpr int RS_O    = RS_MEM + 16384;
constexpr int RS_SX   = RS_O + 2048;
constexpr int RS_BAR  = RS_SX + 2048;
constexpr int RS_TAIL = RS_BAR + 1024;
constexpr int RS_WO5  = RS_TAIL;
constexpr int RS_K    = RS_WO5 + 16384;
constexpr int RS_V    = RS_K + 10240;
constexpr int RS_Q    = RS_V + 10240;
constexpr int RS_QX   = RS_Q + 2048;
constexpr int RS_QEND = RS_QX + 8192;
constexpr int RS_X    = RS_TAIL;
constexpr int X_PITCH = X_SLOTS * 4096;
constexpr int RS_XD   = RS_X + 2 * X_PITCH;
constexpr int RS_WX   = RS_XD + 8192;
constexpr int RS_KEND = RS_WX + 4096;
constexpr int RS_EV   = RS_BAR + 256;
constexpr int R_SMEM  = RS_KEND > RS_QEND ? RS_KEND : RS_QEND;
static_assert(R_SMEM <= 232448, "smem");
static_assert(RS_TAIL % 1024 == 0 && RS_MEM % 1024 == 0, "alignment");

constexpr int RB_G = RS_BAR, RB_WO = RS_BAR + 16, RB_K = RS_BAR + 24, RB_V = RS_BAR + 32, RB_KV = RS_BAR + 40, RB_QX = RS_BAR + 48, RB_O = RS_BAR + 56;
constexpr int RB_ATT = RS_BAR + 64, RB_W = RS_BAR + 72, RB_SF = RS_BAR + 80, RB_SE = RB_SF + 40, RB_XF = RB_SE + 40;
constexpr int RB_T = RB_XF + 64, RS_INV = RB_SF;
static_assert(RB_T + 8 <= RS_EV, "barriers");
constexpr uint32_t SB0 = 1024;
__host__ __device__ constexpr uint32_t cdesc(uint32_t off, uint32_t lbo) { return ((SB0 + off) >> 4) | ((lbo >> 4) << 16); }
#define SCHED_FENCE() __syncwarp()
constexpr int NB_BIG = 1, NB_Q = 2, NB_AUX = 3, NB_WO = 4, NB_XS = 5, NB_WG = 6, NB_PAIR = 8;

DEVI int tid_now() { int t; asm volatile("mov.u32 %0, %%tid.x;" : "=r"(t)); return t; }
DEVI uint32_t a_frag_off(int lane, int warp) { return (uint32_t)((((lane >> 4) * 8 + (lane & 7)) * 128) + (((2 * warp + ((lane >> 3) & 1)) ^ (lane & 7)) * 16)); }
DEVI uint32_t b_frag_off(int lane) { return (uint32_t)((lane & 3) * 64 + (((lane >> 2) * 8) ^ ((lane & 2) * 16))); }
DEVI void lds_b(uint32_t* b, uint32_t a) {
    asm volatile("ld.shared.v2.u32 {%0,%1}, [%2];" : "=r"(b[0]), "=r"(b[1]) : "r"(a) : "memory");
    asm volatile("ld.shared.v2.u32 {%0,%1}, [%2];" : "=r"(b[2]), "=r"(b[3]) : "r"(a + 256) : "memory");
}
DEVI uint32_t clk32() { unsigned long long c; asm volatile("mov.u64 %0, %%clock64;" : "=l"(c)); return (uint32_t)c; }
DEVI bool elect_one() {
    uint32_t e; asm volatile("{.reg .pred p; elect.sync _|p, 0xffffffff; selp.u32 %0, 1, 0, p;}" : "=r"(e)); return e;
}
DEVI void spin_until(uint32_t t) { while ((int)((uint32_t)gtime() - t) < 0) { } }

DEVI void x_load(uint32_t sb, int seg, int j, int g, const CUtensorMap* tmX) {
    const uint32_t bar = sb + RB_XF + g * (8 * X_SLOTS) + 8 * (j % X_SLOTS);
    mbar_expect_tx(bar, 4096);
    tma_load_3d(sb + RS_X + g * X_PITCH + (j % X_SLOTS) * 4096, tmX, g * 32, seg * 32, j * 2, bar);
}
DEVI void x_refill(uint32_t sb, int seg, int j, int g, int warp, const CUtensorMap* tmX) {
    const int sn = j + X_SLOTS < X_NST ? seg : seg + 1;
    if (warp == (j & 3) && sn < NSEG) {
        if (elect_one()) x_load(sb, sn, (j + X_SLOTS) % X_NST, g, tmX);
    }
}
template <int J0, int J1>
DEVI void x_stages(float* xa, const uint32_t* w, uint32_t sb, int seg, int g0, int warp, const CUtensorMap* tmX) {
#pragma unroll
    for (int j = J0; j < J1; j++) {
        const int g = (int)opaque((uint32_t)g0);
        const uint32_t dW0 = cdesc(RS_WSS, 16) + g * 768, dW1 = cdesc(RS_WSS + 8192, 16) - g * 256;
        const uint32_t dX = cdesc(RS_X + (j % X_SLOTS) * 4096, 16) + g * (X_PITCH >> 4);
        mbar_wait(sb + RB_XF + g * (8 * X_SLOTS) + 8 * (j % X_SLOTS), (j / X_SLOTS) & 1);
        wg_fence();
#pragma unroll
        for (int q = 0; q < 8; q++) {
            const int pos = r_tinv(2 * j + (q >> 2)), kk = (q >> 1) & 1, mt = q & 1;
            const uint32_t db = dX + (q >> 2) * 128 + kk * 2;
            if (j == 0 && q < 2)   wgmma_n32_rs_first(xa + 16 * mt, &w[((r_rs(pos) * 2 + kk) * 2 + mt) * 4], db);
            else if (j == 0 && q == 3) wgmma_n32_ss(xa + 16, cdesc(RS_WX, 16) + g * 128, db);
            else if (r_pos_ss(pos)) wgmma_n32_ss(xa + 16 * mt, (mt ? dW1 : dW0) + r_ss(pos) * 1024 + kk * 128, db);
            else                   wgmma_n32_rs(xa + 16 * mt, &w[((r_rs(pos) * 2 + kk) * 2 + mt) * 4], db);
        }
        wg_commit();
        if (j > J0) { wg_wait<1>(); x_refill(sb, seg, j - 1, g, warp, tmX); }
    }
    wg_wait<0>();
    reg_fence<32>(xa);
    if (J1 < X_NST) x_refill(sb, seg, J1 - 1, (int)opaque((uint32_t)g0), warp, tmX);
}
DEVI void x_finish(float* xa, uint32_t sb, int g, int warp, int lane) {
    const uint32_t ring = sb + RS_X + (X_SLOTS - 1) * 4096 + warp * 512 + lane * 16;
    const uint32_t d = sb + RS_XD + (lane >> 4) * 2048 + warp * 256 + (lane & 15) * 16;
    sts128f(d + (g ^ 1) * 1024, xa + 24); sts128f(d + (g ^ 1) * 1024 + 4096, xa + 28);
    nbar_sync(NB_WG + g, 128);
    sts128f(ring + g * X_PITCH, xa + 16); sts128f(ring + g * X_PITCH + 2048, xa + 20);
    nbar_sync(NB_PAIR + warp, 64);
    uint32_t p[8];
#pragma unroll
    for (int i = 0; i < 4; i++) {
        const uint4 v = lds128(i < 2 ? ring + (g ^ 1) * X_PITCH + i * 2048 : d + g * 1024 + (i - 2) * 4096);
        p[2 * i]     = pack_bf16(xa[4 * i] + __uint_as_float(v.x), xa[4 * i + 1] + __uint_as_float(v.y));
        p[2 * i + 1] = pack_bf16(xa[4 * i + 2] + __uint_as_float(v.z), xa[4 * i + 3] + __uint_as_float(v.w));
    }
    __syncwarp();
    stsm4(d + g * 1024, p[0], p[1], p[2], p[3]);
    stsm4(d + g * 1024 + 4096, p[4], p[5], p[6], p[7]);
    nbar_arrive(NB_XS, 256 + 32);
}
DEVI void x_send(uint32_t sb, int seg, uint32_t rank, const CUtensorMap* tmX) {
    mbar_wait(sb + RB_ATT, (seg - 1) & 1);
    nbar_sync(NB_XS, 256 + 32);
    if (elect_one()) {
        fence_proxy_async();
        bulk_copy_s2c(mapa(sb + (rank == 1 ? RS_K : RS_V) + 2048, 0), sb + RS_XD, 8192, mapa(sb + RB_KV, 0));
        if (seg + 1 < NSEG) { x_load(sb, seg + 1, X_SLOTS - 1, 0, tmX); x_load(sb, seg + 1, X_SLOTS - 1, 1, tmX); }
    }
    __syncwarp();
}

template <bool XP>
DEVI void mem_pass(float* c0, float* c1, const uint32_t* w, uint32_t sb, uint32_t aA0, uint32_t aB, int g, int s) {
    const uint32_t aA1 = aA0 + 8192 - g * 16384, par = (s - 1) & 1;
    uint32_t a[16], b[2][4], e[4];
    float d0[4], d1[4];
    if (XP) ldsm4t(e, aA0 + (RS_WX - RS_WSS) - g * (8192 + 2048));
#pragma unroll
    for (int q = 0; q < 4; q++) ldsm4t(a + 4 * q, ((q & 1) ? aA1 : aA0) + (q >> 1) * 2048);
#pragma unroll
    for (int i = 0; i < 4; i++) { c0[i] = 0.f; c1[i] = 0.f; d0[i] = 0.f; d1[i] = 0.f; }
    EV(tid_now() == 0, s, 0);
    mbar_wait(sb + RB_G, par);
    EV(tid_now() == 0, s, 1);
    lds_b(b[0], aB + r_tord(0) * 1024);
    bool in = false;
#pragma unroll
    for (int pos = 0; pos < 16; pos++) {
        if (pos + 1 < 16) {
            if (pos + 1 == R_G1) { if (!in) mbar_wait(sb + RB_G + 8, par); EV(tid_now() == 0, s, 2); }
            lds_b(b[(pos + 1) & 1], aB + r_tord(pos + 1) * 1024);
        }
        if (pos + 2 == R_G1) in = mbar_try(sb + RB_G + 8, par);
        if (XP && pos == 14) in = mbar_try(sb + RB_ATT, par);
        const uint32_t* bb = b[pos & 1];
        const uint32_t* aa = r_pos_ss(pos) ? a : &w[r_rs(pos) * 16];
        mma16816(c1, aa + 4, bb[0], bb[1]);
        mma16816(d1, XP && pos == 0 ? e : aa + 12, bb[2], bb[3]);
        mma16816(c0, aa, bb[0], bb[1]);
        mma16816(d0, aa + 8, bb[2], bb[3]);
        if (r_pos_ss(pos) && pos + 3 < 16) {
#pragma unroll
            for (int q = 0; q < 4; q++) ldsm4t(a + 4 * q, ((q & 1) ? aA1 : aA0) + (r_ss(pos) + 1) * 16384 + (q >> 1) * 2048);
        }
        SCHED_FENCE();
    }
    if (XP && !in) mbar_wait(sb + RB_ATT, par);
#pragma unroll
    for (int i = 0; i < 4; i++) { c1[i] += d1[i]; c0[i] += d0[i]; }
}

DEVI uint32_t k_frag_off(int lane) { return (uint32_t)((((lane >> 3) & 1) * 16 + (lane >> 4) * 8 + (lane & 7)) * 16); }
DEVI uint32_t v_frag_off(int lane) { return (uint32_t)(((lane >> 3) & 1) * 2048 + ((lane >> 4) * 8 + (lane & 7)) * 16); }
DEVI void pv_pair(float (*o)[4], const uint32_t* p, const uint32_t* v) {
#pragma unroll
    for (int n = 0; n < 4; n++) mma16816(o[n], p, v[2 * n], v[2 * n + 1]);
}
DEVI void pv_single(float (*o)[4], const uint32_t* p, const uint32_t* v) {
#pragma unroll
    for (int n = 0; n < 4; n++) mma1688(o[n], p[0], p[1], v[n]);
}
DEVI float inv_sum4(float l) {
    l += __shfl_xor_sync(0xffffffffu, l, 1);
    l += __shfl_xor_sync(0xffffffffu, l, 2);
    return rcp_fast(l);
}

DEVI void mem_attn(uint32_t sb, int s, int warp, int lane) {
    const uint32_t ka = sb + RS_K + k_frag_off(lane), va = sb + RS_V + warp * 512;
    uint32_t qa[16], vx[16];
    float sc[10];
    mbar_wait(sb + RB_KV, s & 1);
    {
        uint32_t kx[16];
#pragma unroll
        for (int q = 0; q < 4; q++) ldsm4t(kx + 4 * q, ka + (1 + warp) * 2048 + q * 512);
        nbar_sync(NB_Q, 256);
        EV(tid_now() == 0 && lds32(sb + RS_Q) != 0x12345678u, s, 8);
#pragma unroll
        for (int q = 0; q < 4; q++) ldsm4t(qa + 4 * q, sb + RS_Q + q * 512 + lane * 16);
        float c[4] = {0.f, 0.f, 0.f, 0.f}, d[4] = {0.f, 0.f, 0.f, 0.f};
#pragma unroll
        for (int q = 0; q < 4; q++) { mma16816(c, qa + 4 * q, kx[4 * q], kx[4 * q + 1]); mma16816(d, qa + 4 * q, kx[4 * q + 2], kx[4 * q + 3]); }
        asm volatile("st.shared.v2.f32 [%0], {%1,%2};" :: "r"(sb + RS_SX + warp * 256 + lane * 8), "f"(c[0] + d[2]), "f"(c[1] + d[3]) : "memory");
    }
    nbar_sync(NB_WG, 128);
#pragma unroll
    for (int n = 0; n < 4; n++) { const float2 v = lds64f(sb + RS_SX + n * 256 + lane * 8); sc[2 + 2 * n] = v.x; sc[3 + 2 * n] = v.y; }
    const uint32_t dst = sb + RS_O + warp * 512 + (lane & 3) * 128 + (lane >> 2) * 16;
    float m = fmaxf(fmaxf(fmaxf(sc[2], sc[3]), fmaxf(sc[4], sc[5])), fmaxf(fmaxf(sc[6], sc[7]), fmaxf(sc[8], sc[9])));
    mbar_wait(sb + RB_K, s & 1);
    EV(tid_now() == 0, s, 9);
    {
        float c[4][4];
#pragma unroll
        for (int q = 0; q < 4; q++) { c[q][0] = c[q][1] = c[q][2] = c[q][3] = 0.f; }
        uint32_t km[16];
#pragma unroll
        for (int q = 0; q < 4; q++) ldsm4t(km + 4 * q, ka + q * 512);
        SCHED_FENCE();
#pragma unroll
        for (int q = 0; q < 4; q++) {
            mma16816(c[2 * (q & 1)], qa + 4 * q, km[4 * q], km[4 * q + 1]);
            mma16816(c[2 * (q & 1) + 1], qa + 4 * q, km[4 * q + 2], km[4 * q + 3]);
        }
        sc[0] = (c[0][0] + c[1][2]) + (c[2][0] + c[3][2]);
        sc[1] = (c[0][1] + c[1][3]) + (c[2][1] + c[3][3]);
    }
    const bool v_in = mbar_try(sb + RB_V, s & 1);
#pragma unroll
    for (int q = 0; q < 4; q++) ldsm4(vx + 4 * q, va + 2048 + (q >> 1) * 4096 + (q & 1) * 256 + v_frag_off(lane));
    m = fmaxf(m, fmaxf(sc[0], sc[1]));
    m = fmaxf(fmaxf(m, __shfl_xor_sync(0xffffffffu, m, 1)), fmaxf(__shfl_xor_sync(0xffffffffu, m, 2), __shfl_xor_sync(0xffffffffu, m, 3)));
    if (!v_in) mbar_wait(sb + RB_V, s & 1);
    uint32_t vm[4], p[10];
    ldsm4(vm, va + lane * 16);
    const float nm = -m * SCALE_LOG2E;
    float l = 0.f;
#pragma unroll
    for (int n = 4; n >= 0; n--) {
        const float e0 = ex2(fmaf(sc[2 * n], SCALE_LOG2E, nm)), e1 = ex2(fmaf(sc[2 * n + 1], SCALE_LOG2E, nm));
        l += e0 + e1;
        p[2 * n] = pack_bf16(e0, e1); p[2 * n + 1] = __float_as_uint(e0);
    }
    float o[4][4];
#pragma unroll
    for (int n = 0; n < 4; n++) { o[n][0] = o[n][1] = o[n][2] = o[n][3] = 0.f; }
    pv_pair(o, p + 6, vx + 8);
    pv_pair(o, p + 2, vx);
    pv_single(o, p, vm);
    l = (l + __shfl_xor_sync(0xffffffffu, l, 1)) + (__shfl_xor_sync(0xffffffffu, l, 2) + __shfl_xor_sync(0xffffffffu, l, 3));
    if ((lane & 3) == 0) {
        if (warp == 0) sts32(sb + RS_INV + lane, __float_as_uint(l));
        else if (warp < 3)
            asm volatile("st.async.weak.shared::cluster.mbarrier::complete_tx::bytes.b32 [%0], %1, [%2];"
                         :: "r"(mapa(sb + RS_INV + lane, warp)), "r"(__float_as_uint(l)), "r"(mapa(sb + RB_O, warp)) : "memory");
    }
    const uint4 u = make_uint4(pack_bf16(o[0][0], o[0][1]), pack_bf16(o[1][0], o[1][1]), pack_bf16(o[2][0], o[2][1]), pack_bf16(o[3][0], o[3][1]));
    st_async128(mapa(dst, 1), u.x, u.y, u.z, u.w, mapa(sb + RB_O, 1));
    st_async128(mapa(dst, 2), u.x, u.y, u.z, u.w, mapa(sb + RB_O, 2));
    sts128(dst, u);
    __syncwarp();
    if (elect_one()) mbar_arrive(sb + RB_O);
}

DEVI void ta_scores(float* c, uint32_t sb, int seg, int cw, int lane) {
    const int mt = cw >= 3, n = cw - 3 * mt;
    const uint32_t qa = sb + RS_QX + (2 * mt + ((lane >> 3) & 1)) * 2048 + ((lane >> 4) * 8 + (lane & 7)) * 16;
    const uint32_t ka = sb + RS_K + n * 2048 + lane * 16;
    float d[4] = {0.f, 0.f, 0.f, 0.f};
    c[0] = c[1] = c[2] = c[3] = 0.f;
    mbar_wait(sb + RB_QX, seg & 1);
    mbar_wait(sb + (n == 0 ? RB_K : RB_KV), seg & 1);
#pragma unroll
    for (int j = 0; j < 4; j++) {
        uint32_t a0[4], a1[4], b[4];
        ldsm4t(a0, qa + j * 512);
        ldsm4t(b, ka + j * 512);
        ldsm4t(a1, qa + j * 512 + 256);
        mma16816(c, a0, b[0], b[1]);
        mma16816(d, a1, b[2], b[3]);
    }
    const int over = 8 * (n - 1) + 2 * (lane & 3) - 16 * mt - (lane >> 2);
    c[0] = over > 0 ? -INFINITY : c[0] + d[0];
    c[1] = over >= 0 ? -INFINITY : c[1] + d[1];
    c[2] = over > 8 ? -INFINITY : c[2] + d[2];
    c[3] = over >= 8 ? -INFINITY : c[3] + d[3];
}
DEVI void ta_output(uint32_t sb, int seg, int head, int mt, int j, int lane) {
    const uint32_t sa = sb + RS_QX + mt * 1536 + lane * 16;
    float sc[5][4];
#pragma unroll
    for (int n = 0; n < 5; n++) {
        uint4 v = make_uint4(0xFF800000u, 0xFF800000u, 0xFF800000u, 0xFF800000u);
        if (n < 2 || n == 4 || mt) v = lds128(sa + (n == 4 ? 1024 + mt * 1024 : n * 512));
        sc[n][0] = __uint_as_float(v.x); sc[n][1] = __uint_as_float(v.y); sc[n][2] = __uint_as_float(v.z); sc[n][3] = __uint_as_float(v.w);
    }
    float m0 = -INFINITY, m1 = -INFINITY;
#pragma unroll
    for (int n = 0; n < 5; n++) { m0 = fmaxf(m0, fmaxf(sc[n][0], sc[n][1])); m1 = fmaxf(m1, fmaxf(sc[n][2], sc[n][3])); }
    m0 = fmaxf(m0, __shfl_xor_sync(0xffffffffu, m0, 1)); m1 = fmaxf(m1, __shfl_xor_sync(0xffffffffu, m1, 1));
    m0 = fmaxf(m0, __shfl_xor_sync(0xffffffffu, m0, 2)); m1 = fmaxf(m1, __shfl_xor_sync(0xffffffffu, m1, 2));
    m0 *= -SCALE_LOG2E; m1 *= -SCALE_LOG2E;
    float l0 = 0.f, l1 = 0.f;
    uint32_t p[10];
#pragma unroll
    for (int n = 0; n < 5; n++) {
        const float e0 = ex2(fmaf(sc[n][0], SCALE_LOG2E, m0)), e1 = ex2(fmaf(sc[n][1], SCALE_LOG2E, m0));
        const float e2 = ex2(fmaf(sc[n][2], SCALE_LOG2E, m1)), e3 = ex2(fmaf(sc[n][3], SCALE_LOG2E, m1));
        l0 += e0 + e1; l1 += e2 + e3;
        p[2 * n] = pack_bf16(e0, e1); p[2 * n + 1] = pack_bf16(e2, e3);
    }
    const float i0 = inv_sum4(l0), i1 = inv_sum4(l1);
    mbar_wait(sb + RB_V, seg & 1);
    mbar_wait(sb + RB_KV, seg & 1);
    const uint32_t vb = sb + RS_V + j * 512;
    float o[4][4];
#pragma unroll
    for (int n = 0; n < 4; n++) { o[n][0] = o[n][1] = o[n][2] = o[n][3] = 0.f; }
    uint32_t v[8];
    ldsm4(v, vb + v_frag_off(lane)); ldsm4(v + 4, vb + v_frag_off(lane) + 256);
    pv_pair(o, p, v);
    SCHED_FENCE();
    ldsm4(v, vb + 4096 + v_frag_off(lane)); ldsm4(v + 4, vb + 4096 + v_frag_off(lane) + 256);
    pv_pair(o, p + 4, v);
    SCHED_FENCE();
    ldsm4(v, vb + 4096 + mt * 4096 + lane * 16);
    pv_single(o, p + 8, v);
    bf16* dst = g_ox + (uint32_t)((seg * 32 + mt * 16 + (lane >> 2)) * HD + head * DH + j * 32 + (lane & 3) * 8);
    asm volatile("st.global.v4.u32 [%0], {%1,%2,%3,%4};" :: "l"(dst), "r"(pack_bf16(o[0][0] * i0, o[0][1] * i0)), "r"(pack_bf16(o[1][0] * i0, o[1][1] * i0)),
                 "r"(pack_bf16(o[2][0] * i0, o[2][1] * i0)), "r"(pack_bf16(o[3][0] * i0, o[3][1] * i0)) : "memory");
    asm volatile("st.global.v4.u32 [%0], {%1,%2,%3,%4};" :: "l"(dst + 8 * HD), "r"(pack_bf16(o[0][2] * i1, o[0][3] * i1)), "r"(pack_bf16(o[1][2] * i1, o[1][3] * i1)),
                 "r"(pack_bf16(o[2][2] * i1, o[2][3] * i1)), "r"(pack_bf16(o[3][2] * i1, o[3][3] * i1)) : "memory");
}

template <bool XP>
DEVI void big_main(const uint32_t* w, const uint32_t sb, const int g, const int warp, const uint32_t rank, const int head,
                   const CUtensorMap* tmX, const bf16* xg, const unsigned E) {
    float xa[32];
    const uint32_t aB = __shfl_sync(0xffffffffu, sb + RS_MEM + (g * 32 + (tid_now() & 31)) * 16, tid_now() & 31);
#define lane0 ((int)(opaque(aB) >> 4) & 31)
    const uint32_t aA0 = sb + RS_WSS + g * (8192 + 4096) + a_frag_off(lane0, warp);
    if constexpr (XP) {
        x_stages<0, X_NST>(xa, w, sb, 0, g, warp, tmX);
        x_finish(xa, sb, g, warp, lane0);
    }
    nbar_sync(NB_BIG, 256);
    for (int s = 0; s < NSEG; s++) {
        {
            float c0[4], c1[4];
            mem_pass<XP>(c0, c1, w, sb, aA0, sb + RS_MEM + g * 512 + b_frag_off(lane0), g, s);
            const int lane = lane0, t = lane & 3;
            const uint32_t xs = aB + (RS_O - RS_MEM) + (warp - g) * 512;
            const int dim = g * 64 + warp * 16 + (lane >> 2) + ((t & 1) ? 8 : 0);
            const uint32_t off = (uint32_t)((XP ? (rank == 1 ? RS_K : RS_V) : RS_Q) + dim * 16 + (t & 2) * 4);
            const uint32_t dst = XP ? mapa(sb + off, 0) : sb + off;
            const uint32_t rbar = XP ? mapa(sb + (rank == 1 ? RB_K : RB_V), 0) : 0u;
            EV(tid_now() == 0 && c0[0] != 1.2345e30f, s, 3);
            sts128f(xs + g * 2048, c1);
            nbar_sync(NB_PAIR + warp, 64);
            const uint4 v = lds128(xs + (g ^ 1) * 2048);
            const uint32_t p0 = pack_bf16(c0[0] + __uint_as_float(v.x), c0[1] + __uint_as_float(v.y));
            const uint32_t p1 = pack_bf16(c0[2] + __uint_as_float(v.z), c0[3] + __uint_as_float(v.w));
            const uint32_t rcv = __shfl_xor_sync(0xffffffffu, (t & 1) ? p0 : p1, 1);
            const uint32_t lo = (t & 1) ? rcv : p0, hi = (t & 1) ? p1 : rcv;
            if constexpr (XP) st_async64(dst, lo, hi, rbar);
            else if (s < NSEG - 1) {
                asm volatile("st.shared.v2.u32 [%0], {%1,%2};" :: "r"(dst), "r"(lo), "r"(hi) : "memory");
                if (g == 1) nbar_arrive(NB_Q, 256);
            }
            EV(tid_now() == 0, s, 4);
        }
        if constexpr (XP) {
            if (s == NSEG - 1) break;
            x_stages<0, X_NA>(xa, w, sb, s + 1, g, warp, tmX);
            EV(tid_now() == 0, s, 5);
            EVCAL(s);
            nbar_sync(NB_WO, 384);
            EV(tid_now() == 0 && lds32(sb + RS_O) != 0x12345678u, s, 6);
            x_stages<X_NA, X_NST>(xa, w, sb, s + 1, g, warp, tmX);
            EV(tid_now() == 0, s, 7);
            x_finish(xa, sb, g, warp, lane0);
        } else {
            if (g == 0) {
                if (s < NSEG - 1) mem_attn(sb, s, warp, lane0);
            } else {
                if (s == 0 && warp == 0) {
                    wait_count_warp(&g_cnt[C_QH], 64 * E);
                    if (elect_one()) {
                        asm volatile("fence.proxy.async;" ::: "memory");
                        mbar_expect_tx(sb + RB_QX, 8192);
                        bulk_load(sb + RS_QX, g_qx + (size_t)head * 4096, 8192, sb + RB_QX);
                    }
                    __syncwarp();
                }
                float sc[8];
                const int t2 = warp == 3 ? 3 : (warp + 1) % 3;
                ta_scores(sc, sb, s, 4 + warp, lane0);
                ta_scores(sc + 4, sb, s, t2, lane0);
                nbar_sync(NB_WG + 1, 128);
                sts128f(aB + (RS_QX - RS_MEM) + (3 + warp) * 512, sc);
                sts128f(aB + (RS_QX - RS_MEM) + (t2 - 1) * 512, sc + 4);
            }
            EVCAL(s);
            if (s < NSEG - 1) nbar_sync(NB_WO, 384); else nbar_sync(NB_BIG, 256);
            EV(tid_now() == 0 && lds32(sb + RS_O) != 0x12345678u, s, 6);
            ta_output(sb, s, head, g, warp, lane0);
            nbar_sync(NB_BIG, 256);
            EV(tid_now() == 0 && lds32(sb + RS_O) != 0x12345678u, s, 7);
            if (g == 0 && warp == 0 && s + 1 < NSEG) {
                if (elect_one()) {
                    mbar_arrive_remote(mapa(sb + RB_ATT, 1));
                    mbar_arrive_remote(mapa(sb + RB_ATT, 2));
                    mbar_expect_tx(sb + RB_KV, 16384);
                    mbar_expect_tx(sb + RB_K, 2048);
                    mbar_expect_tx(sb + RB_V, 2048);
                    mbar_arrive(sb + RB_T);
                }
                __syncwarp();
            }
        }
    }
    if constexpr (!XP) { if (tid_now() == 0) signal_count(&g_prog[(NSEG - 1) >> 2]); }
#undef lane0
}

template <int T, int K0, int K1>
DEVI void wo_part(float* acc) {
    constexpr uint32_t dWo = cdesc(T < 5 ? RS_WO + T * 16384 : RS_WO5, 16), dO = cdesc(RS_O, 128);
#pragma unroll
    for (int kk = K0; kk < K1; kk++) {
        if (kk == 0) { if (T < 3) wgmma_n8_ss_first<0>(acc, dWo, dO); else wgmma_n8_ss<0, 0>(acc, dWo, dO); }
        else wgmma_n8_ss<0, 1>(acc, dWo + kk * 128, dO + kk * 16);
    }
    wg_commit();
}
DEVI void red3(uint8_t* p, uint32_t a, uint32_t b, uint32_t c, uint32_t one) {
    asm volatile("red.relaxed.gpu.global.add.noftz.v4.bf16x2 [%0], {%1,%2,%3,%4};" :: "l"(p), "r"(a), "r"(b), "r"(c), "r"(one) : "memory");
}
constexpr int ACC_CH = 3 * 16 * 1024;
template <bool Q>
DEVI void wo_phase(uint32_t sb, int s, uint8_t* p, uint32_t ainv) {
    float a0[4], a1[4], a2[4];
    fence_proxy_async();
    const float2 iv = lds64f(ainv);
    SCHED_FENCE();
    const float i0 = rcp_fast(iv.x), i1 = rcp_fast(iv.y);
#define WORD(a, h) pack_bf16(a[2 * h] * i0, a[2 * h + 1] * i1)
    wg_fence();
    wo_part<0, 0, 8>(a0); wo_part<1, 0, 8>(a1); wo_part<2, 0, 8>(a2);
    wg_wait<1>(); reg_fence<4>(a0); reg_fence<4>(a1);
    red3(p, WORD(a0, 0), WORD(a0, 1), WORD(a1, 0), 0x3F80u);
    SCHED_FENCE();
    EV(tid_now() == 256, s, 11);
    wg_wait<0>(); reg_fence<4>(a2);
    red3(p + ACC_CH, WORD(a2, 0), WORD(a2, 1), WORD(a1, 1), 0x3F80u);
    SCHED_FENCE();
    wg_fence();
    wo_part<3, 0, 8>(a0); wo_part<4, 0, 8>(a1);
    if (Q) {
        wo_part<5, 0, 8>(a2);
        wg_wait<1>(); reg_fence<4>(a0); reg_fence<4>(a1);
        red3(p + 2 * ACC_CH, WORD(a0, 0), WORD(a0, 1), WORD(a1, 0), 0x3F80u);
        SCHED_FENCE();
        wg_wait<0>(); reg_fence<4>(a2);
        red3(p + 3 * ACC_CH, WORD(a2, 0), WORD(a2, 1), WORD(a1, 1), 0x3F80u);
        nbar_arrive(NB_WO, 384);
    } else {
        wg_wait<1>();
        nbar_arrive(NB_WO, 384);
        wg_wait<0>(); reg_fence<4>(a0); reg_fence<4>(a1);
        red3(p + 2 * ACC_CH, WORD(a0, 0), WORD(a0, 1), WORD(a1, 0), 0x3F80u);
        red3(p + 3 * ACC_CH, 0u, 0u, WORD(a1, 1), 0x3F80u);
    }
#undef WORD
}
DEVI void unit_send(uint32_t d, uint32_t x0, uint32_t x1, uint32_t x2, uint32_t x3, uint32_t bar, uint32_t r1, uint32_t r2) {
    const uint32_t u0 = __byte_perm(x0, x1, 0x5410), u1 = __byte_perm(x2, x3, 0x5410), u2 = __byte_perm(x0, x1, 0x7632), u3 = __byte_perm(x2, x3, 0x7632);
    st_async128(mapa(d, r1), u0, u1, u2, u3, mapa(bar, r1));
    st_async128(mapa(d, r2), u0, u1, u2, u3, mapa(bar, r2));
    sts128(d, make_uint4(u0, u1, u2, u3));
}
template <bool Q>
DEVI void stage_sums(uint32_t sb, int s, uint32_t rank, int warp, const uint8_t* src, uint32_t l, uint32_t gate) {
    uint4 v[4];
    spin_until(gate);
    EV(elect_one(), s, 16 + warp);
#pragma unroll
    for (int j = 0; j < 4; j++) v[j] = ld_rlx4(src + j * 1024);
    const uint32_t col = sb + RS_MEM + ((Q ? 0 : (rank == 1 ? 6 : 11)) + 3 * (warp >> 1)) * 1024 + ((l >> 2) & 0x300) + (l & 0x70);
    const uint32_t r1 = Q ? 1 : 0, r2 = Q ? 2 : 3 - rank, bar = sb + RB_G + 8 * (warp >> 1);
    int n = 0;
    while (!__all_sync(0xffffffffu, v[0].w == 0x4200u && v[1].w == 0x4200u && v[2].w == 0x4200u && v[3].w == 0x4200u)) {
#pragma unroll
        for (int j = 0; j < 4; j++) v[j] = ld_rlx4(src + j * 1024);
        if (++n > SPIN_LIMIT) TRAP(0x20000000u | (s << 8) | warp);
    }
    EV(elect_one(), s, 24 + warp);
    if (Q || warp < 3) {
        unit_send(col + (warp & 1) * 2048, v[0].x, v[1].x, v[2].x, v[3].x, bar, r1, r2);
        unit_send((col ^ 160) + (warp & 1) * 2048, v[0].y, v[1].y, v[2].y, v[3].y, bar, r1, r2);
    }
    unit_send((col ^ ((warp & 1) * 160)) + 1024, v[0].z, v[1].z, v[2].z, v[3].z, bar, r1, r2);
    __syncwarp();
    if (elect_one()) mbar_expect_tx(bar, warp < 2 ? 3072u : (warp == 3 ? 0u : (Q ? 4096u : 5120u)));
    EV(elect_one(), s, 20 + warp);
}
DEVI void wo_permute(uint32_t a, int n) {
    const uint32_t flip = (a >> 3) & 16;
#pragma unroll 2
    for (int i = 0; i < n; i++, a += 4096) {
        const uint4 v = lds128(a ^ flip), u = lds128(a ^ flip ^ 16);
        sts128(a ^ flip, make_uint4(__byte_perm(v.x, v.y, 0x5410), __byte_perm(v.x, v.y, 0x7632), __byte_perm(u.x, u.y, 0x5410), __byte_perm(u.x, u.y, 0x7632)));
        sts128(a ^ flip ^ 16, make_uint4(__byte_perm(v.z, v.w, 0x5410), __byte_perm(v.z, v.w, 0x7632), __byte_perm(u.z, u.w, 0x5410), __byte_perm(u.z, u.w, 0x7632)));
    }
}
DEVI void acc_clear(int slot, int idx) {
    const int lane = tid_now() & 31;
    if (lane < 24) st_rlx4(g_acc + slot * 128 + (idx * 3 + (lane >> 3)) * 1024 + (lane & 7) * 16, 0u, 0u, 0u, 0u);
}

template <bool Q>
DEVI void aux_main(uint32_t sb, int warp, uint32_t rank, int head, const CUtensorMap* tmX, const bf16* xg, unsigned E, int delay, int period, const int4 tune) {
    const uint32_t lo = __shfl_sync(0xffffffffu, ((tid_now() >> 3) & 3) * 1024 + (tid_now() & 7) * 16, tid_now() & 31);
    for (int s = 0; s < NSEG - 1; s++) {
        if (!Q && warp == 0 && elect_one()) mbar_expect_tx(sb + RB_O, 2048 + 32);
        __syncwarp();
        const uint32_t slot = (s & 3) * 128 + rank * 16384;
        mbar_wait(sb + RB_O, s & 1);
        uint32_t pred; asm volatile("ld.relaxed.gpu.global.u32 %0, [%1];" : "=r"(pred) : "l"(&g_pred) : "memory");
        EV(tid_now() == 256, s, 10);
        wo_phase<Q>(sb, s, g_acc + (uint32_t)(slot + warp * 4096 + opaque(lo)), sb + RS_INV + ((opaque(lo) >> 1) & 24));
        SCHED_FENCE();
        const unsigned long long now = gtime();
        if (warp == 0 && elect_one()) asm volatile("red.relaxed.gpu.global.max.u64 [%0], %1;" :: "l"(&g_tlast), "l"(now) : "memory");
        const uint32_t t_o = ((pred ^ s) & 31) == 0 && (pred - (uint32_t)now) < 4096u && s > 0 ? pred : (uint32_t)now;
        EV(tid_now() == 256, s, 12);
        {
            const uint32_t l = opaque(lo);
            const uint8_t* src = g_acc + (uint32_t)(slot + warp * ACC_CH + (l & 0xC00) * 4 + (l & 0x70));
            stage_sums<Q>(sb, s, rank, warp, src, l, t_o + delay);
        }
        EV(tid_now() == 256 + 64, s, 14);
        mbar_wait(sb + RB_G + 8, s & 1);
        if (warp == 3) {
            if (Q) {
                mbar_wait(sb + RB_T, s & 1);
                const bool fresh = (s & 7) == 7 || s == 3;
                if (fresh) wait_count_warp(&g_cnt[C_Q + ((s + 1) >> 3)], 64 * E);
                if (elect_one()) {
                    if (fresh) asm volatile("fence.proxy.async;" ::: "memory"); else fence_proxy_async();
                    mbar_expect_tx(sb + RB_QX, 8192);
                    bulk_load(sb + RS_QX, g_qx + ((size_t)(s + 1) * NH + head) * 4096, 8192, sb + RB_QX);
                    signal_count(&g_prog[s >> 2]);
                    if (s + 8 < NSEG) l2_prefetch(xg + (size_t)((s + 8) * 32 + head) * DM, 2048);
                }
                __syncwarp();
            } else {
                x_send(sb, s + 1, rank, tmX);
                if (s + 2 < NSEG - 1) { acc_clear((s + 2) & 3, 2 * head + (int)rank - 1); __threadfence(); }
            }
        }
        if (Q && head == 0 && warp == 0) {
            if (elect_one()) {
                uint32_t tl; asm volatile("ld.relaxed.gpu.global.u32 %0, [%1];" : "=r"(tl) : "l"(&g_tlast) : "memory");
                const uint32_t st = sb + RS_INV + 32;
                uint32_t pr = s == 0 ? tl : lds32(st);
                int per = s == 0 ? period : (int)lds32(st + 4);
                const bool clean = s > 0 && lds32(st + 8);
                const int err = (int)(tl - pr);
                const bool miss = err > tune.x || s == 0;
                if (clean) per += miss ? min(err, 256) >> 1 : (err + tune.y) >> tune.w;
                pr += per + (miss ? err + tune.z : 0);
                st_rlx(&g_pred, (pr & ~31u) | ((s + 1) & 31));
                sts32(st, pr); sts32(st + 4, (uint32_t)per); sts32(st + 8, !miss);
            }
            __syncwarp();
        }
    }
}

DEVI void load_weights(uint32_t sb, const CUtensorMap* tmW, const CUtensorMap* tmWo, int head, uint32_t rank) {
    const uint32_t bW = sb + RB_W, bSF = sb + RB_SF, bSE = sb + RB_SE;
    const int ntile = rank == 0 ? 6 : 5, tile0 = rank == 0 ? 0 : (rank == 1 ? 6 : 11);
    mbar_expect_tx(bW, R_NSS * 16384);
    mbar_expect_tx(sb + RB_WO, ntile * 16384);
    for (int pass = 0; pass < 2; pass++) {
        for (int pos = 0; pos < 16; pos++) {
            const int k = (int)((R_TORD_PACK >> (4 * pos)) & 15ull) * 64, rd = pos - pos / 3, slot = rd % 5;
            if (r_pos_ss(pos)) {
                if (pass) continue;
                const uint32_t dst = sb + RS_WSS + (pos / 3) * 16384;
                tma_load_2d(dst, tmW, head * DH, k, bW);
                tma_load_2d(dst + 8192, tmW, head * DH + 64, k, bW);
            } else if (pass == (rd >= 5)) {
                if (rd >= 5) mbar_wait(bSE + 8 * slot, ((rd / 5) - 1) & 1);
                mbar_expect_tx(bSF + 8 * slot, 16384);
                const uint32_t dst = sb + RS_WO + slot * 16384;
                tma_load_2d(dst, tmW, head * DH, k, bSF + 8 * slot);
                tma_load_2d(dst + 8192, tmW, head * DH + 64, k, bSF + 8 * slot);
            }
        }
    }
    if (rank == 0) tma_load_wo(sb + RS_WO5, tmWo, 5 * 64, head * 4, sb + RB_WO);
    for (int i = 1; i <= 5; i++) {
        const int slot = i % 5, last = slot + 10 < R_NRS ? slot + 10 : slot + 5;
        mbar_wait(bSE + 8 * slot, (last / 5) & 1);
        tma_load_wo(sb + RS_WO + slot * 16384, tmWo, (tile0 + slot) * 64, head * 4, sb + RB_WO);
    }
}
template <bool XP>
DEVI void big_prologue(uint32_t* w, uint32_t sb, int g, int warp, const bf16* __restrict__ mem0) {
    const int tid = tid_now(), lane = tid & 31;
    {
        const uint32_t* m = (const uint32_t*)(mem0 + (lane >> 2) * DM + (tid >> 5) * 16) + (lane & 3);
        uint32_t u[16];
#pragma unroll
        for (int j = 0; j < 8; j++) { u[2 * j] = m[j * 64]; u[2 * j + 1] = m[j * 64 + 4]; }
#pragma unroll
        for (int j = 0; j < 8; j++) sts64(sb + RS_MEM + ((tid >> 5) + j * 8) * 256 + b_frag_off(lane), u[2 * j], u[2 * j + 1]);
    }
    const uint32_t a0 = sb + RS_WO + g * (8192 + 4096) + a_frag_off(lane, warp), a1 = a0 + 8192 - g * 16384;
#pragma unroll
    for (int rd = 0; rd < R_NRS; rd++) {
        const int slot = rd % 5;
        mbar_wait(sb + RB_SF + 8 * slot, (rd / 5) & 1);
#pragma unroll
        for (int q = 0; q < 4; q++) {
            if (XP && rd == 0 && q == 3) {
                sts128(sb + RS_WX + g * 2048 + (tid & 127) * 16, lds128(sb + RS_WO + 8192 - g * 4096 + 2048 + (tid & 127) * 16));
                fence_proxy_async();
                nbar_sync(NB_WG + g, 128);
            } else ldsm4t(&w[rd * 16 + q * 4], ((q & 1) ? a1 : a0) + slot * 16384 + (q >> 1) * 2048);
        }
        mbar_arrive(sb + RB_SE + 8 * slot);
    }
    mbar_wait(sb + RB_W, 0);
}

__global__ void __cluster_dims__(3, 1, 1) __launch_bounds__(384, 1)
k_rec(const __grid_constant__ CUtensorMap tmWq, const __grid_constant__ CUtensorMap tmWk, const __grid_constant__ CUtensorMap tmWv,
      const __grid_constant__ CUtensorMap tmWo, const __grid_constant__ CUtensorMap tmX, const bf16* __restrict__ mem0, const bf16* __restrict__ xg,
      int hq0, int hqw, int hq2, int hk0, int hkw, int hk2, int period, int4 tune) {
    extern __shared__ __align__(1024) uint8_t smem_raw[];
    const uint32_t sb = smem_u32(smem_raw);
    if ((sb & 0x3FFFFu) != SB0) __trap();
    const int tid = threadIdx.x;
    const int wg = __shfl_sync(0xffffffffu, tid >> 7, 0), warp = __shfl_sync(0xffffffffu, (tid >> 5) & 3, 0);
    uint32_t rank; asm("mov.u32 %0, %%cluster_ctarank;" : "=r"(rank));
    const int head = blockIdx.x / 3;
    asm volatile("griddepcontrol.launch_dependents;");
    if (tid == 0) {
        mbar_init(sb + RB_G, 2);
        mbar_init(sb + RB_G + 8, 2);
        mbar_init(sb + RB_T, 1); mbar_init(sb + RB_WO, 1);
        mbar_init(sb + RB_K, 1); mbar_init(sb + RB_V, 1); mbar_init(sb + RB_KV, 1); mbar_init(sb + RB_QX, 1);
        mbar_init(sb + RB_O, rank == 0 ? 4 : 1); mbar_init(sb + RB_ATT, 1); mbar_init(sb + RB_W, 1);
        for (int i = 0; i < 5; i++) { mbar_init(sb + RB_SF + 8 * i, 1); mbar_init(sb + RB_SE + 8 * i, 256); }
        for (int i = 0; i < 2 * X_SLOTS; i++) mbar_init(sb + RB_XF + 8 * i, 1);
        fence_mbar_init();
        if (rank == 0) { mbar_expect_tx(sb + RB_KV, 16384); mbar_expect_tx(sb + RB_K, 2048); mbar_expect_tx(sb + RB_V, 2048); }
    }
    __syncthreads();
    cluster_sync();

    if (wg < 2) {
        reg_inc<REG_KB>();
        if (rank != 0) {
            uint32_t w[R_NRS * 16];
            if ((tid & 127) == 0) for (int j = 0; j < X_SLOTS; j++) x_load(sb, 0, j, wg, &tmX);
            __syncwarp();
            big_prologue<true>(w, sb, wg, warp, mem0);
            big_main<true>(w, sb, wg, warp, rank, head, &tmX, xg, 0u);
        } else {
            uint32_t w[R_NRS * 16];
            big_prologue<false>(w, sb, wg, warp, mem0);
            big_main<false>(w, sb, wg, warp, rank, head, &tmX, xg, *(volatile unsigned*)&g_epoch + 1);
        }
    } else {
        reg_dec<504 - 2 * REG_KB>();
        const unsigned E = __shfl_sync(0xffffffffu, *(volatile unsigned*)&g_epoch + 1, 0);
        if (warp == 3 && rank != 0) {
            acc_clear(0, 2 * head + (int)rank - 1); acc_clear(1, 2 * head + (int)rank - 1);
            __threadfence();
            __syncwarp();
            if (tid == 256 + 96) atomicAdd(&g_zero, 1u);
        }
        if (tid == 256) {
            if (rank == 0) l2_prefetch(xg + (size_t)head * 8 * DM, 16384);
            load_weights(sb, rank == 0 ? &tmWq : (rank == 1 ? &tmWk : &tmWv), &tmWo, head, rank);
            wait_count(&g_zero, E * 64u);
        }
        __syncwarp();
        if (warp == 3 && rank != 0) x_send(sb, 0, rank, &tmX);
        mbar_wait(sb + RB_WO, 0);
        wo_permute(sb + RS_WO + (tid & 127) * 32, 20);
        if (rank == 0) wo_permute(sb + RS_WO5 + (tid & 127) * 32, 4);
        fence_proxy_async();
        nbar_sync(NB_AUX, 128);
        if (rank == 0) aux_main<true>(sb, warp, rank, head, &tmX, xg, E, hq0 + (warp & 1) * hqw + (warp >> 1) * hq2, period, tune);
        else           aux_main<false>(sb, warp, rank, head, &tmX, xg, E, hk0 + (warp == 1) * hkw + (warp >> 1) * hk2, period, tune);
    }
    __syncthreads();
    cluster_sync();
}

typedef CUresult (*EncodeFn)(CUtensorMap*, CUtensorMapDataType, cuuint32_t, void*, const cuuint64_t*, const cuuint64_t*,
                             const cuuint32_t*, const cuuint32_t*, CUtensorMapInterleave, CUtensorMapSwizzle,
                             CUtensorMapL2promotion, CUtensorMapFloatOOBfill);

static CUtensorMap make_map(EncodeFn fn, const void* ptr, uint64_t inner, uint64_t outer, uint32_t box_inner, uint32_t box_outer) {
    CUtensorMap m;
    cuuint64_t dims[2] = {inner, outer};
    cuuint64_t strides[1] = {inner * 2};
    cuuint32_t box[2] = {box_inner, box_outer};
    cuuint32_t es[2] = {1, 1};
    fn(&m, CU_TENSOR_MAP_DATA_TYPE_BFLOAT16, 2, const_cast<void*>(ptr), dims, strides, box, es,
       CU_TENSOR_MAP_INTERLEAVE_NONE, CU_TENSOR_MAP_SWIZZLE_128B, CU_TENSOR_MAP_L2_PROMOTION_L2_256B, CU_TENSOR_MAP_FLOAT_OOB_FILL_NONE);
    return m;
}

static CUtensorMap make_wo_map(EncodeFn fn, const void* ptr, uint32_t ngrp) {
    CUtensorMap m;
    cuuint64_t dims[5] = {DM, 2, 4, 4, HD / 32};
    cuuint64_t strides[4] = {DM * 2, 8 * DM * 2, 2 * DM * 2, 32 * DM * 2};
    cuuint32_t box[5] = {64, 2, 4, 4, ngrp};
    cuuint32_t es[5] = {1, 1, 1, 1, 1};
    fn(&m, CU_TENSOR_MAP_DATA_TYPE_BFLOAT16, 5, const_cast<void*>(ptr), dims, strides, box, es,
       CU_TENSOR_MAP_INTERLEAVE_NONE, CU_TENSOR_MAP_SWIZZLE_128B, CU_TENSOR_MAP_L2_PROMOTION_L2_256B, CU_TENSOR_MAP_FLOAT_OOB_FILL_NONE);
    return m;
}

struct Maps {
    PMaps post;
    CUtensorMap wq16, wk16, wv16, wo128, x32;
};

extern "C" void kernel_launch(void* const* d_in, const int* in_sizes, int n_in, void* d_out, int out_size) {
    const bf16* A_x   = (const bf16*)d_in[0];
    const bf16* A_mem = (const bf16*)d_in[1];
    const bf16* A_Wq  = (const bf16*)d_in[2];
    const bf16* A_Wk  = (const bf16*)d_in[3];
    const bf16* A_Wv  = (const bf16*)d_in[4];
    const bf16* A_Wo  = (const bf16*)d_in[5];
    const bf16* B_x   = (const bf16*)d_in[7];
    const bf16* B_w   = (const bf16*)d_in[8];
    const bf16* B_wo  = (const bf16*)d_in[9];

    static EncodeFn fn = nullptr;
    static Maps mp;
    static const void* cached[10];
    const void* cur[10] = {A_x, A_mem, A_Wq, A_Wk, A_Wv, A_Wo, B_x, B_w, B_wo, d_out};
    bool same = fn != nullptr;
    for (int i = 0; i < 10 && same; i++) same = cached[i] == cur[i];
    if (!same) {
        if (!fn) {
            void* p = nullptr; cudaDriverEntryPointQueryResult qr;
            cudaGetDriverEntryPoint("cuTensorMapEncodeTiled", &p, cudaEnableDefault, &qr);
            fn = (EncodeFn)p;
            cudaFuncSetAttribute(k_post, cudaFuncAttributeMaxDynamicSharedMemorySize, P_SMEM);
            cudaFuncSetAttribute(k_rec, cudaFuncAttributeMaxDynamicSharedMemorySize, R_SMEM);
        }
        void *p_ox, *p_bqkv, *p_bo, *p_qx;
        cudaGetSymbolAddress(&p_qx, g_qx);
        cudaGetSymbolAddress(&p_ox, g_ox); cudaGetSymbolAddress(&p_bqkv, g_bqkv); cudaGetSymbolAddress(&p_bo, g_bo);
        mp.post.wq   = make_map(fn, A_Wq, HD, DM, 64, 64);
        mp.post.wo   = make_wo_map(fn, A_Wo, 2);
        mp.post.bw   = make_map(fn, B_w, 3 * DM, DM, 64, 64);
        mp.post.bwo  = make_map(fn, B_wo, DM, DM, 64, 64);
        mp.post.x    = make_map(fn, A_x, DM, S_TOK, 64, 128);
        mp.post.bx   = make_map(fn, B_x, DM, S_TOK, 64, 128);
        mp.post.bo   = make_map(fn, p_bo, DM, S_TOK, 64, 128);
        mp.post.ox   = make_map(fn, p_ox, HD, S_TOK, 64, 128);
        mp.post.cb   = make_map(fn, p_bqkv, 3 * DM, S_TOK, 64, 64);
        mp.post.cout = make_map(fn, d_out, 2 * DM, S_TOK, 64, 64);
        {
            cuuint64_t dims[4] = {256, 4, NH * 4, NSEG};
            cuuint64_t strides[3] = {512, 2048, NH * 8192};
            cuuint32_t box[4] = {256, 2, 4, 2};
            cuuint32_t es[4] = {1, 1, 1, 1};
            fn(&mp.post.cq, CU_TENSOR_MAP_DATA_TYPE_BFLOAT16, 4, p_qx, dims, strides, box, es,
               CU_TENSOR_MAP_INTERLEAVE_NONE, CU_TENSOR_MAP_SWIZZLE_NONE, CU_TENSOR_MAP_L2_PROMOTION_NONE, CU_TENSOR_MAP_FLOAT_OOB_FILL_NONE);
        }
        {
            int runs[48] = {K_QH, 0, 2, K_Q, 1, 7, K_B1, 0, 8, K_A4, 0, 4, K_B2, 0, 32, K_A4, 4, 2, K_B3, 0, 4, K_A3, 12, 2, K_B3, 4, 4, K_SK, 14, 2, -1};
            const int per[8] = {32, 24, 8, 8, 32, 8, 32, 1};
            int n = 0, id = 0;
            for (; runs[3 * n] >= 0; n++) {
                mp.post.list.run[n] = make_int4(runs[3 * n], runs[3 * n + 1], id, id + runs[3 * n + 2] * per[runs[3 * n]]);
                id = mp.post.list.run[n].w;
            }
            mp.post.list.n = n;
        }
        {
            cuuint64_t dims[4] = {DM, 3, 2, S_TOK / 2};
            cuuint64_t strides[3] = {DM * 2, 3 * DM * 2, 3 * DM * 4};
            cuuint32_t box[4] = {64, 3, 1, 40};
            cuuint32_t es[4] = {1, 1, 1, 1};
            fn(&mp.post.b40, CU_TENSOR_MAP_DATA_TYPE_BFLOAT16, 4, p_bqkv, dims, strides, box, es,
               CU_TENSOR_MAP_INTERLEAVE_NONE, CU_TENSOR_MAP_SWIZZLE_128B, CU_TENSOR_MAP_L2_PROMOTION_L2_256B, CU_TENSOR_MAP_FLOAT_OOB_FILL_NONE);
        }
        mp.wq16 = make_map(fn, A_Wq, HD, DM, 64, 64);
        mp.wk16 = make_map(fn, A_Wk, HD, DM, 64, 64);
        mp.wv16 = make_map(fn, A_Wv, HD, DM, 64, 64);
        mp.wo128 = make_wo_map(fn, A_Wo, 4);
        {
            cuuint64_t dims[3] = {64, S_TOK, DM / 64};
            cuuint64_t strides[2] = {DM * 2, 128};
            cuuint32_t box[3] = {32, 32, 2};
            cuuint32_t es[3] = {1, 1, 1};
            fn(&mp.x32, CU_TENSOR_MAP_DATA_TYPE_BFLOAT16, 3, const_cast<bf16*>(A_x), dims, strides, box, es,
               CU_TENSOR_MAP_INTERLEAVE_NONE, CU_TENSOR_MAP_SWIZZLE_64B, CU_TENSOR_MAP_L2_PROMOTION_L2_128B, CU_TENSOR_MAP_FLOAT_OOB_FILL_NONE);
        }
        for (int i = 0; i < 10; i++) cached[i] = cur[i];
    }

    cudaStream_t st = cudaStreamPerThread;
    int hq0 = -64, hqw = 0, hq2 = 224, hk0 = -64, hkw = 0, hk2 = 224, period = 3200;
    int4 tune = make_int4(32, 64, 200, 2);
    k_rec<<<96, 384, R_SMEM, st>>>(mp.wq16, mp.wk16, mp.wv16, mp.wo128, mp.x32, A_mem, A_x, hq0, hqw, hq2, hk0, hkw, hk2, period, tune);
    cudaLaunchConfig_t cfg = {};
    cfg.gridDim = dim3(132); cfg.blockDim = dim3(384); cfg.dynamicSmemBytes = P_SMEM; cfg.stream = st;
    cudaLaunchAttribute at[1];
    at[0].id = cudaLaunchAttributeProgrammaticStreamSerialization;
    at[0].val.programmaticStreamSerializationAllowed = 1;
    cfg.attrs = at; cfg.numAttrs = 1;
    cudaLaunchKernelEx(&cfg, k_post, mp.post);
}
```

```cpp
#include <cuda_runtime.h>
#include <cuda_bf16.h>
#include <cuda.h>
#include <stdint.h>

typedef __nv_bfloat16 bf16;

constexpr int S_TOK = 2048;
constexpr int DM    = 1024;
constexpr int NH    = 32;
constexpr int DH    = 128;
constexpr int NSEG  = 64;
constexpr int HD    = NH * DH;

__device__ __align__(1024) bf16 g_qx[NSEG * NH * 4 * DH * 8];
__device__ __align__(1024) bf16 g_ox[S_TOK * HD];
__device__ __align__(1024) bf16 g_bqkv[S_TOK * 3 * DM];
__device__ __align__(1024) bf16 g_bo[S_TOK * DM];
__device__ __align__(1024) uint8_t g_acc[192 * 1024];

#define EV(cond, s, k) do {} while (0)
#define EVCAL(s) do {} while (0)

constexpr int P_NSK = 4;
__device__ unsigned g_epoch, g_qctr, g_done, g_zero;
enum { C_B1 = 0, C_B2 = 8, C_Q = 16, C_QH = 24, C_NONE = 31 };
__device__ unsigned g_cnt[32], g_prog[16], g_cnt_sk[P_NSK * 16];
__device__ __align__(1024) float g_skp[P_NSK * 8 * 4 * 2 * 128 * 64];
#define TLOG(i, k, v) do {} while (0)

#define DEVI __device__ __forceinline__

DEVI uint32_t opaque(uint32_t v) { uint32_t r; asm volatile("mov.u32 %0, %1;" : "=r"(r) : "r"(v)); return r; }
DEVI uint32_t smem_u32(const void* p) { return (uint32_t)__cvta_generic_to_shared(p); }

#define TRAP(code) __trap()
constexpr int SPIN_LIMIT = 1 << 22;
#define MBAR_HINT_NS 20000u
constexpr int SPIN_LIMIT_MBAR = 1 << 17;

DEVI void mbar_init(uint32_t bar, uint32_t cnt) { asm volatile("mbarrier.init.shared::cta.b64 [%0], %1;" :: "r"(bar), "r"(cnt)); }
DEVI void mbar_expect_tx(uint32_t bar, uint32_t bytes) {
    asm volatile("mbarrier.arrive.expect_tx.shared::cta.b64 _, [%0], %1;" :: "r"(bar), "r"(bytes) : "memory");
}
DEVI void mbar_arrive(uint32_t bar) { asm volatile("mbarrier.arrive.shared::cta.b64 _, [%0];" :: "r"(bar) : "memory"); }
DEVI bool mbar_try(uint32_t bar, uint32_t parity) {
    uint32_t ok;
    asm volatile("{.reg .pred p; mbarrier.try_wait.parity.shared::cta.b64 p, [%1], %2; selp.u32 %0, 1, 0, p;}"
                 : "=r"(ok) : "r"(bar), "r"(parity) : "memory");
    return ok;
}
DEVI bool mbar_try_cluster(uint32_t bar, uint32_t parity) {
    uint32_t ok;
    asm volatile("{.reg .pred p; mbarrier.try_wait.parity.acquire.cluster.shared::cta.b64 p, [%1], %2; selp.u32 %0, 1, 0, p;}"
                 : "=r"(ok) : "r"(bar), "r"(parity) : "memory");
    return ok;
}
DEVI bool mbar_try_hint(uint32_t bar, uint32_t parity) {
    uint32_t ok;
    asm volatile("{.reg .pred p; mbarrier.try_wait.parity.shared::cta.b64 p, [%1], %2, %3; selp.u32 %0, 1, 0, p;}"
                 : "=r"(ok) : "r"(bar), "r"(parity), "r"(MBAR_HINT_NS) : "memory");
    return ok;
}
DEVI void mbar_wait(uint32_t bar, uint32_t parity) {
    int n = 0;
    while (!mbar_try(bar, parity)) { if (++n > SPIN_LIMIT) TRAP(bar | (parity << 31)); }
}
DEVI void mbar_wait_sleepy(uint32_t bar, uint32_t parity) {
    int n = 0;
    while (!mbar_try_hint(bar, parity)) { if (++n > SPIN_LIMIT_MBAR) __trap(); }
}
DEVI void mbar_wait_cluster(uint32_t bar, uint32_t parity) {
    int n = 0;
    while (!mbar_try_cluster(bar, parity)) { if (++n > SPIN_LIMIT) __trap(); }
}
DEVI void mbar_spin(uint32_t bar, uint32_t parity) {
    uint32_t ok; int n = 0;
    do {
        asm volatile("{.reg .pred p; mbarrier.test_wait.parity.shared::cta.b64 p, [%1], %2; selp.u32 %0, 1, 0, p;}"
                     : "=r"(ok) : "r"(bar), "r"(parity) : "memory");
        if (++n > SPIN_LIMIT) __trap();
    } while (!ok);
}
DEVI void fence_mbar_init() { asm volatile("fence.mbarrier_init.release.cluster;" ::: "memory"); }
DEVI void fence_proxy_async() { asm volatile("fence.proxy.async.shared::cta;" ::: "memory"); }
DEVI void cluster_sync() {
    asm volatile("barrier.cluster.arrive.release.aligned;\n barrier.cluster.wait.acquire.aligned;" ::: "memory");
}
DEVI void nbar_sync(int id, int n) { asm volatile("bar.sync %0, %1;" :: "r"(id), "r"(n) : "memory"); }
DEVI void nbar_arrive(int id, int n) { asm volatile("bar.arrive %0, %1;" :: "r"(id), "r"(n) : "memory"); }

DEVI void tma_load_2d(uint32_t dst, const CUtensorMap* map, int x, int y, uint32_t bar) {
    asm volatile("cp.async.bulk.tensor.2d.shared::cluster.global.mbarrier::complete_tx::bytes [%0], [%1, {%3, %4}], [%2];"
                 :: "r"(dst), "l"(map), "r"(bar), "r"(x), "r"(y) : "memory");
}
DEVI void tma_load_3d(uint32_t dst, const CUtensorMap* map, int x, int y, int z, uint32_t bar) {
    asm volatile("cp.async.bulk.tensor.3d.shared::cluster.global.mbarrier::complete_tx::bytes [%0], [%1, {%3, %4, %5}], [%2];"
                 :: "r"(dst), "l"(map), "r"(bar), "r"(x), "r"(y), "r"(z) : "memory");
}
DEVI void tma_load_wo(uint32_t dst, const CUtensorMap* map, int col, int k32, uint32_t bar) {
    asm volatile("cp.async.bulk.tensor.5d.shared::cluster.global.mbarrier::complete_tx::bytes [%0], [%1, {%3, %5, %5, %5, %4}], [%2];"
                 :: "r"(dst), "l"(map), "r"(bar), "r"(col), "r"(k32), "r"(0) : "memory");
}
DEVI void tma_store_2d(const CUtensorMap* map, uint32_t src, int x, int y) {
    asm volatile("cp.async.bulk.tensor.2d.global.shared::cta.bulk_group [%0, {%2, %3}], [%1];"
                 :: "l"(map), "r"(src), "r"(x), "r"(y) : "memory");
}
DEVI void bulk_load(uint32_t dst, const void* src, uint32_t bytes, uint32_t bar) {
    asm volatile("cp.async.bulk.shared::cluster.global.mbarrier::complete_tx::bytes [%0], [%1], %2, [%3];"
                 :: "r"(dst), "l"(src), "r"(bytes), "r"(bar) : "memory");
}
DEVI void tma_load_2d_mc(uint32_t dst, const CUtensorMap* map, int x, int y, uint32_t bar, uint16_t mask) {
    asm volatile("cp.async.bulk.tensor.2d.shared::cluster.global.mbarrier::complete_tx::bytes.multicast::cluster [%0], [%1, {%3, %4}], [%2], %5;"
                 :: "r"(dst), "l"(map), "r"(bar), "r"(x), "r"(y), "h"(mask) : "memory");
}
DEVI void bulk_copy_s2c(uint32_t dst_cluster, uint32_t src, uint32_t bytes, uint32_t bar_cluster) {
    asm volatile("cp.async.bulk.shared::cluster.shared::cta.mbarrier::complete_tx::bytes [%0], [%1], %2, [%3];"
                 :: "r"(dst_cluster), "r"(src), "r"(bytes), "r"(bar_cluster) : "memory");
}
DEVI void bulk_store(void* dst, uint32_t src, uint32_t bytes) {
    asm volatile("cp.async.bulk.global.shared::cta.bulk_group [%0], [%1], %2;" :: "l"(dst), "r"(src), "r"(bytes) : "memory");
}
DEVI void bulk_wait_read() { asm volatile("cp.async.bulk.wait_group.read 0;" ::: "memory"); }
DEVI void mbar_arrive_remote(uint32_t bar_cluster) {
    asm volatile("mbarrier.arrive.shared::cluster.b64 _, [%0];" :: "r"(bar_cluster) : "memory");
}
DEVI void mbar_expect_tx_remote(uint32_t bar_cluster, uint32_t bytes) {
    asm volatile("mbarrier.arrive.expect_tx.shared::cluster.b64 _, [%0], %1;" :: "r"(bar_cluster), "r"(bytes) : "memory");
}
DEVI void l2_prefetch(const void* p, uint32_t bytes) {
    asm volatile("cp.async.bulk.prefetch.L2.global [%0], %1;" :: "l"(p), "r"(bytes) : "memory");
}
DEVI void bulk_commit() { asm volatile("cp.async.bulk.commit_group;" ::: "memory"); }
DEVI void bulk_wait_all() { asm volatile("cp.async.bulk.wait_group 0;" ::: "memory"); }

DEVI void wg_fence() { asm volatile("wgmma.fence.sync.aligned;" ::: "memory"); }
DEVI void wg_commit() { asm volatile("wgmma.commit_group.sync.aligned;" ::: "memory"); }
template <int N> DEVI void wg_wait() { asm volatile("wgmma.wait_group.sync.aligned %0;" :: "n"(N) : "memory"); }

template <int R> DEVI void reg_dec() { asm volatile("setmaxnreg.dec.sync.aligned.u32 %0;" :: "n"(R)); }
template <int R> DEVI void reg_inc() { asm volatile("setmaxnreg.inc.sync.aligned.u32 %0;" :: "n"(R)); }

DEVI uint64_t mk_desc(uint32_t addr, uint32_t lbo, uint32_t sbo, uint32_t sw) {
    return (uint64_t)((addr & 0x3FFFF) >> 4) | ((uint64_t)(lbo >> 4) << 16) | ((uint64_t)(sbo >> 4) << 32) | ((uint64_t)sw << 62);
}

DEVI uint32_t desc_lo(uint32_t addr, uint32_t lbo) { return ((addr & 0x3FFFF) >> 4) | ((lbo >> 4) << 16); }
constexpr uint32_t DHI_SW128 = (1024u >> 4) | (1u << 30);
constexpr uint32_t DHI_SW64  = (512u >> 4) | (2u << 30);
constexpr uint32_t DHI_NONE  = (128u >> 4);

template <int TB, int SCALE_D>
DEVI void wgmma_n8_ss(float* d, uint32_t alo, uint32_t blo) {
    asm volatile("{.reg .b64 da, db; mov.b64 da, {%4, %6}; mov.b64 db, {%5, %7};\n"
                 "wgmma.mma_async.sync.aligned.m64n8k16.f32.bf16.bf16 {%0,%1,%2,%3}, da, db, %8, 1, 1, 1, %9;}"
                 : "+f"(d[0]), "+f"(d[1]), "+f"(d[2]), "+f"(d[3])
                 : "r"(alo), "r"(blo), "n"(DHI_SW128), "n"(DHI_NONE), "n"(SCALE_D), "n"(TB));
}

template <int TB>
DEVI void wgmma_n8_ss_first(float* d, uint32_t alo, uint32_t blo) {
    asm volatile("{.reg .b64 da, db; mov.b64 da, {%4, %6}; mov.b64 db, {%5, %7};\n"
                 "wgmma.mma_async.sync.aligned.m64n8k16.f32.bf16.bf16 {%0,%1,%2,%3}, da, db, 0, 1, 1, 1, %8;}"
                 : "=f"(d[0]), "=f"(d[1]), "=f"(d[2]), "=f"(d[3])
                 : "r"(alo), "r"(blo), "n"(DHI_SW128), "n"(DHI_NONE), "n"(TB));
}
DEVI void wgmma_n32_rs_first(float* d, const uint32_t* a, uint32_t blo) {
    asm volatile("{.reg .b64 db; mov.b64 db, {%20, %21};\n"
                 "wgmma.mma_async.sync.aligned.m64n32k16.f32.bf16.bf16 {%0,%1,%2,%3,%4,%5,%6,%7,%8,%9,%10,%11,%12,%13,%14,%15}, "
                 "{%16,%17,%18,%19}, db, 0, 1, 1, 0;}"
                 : "=f"(d[0]), "=f"(d[1]), "=f"(d[2]), "=f"(d[3]), "=f"(d[4]), "=f"(d[5]), "=f"(d[6]), "=f"(d[7]),
                   "=f"(d[8]), "=f"(d[9]), "=f"(d[10]), "=f"(d[11]), "=f"(d[12]), "=f"(d[13]), "=f"(d[14]), "=f"(d[15])
                 : "r"(a[0]), "r"(a[1]), "r"(a[2]), "r"(a[3]), "r"(blo), "n"(DHI_SW64));
}
template <int N> DEVI void reg_fence(float* d) {
#pragma unroll
    for (int i = 0; i < N; i++) asm volatile("" : "+f"(d[i]) :: "memory");
}
DEVI void wgmma_n32_rs(float* d, const uint32_t* a, uint32_t blo) {
    asm volatile("{.reg .b64 db; mov.b64 db, {%20, %21};\n"
                 "wgmma.mma_async.sync.aligned.m64n32k16.f32.bf16.bf16 {%0,%1,%2,%3,%4,%5,%6,%7,%8,%9,%10,%11,%12,%13,%14,%15}, "
                 "{%16,%17,%18,%19}, db, 1, 1, 1, 0;}"
                 : "+f"(d[0]), "+f"(d[1]), "+f"(d[2]), "+f"(d[3]), "+f"(d[4]), "+f"(d[5]), "+f"(d[6]), "+f"(d[7]),
                   "+f"(d[8]), "+f"(d[9]), "+f"(d[10]), "+f"(d[11]), "+f"(d[12]), "+f"(d[13]), "+f"(d[14]), "+f"(d[15])
                 : "r"(a[0]), "r"(a[1]), "r"(a[2]), "r"(a[3]), "r"(blo), "n"(DHI_SW64));
}
DEVI void wgmma_n32_ss(float* d, uint32_t alo, uint32_t blo) {
    asm volatile("{.reg .b64 da, db; mov.b64 da, {%16, %18}; mov.b64 db, {%17, %19};\n"
                 "wgmma.mma_async.sync.aligned.m64n32k16.f32.bf16.bf16 {%0,%1,%2,%3,%4,%5,%6,%7,%8,%9,%10,%11,%12,%13,%14,%15}, "
                 "da, db, 1, 1, 1, 1, 0;}"
                 : "+f"(d[0]), "+f"(d[1]), "+f"(d[2]), "+f"(d[3]), "+f"(d[4]), "+f"(d[5]), "+f"(d[6]), "+f"(d[7]),
                   "+f"(d[8]), "+f"(d[9]), "+f"(d[10]), "+f"(d[11]), "+f"(d[12]), "+f"(d[13]), "+f"(d[14]), "+f"(d[15])
                 : "r"(alo), "r"(blo), "n"(DHI_SW128), "n"(DHI_SW64));
}

template <bool FIRST>
DEVI void wgmma_n256_ss(float* d, uint64_t a, uint64_t b) {
    if (FIRST)
        asm volatile("wgmma.mma_async.sync.aligned.m64n256k16.f32.bf16.bf16 {%0,%1,%2,%3,%4,%5,%6,%7,%8,%9,%10,%11,%12,%13,%14,%15,%16,%17,%18,%19,%20,%21,%22,%23,%24,%25,%26,%27,%28,%29,%30,%31,%32,%33,%34,%35,%36,%37,%38,%39,%40,%41,%42,%43,%44,%45,%46,%47,%48,%49,%50,%51,%52,%53,%54,%55,%56,%57,%58,%59,%60,%61,%62,%63,%64,%65,%66,%67,%68,%69,%70,%71,%72,%73,%74,%75,%76,%77,%78,%79,%80,%81,%82,%83,%84,%85,%86,%87,%88,%89,%90,%91,%92,%93,%94,%95,%96,%97,%98,%99,%100,%101,%102,%103,%104,%105,%106,%107,%108,%109,%110,%111,%112,%113,%114,%115,%116,%117,%118,%119,%120,%121,%122,%123,%124,%125,%126,%127}, %128, %129, 0, 1, 1, 1, 0;"
            : "=f"(d[0]), "=f"(d[1]), "=f"(d[2]), "=f"(d[3]), "=f"(d[4]), "=f"(d[5]), "=f"(d[6]), "=f"(d[7]), "=f"(d[8]), "=f"(d[9]), "=f"(d[10]), "=f"(d[11]), "=f"(d[12]), "=f"(d[13]), "=f"(d[14]), "=f"(d[15]), "=f"(d[16]), "=f"(d[17]), "=f"(d[18]), "=f"(d[19]), "=f"(d[20]), "=f"(d[21]), "=f"(d[22]), "=f"(d[23]), "=f"(d[24]), "=f"(d[25]), "=f"(d[26]), "=f"(d[27]), "=f"(d[28]), "=f"(d[29]), "=f"(d[30]), "=f"(d[31]), "=f"(d[32]), "=f"(d[33]), "=f"(d[34]), "=f"(d[35]), "=f"(d[36]), "=f"(d[37]), "=f"(d[38]), "=f"(d[39]), "=f"(d[40]), "=f"(d[41]), "=f"(d[42]), "=f"(d[43]), "=f"(d[44]), "=f"(d[45]), "=f"(d[46]), "=f"(d[47]), "=f"(d[48]), "=f"(d[49]), "=f"(d[50]), "=f"(d[51]), "=f"(d[52]), "=f"(d[53]), "=f"(d[54]), "=f"(d[55]), "=f"(d[56]), "=f"(d[57]), "=f"(d[58]), "=f"(d[59]), "=f"(d[60]), "=f"(d[61]), "=f"(d[62]), "=f"(d[63]), "=f"(d[64]), "=f"(d[65]), "=f"(d[66]), "=f"(d[67]), "=f"(d[68]), "=f"(d[69]), "=f"(d[70]), "=f"(d[71]), "=f"(d[72]), "=f"(d[73]), "=f"(d[74]), "=f"(d[75]), "=f"(d[76]), "=f"(d[77]), "=f"(d[78]), "=f"(d[79]), "=f"(d[80]), "=f"(d[81]), "=f"(d[82]), "=f"(d[83]), "=f"(d[84]), "=f"(d[85]), "=f"(d[86]), "=f"(d[87]), "=f"(d[88]), "=f"(d[89]), "=f"(d[90]), "=f"(d[91]), "=f"(d[92]), "=f"(d[93]), "=f"(d[94]), "=f"(d[95]), "=f"(d[96]), "=f"(d[97]), "=f"(d[98]), "=f"(d[99]), "=f"(d[100]), "=f"(d[101]), "=f"(d[102]), "=f"(d[103]), "=f"(d[104]), "=f"(d[105]), "=f"(d[106]), "=f"(d[107]), "=f"(d[108]), "=f"(d[109]), "=f"(d[110]), "=f"(d[111]), "=f"(d[112]), "=f"(d[113]), "=f"(d[114]), "=f"(d[115]), "=f"(d[116]), "=f"(d[117]), "=f"(d[118]), "=f"(d[119]), "=f"(d[120]), "=f"(d[121]), "=f"(d[122]), "=f"(d[123]), "=f"(d[124]), "=f"(d[125]), "=f"(d[126]), "=f"(d[127]) : "l"(a), "l"(b));
    else
        asm volatile("wgmma.mma_async.sync.aligned.m64n256k16.f32.bf16.bf16 {%0,%1,%2,%3,%4,%5,%6,%7,%8,%9,%10,%11,%12,%13,%14,%15,%16,%17,%18,%19,%20,%21,%22,%23,%24,%25,%26,%27,%28,%29,%30,%31,%32,%33,%34,%35,%36,%37,%38,%39,%40,%41,%42,%43,%44,%45,%46,%47,%48,%49,%50,%51,%52,%53,%54,%55,%56,%57,%58,%59,%60,%61,%62,%63,%64,%65,%66,%67,%68,%69,%70,%71,%72,%73,%74,%75,%76,%77,%78,%79,%80,%81,%82,%83,%84,%85,%86,%87,%88,%89,%90,%91,%92,%93,%94,%95,%96,%97,%98,%99,%100,%101,%102,%103,%104,%105,%106,%107,%108,%109,%110,%111,%112,%113,%114,%115,%116,%117,%118,%119,%120,%121,%122,%123,%124,%125,%126,%127}, %128, %129, 1, 1, 1, 1, 0;"
            : "+f"(d[0]), "+f"(d[1]), "+f"(d[2]), "+f"(d[3]), "+f"(d[4]), "+f"(d[5]), "+f"(d[6]), "+f"(d[7]), "+f"(d[8]), "+f"(d[9]), "+f"(d[10]), "+f"(d[11]), "+f"(d[12]), "+f"(d[13]), "+f"(d[14]), "+f"(d[15]), "+f"(d[16]), "+f"(d[17]), "+f"(d[18]), "+f"(d[19]), "+f"(d[20]), "+f"(d[21]), "+f"(d[22]), "+f"(d[23]), "+f"(d[24]), "+f"(d[25]), "+f"(d[26]), "+f"(d[27]), "+f"(d[28]), "+f"(d[29]), "+f"(d[30]), "+f"(d[31]), "+f"(d[32]), "+f"(d[33]), "+f"(d[34]), "+f"(d[35]), "+f"(d[36]), "+f"(d[37]), "+f"(d[38]), "+f"(d[39]), "+f"(d[40]), "+f"(d[41]), "+f"(d[42]), "+f"(d[43]), "+f"(d[44]), "+f"(d[45]), "+f"(d[46]), "+f"(d[47]), "+f"(d[48]), "+f"(d[49]), "+f"(d[50]), "+f"(d[51]), "+f"(d[52]), "+f"(d[53]), "+f"(d[54]), "+f"(d[55]), "+f"(d[56]), "+f"(d[57]), "+f"(d[58]), "+f"(d[59]), "+f"(d[60]), "+f"(d[61]), "+f"(d[62]), "+f"(d[63]), "+f"(d[64]), "+f"(d[65]), "+f"(d[66]), "+f"(d[67]), "+f"(d[68]), "+f"(d[69]), "+f"(d[70]), "+f"(d[71]), "+f"(d[72]), "+f"(d[73]), "+f"(d[74]), "+f"(d[75]), "+f"(d[76]), "+f"(d[77]), "+f"(d[78]), "+f"(d[79]), "+f"(d[80]), "+f"(d[81]), "+f"(d[82]), "+f"(d[83]), "+f"(d[84]), "+f"(d[85]), "+f"(d[86]), "+f"(d[87]), "+f"(d[88]), "+f"(d[89]), "+f"(d[90]), "+f"(d[91]), "+f"(d[92]), "+f"(d[93]), "+f"(d[94]), "+f"(d[95]), "+f"(d[96]), "+f"(d[97]), "+f"(d[98]), "+f"(d[99]), "+f"(d[100]), "+f"(d[101]), "+f"(d[102]), "+f"(d[103]), "+f"(d[104]), "+f"(d[105]), "+f"(d[106]), "+f"(d[107]), "+f"(d[108]), "+f"(d[109]), "+f"(d[110]), "+f"(d[111]), "+f"(d[112]), "+f"(d[113]), "+f"(d[114]), "+f"(d[115]), "+f"(d[116]), "+f"(d[117]), "+f"(d[118]), "+f"(d[119]), "+f"(d[120]), "+f"(d[121]), "+f"(d[122]), "+f"(d[123]), "+f"(d[124]), "+f"(d[125]), "+f"(d[126]), "+f"(d[127]) : "l"(a), "l"(b));
}
template <bool FIRST>
DEVI void wgmma_n128_ss(float* d, uint64_t a, uint64_t b) {
    if (FIRST)
        asm volatile("wgmma.mma_async.sync.aligned.m64n128k16.f32.bf16.bf16 {%0,%1,%2,%3,%4,%5,%6,%7,%8,%9,%10,%11,%12,%13,%14,%15,%16,%17,%18,%19,%20,%21,%22,%23,%24,%25,%26,%27,%28,%29,%30,%31,%32,%33,%34,%35,%36,%37,%38,%39,%40,%41,%42,%43,%44,%45,%46,%47,%48,%49,%50,%51,%52,%53,%54,%55,%56,%57,%58,%59,%60,%61,%62,%63}, %64, %65, 0, 1, 1, 1, 0;"
            : "=f"(d[0]), "=f"(d[1]), "=f"(d[2]), "=f"(d[3]), "=f"(d[4]), "=f"(d[5]), "=f"(d[6]), "=f"(d[7]), "=f"(d[8]), "=f"(d[9]), "=f"(d[10]), "=f"(d[11]), "=f"(d[12]), "=f"(d[13]), "=f"(d[14]), "=f"(d[15]), "=f"(d[16]), "=f"(d[17]), "=f"(d[18]), "=f"(d[19]), "=f"(d[20]), "=f"(d[21]), "=f"(d[22]), "=f"(d[23]), "=f"(d[24]), "=f"(d[25]), "=f"(d[26]), "=f"(d[27]), "=f"(d[28]), "=f"(d[29]), "=f"(d[30]), "=f"(d[31]), "=f"(d[32]), "=f"(d[33]), "=f"(d[34]), "=f"(d[35]), "=f"(d[36]), "=f"(d[37]), "=f"(d[38]), "=f"(d[39]), "=f"(d[40]), "=f"(d[41]), "=f"(d[42]), "=f"(d[43]), "=f"(d[44]), "=f"(d[45]), "=f"(d[46]), "=f"(d[47]), "=f"(d[48]), "=f"(d[49]), "=f"(d[50]), "=f"(d[51]), "=f"(d[52]), "=f"(d[53]), "=f"(d[54]), "=f"(d[55]), "=f"(d[56]), "=f"(d[57]), "=f"(d[58]), "=f"(d[59]), "=f"(d[60]), "=f"(d[61]), "=f"(d[62]), "=f"(d[63]) : "l"(a), "l"(b));
    else
        asm volatile("wgmma.mma_async.sync.aligned.m64n128k16.f32.bf16.bf16 {%0,%1,%2,%3,%4,%5,%6,%7,%8,%9,%10,%11,%12,%13,%14,%15,%16,%17,%18,%19,%20,%21,%22,%23,%24,%25,%26,%27,%28,%29,%30,%31,%32,%33,%34,%35,%36,%37,%38,%39,%40,%41,%42,%43,%44,%45,%46,%47,%48,%49,%50,%51,%52,%53,%54,%55,%56,%57,%58,%59,%60,%61,%62,%63}, %64, %65, 1, 1, 1, 1, 0;"
            : "+f"(d[0]), "+f"(d[1]), "+f"(d[2]), "+f"(d[3]), "+f"(d[4]), "+f"(d[5]), "+f"(d[6]), "+f"(d[7]), "+f"(d[8]), "+f"(d[9]), "+f"(d[10]), "+f"(d[11]), "+f"(d[12]), "+f"(d[13]), "+f"(d[14]), "+f"(d[15]), "+f"(d[16]), "+f"(d[17]), "+f"(d[18]), "+f"(d[19]), "+f"(d[20]), "+f"(d[21]), "+f"(d[22]), "+f"(d[23]), "+f"(d[24]), "+f"(d[25]), "+f"(d[26]), "+f"(d[27]), "+f"(d[28]), "+f"(d[29]), "+f"(d[30]), "+f"(d[31]), "+f"(d[32]), "+f"(d[33]), "+f"(d[34]), "+f"(d[35]), "+f"(d[36]), "+f"(d[37]), "+f"(d[38]), "+f"(d[39]), "+f"(d[40]), "+f"(d[41]), "+f"(d[42]), "+f"(d[43]), "+f"(d[44]), "+f"(d[45]), "+f"(d[46]), "+f"(d[47]), "+f"(d[48]), "+f"(d[49]), "+f"(d[50]), "+f"(d[51]), "+f"(d[52]), "+f"(d[53]), "+f"(d[54]), "+f"(d[55]), "+f"(d[56]), "+f"(d[57]), "+f"(d[58]), "+f"(d[59]), "+f"(d[60]), "+f"(d[61]), "+f"(d[62]), "+f"(d[63]) : "l"(a), "l"(b));
}

DEVI void mma16816(float* d, const uint32_t* a, uint32_t b0, uint32_t b1) {
    asm volatile("mma.sync.aligned.m16n8k16.row.col.f32.bf16.bf16.f32 {%0,%1,%2,%3}, {%4,%5,%6,%7}, {%8,%9}, {%0,%1,%2,%3};"
                 : "+f"(d[0]), "+f"(d[1]), "+f"(d[2]), "+f"(d[3])
                 : "r"(a[0]), "r"(a[1]), "r"(a[2]), "r"(a[3]), "r"(b0), "r"(b1));
}
DEVI void mma1688(float* d, uint32_t a0, uint32_t a1, uint32_t b0) {
    asm volatile("mma.sync.aligned.m16n8k8.row.col.f32.bf16.bf16.f32 {%0,%1,%2,%3}, {%4,%5}, {%6}, {%0,%1,%2,%3};"
                 : "+f"(d[0]), "+f"(d[1]), "+f"(d[2]), "+f"(d[3]) : "r"(a0), "r"(a1), "r"(b0));
}
DEVI void ldsm4(uint32_t* r, uint32_t addr) {
    asm volatile("ldmatrix.sync.aligned.m8n8.x4.shared.b16 {%0,%1,%2,%3}, [%4];"
                 : "=r"(r[0]), "=r"(r[1]), "=r"(r[2]), "=r"(r[3]) : "r"(addr) : "memory");
}
DEVI void ldsm4t(uint32_t* r, uint32_t addr) {
    asm volatile("ldmatrix.sync.aligned.m8n8.x4.trans.shared.b16 {%0,%1,%2,%3}, [%4];"
                 : "=r"(r[0]), "=r"(r[1]), "=r"(r[2]), "=r"(r[3]) : "r"(addr) : "memory");
}
DEVI void ldsm2(uint32_t* r, uint32_t addr) {
    asm volatile("ldmatrix.sync.aligned.m8n8.x2.shared.b16 {%0,%1}, [%2];" : "=r"(r[0]), "=r"(r[1]) : "r"(addr) : "memory");
}
DEVI void ldsm1t(uint32_t& r, uint32_t addr) {
    asm volatile("ldmatrix.sync.aligned.m8n8.x1.trans.shared.b16 {%0}, [%1];" : "=r"(r) : "r"(addr) : "memory");
}
DEVI void stsm4(uint32_t addr, uint32_t r0, uint32_t r1, uint32_t r2, uint32_t r3) {
    asm volatile("stmatrix.sync.aligned.m8n8.x4.shared.b16 [%0], {%1,%2,%3,%4};" :: "r"(addr), "r"(r0), "r"(r1), "r"(r2), "r"(r3) : "memory");
}
DEVI void stsm4t(uint32_t addr, uint32_t r0, uint32_t r1, uint32_t r2, uint32_t r3) {
    asm volatile("stmatrix.sync.aligned.m8n8.x4.trans.shared.b16 [%0], {%1,%2,%3,%4};" :: "r"(addr), "r"(r0), "r"(r1), "r"(r2), "r"(r3) : "memory");
}
DEVI uint32_t movm_t(uint32_t a) {
    uint32_t d; asm volatile("movmatrix.sync.aligned.m8n8.trans.b16 %0, %1;" : "=r"(d) : "r"(a)); return d;
}
DEVI uint32_t pack_bf16(float lo, float hi) {
    uint32_t r; asm("cvt.rn.bf16x2.f32 %0, %1, %2;" : "=r"(r) : "f"(hi), "f"(lo)); return r;
}
DEVI float ex2(float x) { float y; asm("ex2.approx.ftz.f32 %0, %1;" : "=f"(y) : "f"(x)); return y; }

DEVI uint4 ld_rlx4(const void* p) {
    uint4 v;
    asm volatile("ld.relaxed.gpu.global.v4.u32 {%0,%1,%2,%3}, [%4];" : "=r"(v.x), "=r"(v.y), "=r"(v.z), "=r"(v.w) : "l"(p) : "memory");
    return v;
}
DEVI void ld_rlx4f(float* d, const void* p) {
    asm volatile("ld.relaxed.gpu.global.v4.f32 {%0,%1,%2,%3}, [%4];" : "=f"(d[0]), "=f"(d[1]), "=f"(d[2]), "=f"(d[3]) : "l"(p) : "memory");
}
DEVI bool all_nzf(const float* d) { return __float_as_uint(d[0]) && __float_as_uint(d[1]) && __float_as_uint(d[2]) && __float_as_uint(d[3]); }
DEVI void sts128f(uint32_t addr, const float* d) {
    asm volatile("st.shared.v4.f32 [%0], {%1,%2,%3,%4};" :: "r"(addr), "f"(d[0]), "f"(d[1]), "f"(d[2]), "f"(d[3]) : "memory");
}
DEVI void st_rlx4(void* p, uint32_t a, uint32_t b, uint32_t c, uint32_t d) {
    asm volatile("st.relaxed.gpu.global.v4.u32 [%0], {%1,%2,%3,%4};" :: "l"(p), "r"(a), "r"(b), "r"(c), "r"(d) : "memory");
}
DEVI void st_rlx(void* p, uint32_t v) { asm volatile("st.relaxed.gpu.global.u32 [%0], %1;" :: "l"(p), "r"(v) : "memory"); }
DEVI void sts128(uint32_t addr, uint4 v) {
    asm volatile("st.shared.v4.u32 [%0], {%1,%2,%3,%4};" :: "r"(addr), "r"(v.x), "r"(v.y), "r"(v.z), "r"(v.w) : "memory");
}
DEVI void sts64(uint32_t addr, uint32_t a, uint32_t b) { asm volatile("st.shared.v2.u32 [%0], {%1,%2};" :: "r"(addr), "r"(a), "r"(b) : "memory"); }
DEVI void sts32(uint32_t addr, uint32_t v) { asm volatile("st.shared.u32 [%0], %1;" :: "r"(addr), "r"(v) : "memory"); }
DEVI uint4 lds128(uint32_t addr) {
    uint4 v; asm volatile("ld.shared.v4.u32 {%0,%1,%2,%3}, [%4];" : "=r"(v.x), "=r"(v.y), "=r"(v.z), "=r"(v.w) : "r"(addr) : "memory"); return v;
}
DEVI float2 lds64f(uint32_t addr) {
    float2 v; asm volatile("ld.shared.v2.f32 {%0,%1}, [%2];" : "=f"(v.x), "=f"(v.y) : "r"(addr) : "memory"); return v;
}
DEVI void cp_async16(uint32_t dst, const void* src) {
    asm volatile("cp.async.cg.shared.global [%0], [%1], 16;" :: "r"(dst), "l"(src) : "memory");
}
DEVI void cp_async_commit() { asm volatile("cp.async.commit_group;" ::: "memory"); }
DEVI void cp_async_wait0() { asm volatile("cp.async.wait_group 0;" ::: "memory"); }
DEVI uint32_t lds32(uint32_t addr) { uint32_t v; asm volatile("ld.shared.u32 %0, [%1];" : "=r"(v) : "r"(addr) : "memory"); return v; }
DEVI float rcp_fast(float x) { float y; asm("rcp.approx.ftz.f32 %0, %1;" : "=f"(y) : "f"(x)); return y; }
DEVI bool all_nz(const uint4& v) { return v.x && v.y && v.z && v.w; }
DEVI uint32_t mapa(uint32_t addr, uint32_t rank) {
    uint32_t r; asm("mapa.shared::cluster.u32 %0, %1, %2;" : "=r"(r) : "r"(addr), "r"(rank)); return r;
}
DEVI void st_async32(uint32_t dst, uint32_t a, uint32_t bar) {
    asm volatile("st.async.weak.shared::cluster.mbarrier::complete_tx::bytes.b32 [%0], %1, [%2];" :: "r"(dst), "r"(a), "r"(bar) : "memory");
}
DEVI void st_async64(uint32_t dst, uint32_t a, uint32_t b, uint32_t bar) {
    asm volatile("st.async.weak.shared::cluster.mbarrier::complete_tx::bytes.v2.b32 [%0], {%1,%2}, [%3];"
                 :: "r"(dst), "r"(a), "r"(b), "r"(bar) : "memory");
}

DEVI void st_async128(uint32_t dst, uint32_t a, uint32_t b, uint32_t c, uint32_t d, uint32_t bar) {
    asm volatile("st.async.weak.shared::cluster.mbarrier::complete_tx::bytes.v4.b32 [%0], {%1,%2,%3,%4}, [%5];"
                 :: "r"(dst), "r"(a), "r"(b), "r"(c), "r"(d), "r"(bar) : "memory");
}

DEVI uint32_t b_addr(uint32_t sb, int row, int which, int chunk) { const int l = 3 * row + which; return sb + l * 128 + ((chunk ^ (l & 7)) * 16); }
DEVI void battn_warp(uint32_t st, uint32_t so, int i0, int par, int head, int hh, int mt, int lane) {
    const int gq = lane >> 2, t = lane & 3;
    float s[3][4];
#pragma unroll
    for (int n = 0; n < 3; n++) { s[n][0] = s[n][1] = s[n][2] = s[n][3] = 0.f; }
    const int arow = 16 * mt + (lane & 7) + ((lane >> 3) & 1) * 8;
#pragma unroll
    for (int ks = 0; ks < 2; ks++) {
        uint32_t a[4], b[4], b2[2];
        ldsm4(a, b_addr(st, 8 + arow, 0, hh * 4 + ks * 2 + (lane >> 4)));
        const int brow = 16 * mt + (lane >> 4) * 8 + (lane & 7);
        ldsm4(b, b_addr(st, brow, 1, hh * 4 + ks * 2 + ((lane >> 3) & 1)));
        const int crow = 16 * mt + 16 + (lane & 7);
        ldsm2(b2, b_addr(st, crow, 1, hh * 4 + ks * 2 + ((lane >> 3) & 1)));
        mma16816(s[0], a, b[0], b[1]);
        mma16816(s[1], a, b[2], b[3]);
        mma16816(s[2], a, b2[0], b2[1]);
    }
    float m0 = -INFINITY, m1 = -INFINITY;
#pragma unroll
    for (int n = 0; n < 3; n++) {
#pragma unroll
        for (int c = 0; c < 2; c++) {
            const int dj = 8 * n - 8 + 2 * t + c;
            const bool ex = i0 + 16 * mt + dj >= 0;
            if (!(ex && gq - dj >= 0 && gq - dj <= 7)) s[n][c] = -INFINITY;
            if (!(ex && gq + 8 - dj >= 0 && gq + 8 - dj <= 7)) s[n][2 + c] = -INFINITY;
            m0 = fmaxf(m0, s[n][c]); m1 = fmaxf(m1, s[n][2 + c]);
        }
    }
    m0 = fmaxf(m0, __shfl_xor_sync(0xffffffffu, m0, 1)); m0 = fmaxf(m0, __shfl_xor_sync(0xffffffffu, m0, 2));
    m1 = fmaxf(m1, __shfl_xor_sync(0xffffffffu, m1, 1)); m1 = fmaxf(m1, __shfl_xor_sync(0xffffffffu, m1, 2));
    constexpr float C = 0.17677669529663687f * 1.4426950408889634f;
    float l0 = 0.f, l1 = 0.f;
    uint32_t p[3][2];
#pragma unroll
    for (int n = 0; n < 3; n++) {
        const float e0 = ex2((s[n][0] - m0) * C), e1 = ex2((s[n][1] - m0) * C), e2 = ex2((s[n][2] - m1) * C), e3 = ex2((s[n][3] - m1) * C);
        l0 += e0 + e1; l1 += e2 + e3;
        p[n][0] = pack_bf16(e0, e1); p[n][1] = pack_bf16(e2, e3);
    }
    l0 += __shfl_xor_sync(0xffffffffu, l0, 1); l0 += __shfl_xor_sync(0xffffffffu, l0, 2);
    l1 += __shfl_xor_sync(0xffffffffu, l1, 1); l1 += __shfl_xor_sync(0xffffffffu, l1, 2);
    const float i0f = rcp_fast(l0), i1f = rcp_fast(l1);
    float o[4][4];
#pragma unroll
    for (int n = 0; n < 4; n++) { o[n][0] = o[n][1] = o[n][2] = o[n][3] = 0.f; }
    {
        const uint32_t a0[4] = {p[0][0], p[0][1], p[1][0], p[1][1]}, a1[4] = {p[2][0], p[2][1], 0u, 0u};
#pragma unroll
        for (int n = 0; n < 4; n += 2) {
            uint32_t b[4], b2[4];
            const int vrow = 16 * mt + ((lane >> 3) & 1) * 8 + (lane & 7);
            ldsm4t(b, b_addr(st, vrow, 2, hh * 4 + n + (lane >> 4)));
            const int wrow = 16 * mt + 16 + (lane & 7);
            ldsm4t(b2, b_addr(st, wrow, 2, hh * 4 + n + (lane >> 4)));
            mma16816(o[n], a0, b[0], b[1]);
            mma16816(o[n + 1], a0, b[2], b[3]);
            mma16816(o[n], a1, b2[0], 0u);
            mma16816(o[n + 1], a1, b2[2], 0u);
        }
    }
    {
        const int row = (lane & 7) + ((lane >> 3) & 1) * 8;
#pragma unroll
        for (int n = 0; n < 4; n += 2)
            stsm4(so + row * 64 + (((n + (lane >> 4)) ^ ((row >> 1) & 3)) * 16),
                  pack_bf16(o[n][0] * i0f, o[n][1] * i0f), pack_bf16(o[n][2] * i1f, o[n][3] * i1f),
                  pack_bf16(o[n + 1][0] * i0f, o[n + 1][1] * i0f), pack_bf16(o[n + 1][2] * i1f, o[n + 1][3] * i1f));
    }
    __syncwarp();
#pragma unroll
    for (int i = 0; i < 2; i++) {
        const int idx = lane + i * 32, row = idx >> 2, ch = idx & 3;
        const uint4 v = lds128(so + row * 64 + ((ch ^ ((row >> 1) & 3)) * 16));
        *(uint4*)(g_bo + (size_t)(2 * (i0 + 16 * mt + row) + par) * 1024 + head * 32 + ch * 8) = v;
    }
    __syncwarp();
}

constexpr float SCALE_LOG2E = 0.08838834764831845f * 1.4426950408889634f;

constexpr int P_STAGES = 4, P_STAGE = 16384 + 32768;
constexpr int PS_STG = P_STAGES * P_STAGE;
constexpr int PS_BAR = PS_STG + 32768;
constexpr int P_SMEM = PS_BAR + 256;
static_assert(P_SMEM <= 232448, "smem");
enum { K_Q, K_B1, K_B3, K_A4, K_QH, K_A3, K_SK, K_B2, K_END };
struct PList { int n; int4 run[16]; };
struct PTask { int kind, a, b, c; };
DEVI PTask p_decode(const PList& pl, int id) {
    for (int i = 0; i < pl.n; i++) {
        const int4 r = pl.run[i];
        if (id < r.w) {
            const int j = id - r.z;
            if (r.x == K_Q || r.x == K_QH) return {r.x, j & 31, r.y + (j >> 5), 0};
            if (r.x == K_B1) return {r.x, j % 24, r.y + j / 24, 0};
            if (r.x == K_B2) return {r.x, 0, r.y + j, 0};
            if (r.x == K_SK) return {r.x, (j >> 2) & 7, r.y + (j >> 5), j & 3};
            return {r.x, j & 7, r.y + (j >> 3), 0};
        }
    }
    return {K_END, 0, 0, 0};
}
DEVI void wait_count(const unsigned* p, unsigned target) {
    int n = 0;
    while (true) {
        unsigned v; asm volatile("ld.acquire.gpu.global.u32 %0, [%1];" : "=r"(v) : "l"(p) : "memory");
        if ((int)(v - target) >= 0) break;
        __nanosleep(100);
        if (++n > SPIN_LIMIT) TRAP(0x10000000u | ((unsigned)(size_t)p & 0xFFFFu));
    }
}
DEVI void wait_count_warp(const unsigned* p, unsigned target) {
    int n = 0;
    while (true) {
        unsigned v; asm volatile("ld.acquire.gpu.global.u32 %0, [%1];" : "=r"(v) : "l"(p) : "memory");
        if (__all_sync(0xffffffffu, (int)(v - target) >= 0)) break;
        __nanosleep(100);
        if (++n > SPIN_LIMIT) TRAP(0x10000000u | ((unsigned)(size_t)p & 0xFFFFu));
    }
}
DEVI void signal_count(unsigned* p) { __threadfence(); atomicAdd(p, 1u); }

struct PMaps { CUtensorMap wq, bw, bwo, wo, x, bx, bo, ox, cb, cout, cq, b40; PList list; };
constexpr int PB_F = PS_BAR, PB_E = PB_F + 32, PB_TF = PB_F + 64, PB_TE = PB_F + 80, PB_S = PB_F + 96;
constexpr int PS_T = PB_F + 112, PS_SIG = PS_T + 32, PS_SK = PS_SIG + 16;

struct POut { const CUtensorMap* map; int col, tok, cnt; bool blocked; };
DEVI void p_store(const uint32_t* pk, const POut& o, int c, uint32_t stg, int warp, int lane_, int barid, bool elected) {
    const int lane = (int)opaque((uint32_t)lane_);
    const int mi = lane >> 3, r = lane & 7;
    const uint32_t buf = stg + (c & 1) * 8192;
    if (elected) asm volatile("cp.async.bulk.wait_group.read 1;" ::: "memory");
    nbar_sync(barid, 128);
    if (o.blocked) {
#pragma unroll
        for (int j = 0; j < 8; j += 2)
            stsm4(buf + (j + (mi >> 1)) * 1024 + (warp * 16 + (mi & 1) * 8 + r) * 16, pk[2 * j], pk[2 * j + 1], pk[2 * j + 2], pk[2 * j + 3]);
    } else {
#pragma unroll
        for (int j = 0; j < 8; j += 2)
            stsm4t(buf + (8 * (j + (mi >> 1)) + r) * 128 + ((2 * warp + (mi & 1)) ^ r) * 16, pk[2 * j], pk[2 * j + 1], pk[2 * j + 2], pk[2 * j + 3]);
    }
    fence_proxy_async();
    nbar_sync(barid, 128);
    if (elected) {
        if (o.blocked)
            asm volatile("cp.async.bulk.tensor.4d.global.shared::cta.bulk_group [%0, {%2, %3, %4, %5}], [%1];"
                         :: "l"(o.map), "r"(buf), "r"(0), "r"((o.col >> 5) & 2), "r"((o.col >> 7) * 4), "r"((o.tok >> 5) + 2 * c) : "memory");
        else tma_store_2d(o.map, buf, o.col, o.tok + c * 64);
        bulk_commit();
    }
}
DEVI void p_signal(uint32_t sb, int g, int cnt, int& nsig) {
    sts32(sb + PS_SIG + g * 8 + (nsig & 1) * 4, (uint32_t)cnt);
    mbar_arrive(sb + PB_S + g * 8);
    nsig++;
}
template <int BN, bool FIRST>
DEVI void p_kblock(float* d, uint32_t sb, int g, int it, bool elected) {
    const int st = it % P_STAGES;
    mbar_wait(sb + PB_F + st * 8, (it / P_STAGES) & 1);
    const uint32_t a = sb + st * P_STAGE;
    const uint64_t da = mk_desc(a + g * 8192, 16, 1024, 1), db = mk_desc(a + 16384, 16, 1024, 1);
    wg_fence();
#pragma unroll
    for (int kk = 0; kk < 4; kk++) {
        if (BN == 256) { if (FIRST && kk == 0) wgmma_n256_ss<true>(d, da, db); else wgmma_n256_ss<false>(d, da + (uint64_t)(kk * 128), db + (uint64_t)(kk * 2)); }
        else           { if (FIRST && kk == 0) wgmma_n128_ss<true>(d, da, db); else wgmma_n128_ss<false>(d, da + (uint64_t)(kk * 128), db + (uint64_t)(kk * 2)); }
    }
    wg_commit();
    if (!FIRST) {
        wg_wait<1>();
        if (elected) mbar_arrive(sb + PB_E + ((it - 1) % P_STAGES) * 8);
    }
}

DEVI void post_producer(const PMaps& mp, uint32_t sb, int nworker) {
    const uint32_t bF = sb + PB_F, bE = sb + PB_E;
    const unsigned E = *(volatile unsigned*)&g_epoch + 1;
    const unsigned qbase = (E - 1) * (unsigned)(mp.list.run[mp.list.n - 1].w + nworker);
    int it = 0;
    for (int i = 0;; i++) {
        mbar_wait(sb + PB_TE + (i & 1) * 8, ((i >> 1) & 1) ^ 1);
        const int id = (int)(atomicAdd(&g_qctr, 1u) - qbase);
        const PTask tk = p_decode(mp.list, id);
        if (tk.kind == K_B2) {
            wait_count(&g_cnt[C_B1 + (tk.b >> 2)], 48 * E);
            if ((tk.b & 3) == 0 && tk.b > 0) wait_count(&g_cnt[C_B1 + (tk.b >> 2) - 1], 48 * E);
        } else if (tk.kind == K_B3) wait_count(&g_cnt[C_B2 + tk.b], 8 * E);
        else if (tk.kind == K_A4) wait_count(&g_prog[2 * tk.b + 1], 128 * E);
        else if (tk.kind == K_A3 || tk.kind == K_SK) wait_count(&g_prog[tk.b], 128 * E);
        if (tk.kind != K_Q && tk.kind != K_QH && tk.kind != K_B1) asm volatile("fence.proxy.async;" ::: "memory");
        sts128(sb + PS_T + (i & 1) * 16, make_uint4((uint32_t)tk.kind | ((uint32_t)id << 8), (uint32_t)tk.a, (uint32_t)tk.b, (uint32_t)tk.c));
        mbar_arrive(sb + PB_TF + (i & 1) * 8);
        if (tk.kind == K_END) break;
        if (tk.kind == K_B2) {
            const int i0 = tk.b * 32;
            for (int j = 0; j < 16; j++, it++) {
                const int st = it % P_STAGES;
                mbar_wait(bE + st * 8, ((it / P_STAGES) & 1) ^ 1);
                const uint32_t a = sb + st * P_STAGE, bar = bF + st * 8;
                mbar_expect_tx(bar, 2 * 15360);
                for (int u = 0; u < 2; u++)
                    asm volatile("cp.async.bulk.tensor.4d.shared::cluster.global.mbarrier::complete_tx::bytes [%0], [%1, {%3, %4, %5, %6}], [%2];"
                                 :: "r"(a + u * 15360), "l"(&mp.b40), "r"(bar), "r"(j * 64), "r"(0), "r"(u), "r"(i0 - 8) : "memory");
            }
            continue;
        }
        const bool qk = tk.kind == K_Q || tk.kind == K_QH, ak = tk.kind == K_A4 || tk.kind == K_A3 || tk.kind == K_SK, wide = tk.kind <= K_A4;
        const CUtensorMap* tw = tk.kind == K_B1 ? &mp.bw : (qk ? &mp.wq : &mp.bwo);
        const CUtensorMap* tx = tk.kind == K_B1 ? &mp.bx : (qk ? &mp.x : (ak ? &mp.ox : &mp.bo));
        const int nk = tk.kind == K_A3 || tk.kind == K_A4 ? HD / 64 : DM / 64, kb0 = tk.c * 16;
        for (int kb = kb0; kb < kb0 + nk; kb++, it++) {
            const int st = it % P_STAGES;
            mbar_wait(bE + st * 8, ((it / P_STAGES) & 1) ^ 1);
            const uint32_t a = sb + st * P_STAGE, bar = bF + st * 8;
            mbar_expect_tx(bar, wide ? P_STAGE : 32768);
            if (ak) {
                tma_load_wo(a, &mp.wo, tk.a * 128, kb * 2, bar);
                tma_load_wo(a + 8192, &mp.wo, tk.a * 128 + 64, kb * 2, bar);
            } else {
                tma_load_2d(a, tw, tk.a * 128, kb * 64, bar);
                tma_load_2d(a + 8192, tw, tk.a * 128 + 64, kb * 64, bar);
            }
            tma_load_2d(a + 16384, tx, kb * 64, tk.b * (wide ? 256 : 128), bar);
            if (wide) tma_load_2d(a + 32768, tx, kb * 64, tk.b * 256 + 128, bar);
        }
    }
    __threadfence();
    if (atomicAdd(&g_done, 1u) == E * nworker - 1) { __threadfence(); *(volatile unsigned*)&g_epoch = E; }
}
DEVI void post_helper(uint32_t sb, int g) {
    for (int n = 0;; n++) {
        mbar_wait_sleepy(sb + PB_S + g * 8, n & 1);
        const int cnt = (int)lds32(sb + PS_SIG + g * 8 + (n & 1) * 4);
        if (cnt < 0) break;
        signal_count(&g_cnt[cnt]);
    }
}
DEVI void post_consumer(const PMaps& mp, uint32_t sb, int g, int warp) {
    const int barid = 1 + g, tid = threadIdx.x, lane = tid & 31;
    const bool elected = (tid & 127) == 0;
    const uint32_t stg = sb + PS_STG + g * 16384;
    int it = 0, nsig = 0;
    uint32_t pk[64];
    POut out;
    bool pend = false;
#pragma unroll
    for (int i = 0; i < 64; i++) pk[i] = 0u;
    for (int i = 0;; i++) {
        const uint32_t bTF = sb + PB_TF + (i & 1) * 8;
        if (pend) {
            uint32_t now;
            asm volatile("{.reg .pred p, q; mbarrier.test_wait.parity.shared::cta.b64 p, [%1], %2; bar.red.and.pred q, %3, 128, p; selp.u32 %0, 1, 0, q;}"
                         : "=r"(now) : "r"(bTF), "r"((i >> 1) & 1), "r"(barid) : "memory");
            if (!now || (lds32(sb + PS_T + (i & 1) * 16) & 255u) > K_A4) {
#pragma unroll
                for (int c = 0; c < 4; c++) p_store(pk + 16 * c, out, c, stg, warp, lane, barid, elected);
                if (elected && out.cnt != C_NONE) { bulk_wait_all(); p_signal(sb, g, out.cnt, nsig); }
                pend = false;
            }
        }
        mbar_wait(bTF, (i >> 1) & 1);
        const uint4 tw = lds128(sb + PS_T + (i & 1) * 16);
        mbar_arrive(sb + PB_TE + (i & 1) * 8);
        const PTask tk = {(int)(tw.x & 255u), (int)tw.y, (int)tw.z, (int)tw.w};
        if (tk.kind == K_END) break;
        if (tk.kind <= K_A4) {
            float d[128];
            const int nk = tk.kind == K_A4 ? HD / 64 : DM / 64;
            p_kblock<256, true>(d, sb, g, it, elected);
            if (pend) p_store(pk, out, 0, stg, warp, lane, barid, elected);
#pragma unroll
            for (int c = 1; c < 4; c++) {
                p_kblock<256, false>(d, sb, g, it + c, elected);
                if (pend) p_store(pk + 16 * c, out, c, stg, warp, lane, barid, elected);
            }
#pragma unroll 1
            for (int kb = 4; kb < nk; kb++) {
                p_kblock<256, false>(d, sb, g, it + kb, elected);
                if (kb == 6 && pend && elected && out.cnt != C_NONE) { bulk_wait_all(); p_signal(sb, g, out.cnt, nsig); }
            }
            it += nk;
            wg_wait<0>();
            reg_fence<128>(d);
            if (elected) mbar_arrive(sb + PB_E + ((it - 1) % P_STAGES) * 8);
#pragma unroll
            for (int j = 0; j < 64; j++) pk[j] = pack_bf16(d[2 * j], d[2 * j + 1]);
            out.map = tk.kind == K_Q ? &mp.cq : (tk.kind == K_B1 ? &mp.cb : &mp.cout);
            out.col = tk.a * 128 + g * 64 + (tk.kind == K_B3 ? DM : 0);
            out.tok = tk.b * 256;
            out.cnt = tk.kind == K_Q ? C_Q + tk.b : (tk.kind == K_B1 ? C_B1 + tk.b : C_NONE);
            out.blocked = tk.kind == K_Q;
            pend = true;
        } else if (tk.kind == K_B2) {
            if (elected) bulk_wait_all();
            nbar_sync(barid, 128);
#pragma unroll 1
            for (int j = 0; j < 16; j++, it++) {
                const int st = it % P_STAGES;
                mbar_wait(sb + PB_F + st * 8, (it / P_STAGES) & 1);
                const uint32_t a = sb + st * P_STAGE + g * 15360;
                battn_warp(a, stg + warp * 1024, tk.b * 32, g, j * 2 + (warp >> 1), warp >> 1, warp & 1, (int)opaque((uint32_t)lane));
                nbar_sync(barid, 128);
                if (elected) mbar_arrive(sb + PB_E + st * 8);
            }
            if (elected) p_signal(sb, g, C_B2 + (tk.b >> 2), nsig);
#pragma unroll
            for (int j = 0; j < 64; j++) pk[j] = 0u;
        } else {
            float d[64];
            const int nk = tk.kind == K_A3 ? HD / 64 : DM / 64;
            p_kblock<128, true>(d, sb, g, it, elected);
#pragma unroll 1
            for (int kb = 1; kb < nk; kb++) p_kblock<128, false>(d, sb, g, it + kb, elected);
            it += nk;
            wg_wait<0>();
            reg_fence<64>(d);
            if (elected) mbar_arrive(sb + PB_E + ((it - 1) % P_STAGES) * 8);
            bool finish = true;
            if (tk.kind == K_SK) {
                const int tile = ((tk.b - (16 - P_NSK)) * 8 + tk.a);
                float4* mine = (float4*)(g_skp + ((size_t)(tile * 4 + tk.c) * 2 + g) * 8192) + (tid & 127);
#pragma unroll
                for (int j = 0; j < 16; j++) mine[j * 128] = make_float4(d[4 * j], d[4 * j + 1], d[4 * j + 2], d[4 * j + 3]);
                nbar_sync(barid, 128);
                if (elected) { __threadfence(); const unsigned old = atomicAdd(&g_cnt_sk[tile * 2 + g], 1u); __threadfence(); sts32(sb + PS_SK + g * 4, old & 3u); }
                nbar_sync(barid, 128);
                finish = lds32(sb + PS_SK + g * 4) == 3u;
                if (finish) {
#pragma unroll 1
                    for (int q = 1; q < 4; q++) {
                        const float4* o = (const float4*)(g_skp + ((size_t)(tile * 4 + ((tk.c + q) & 3)) * 2 + g) * 8192) + (tid & 127);
#pragma unroll
                        for (int j = 0; j < 16; j++) {
                            const float4 v = __ldcg(o + j * 128);
                            d[4 * j] += v.x; d[4 * j + 1] += v.y; d[4 * j + 2] += v.z; d[4 * j + 3] += v.w;
                        }
                    }
                }
                nbar_sync(barid, 128);
            }
            if (finish) {
                const POut o = {tk.kind == K_QH ? &mp.cq : &mp.cout, tk.a * 128 + g * 64, tk.b * 128, 0, tk.kind == K_QH};
                uint32_t q[32];
#pragma unroll
                for (int j = 0; j < 32; j++) q[j] = pack_bf16(d[2 * j], d[2 * j + 1]);
                p_store(q, o, 0, stg, warp, lane, barid, elected);
                p_store(q + 16, o, 1, stg, warp, lane, barid, elected);
                if (elected && tk.kind == K_QH) { bulk_wait_all(); p_signal(sb, g, tk.b == 0 ? C_QH : C_Q, nsig); }
            }
#pragma unroll
            for (int j = 0; j < 64; j++) pk[j] = 0u;
        }
    }
    if (elected) { bulk_wait_all(); p_signal(sb, g, -1, nsig); }
}
DEVI void post_init(uint32_t sb) {
    for (int i = 0; i < P_STAGES; i++) { mbar_init(sb + PB_F + i * 8, 1); mbar_init(sb + PB_E + i * 8, 2); }
    for (int i = 0; i < 2; i++) { mbar_init(sb + PB_TF + i * 8, 1); mbar_init(sb + PB_TE + i * 8, 256); mbar_init(sb + PB_S + i * 8, 1); }
    fence_mbar_init();
}

__global__ void __launch_bounds__(384, 1) k_post(const __grid_constant__ PMaps mp) {
    extern __shared__ __align__(1024) uint8_t smem_raw[];
    const uint32_t sb = smem_u32(smem_raw);
    if (sb & 1023u) __trap();
    const int tid = threadIdx.x;
    const int wg = __shfl_sync(0xffffffffu, tid >> 7, 0), warp = __shfl_sync(0xffffffffu, (tid >> 5) & 3, 0);
    if (tid == 0) post_init(sb);
    __syncthreads();
    if (wg < 2) {
        reg_inc<232>();
        post_consumer(mp, sb, wg, warp);
    } else {
        reg_dec<40>();
        if (tid == 256) post_producer(mp, sb, gridDim.x);
        else if (tid == 288 || tid == 320) post_helper(sb, warp - 1);
    }
    __syncthreads();
    asm volatile("griddepcontrol.wait;" ::: "memory");
}

constexpr unsigned long long R_TORD_PACK = 0xf5ea4937dc6b8120ull;
__host__ __device__ constexpr int r_tord(int pos) { return (int)((R_TORD_PACK >> (4 * pos)) & 15ull); }
__host__ __device__ constexpr int r_tinv(int T) { for (int p = 0; p < 16; p++) if (r_tord(p) == T) return p; return 0; }
__host__ __device__ constexpr bool r_pos_ss(int pos) { return pos % 3 == 2; }
__host__ __device__ constexpr int r_ss(int pos) { return pos / 3; }
__host__ __device__ constexpr int r_rs(int pos) { return pos - pos / 3; }
constexpr int R_NRS = 11, R_NSS = 5;
constexpr int R_G1 = 9;
#define REG_KB 232
#define TA_LATE 0
#define WO_REL 0
constexpr int X_SLOTS = 4;
constexpr int X_NST = 8;

constexpr int RS_WSS  = 0;
constexpr int RS_WO   = RS_WSS + R_NSS * 16384;
constexpr int RS_MEM  = RS_WO + 5 * 16384;
constexpr int RS_O    = RS_MEM + 16384;
constexpr int RS_SX   = RS_O + 2048;
constexpr int RS_BAR  = RS_SX + 2048;
constexpr int RS_TAIL = RS_BAR + 1024;
constexpr int RS_WO5  = RS_TAIL;
constexpr int RS_K    = RS_WO5 + 16384;
constexpr int RS_V    = RS_K + 10240;
constexpr int RS_Q    = RS_V + 10240;
constexpr int RS_QX   = RS_Q + 2048;
constexpr int RS_QEND = RS_QX + 8192;
constexpr int RS_X    = RS_TAIL;
constexpr int X_PITCH = X_SLOTS * 4096;
constexpr int RS_XD   = RS_X + 2 * X_PITCH;
constexpr int RS_WX   = RS_XD + 8192;
constexpr int RS_KEND = RS_WX + 4096;
constexpr int RS_EV   = RS_BAR + 256;
constexpr int R_SMEM  = RS_KEND > RS_QEND ? RS_KEND : RS_QEND;
static_assert(R_SMEM <= 232448, "smem");
static_assert(RS_TAIL % 1024 == 0 && RS_MEM % 1024 == 0, "alignment");

constexpr int RB_G = RS_BAR, RB_WO = RS_BAR + 16, RB_K = RS_BAR + 24, RB_V = RS_BAR + 32, RB_KV = RS_BAR + 40, RB_QX = RS_BAR + 48, RB_O = RS_BAR + 56;
constexpr int RB_ATT = RS_BAR + 64, RB_W = RS_BAR + 72, RB_SF = RS_BAR + 80, RB_SE = RB_SF + 40, RB_XF = RB_SE + 40;
constexpr int RB_T = RB_XF + 64, RS_INV = RS_SX + 1024;
static_assert(RB_T + 8 <= RS_EV, "barriers");
constexpr uint32_t SB0 = 1024;
__host__ __device__ constexpr uint32_t cdesc(uint32_t off, uint32_t lbo) { return ((SB0 + off) >> 4) | ((lbo >> 4) << 16); }
#define SCHED_FENCE() __syncwarp()
constexpr int NB_BIG = 1, NB_Q = 2, NB_AUX = 3, NB_WO = 4, NB_XS = 5, NB_WG = 6, NB_PAIR = 8;

DEVI int tid_now() { int t; asm volatile("mov.u32 %0, %%tid.x;" : "=r"(t)); return t; }
DEVI uint32_t a_frag_off(int lane, int warp) { return (uint32_t)((((lane >> 4) * 8 + (lane & 7)) * 128) + (((2 * warp + ((lane >> 3) & 1)) ^ (lane & 7)) * 16)); }
DEVI uint32_t b_frag_off(int lane) { return (uint32_t)((lane & 3) * 64 + (((lane >> 2) * 8) ^ ((lane & 2) * 16))); }
DEVI void lds_b(uint32_t* b, uint32_t a) {
    asm volatile("ld.shared.v2.u32 {%0,%1}, [%2];" : "=r"(b[0]), "=r"(b[1]) : "r"(a) : "memory");
    asm volatile("ld.shared.v2.u32 {%0,%1}, [%2];" : "=r"(b[2]), "=r"(b[3]) : "r"(a + 256) : "memory");
}
DEVI uint32_t clk32() { unsigned long long c; asm volatile("mov.u64 %0, %%clock64;" : "=l"(c)); return (uint32_t)c; }
DEVI bool elect_one() {
    uint32_t e; asm volatile("{.reg .pred p; elect.sync _|p, 0xffffffff; selp.u32 %0, 1, 0, p;}" : "=r"(e)); return e;
}

__host__ __device__ constexpr int x_pair(int j) { return j == 0 || j > 3 ? j : (j == 3 ? 1 : j + 1); }
DEVI void x_load(uint32_t sb, int seg, int j, int g, const CUtensorMap* tmX) {
    const uint32_t bar = sb + RB_XF + g * 8;
    mbar_expect_tx(bar, 4096);
    tma_load_3d(sb + RS_X + g * X_PITCH + (j % X_SLOTS) * 4096, tmX, g * 32, seg * 32, x_pair(j) * 2, bar);
}
DEVI void x_refill(uint32_t sb, int seg, int j, int g, int warp, const CUtensorMap* tmX) {
    const int sn = j + X_SLOTS < X_NST ? seg : seg + 1;
    if (warp == (j & 3) && sn < NSEG) {
        if (elect_one()) x_load(sb, sn, (j + X_SLOTS) % X_NST, g, tmX);
    }
}
template <int H>
DEVI void x_half(float* xa, const uint32_t* w, uint32_t sb, int seg, int g0, int warp, const CUtensorMap* tmX) {
    wg_fence();
#pragma unroll
    for (int grp = 0; grp < 4; grp++) {
        const int g = (int)opaque((uint32_t)g0);
        const uint32_t dW0 = cdesc(RS_WSS, 16) + g * 768, dW1 = cdesc(RS_WSS + 8192, 16) - g * 256;
#pragma unroll
        for (int i = 0; i < 8; i++) {
            const bool last = H == 1 && grp >= 2;
            const int j = last ? 6 + (i >> 2) : 4 * H + grp, q = last ? 2 * (i & 3) + (grp == 2) : i;
            const int pos = r_tinv(2 * x_pair(j) + (q >> 2)), kk = (q >> 1) & 1, mt = q & 1;
            const uint32_t db = cdesc(RS_X + (j % X_SLOTS) * 4096, 16) + g * (X_PITCH >> 4) + (q >> 2) * 128 + kk * 2;
            if (j == 0 && q < 2)   wgmma_n32_rs_first(xa + 16 * mt, &w[((r_rs(pos) * 2 + kk) * 2 + mt) * 4], db);
            else if (j == 0 && q == 3) wgmma_n32_ss(xa + 16, cdesc(RS_WX, 16) + g * 128, db);
            else if (r_pos_ss(pos)) wgmma_n32_ss(xa + 16 * mt, (mt ? dW1 : dW0) + r_ss(pos) * 1024 + kk * 128, db);
            else                   wgmma_n32_rs(xa + 16 * mt, &w[((r_rs(pos) * 2 + kk) * 2 + mt) * 4], db);
        }
        wg_commit();
    }
    const int g = (int)opaque((uint32_t)g0);
    wg_wait<3>(); x_refill(sb, seg, 4 * H, g, warp, tmX);
    wg_wait<2>(); x_refill(sb, seg, 4 * H + 1, g, warp, tmX);
    wg_wait<1>();
    if (H == 0) {
        x_refill(sb, seg, 2, g, warp, tmX);
        wg_wait<0>(); reg_fence<32>(xa); x_refill(sb, seg, 3, g, warp, tmX);
    } else reg_fence<16>(xa + 16);
}
DEVI void x_finish(float* xa, uint32_t sb, int seg, int g, int warp, int lane, const CUtensorMap* tmX) {
    const uint32_t d = sb + RS_XD + (lane >> 4) * 2048 + warp * 256 + (lane & 15) * 16;
#pragma unroll
    for (int i = 0; i < 2; i++) {
        const float* x = xa + 16 + 8 * i;
        sts128(d + (g ^ 1) * 1024 + i * 4096, make_uint4(pack_bf16(x[0], x[1]), pack_bf16(x[2], x[3]), pack_bf16(x[4], x[5]), pack_bf16(x[6], x[7])));
    }
    nbar_sync(NB_PAIR + warp, 64);
    float y[16];
#pragma unroll
    for (int i = 0; i < 2; i++) {
        const uint4 v = lds128(d + g * 1024 + i * 4096);
        const uint32_t u[4] = {v.x, v.y, v.z, v.w};
#pragma unroll
        for (int j = 0; j < 4; j++) { y[8 * i + 2 * j] = __uint_as_float(u[j] << 16); y[8 * i + 2 * j + 1] = __uint_as_float(u[j] & 0xFFFF0000u); }
    }
    reg_fence<16>(y);
    wg_wait<0>();
    reg_fence<16>(xa);
    uint32_t p[8];
#pragma unroll
    for (int j = 0; j < 8; j++) p[j] = pack_bf16(xa[2 * j] + y[2 * j], xa[2 * j + 1] + y[2 * j + 1]);
    __syncwarp();
    stsm4(d + g * 1024, p[0], p[1], p[2], p[3]);
    stsm4(d + g * 1024 + 4096, p[4], p[5], p[6], p[7]);
    nbar_arrive(NB_XS, 256 + 32);
    x_refill(sb, seg, X_NST - 2, g, warp, tmX);
    x_refill(sb, seg, X_NST - 1, g, warp, tmX);
}
DEVI void x_send(uint32_t sb, int seg, uint32_t rank, int vdelay) {
    mbar_wait(sb + RB_ATT, (seg - 1) & 1);
    nbar_sync(NB_XS, 256 + 32);
    if (rank == 2) { const uint32_t t = clk32() + vdelay; while ((int)(clk32() - t) < 0) { } }
    if (elect_one()) {
        fence_proxy_async();
        bulk_copy_s2c(mapa(sb + (rank == 1 ? RS_K : RS_V) + 2048, 0), sb + RS_XD, 8192, mapa(sb + (rank == 1 ? RB_KV : RB_V), 0));
    }
    __syncwarp();
}

template <bool XP>
DEVI void mem_pass(float* c0, float* c1, const uint32_t* w, uint32_t sb, uint32_t aA0, uint32_t aB, int g, int warp, int s) {
    const uint32_t aA1 = aA0 + 8192 - g * 16384, par = (s - 1) & 1;
    uint32_t a[16], b[2][4], e[4];
    float d0[4], d1[4];
    if (XP) ldsm4t(e, aA0 + (RS_WX - RS_WSS) - g * (8192 + 2048));
#pragma unroll
    for (int q = 0; q < 4; q++) ldsm4t(a + 4 * q, ((q & 1) ? aA1 : aA0) + (q >> 1) * 2048);
#pragma unroll
    for (int i = 0; i < 4; i++) { c0[i] = 0.f; c1[i] = 0.f; d0[i] = 0.f; d1[i] = 0.f; }
    EV(EV_BIG0, s, 0);
    mbar_wait(sb + RB_G, par);
    EV(EV_BIG0, s, 1);
    lds_b(b[0], aB + r_tord(0) * 1024);
    bool in = false;
#pragma unroll
    for (int pos = 0; pos < 16; pos++) {
        if (pos + 1 < 16) {
            if (pos + 1 == R_G1) { if (!in) mbar_wait(sb + RB_G + 8, par); EV(EV_BIG0, s, 2); }
            lds_b(b[(pos + 1) & 1], aB + r_tord(pos + 1) * 1024);
        }
        if (pos + 2 == R_G1) in = mbar_try(sb + RB_G + 8, par);
        if (XP && pos == 12) in = s == NSEG - 1 || mbar_try(sb + RB_XF + g * 8, 0);
        if (XP && pos == 14) { if (!in) mbar_wait(sb + RB_XF + g * 8, 0); in = mbar_try(sb + RB_ATT, par); }
        const uint32_t* bb = b[pos & 1];
        const uint32_t* aa = r_pos_ss(pos) ? a : &w[r_rs(pos) * 16];
        mma16816(c1, aa + 4, bb[0], bb[1]);
        mma16816(d1, XP && pos == 0 ? e : aa + 12, bb[2], bb[3]);
        mma16816(c0, aa, bb[0], bb[1]);
        mma16816(d0, aa + 8, bb[2], bb[3]);
        if (r_pos_ss(pos) && pos + 3 < 16) {
#pragma unroll
            for (int q = 0; q < 4; q++) ldsm4t(a + 4 * q, ((q & 1) ? aA1 : aA0) + (r_ss(pos) + 1) * 16384 + (q >> 1) * 2048);
        }
        SCHED_FENCE();
    }
    if (XP && !in) mbar_wait(sb + RB_ATT, par);
#pragma unroll
    for (int i = 0; i < 4; i++) { c1[i] += d1[i]; c0[i] += d0[i]; }
}

DEVI uint32_t k_frag_off(int lane) { return (uint32_t)((((lane >> 3) & 1) * 16 + (lane >> 4) * 8 + (lane & 7)) * 16); }
DEVI uint32_t v_frag_off(int lane) { return (uint32_t)(((lane >> 3) & 1) * 2048 + ((lane >> 4) * 8 + (lane & 7)) * 16); }
DEVI void pv_pair(float (*o)[4], const uint32_t* p, const uint32_t* v) {
#pragma unroll
    for (int n = 0; n < 4; n++) mma16816(o[n], p, v[2 * n], v[2 * n + 1]);
}
DEVI void pv_single(float (*o)[4], const uint32_t* p, const uint32_t* v) {
#pragma unroll
    for (int n = 0; n < 4; n++) mma1688(o[n], p[0], p[1], v[n]);
}
DEVI float inv_sum4(float l) {
    l += __shfl_xor_sync(0xffffffffu, l, 1);
    l += __shfl_xor_sync(0xffffffffu, l, 2);
    return rcp_fast(l);
}

DEVI void s_tile(const uint32_t* qa, const uint32_t* k, float& s0, float& s1) {
    float c[4][4];
#pragma unroll
    for (int q = 0; q < 4; q++) { c[q][0] = c[q][1] = c[q][2] = c[q][3] = 0.f; }
#pragma unroll
    for (int q = 0; q < 4; q++) {
        mma16816(c[2 * (q & 1)], qa + 4 * q, k[4 * q], k[4 * q + 1]);
        mma16816(c[2 * (q & 1) + 1], qa + 4 * q, k[4 * q + 2], k[4 * q + 3]);
    }
    s0 = (c[0][0] + c[1][2]) + (c[2][0] + c[3][2]);
    s1 = (c[0][1] + c[1][3]) + (c[2][1] + c[3][3]);
}
DEVI void mem_scores(uint32_t sb, int s, int warp, int lane) {
    const uint32_t ka = sb + RS_K + k_frag_off(lane) + (1 + warp) * 2048;
    uint32_t qa[16], kx[16];
    const bool in = mbar_try(sb + RB_KV, s & 1);
    nbar_sync(NB_Q, 256);
#pragma unroll
    for (int q = 0; q < 4; q++) ldsm4t(qa + 4 * q, sb + RS_Q + q * 512 + lane * 16);
    if (!in) mbar_wait(sb + RB_KV, s & 1);
#pragma unroll
    for (int q = 0; q < 4; q++) ldsm4t(kx + 4 * q, ka + q * 512);
    SCHED_FENCE();
    float s0, s1;
    s_tile(qa, kx, s0, s1);
    asm volatile("st.shared.v2.f32 [%0], {%1,%2};" :: "r"(sb + RS_SX + warp * 256 + lane * 8), "f"(s0), "f"(s1) : "memory");
    nbar_arrive(NB_XS, 256);
}
DEVI void mem_attn(uint32_t sb, int s, int warp, int lane) {
    const uint32_t ka = sb + RS_K + k_frag_off(lane), va = sb + RS_V + warp * 512;
    const uint32_t dst = sb + RS_O + warp * 512 + (lane & 3) * 128 + (lane >> 2) * 16;
    [[maybe_unused]] constexpr int g = 0;
    uint32_t qa[16], vx[16];
    float sc[10];
    nbar_sync(NB_Q, 256);
    EV(EV_BIG0 && lds32(sb + RS_Q) != 0x12345678u, s, 8);
#pragma unroll
    for (int q = 0; q < 4; q++) ldsm4t(qa + 4 * q, sb + RS_Q + q * 512 + lane * 16);
    mbar_wait(sb + RB_K, s & 1);
    EV(EV_BIG0, s, 9);
    {
        uint32_t km[16];
#pragma unroll
        for (int q = 0; q < 4; q++) ldsm4t(km + 4 * q, ka + q * 512);
        nbar_sync(NB_XS, 256);
        s_tile(qa, km, sc[0], sc[1]);
    }
#pragma unroll
    for (int n = 0; n < 4; n++) { const float2 v = lds64f(sb + RS_SX + n * 256 + lane * 8); sc[2 + 2 * n] = v.x; sc[3 + 2 * n] = v.y; }
    const bool v_in = mbar_try(sb + RB_V, s & 1);
    float m = fmaxf(fmaxf(fmaxf(sc[2], sc[3]), fmaxf(sc[4], sc[5])), fmaxf(fmaxf(sc[6], sc[7]), fmaxf(sc[8], sc[9])));
    m = fmaxf(m, fmaxf(sc[0], sc[1]));
    m = fmaxf(fmaxf(m, __shfl_xor_sync(0xffffffffu, m, 1)), fmaxf(__shfl_xor_sync(0xffffffffu, m, 2), __shfl_xor_sync(0xffffffffu, m, 3)));
    EV(warp == 0 && m != 1.2345e30f && elect_one(), s, 5);
    if (!v_in) mbar_wait(sb + RB_V, s & 1);
    EV(warp == 0 && elect_one(), s, 13);
    uint32_t vm[4], p[10];
#pragma unroll
    for (int q = 3; q >= 0; q--) ldsm4(vx + 4 * q, va + 2048 + (q >> 1) * 4096 + (q & 1) * 256 + v_frag_off(lane));
    ldsm4(vm, va + lane * 16);
    SCHED_FENCE();
    const float nm = -m * SCALE_LOG2E;
    float l = 0.f;
#pragma unroll
    for (int n = 4; n >= 0; n--) {
        const float e0 = ex2(fmaf(sc[2 * n], SCALE_LOG2E, nm)), e1 = ex2(fmaf(sc[2 * n + 1], SCALE_LOG2E, nm));
        l += e0 + e1;
        p[2 * n] = pack_bf16(e0, e1); p[2 * n + 1] = __float_as_uint(e0);
    }
    float o[4][4];
#pragma unroll
    for (int n = 0; n < 4; n++) { o[n][0] = o[n][1] = o[n][2] = o[n][3] = 0.f; }
    pv_pair(o, p + 6, vx + 8);
    pv_pair(o, p + 2, vx);
    pv_single(o, p, vm);
    l = (l + __shfl_xor_sync(0xffffffffu, l, 1)) + (__shfl_xor_sync(0xffffffffu, l, 2) + __shfl_xor_sync(0xffffffffu, l, 3));
    const uint4 u = make_uint4(pack_bf16(o[0][0], o[0][1]), pack_bf16(o[1][0], o[1][1]), pack_bf16(o[2][0], o[2][1]), pack_bf16(o[3][0], o[3][1]));
    st_async128(mapa(dst, 1), u.x, u.y, u.z, u.w, mapa(sb + RB_O, 1));
    st_async128(mapa(dst, 2), u.x, u.y, u.z, u.w, mapa(sb + RB_O, 2));
    const uint32_t dl = sb + RS_INV + (lane & 3) * 32 + (lane & 28);
    asm volatile("st.async.weak.shared::cluster.mbarrier::complete_tx::bytes.b32 [%0], %1, [%2];"
                 :: "r"(mapa(dl, 1 + (warp & 1))), "r"(__float_as_uint(l)), "r"(mapa(sb + RB_O, 1 + (warp & 1))) : "memory");
    sts128(dst, u);
    sts32(dl, __float_as_uint(l));
    __syncwarp();
    if (elect_one()) mbar_arrive(sb + RB_O);
    EV(warp == 0 && elect_one(), s, 15);
}

DEVI void ta_scores(float* c, uint32_t sb, int seg, int cw, int lane) {
    const int mt = cw >= 3, n = cw - 3 * mt;
    const uint32_t qa = sb + RS_QX + (2 * mt + ((lane >> 3) & 1)) * 2048 + ((lane >> 4) * 8 + (lane & 7)) * 16;
    const uint32_t ka = sb + RS_K + n * 2048 + lane * 16;
    float d[4] = {0.f, 0.f, 0.f, 0.f};
    c[0] = c[1] = c[2] = c[3] = 0.f;
    mbar_wait(sb + RB_QX, seg & 1);
    if (n == 0) mbar_wait(sb + RB_K, seg & 1);
#pragma unroll
    for (int j = 0; j < 4; j++) {
        uint32_t a0[4], a1[4], b[4];
        ldsm4t(a0, qa + j * 512);
        ldsm4t(b, ka + j * 512);
        ldsm4t(a1, qa + j * 512 + 256);
        mma16816(c, a0, b[0], b[1]);
        mma16816(d, a1, b[2], b[3]);
    }
    const int over = 8 * (n - 1) + 2 * (lane & 3) - 16 * mt - (lane >> 2);
    c[0] = over > 0 ? -INFINITY : c[0] + d[0];
    c[1] = over >= 0 ? -INFINITY : c[1] + d[1];
    c[2] = over > 8 ? -INFINITY : c[2] + d[2];
    c[3] = over >= 8 ? -INFINITY : c[3] + d[3];
}
DEVI void ta_output(uint32_t sb, int seg, int head, int mt, int j, int lane) {
    const uint32_t sa = sb + RS_QX + mt * 1536 + lane * 16;
    float sc[5][4];
#pragma unroll
    for (int n = 0; n < 5; n++) {
        uint4 v = make_uint4(0xFF800000u, 0xFF800000u, 0xFF800000u, 0xFF800000u);
        if (n < 2 || n == 4 || mt) v = lds128(sa + (n == 4 ? 1024 + mt * 1024 : n * 512));
        sc[n][0] = __uint_as_float(v.x); sc[n][1] = __uint_as_float(v.y); sc[n][2] = __uint_as_float(v.z); sc[n][3] = __uint_as_float(v.w);
    }
    float m0 = -INFINITY, m1 = -INFINITY;
#pragma unroll
    for (int n = 0; n < 5; n++) { m0 = fmaxf(m0, fmaxf(sc[n][0], sc[n][1])); m1 = fmaxf(m1, fmaxf(sc[n][2], sc[n][3])); }
    m0 = fmaxf(m0, __shfl_xor_sync(0xffffffffu, m0, 1)); m1 = fmaxf(m1, __shfl_xor_sync(0xffffffffu, m1, 1));
    m0 = fmaxf(m0, __shfl_xor_sync(0xffffffffu, m0, 2)); m1 = fmaxf(m1, __shfl_xor_sync(0xffffffffu, m1, 2));
    m0 *= -SCALE_LOG2E; m1 *= -SCALE_LOG2E;
    float l0 = 0.f, l1 = 0.f;
    uint32_t p[10];
#pragma unroll
    for (int n = 0; n < 5; n++) {
        const float e0 = ex2(fmaf(sc[n][0], SCALE_LOG2E, m0)), e1 = ex2(fmaf(sc[n][1], SCALE_LOG2E, m0));
        const float e2 = ex2(fmaf(sc[n][2], SCALE_LOG2E, m1)), e3 = ex2(fmaf(sc[n][3], SCALE_LOG2E, m1));
        l0 += e0 + e1; l1 += e2 + e3;
        p[2 * n] = pack_bf16(e0, e1); p[2 * n + 1] = pack_bf16(e2, e3);
    }
    const float i0 = inv_sum4(l0), i1 = inv_sum4(l1);
    mbar_wait(sb + RB_V, seg & 1);
    const uint32_t vb = sb + RS_V + j * 512;
    float o[4][4];
#pragma unroll
    for (int n = 0; n < 4; n++) { o[n][0] = o[n][1] = o[n][2] = o[n][3] = 0.f; }
    uint32_t v[8];
    ldsm4(v, vb + v_frag_off(lane)); ldsm4(v + 4, vb + v_frag_off(lane) + 256);
    pv_pair(o, p, v);
    SCHED_FENCE();
    ldsm4(v, vb + 4096 + v_frag_off(lane)); ldsm4(v + 4, vb + 4096 + v_frag_off(lane) + 256);
    pv_pair(o, p + 4, v);
    SCHED_FENCE();
    ldsm4(v, vb + 4096 + mt * 4096 + lane * 16);
    pv_single(o, p + 8, v);
    bf16* dst = g_ox + (uint32_t)((seg * 32 + mt * 16 + (lane >> 2)) * HD + head * DH + j * 32 + (lane & 3) * 8);
    asm volatile("st.global.v4.u32 [%0], {%1,%2,%3,%4};" :: "l"(dst), "r"(pack_bf16(o[0][0] * i0, o[0][1] * i0)), "r"(pack_bf16(o[1][0] * i0, o[1][1] * i0)),
                 "r"(pack_bf16(o[2][0] * i0, o[2][1] * i0)), "r"(pack_bf16(o[3][0] * i0, o[3][1] * i0)) : "memory");
    asm volatile("st.global.v4.u32 [%0], {%1,%2,%3,%4};" :: "l"(dst + 8 * HD), "r"(pack_bf16(o[0][2] * i1, o[0][3] * i1)), "r"(pack_bf16(o[1][2] * i1, o[1][3] * i1)),
                 "r"(pack_bf16(o[2][2] * i1, o[2][3] * i1)), "r"(pack_bf16(o[3][2] * i1, o[3][3] * i1)) : "memory");
}

template <bool XP>
DEVI void big_main(const uint32_t* w, const uint32_t sb, const int g, const int warp, const uint32_t rank, const int head,
                   const CUtensorMap* tmX, const bf16* xg, const unsigned E) {
    float xa[32];
    const uint32_t aB = __shfl_sync(0xffffffffu, sb + RS_MEM + (g * 32 + (tid_now() & 31)) * 16, tid_now() & 31);
#define lane0 ((int)(opaque(aB) >> 4) & 31)
    const uint32_t aA0 = sb + RS_WSS + g * (8192 + 4096) + a_frag_off(lane0, warp);
    const uint32_t aBf = sb + RS_MEM + g * 512 + b_frag_off(lane0);
    if constexpr (XP) {
        mbar_wait(sb + RB_XF + g * 8, 0);
        x_half<0>(xa, w, sb, 0, g, warp, tmX);
        mbar_wait(sb + RB_XF + g * 8, 1);
        x_half<1>(xa, w, sb, 0, g, warp, tmX);
        x_finish(xa, sb, 0, g, warp, lane0, tmX);
    }
    nbar_sync(NB_BIG, 256);
    for (int s = 0; s < NSEG; s++) {
        float c0[4], c1[4];
        mem_pass<XP>(c0, c1, w, sb, aA0, aBf, g, warp, s);
        EV(EV_BIG0 && c0[0] != 1.2345e30f, s, 3);
        const uint32_t xs = aB + (RS_O - RS_MEM) + (warp - g) * 512;
        sts128f(xs + g * 2048, c1);
        auto combine = [&]() {
            const uint32_t d = sb + (XP ? (rank == 1 ? RS_K : RS_V) : RS_Q) + (g * 4 + warp) * 256 + lane0 * 4;
            const uint32_t rbar = XP ? mapa(sb + (rank == 1 ? RB_K : RB_V), 0) : 0u;
            nbar_sync(NB_PAIR + warp, 64);
            const uint4 v = lds128(xs + (g ^ 1) * 2048);
            const uint32_t p0 = pack_bf16(c0[0] + __uint_as_float(v.x), c0[1] + __uint_as_float(v.y));
            const uint32_t p1 = pack_bf16(c0[2] + __uint_as_float(v.z), c0[3] + __uint_as_float(v.w));
            if constexpr (XP) { st_async32(mapa(d, 0), p0, rbar); st_async32(mapa(d + 128, 0), p1, rbar); }
            else { sts32(d, p0); sts32(d + 128, p1); }
            EV(EV_BIG0, s, 4);
        };
        combine();
        if constexpr (XP) {
            if (s == NSEG - 1) break;
            x_half<0>(xa, w, sb, s + 1, g, warp, tmX);
            EV(EV_BIG0, s, 5);
            EVCAL(s);
            mbar_wait(sb + RB_XF + g * 8, 1);
            nbar_sync(NB_WO, 384);
            EV(EV_BIG0 && lds32(sb + RS_O) != 0x12345678u, s, 6);
            x_half<1>(xa, w, sb, s + 1, g, warp, tmX);
            EV(EV_BIG0, s, 7);
            x_finish(xa, sb, s + 1, g, warp, lane0, tmX);
        } else {
            if (g == 0) {
                if (s < NSEG - 1) mem_attn(sb, s, warp, lane0);
            } else {
                if (s < NSEG - 1) mem_scores(sb, s, warp, lane0); else mbar_wait(sb + RB_KV, s & 1);
                if (s == 0 && warp == 0) {
                    wait_count_warp(&g_cnt[C_QH], 64 * E);
                    if (elect_one()) {
                        asm volatile("fence.proxy.async;" ::: "memory");
                        mbar_expect_tx(sb + RB_QX, 8192);
                        bulk_load(sb + RS_QX, g_qx + (size_t)head * 4096, 8192, sb + RB_QX);
                    }
                    __syncwarp();
                }
                if (TA_LATE && s < NSEG - 1) mbar_wait(sb + RB_O, s & 1);
                float sc[8];
                const int t2 = warp == 3 ? 3 : (warp + 1) % 3;
                ta_scores(sc, sb, s, 4 + warp, lane0);
                ta_scores(sc + 4, sb, s, t2, lane0);
                nbar_sync(NB_WG + 1, 128);
                sts128f(aB + (RS_QX - RS_MEM) + (3 + warp) * 512, sc);
                sts128f(aB + (RS_QX - RS_MEM) + (t2 - 1) * 512, sc + 4);
            }
            EVCAL(s);
            if (s < NSEG - 1) nbar_sync(NB_WO, 384); else nbar_sync(NB_BIG, 256);
            EV(EV_BIG0 && lds32(sb + RS_O) != 0x12345678u, s, 6);
            ta_output(sb, s, head, g, warp, lane0);
            nbar_sync(NB_BIG, 256);
            EV(EV_BIG0 && lds32(sb + RS_O) != 0x12345678u, s, 7);
            if (g == 0 && warp == 0 && s + 1 < NSEG) {
                if (elect_one()) {
                    mbar_arrive_remote(mapa(sb + RB_ATT, 1));
                    mbar_arrive_remote(mapa(sb + RB_ATT, 2));
                    mbar_expect_tx(sb + RB_KV, 8192);
                    mbar_expect_tx(sb + RB_K, 2048);
                    mbar_expect_tx(sb + RB_V, 2048 + 8192);
                    mbar_arrive(sb + RB_T);
                }
                __syncwarp();
            }
        }
    }
    if constexpr (!XP) { if (tid_now() == 0) signal_count(&g_prog[(NSEG - 1) >> 2]); }
#undef lane0
}

template <int T, int K0, int K1>
DEVI void wo_part(float* acc) {
    constexpr uint32_t dWo = cdesc(T < 5 ? RS_WO + T * 16384 : RS_WO5, 16), dO = cdesc(RS_O, 128);
#pragma unroll
    for (int kk = K0; kk < K1; kk++) {
        if (kk == 0) { if (T < 3) wgmma_n8_ss_first<0>(acc, dWo, dO); else wgmma_n8_ss<0, 0>(acc, dWo, dO); }
        else wgmma_n8_ss<0, 1>(acc, dWo + kk * 128, dO + kk * 16);
    }
    wg_commit();
}
DEVI void red3(uint8_t* p, uint32_t a, uint32_t b, uint32_t c, uint32_t one) {
    asm volatile("red.relaxed.gpu.global.add.noftz.v4.bf16x2 [%0], {%1,%2,%3,%4};" :: "l"(p), "r"(a), "r"(b), "r"(c), "r"(one) : "memory");
}
constexpr int ACC_CH = 3 * 16 * 1024;
template <bool Q>
DEVI void wo_phase(uint32_t sb, int s, int warp, uint8_t* p, uint32_t ainv, int gap) {
    float a0[4], a1[4], a2[4];
    fence_proxy_async();
    const float2 iv = lds64f(ainv);
    SCHED_FENCE();
    const float i0 = rcp_fast(iv.x), i1 = rcp_fast(iv.y);
#define WORD(a, h) pack_bf16(a[2 * h] * i0, a[2 * h + 1] * i1)
    wg_fence();
    wo_part<0, 0, 8>(a0); wo_part<1, 0, 8>(a1); wo_part<2, 0, 8>(a2);
    if (!Q && WO_REL == 4) nbar_arrive(NB_WO, 384);
    wg_wait<1>(); reg_fence<4>(a0); reg_fence<4>(a1);
    if (!Q && WO_REL == 3) nbar_arrive(NB_WO, 384);
    red3(p, WORD(a0, 0), WORD(a0, 1), WORD(a1, 0), 0x3F80u);
    SCHED_FENCE();
    EV(warp == 0 && elect_one(), s, 11);
    wg_wait<0>(); reg_fence<4>(a2);
    if (!Q && WO_REL == 2) nbar_arrive(NB_WO, 384);
    red3(p + ACC_CH, WORD(a2, 0), WORD(a2, 1), WORD(a1, 1), 0x3F80u);
    SCHED_FENCE();
    if (Q || WO_REL < 2) { const uint32_t t = clk32() + gap; while ((int)(clk32() - t) < 0) { } }
    wg_fence();
    wo_part<3, 0, 8>(a0); wo_part<4, 0, 8>(a1);
    if (Q) {
        wo_part<5, 0, 8>(a2);
        wg_wait<1>(); reg_fence<4>(a0); reg_fence<4>(a1);
        red3(p + 2 * ACC_CH, WORD(a0, 0), WORD(a0, 1), WORD(a1, 0), 0x3F80u);
        SCHED_FENCE();
        wg_wait<0>(); reg_fence<4>(a2);
        red3(p + 3 * ACC_CH, WORD(a2, 0), WORD(a2, 1), WORD(a1, 1), 0x3F80u);
        nbar_arrive(NB_WO, 384);
    } else {
        wg_wait<1>();
        nbar_arrive(NB_WO, 384);
        wg_wait<0>(); reg_fence<4>(a0); reg_fence<4>(a1);
        red3(p + 2 * ACC_CH, WORD(a0, 0), WORD(a0, 1), WORD(a1, 0), 0x3F80u);
        red3(p + 3 * ACC_CH, 0u, 0u, WORD(a1, 1), 0x3F80u);
    }
#undef WORD
}
template <bool SEND>
DEVI void unit_put(uint32_t d, uint32_t x0, uint32_t x1, uint32_t x2, uint32_t x3, uint32_t bar, uint32_t nxt) {
    const uint32_t u0 = __byte_perm(x0, x1, 0x5410), u1 = __byte_perm(x2, x3, 0x5410), u2 = __byte_perm(x0, x1, 0x7632), u3 = __byte_perm(x2, x3, 0x7632);
    if (SEND) st_async128(mapa(d, nxt), u0, u1, u2, u3, mapa(bar, nxt));
    sts128(d, make_uint4(u0, u1, u2, u3));
}
template <bool SEND, int R>
DEVI void stage_round(uint32_t sb, int s, uint32_t rr, uint32_t nxt, int warp, const uint8_t* src, uint32_t col, uint32_t gate, uint32_t bytes) {
    uint4 v[4];
    while ((int)(clk32() - gate) < 0) { }
    EV(elect_one(), s, 16 + 2 * R + (warp & 1) + (warp & 2) * 50);
#pragma unroll
    for (int j = 0; j < 4; j++) v[j] = ld_rlx4(src + R * 2 * ACC_CH + j * 1024);
    const uint32_t bar = sb + RB_G + 8 * R, c0 = col + R * 3072;
    int n = 0;
    while (!__all_sync(0xffffffffu, v[0].w == 0x4200u && v[1].w == 0x4200u && v[2].w == 0x4200u && v[3].w == 0x4200u)) {
#pragma unroll
        for (int j = 0; j < 4; j++) v[j] = ld_rlx4(src + R * 2 * ACC_CH + j * 1024);
        if (++n > SPIN_LIMIT) TRAP(0x20000000u | (s << 8) | warp);
    }
    EV(elect_one(), s, 24 + 2 * R + (warp & 1) + (warp & 2) * 50);
    if (R == 0 || rr == 0 || !(warp & 1)) {
        unit_put<SEND>(c0 + (warp & 1) * 2048, v[0].x, v[1].x, v[2].x, v[3].x, bar, nxt);
        unit_put<SEND>((c0 ^ 160) + (warp & 1) * 2048, v[0].y, v[1].y, v[2].y, v[3].y, bar, nxt);
    }
    unit_put<SEND>((c0 ^ ((warp & 1) * 160)) + 1024, v[0].z, v[1].z, v[2].z, v[3].z, bar, nxt);
    __syncwarp();
    if (elect_one()) mbar_expect_tx(bar, bytes);
    EV(elect_one(), s, 20 + 2 * R + (warp & 1) + (warp & 2) * 50);
    SCHED_FENCE();
}
DEVI void wo_permute(uint32_t a, int n) {
    const uint32_t flip = (a >> 3) & 16;
#pragma unroll 2
    for (int i = 0; i < n; i++, a += 4096) {
        const uint4 v = lds128(a ^ flip), u = lds128(a ^ flip ^ 16);
        sts128(a ^ flip, make_uint4(__byte_perm(v.x, v.y, 0x5410), __byte_perm(v.x, v.y, 0x7632), __byte_perm(u.x, u.y, 0x5410), __byte_perm(u.x, u.y, 0x7632)));
        sts128(a ^ flip ^ 16, make_uint4(__byte_perm(v.z, v.w, 0x5410), __byte_perm(v.z, v.w, 0x7632), __byte_perm(u.z, u.w, 0x5410), __byte_perm(u.z, u.w, 0x7632)));
    }
}
DEVI uint32_t acc_clear(int slot, int idx, uint32_t lo) {
    uint8_t* p = g_acc + (uint32_t)(slot * 128 + idx * 3072 + (lo < 3072 ? lo : lo - 1024));
    st_rlx4(p, 0u, 0u, 0u, 0u);
    uint32_t z; asm volatile("ld.relaxed.gpu.global.u32 %0, [%1];" : "=r"(z) : "l"(p) : "memory");
    return z;
}

template <bool Q>
DEVI void aux_main(uint32_t sb, int warp, uint32_t rank, int head, const CUtensorMap* tmX, const bf16* xg, unsigned E, const int4 tune) {
    const uint32_t lo = __shfl_sync(0xffffffffu, ((tid_now() >> 3) & 3) * 1024 + (tid_now() & 7) * 16, tid_now() & 31);
    for (int s = 0; s < NSEG - 1; s++) {
        if (!Q && warp == 0 && elect_one()) mbar_expect_tx(sb + RB_O, 2048 + 256);
        __syncwarp();
        const uint32_t slot = (s & 3) * 128;
        mbar_wait(sb + RB_O, s & 1);
        EV(warp == 0 && elect_one(), s, 10);
        wo_phase<Q>(sb, s, warp, g_acc + (uint32_t)(slot + (rank * 4 + warp) * 4096 + opaque(lo)), sb + RS_INV + ((opaque(lo) >> 1) & 24), tune.z);
        SCHED_FENCE();
        const uint32_t t_o = clk32();
        EV(warp == 0 && elect_one(), s, 12);
        {
            const uint32_t l = opaque(lo), nxt = Q ? 1 : (rank == 1 ? 2 : 0), rr = warp < 2 ? rank : nxt;
            const uint8_t* src = g_acc + (uint32_t)(slot + rr * 16384 + (warp & 1) * ACC_CH + (l & 0xC00) * 4 + (l & 0x70));
            const uint32_t col = sb + RS_MEM + (rr == 0 ? 0 : rr * 5 + 1) * 1024 + ((l >> 2) & 0x300) + (l & 0x70);
            if (warp < 2) {
                stage_round<true, 0>(sb, s, rr, nxt, warp, src, col, t_o + tune.x, 1536u);
                stage_round<true, 1>(sb, s, rr, nxt, warp, src, col, t_o + tune.y, rank == 1 ? 1536u : 1024u);
            } else {
                stage_round<false, 0>(sb, s, rr, nxt, warp, src, col, t_o + tune.x, 0u);
                stage_round<false, 1>(sb, s, rr, nxt, warp, src, col, t_o + tune.y, 0u);
            }
        }
        EV(warp == 2 && elect_one(), s, 14);
        if (warp == 3) {
            if (Q) {
                mbar_wait(sb + RB_T, s & 1);
                if (s == 3) wait_count_warp(&g_cnt[C_Q], 64 * E);
                if (elect_one()) {
                    if (s == 3) asm volatile("fence.proxy.async;" ::: "memory"); else fence_proxy_async();
                    mbar_expect_tx(sb + RB_QX, 8192);
                    bulk_load(sb + RS_QX, g_qx + ((size_t)(s + 1) * NH + head) * 4096, 8192, sb + RB_QX);
                    if (head == 0) { TLOG(1400 + s, 0, gtime()); TLOG(1400 + s, 1, clock64()); }
                }
                __syncwarp();
                const bool fresh = (s & 7) == 6 && s + 2 < NSEG;
                if (fresh) wait_count_warp(&g_cnt[C_Q + ((s + 2) >> 3)], 64 * E);
                if (elect_one()) {
                    if (fresh) asm volatile("fence.proxy.async;" ::: "memory");
                    if (s + 2 < NSEG && s != 2) l2_prefetch(g_qx + ((size_t)(s + 2) * NH + head) * 4096, 8192);
                    if (s + 4 < NSEG) l2_prefetch(xg + (size_t)((s + 4) * 32 + head) * DM, 2048);
                    signal_count(&g_prog[s >> 2]);
                }
                __syncwarp();
            } else {
                const uint32_t zero = acc_clear((s + 2) & 3, 2 * head + (int)rank - 1, opaque(lo));
                mbar_wait(sb + RB_G + 8, s & 1);
                x_send(sb, s + 1, rank, tune.w);
                if (__any_sync(0xffffffffu, zero != 0u)) __trap();
            }
        }
    }
}

DEVI void load_weights(uint32_t sb, const CUtensorMap* tmW, const CUtensorMap* tmWo, int head, uint32_t rank) {
    const uint32_t bW = sb + RB_W, bSF = sb + RB_SF, bSE = sb + RB_SE;
    const int ntile = rank == 0 ? 6 : 5, tile0 = rank == 0 ? 0 : (rank == 1 ? 6 : 11);
    mbar_expect_tx(bW, R_NSS * 16384);
    mbar_expect_tx(sb + RB_WO, ntile * 16384);
    for (int pass = 0; pass < 2; pass++) {
        for (int pos = 0; pos < 16; pos++) {
            const int k = (int)((R_TORD_PACK >> (4 * pos)) & 15ull) * 64, rd = pos - pos / 3, slot = rd % 5;
            if (r_pos_ss(pos)) {
                if (pass) continue;
                const uint32_t dst = sb + RS_WSS + (pos / 3) * 16384;
                tma_load_2d(dst, tmW, head * DH, k, bW);
                tma_load_2d(dst + 8192, tmW, head * DH + 64, k, bW);
            } else if (pass == (rd >= 5)) {
                if (rd >= 5) mbar_wait(bSE + 8 * slot, ((rd / 5) - 1) & 1);
                mbar_expect_tx(bSF + 8 * slot, 16384);
                const uint32_t dst = sb + RS_WO + slot * 16384;
                tma_load_2d(dst, tmW, head * DH, k, bSF + 8 * slot);
                tma_load_2d(dst + 8192, tmW, head * DH + 64, k, bSF + 8 * slot);
            }
        }
    }
    if (rank == 0) tma_load_wo(sb + RS_WO5, tmWo, 5 * 64, head * 4, sb + RB_WO);
    for (int i = 1; i <= 5; i++) {
        const int slot = i % 5, last = slot + 10 < R_NRS ? slot + 10 : slot + 5;
        mbar_wait(bSE + 8 * slot, (last / 5) & 1);
        tma_load_wo(sb + RS_WO + slot * 16384, tmWo, (tile0 + slot) * 64, head * 4, sb + RB_WO);
    }
}
template <bool XP>
DEVI void big_prologue(uint32_t* w, uint32_t sb, int g, int warp, const bf16* __restrict__ mem0) {
    const int tid = tid_now(), lane = tid & 31;
    {
        const uint32_t* m = (const uint32_t*)(mem0 + (lane >> 2) * DM + (tid >> 5) * 16) + (lane & 3);
        uint32_t u[16];
#pragma unroll
        for (int j = 0; j < 8; j++) { u[2 * j] = m[j * 64]; u[2 * j + 1] = m[j * 64 + 4]; }
#pragma unroll
        for (int j = 0; j < 8; j++) sts64(sb + RS_MEM + ((tid >> 5) + j * 8) * 256 + b_frag_off(lane), u[2 * j], u[2 * j + 1]);
    }
    const uint32_t a0 = sb + RS_WO + g * (8192 + 4096) + a_frag_off(lane, warp), a1 = a0 + 8192 - g * 16384;
#pragma unroll
    for (int rd = 0; rd < R_NRS; rd++) {
        const int slot = rd % 5;
        mbar_wait(sb + RB_SF + 8 * slot, (rd / 5) & 1);
#pragma unroll
        for (int q = 0; q < 4; q++) {
            if (XP && rd == 0 && q == 3) {
                sts128(sb + RS_WX + g * 2048 + (tid & 127) * 16, lds128(sb + RS_WO + 8192 - g * 4096 + 2048 + (tid & 127) * 16));
                fence_proxy_async();
                nbar_sync(NB_WG + g, 128);
            } else ldsm4t(&w[rd * 16 + q * 4], ((q & 1) ? a1 : a0) + slot * 16384 + (q >> 1) * 2048);
        }
        mbar_arrive(sb + RB_SE + 8 * slot);
    }
    mbar_wait(sb + RB_W, 0);
}

__global__ void __cluster_dims__(3, 1, 1) __launch_bounds__(384, 1)
k_rec(const __grid_constant__ CUtensorMap tmWq, const __grid_constant__ CUtensorMap tmWk, const __grid_constant__ CUtensorMap tmWv,
      const __grid_constant__ CUtensorMap tmWo, const __grid_constant__ CUtensorMap tmX, const bf16* __restrict__ mem0, const bf16* __restrict__ xg,
      int4 tq, int4 tk) {
    extern __shared__ __align__(1024) uint8_t smem_raw[];
    const uint32_t sb = smem_u32(smem_raw);
    if ((sb & 0x3FFFFu) != SB0) __trap();
    const int tid = threadIdx.x;
    const int wg = __shfl_sync(0xffffffffu, tid >> 7, 0), warp = __shfl_sync(0xffffffffu, (tid >> 5) & 3, 0);
    uint32_t rank; asm("mov.u32 %0, %%cluster_ctarank;" : "=r"(rank));
    const int head = blockIdx.x / 3;
    asm volatile("griddepcontrol.launch_dependents;");
    if (tid == 0) {
        mbar_init(sb + RB_G, 4);
        mbar_init(sb + RB_G + 8, 4);
        mbar_init(sb + RB_T, 1); mbar_init(sb + RB_WO, 1);
        mbar_init(sb + RB_K, 1); mbar_init(sb + RB_V, 1); mbar_init(sb + RB_KV, 1); mbar_init(sb + RB_QX, 1);
        mbar_init(sb + RB_O, rank == 0 ? 4 : 1); mbar_init(sb + RB_ATT, 1); mbar_init(sb + RB_W, 1);
        for (int i = 0; i < 5; i++) { mbar_init(sb + RB_SF + 8 * i, 1); mbar_init(sb + RB_SE + 8 * i, 256); }
        for (int i = 0; i < 2; i++) mbar_init(sb + RB_XF + 8 * i, X_SLOTS);
        fence_mbar_init();
        if (rank == 0) { mbar_expect_tx(sb + RB_KV, 8192); mbar_expect_tx(sb + RB_K, 2048); mbar_expect_tx(sb + RB_V, 2048 + 8192); }
    }
    __syncthreads();
    cluster_sync();

    if (wg < 2) {
        reg_inc<REG_KB>();
        if (rank != 0) {
            uint32_t w[R_NRS * 16];
            if ((tid & 127) == 0) for (int j = 0; j < X_SLOTS; j++) x_load(sb, 0, j, wg, &tmX);
            __syncwarp();
            big_prologue<true>(w, sb, wg, warp, mem0);
            big_main<true>(w, sb, wg, warp, rank, head, &tmX, xg, 0u);
        } else {
            uint32_t w[R_NRS * 16];
            big_prologue<false>(w, sb, wg, warp, mem0);
            big_main<false>(w, sb, wg, warp, rank, head, &tmX, xg, *(volatile unsigned*)&g_epoch + 1);
        }
    } else {
        reg_dec<504 - 2 * REG_KB>();
        const unsigned E = __shfl_sync(0xffffffffu, *(volatile unsigned*)&g_epoch + 1, 0);
        if (warp == 3 && rank != 0) {
            const uint32_t lo = ((tid >> 3) & 3) * 1024 + (tid & 7) * 16;
            acc_clear(0, 2 * head + (int)rank - 1, lo); acc_clear(1, 2 * head + (int)rank - 1, lo);
            __threadfence();
            __syncwarp();
            if (tid == 256 + 96) atomicAdd(&g_zero, 1u);
        }
        if (tid == 256) {
            if (rank == 0) l2_prefetch(xg + (size_t)head * 8 * DM, 16384);
            load_weights(sb, rank == 0 ? &tmWq : (rank == 1 ? &tmWk : &tmWv), &tmWo, head, rank);
            wait_count(&g_zero, E * 64u);
        }
        __syncwarp();
        if (warp == 3 && rank != 0) x_send(sb, 0, rank, 0);
        mbar_wait(sb + RB_WO, 0);
        wo_permute(sb + RS_WO + (tid & 127) * 32, 20);
        if (rank == 0) wo_permute(sb + RS_WO5 + (tid & 127) * 32, 4);
        fence_proxy_async();
        nbar_sync(NB_AUX, 128);
        if (rank == 0) aux_main<true>(sb, warp, rank, head, &tmX, xg, E, tq);
        else           aux_main<false>(sb, warp, rank, head, &tmX, xg, E, tk);
    }
    __syncthreads();
    cluster_sync();
}

typedef CUresult (*EncodeFn)(CUtensorMap*, CUtensorMapDataType, cuuint32_t, void*, const cuuint64_t*, const cuuint64_t*,
                             const cuuint32_t*, const cuuint32_t*, CUtensorMapInterleave, CUtensorMapSwizzle,
                             CUtensorMapL2promotion, CUtensorMapFloatOOBfill);

static CUtensorMap make_map(EncodeFn fn, const void* ptr, uint64_t inner, uint64_t outer, uint32_t box_inner, uint32_t box_outer) {
    CUtensorMap m;
    cuuint64_t dims[2] = {inner, outer};
    cuuint64_t strides[1] = {inner * 2};
    cuuint32_t box[2] = {box_inner, box_outer};
    cuuint32_t es[2] = {1, 1};
    fn(&m, CU_TENSOR_MAP_DATA_TYPE_BFLOAT16, 2, const_cast<void*>(ptr), dims, strides, box, es,
       CU_TENSOR_MAP_INTERLEAVE_NONE, CU_TENSOR_MAP_SWIZZLE_128B, CU_TENSOR_MAP_L2_PROMOTION_L2_256B, CU_TENSOR_MAP_FLOAT_OOB_FILL_NONE);
    return m;
}

static CUtensorMap make_wo_map(EncodeFn fn, const void* ptr, uint32_t ngrp) {
    CUtensorMap m;
    cuuint64_t dims[5] = {DM, 2, 4, 4, HD / 32};
    cuuint64_t strides[4] = {DM * 2, 8 * DM * 2, 2 * DM * 2, 32 * DM * 2};
    cuuint32_t box[5] = {64, 2, 4, 4, ngrp};
    cuuint32_t es[5] = {1, 1, 1, 1, 1};
    fn(&m, CU_TENSOR_MAP_DATA_TYPE_BFLOAT16, 5, const_cast<void*>(ptr), dims, strides, box, es,
       CU_TENSOR_MAP_INTERLEAVE_NONE, CU_TENSOR_MAP_SWIZZLE_128B, CU_TENSOR_MAP_L2_PROMOTION_L2_256B, CU_TENSOR_MAP_FLOAT_OOB_FILL_NONE);
    return m;
}

struct Maps {
    PMaps post;
    CUtensorMap wq16, wk16, wv16, wo128, x32;
};

extern "C" void kernel_launch(void* const* d_in, const int* in_sizes, int n_in, void* d_out, int out_size) {
    const bf16* A_x   = (const bf16*)d_in[0];
    const bf16* A_mem = (const bf16*)d_in[1];
    const bf16* A_Wq  = (const bf16*)d_in[2];
    const bf16* A_Wk  = (const bf16*)d_in[3];
    const bf16* A_Wv  = (const bf16*)d_in[4];
    const bf16* A_Wo  = (const bf16*)d_in[5];
    const bf16* B_x   = (const bf16*)d_in[7];
    const bf16* B_w   = (const bf16*)d_in[8];
    const bf16* B_wo  = (const bf16*)d_in[9];

    static EncodeFn fn = nullptr;
    static Maps mp;
    static const void* cached[10];
    const void* cur[10] = {A_x, A_mem, A_Wq, A_Wk, A_Wv, A_Wo, B_x, B_w, B_wo, d_out};
    bool same = fn != nullptr;
    for (int i = 0; i < 10 && same; i++) same = cached[i] == cur[i];
    if (!same) {
        if (!fn) {
            void* p = nullptr; cudaDriverEntryPointQueryResult qr;
            cudaGetDriverEntryPoint("cuTensorMapEncodeTiled", &p, cudaEnableDefault, &qr);
            fn = (EncodeFn)p;
            cudaFuncSetAttribute(k_post, cudaFuncAttributeMaxDynamicSharedMemorySize, P_SMEM);
            cudaFuncSetAttribute(k_rec, cudaFuncAttributeMaxDynamicSharedMemorySize, R_SMEM);
        }
        void *p_ox, *p_bqkv, *p_bo, *p_qx;
        cudaGetSymbolAddress(&p_qx, g_qx);
        cudaGetSymbolAddress(&p_ox, g_ox); cudaGetSymbolAddress(&p_bqkv, g_bqkv); cudaGetSymbolAddress(&p_bo, g_bo);
        mp.post.wq   = make_map(fn, A_Wq, HD, DM, 64, 64);
        mp.post.wo   = make_wo_map(fn, A_Wo, 2);
        mp.post.bw   = make_map(fn, B_w, 3 * DM, DM, 64, 64);
        mp.post.bwo  = make_map(fn, B_wo, DM, DM, 64, 64);
        mp.post.x    = make_map(fn, A_x, DM, S_TOK, 64, 128);
        mp.post.bx   = make_map(fn, B_x, DM, S_TOK, 64, 128);
        mp.post.bo   = make_map(fn, p_bo, DM, S_TOK, 64, 128);
        mp.post.ox   = make_map(fn, p_ox, HD, S_TOK, 64, 128);
        mp.post.cb   = make_map(fn, p_bqkv, 3 * DM, S_TOK, 64, 64);
        mp.post.cout = make_map(fn, d_out, 2 * DM, S_TOK, 64, 64);
        {
            cuuint64_t dims[4] = {256, 4, NH * 4, NSEG};
            cuuint64_t strides[3] = {512, 2048, NH * 8192};
            cuuint32_t box[4] = {256, 2, 4, 2};
            cuuint32_t es[4] = {1, 1, 1, 1};
            fn(&mp.post.cq, CU_TENSOR_MAP_DATA_TYPE_BFLOAT16, 4, p_qx, dims, strides, box, es,
               CU_TENSOR_MAP_INTERLEAVE_NONE, CU_TENSOR_MAP_SWIZZLE_NONE, CU_TENSOR_MAP_L2_PROMOTION_NONE, CU_TENSOR_MAP_FLOAT_OOB_FILL_NONE);
        }
        {
            int runs[48] = {K_QH, 0, 2, K_Q, 1, 7, K_B1, 0, 8, K_A4, 0, 4, K_B2, 0, 32, K_A4, 4, 2, K_B3, 0, 4, K_A3, 12, 2, K_B3, 4, 4, K_SK, 14, 2, -1};
            const int per[8] = {32, 24, 8, 8, 32, 8, 32, 1};
            int n = 0, id = 0;
            for (; runs[3 * n] >= 0; n++) {
                mp.post.list.run[n] = make_int4(runs[3 * n], runs[3 * n + 1], id, id + runs[3 * n + 2] * per[runs[3 * n]]);
                id = mp.post.list.run[n].w;
            }
            mp.post.list.n = n;
        }
        {
            cuuint64_t dims[4] = {DM, 3, 2, S_TOK / 2};
            cuuint64_t strides[3] = {DM * 2, 3 * DM * 2, 3 * DM * 4};
            cuuint32_t box[4] = {64, 3, 1, 40};
            cuuint32_t es[4] = {1, 1, 1, 1};
            fn(&mp.post.b40, CU_TENSOR_MAP_DATA_TYPE_BFLOAT16, 4, p_bqkv, dims, strides, box, es,
               CU_TENSOR_MAP_INTERLEAVE_NONE, CU_TENSOR_MAP_SWIZZLE_128B, CU_TENSOR_MAP_L2_PROMOTION_L2_256B, CU_TENSOR_MAP_FLOAT_OOB_FILL_NONE);
        }
        mp.wq16 = make_map(fn, A_Wq, HD, DM, 64, 64);
        mp.wk16 = make_map(fn, A_Wk, HD, DM, 64, 64);
        mp.wv16 = make_map(fn, A_Wv, HD, DM, 64, 64);
        mp.wo128 = make_wo_map(fn, A_Wo, 4);
        {
            cuuint64_t dims[3] = {64, S_TOK, DM / 64};
            cuuint64_t strides[2] = {DM * 2, 128};
            cuuint32_t box[3] = {32, 32, 2};
            cuuint32_t es[3] = {1, 1, 1};
            fn(&mp.x32, CU_TENSOR_MAP_DATA_TYPE_BFLOAT16, 3, const_cast<bf16*>(A_x), dims, strides, box, es,
               CU_TENSOR_MAP_INTERLEAVE_NONE, CU_TENSOR_MAP_SWIZZLE_64B, CU_TENSOR_MAP_L2_PROMOTION_L2_128B, CU_TENSOR_MAP_FLOAT_OOB_FILL_NONE);
        }
        for (int i = 0; i < 10; i++) cached[i] = cur[i];
    }

    cudaStream_t st = cudaStreamPerThread;
    int4 tq = make_int4(250, 0, 80, 350), tk = make_int4(350, 0, 80, 200);
    k_rec<<<96, 384, R_SMEM, st>>>(mp.wq16, mp.wk16, mp.wv16, mp.wo128, mp.x32, A_mem, A_x, tq, tk);
    cudaLaunchConfig_t cfg = {};
    cfg.gridDim = dim3(132); cfg.blockDim = dim3(384); cfg.dynamicSmemBytes = P_SMEM; cfg.stream = st;
    cudaLaunchAttribute at[1];
    at[0].id = cudaLaunchAttributeProgrammaticStreamSerialization;
    at[0].val.programmaticStreamSerializationAllowed = 1;
    cfg.attrs = at; cfg.numAttrs = 1;
    cudaLaunchKernelEx(&cfg, k_post, mp.post);
}
```

```cpp
#include <cuda_runtime.h>
#include <cuda_bf16.h>
#include <cuda.h>
#include <stdint.h>

typedef __nv_bfloat16 bf16;

constexpr int S_TOK = 2048;
constexpr int DM    = 1024;
constexpr int NH    = 32;
constexpr int DH    = 128;
constexpr int NSEG  = 64;
constexpr int HD    = NH * DH;

__device__ __align__(1024) bf16 g_qx[NSEG * NH * 4 * DH * 8];
__device__ __align__(1024) bf16 g_ox[S_TOK * HD];
__device__ __align__(1024) bf16 g_bqkv[S_TOK * 3 * DM];
__device__ __align__(1024) bf16 g_bo[S_TOK * DM];
__device__ __align__(1024) uint8_t g_acc[192 * 1024];

#define EV(cond, s, k) do {} while (0)
#define EVCAL(s) do {} while (0)

constexpr int P_NSK = 4;
__device__ unsigned g_epoch, g_qctr, g_done, g_zero;
enum { C_B1 = 0, C_B2 = 8, C_Q = 16, C_QH = 24, C_NONE = 31 };
__device__ unsigned g_cnt[32], g_prog[16], g_cnt_sk[P_NSK * 16];
#define P_SPLIT 4
__device__ __align__(1024) uint4 g_skp[P_NSK * 8 * P_SPLIT * 2 * 8 * 128];
#define TLOG(i, k, v) do {} while (0)

#define DEVI __device__ __forceinline__

DEVI uint32_t opaque(uint32_t v) { uint32_t r; asm volatile("mov.u32 %0, %1;" : "=r"(r) : "r"(v)); return r; }
DEVI uint32_t smem_u32(const void* p) { return (uint32_t)__cvta_generic_to_shared(p); }

#define TRAP(code) __trap()
constexpr int SPIN_LIMIT = 1 << 22;
#define MBAR_HINT_NS 20000u
constexpr int SPIN_LIMIT_MBAR = 1 << 17;

DEVI void mbar_init(uint32_t bar, uint32_t cnt) { asm volatile("mbarrier.init.shared::cta.b64 [%0], %1;" :: "r"(bar), "r"(cnt)); }
DEVI void mbar_expect_tx(uint32_t bar, uint32_t bytes) {
    asm volatile("mbarrier.arrive.expect_tx.shared::cta.b64 _, [%0], %1;" :: "r"(bar), "r"(bytes) : "memory");
}
DEVI void mbar_arrive(uint32_t bar) { asm volatile("mbarrier.arrive.shared::cta.b64 _, [%0];" :: "r"(bar) : "memory"); }
DEVI bool mbar_try(uint32_t bar, uint32_t parity) {
    uint32_t ok;
    asm volatile("{.reg .pred p; mbarrier.try_wait.parity.shared::cta.b64 p, [%1], %2; selp.u32 %0, 1, 0, p;}"
                 : "=r"(ok) : "r"(bar), "r"(parity) : "memory");
    return ok;
}
DEVI bool mbar_try_cluster(uint32_t bar, uint32_t parity) {
    uint32_t ok;
    asm volatile("{.reg .pred p; mbarrier.try_wait.parity.acquire.cluster.shared::cta.b64 p, [%1], %2; selp.u32 %0, 1, 0, p;}"
                 : "=r"(ok) : "r"(bar), "r"(parity) : "memory");
    return ok;
}
DEVI bool mbar_try_hint(uint32_t bar, uint32_t parity) {
    uint32_t ok;
    asm volatile("{.reg .pred p; mbarrier.try_wait.parity.shared::cta.b64 p, [%1], %2, %3; selp.u32 %0, 1, 0, p;}"
                 : "=r"(ok) : "r"(bar), "r"(parity), "r"(MBAR_HINT_NS) : "memory");
    return ok;
}
DEVI void mbar_wait(uint32_t bar, uint32_t parity) {
    int n = 0;
    while (!mbar_try(bar, parity)) { if (++n > SPIN_LIMIT) TRAP(bar | (parity << 31)); }
}
DEVI void mbar_wait_sleepy(uint32_t bar, uint32_t parity) {
    int n = 0;
    while (!mbar_try_hint(bar, parity)) { if (++n > SPIN_LIMIT_MBAR) __trap(); }
}
DEVI void mbar_wait_cluster(uint32_t bar, uint32_t parity) {
    int n = 0;
    while (!mbar_try_cluster(bar, parity)) { if (++n > SPIN_LIMIT) __trap(); }
}
DEVI void mbar_spin(uint32_t bar, uint32_t parity) {
    uint32_t ok; int n = 0;
    do {
        asm volatile("{.reg .pred p; mbarrier.test_wait.parity.shared::cta.b64 p, [%1], %2; selp.u32 %0, 1, 0, p;}"
                     : "=r"(ok) : "r"(bar), "r"(parity) : "memory");
        if (++n > SPIN_LIMIT) __trap();
    } while (!ok);
}
DEVI void fence_mbar_init() { asm volatile("fence.mbarrier_init.release.cluster;" ::: "memory"); }
DEVI void fence_proxy_async() { asm volatile("fence.proxy.async.shared::cta;" ::: "memory"); }
DEVI void cluster_sync() {
    asm volatile("barrier.cluster.arrive.release.aligned;\n barrier.cluster.wait.acquire.aligned;" ::: "memory");
}
DEVI void cluster_wait() { asm volatile("barrier.cluster.wait.acquire.aligned;" ::: "memory"); }
DEVI void nbar_sync(int id, int n) { asm volatile("bar.sync %0, %1;" :: "r"(id), "r"(n) : "memory"); }
DEVI void nbar_arrive(int id, int n) { asm volatile("bar.arrive %0, %1;" :: "r"(id), "r"(n) : "memory"); }

DEVI void tma_load_2d(uint32_t dst, const CUtensorMap* map, int x, int y, uint32_t bar) {
    asm volatile("cp.async.bulk.tensor.2d.shared::cluster.global.mbarrier::complete_tx::bytes [%0], [%1, {%3, %4}], [%2];"
                 :: "r"(dst), "l"(map), "r"(bar), "r"(x), "r"(y) : "memory");
}
DEVI void tma_load_3d(uint32_t dst, const CUtensorMap* map, int x, int y, int z, uint32_t bar) {
    asm volatile("cp.async.bulk.tensor.3d.shared::cluster.global.mbarrier::complete_tx::bytes [%0], [%1, {%3, %4, %5}], [%2];"
                 :: "r"(dst), "l"(map), "r"(bar), "r"(x), "r"(y), "r"(z) : "memory");
}
DEVI void tma_load_wo(uint32_t dst, const CUtensorMap* map, int col, int k32, uint32_t bar) {
    asm volatile("cp.async.bulk.tensor.5d.shared::cluster.global.mbarrier::complete_tx::bytes [%0], [%1, {%3, %5, %5, %5, %4}], [%2];"
                 :: "r"(dst), "l"(map), "r"(bar), "r"(col), "r"(k32), "r"(0) : "memory");
}
DEVI void tma_store_2d(const CUtensorMap* map, uint32_t src, int x, int y) {
    asm volatile("cp.async.bulk.tensor.2d.global.shared::cta.bulk_group [%0, {%2, %3}], [%1];"
                 :: "l"(map), "r"(src), "r"(x), "r"(y) : "memory");
}
DEVI void bulk_load(uint32_t dst, const void* src, uint32_t bytes, uint32_t bar) {
    asm volatile("cp.async.bulk.shared::cluster.global.mbarrier::complete_tx::bytes [%0], [%1], %2, [%3];"
                 :: "r"(dst), "l"(src), "r"(bytes), "r"(bar) : "memory");
}
DEVI void tma_load_2d_mc(uint32_t dst, const CUtensorMap* map, int x, int y, uint32_t bar, uint16_t mask) {
    asm volatile("cp.async.bulk.tensor.2d.shared::cluster.global.mbarrier::complete_tx::bytes.multicast::cluster [%0], [%1, {%3, %4}], [%2], %5;"
                 :: "r"(dst), "l"(map), "r"(bar), "r"(x), "r"(y), "h"(mask) : "memory");
}
DEVI void bulk_copy_s2c(uint32_t dst_cluster, uint32_t src, uint32_t bytes, uint32_t bar_cluster) {
    asm volatile("cp.async.bulk.shared::cluster.shared::cta.mbarrier::complete_tx::bytes [%0], [%1], %2, [%3];"
                 :: "r"(dst_cluster), "r"(src), "r"(bytes), "r"(bar_cluster) : "memory");
}
DEVI void bulk_store(void* dst, uint32_t src, uint32_t bytes) {
    asm volatile("cp.async.bulk.global.shared::cta.bulk_group [%0], [%1], %2;" :: "l"(dst), "r"(src), "r"(bytes) : "memory");
}
DEVI void bulk_wait_read() { asm volatile("cp.async.bulk.wait_group.read 0;" ::: "memory"); }
DEVI void mbar_arrive_remote(uint32_t bar_cluster) {
    asm volatile("mbarrier.arrive.shared::cluster.b64 _, [%0];" :: "r"(bar_cluster) : "memory");
}
DEVI void mbar_expect_tx_remote(uint32_t bar_cluster, uint32_t bytes) {
    asm volatile("mbarrier.arrive.expect_tx.shared::cluster.b64 _, [%0], %1;" :: "r"(bar_cluster), "r"(bytes) : "memory");
}
DEVI void l2_prefetch(const void* p, uint32_t bytes) {
    asm volatile("cp.async.bulk.prefetch.L2.global [%0], %1;" :: "l"(p), "r"(bytes) : "memory");
}
DEVI void bulk_commit() { asm volatile("cp.async.bulk.commit_group;" ::: "memory"); }
DEVI void bulk_wait_all() { asm volatile("cp.async.bulk.wait_group 0;" ::: "memory"); }

DEVI void wg_fence() { asm volatile("wgmma.fence.sync.aligned;" ::: "memory"); }
DEVI void wg_commit() { asm volatile("wgmma.commit_group.sync.aligned;" ::: "memory"); }
template <int N> DEVI void wg_wait() { asm volatile("wgmma.wait_group.sync.aligned %0;" :: "n"(N) : "memory"); }

template <int R> DEVI void reg_dec() { asm volatile("setmaxnreg.dec.sync.aligned.u32 %0;" :: "n"(R)); }
template <int R> DEVI void reg_inc() { asm volatile("setmaxnreg.inc.sync.aligned.u32 %0;" :: "n"(R)); }

DEVI uint64_t mk_desc(uint32_t addr, uint32_t lbo, uint32_t sbo, uint32_t sw) {
    return (uint64_t)((addr & 0x3FFFF) >> 4) | ((uint64_t)(lbo >> 4) << 16) | ((uint64_t)(sbo >> 4) << 32) | ((uint64_t)sw << 62);
}

DEVI uint32_t desc_lo(uint32_t addr, uint32_t lbo) { return ((addr & 0x3FFFF) >> 4) | ((lbo >> 4) << 16); }
constexpr uint32_t DHI_SW128 = (1024u >> 4) | (1u << 30);
constexpr uint32_t DHI_SW64  = (512u >> 4) | (2u << 30);
constexpr uint32_t DHI_NONE  = (128u >> 4);

template <int TB, int SCALE_D>
DEVI void wgmma_n8_ss(float* d, uint32_t alo, uint32_t blo) {
    asm volatile("{.reg .b64 da, db; mov.b64 da, {%4, %6}; mov.b64 db, {%5, %7};\n"
                 "wgmma.mma_async.sync.aligned.m64n8k16.f32.bf16.bf16 {%0,%1,%2,%3}, da, db, %8, 1, 1, 1, %9;}"
                 : "+f"(d[0]), "+f"(d[1]), "+f"(d[2]), "+f"(d[3])
                 : "r"(alo), "r"(blo), "n"(DHI_SW128), "n"(DHI_NONE), "n"(SCALE_D), "n"(TB));
}

template <int TB>
DEVI void wgmma_n8_ss_first(float* d, uint32_t alo, uint32_t blo) {
    asm volatile("{.reg .b64 da, db; mov.b64 da, {%4, %6}; mov.b64 db, {%5, %7};\n"
                 "wgmma.mma_async.sync.aligned.m64n8k16.f32.bf16.bf16 {%0,%1,%2,%3}, da, db, 0, 1, 1, 1, %8;}"
                 : "=f"(d[0]), "=f"(d[1]), "=f"(d[2]), "=f"(d[3])
                 : "r"(alo), "r"(blo), "n"(DHI_SW128), "n"(DHI_NONE), "n"(TB));
}
DEVI void wgmma_n32_rs_first(float* d, const uint32_t* a, uint32_t blo) {
    asm volatile("{.reg .b64 db; mov.b64 db, {%20, %21};\n"
                 "wgmma.mma_async.sync.aligned.m64n32k16.f32.bf16.bf16 {%0,%1,%2,%3,%4,%5,%6,%7,%8,%9,%10,%11,%12,%13,%14,%15}, "
                 "{%16,%17,%18,%19}, db, 0, 1, 1, 0;}"
                 : "=f"(d[0]), "=f"(d[1]), "=f"(d[2]), "=f"(d[3]), "=f"(d[4]), "=f"(d[5]), "=f"(d[6]), "=f"(d[7]),
                   "=f"(d[8]), "=f"(d[9]), "=f"(d[10]), "=f"(d[11]), "=f"(d[12]), "=f"(d[13]), "=f"(d[14]), "=f"(d[15])
                 : "r"(a[0]), "r"(a[1]), "r"(a[2]), "r"(a[3]), "r"(blo), "n"(DHI_SW64));
}
template <int N> DEVI void reg_fence(float* d) {
#pragma unroll
    for (int i = 0; i < N; i++) asm volatile("" : "+f"(d[i]) :: "memory");
}
DEVI void wgmma_n32_rs(float* d, const uint32_t* a, uint32_t blo) {
    asm volatile("{.reg .b64 db; mov.b64 db, {%20, %21};\n"
                 "wgmma.mma_async.sync.aligned.m64n32k16.f32.bf16.bf16 {%0,%1,%2,%3,%4,%5,%6,%7,%8,%9,%10,%11,%12,%13,%14,%15}, "
                 "{%16,%17,%18,%19}, db, 1, 1, 1, 0;}"
                 : "+f"(d[0]), "+f"(d[1]), "+f"(d[2]), "+f"(d[3]), "+f"(d[4]), "+f"(d[5]), "+f"(d[6]), "+f"(d[7]),
                   "+f"(d[8]), "+f"(d[9]), "+f"(d[10]), "+f"(d[11]), "+f"(d[12]), "+f"(d[13]), "+f"(d[14]), "+f"(d[15])
                 : "r"(a[0]), "r"(a[1]), "r"(a[2]), "r"(a[3]), "r"(blo), "n"(DHI_SW64));
}
DEVI void wgmma_n32_ss(float* d, uint32_t alo, uint32_t blo) {
    asm volatile("{.reg .b64 da, db; mov.b64 da, {%16, %18}; mov.b64 db, {%17, %19};\n"
                 "wgmma.mma_async.sync.aligned.m64n32k16.f32.bf16.bf16 {%0,%1,%2,%3,%4,%5,%6,%7,%8,%9,%10,%11,%12,%13,%14,%15}, "
                 "da, db, 1, 1, 1, 1, 0;}"
                 : "+f"(d[0]), "+f"(d[1]), "+f"(d[2]), "+f"(d[3]), "+f"(d[4]), "+f"(d[5]), "+f"(d[6]), "+f"(d[7]),
                   "+f"(d[8]), "+f"(d[9]), "+f"(d[10]), "+f"(d[11]), "+f"(d[12]), "+f"(d[13]), "+f"(d[14]), "+f"(d[15])
                 : "r"(alo), "r"(blo), "n"(DHI_SW128), "n"(DHI_SW64));
}

template <bool FIRST>
DEVI void wgmma_n256_ss(float* d, uint64_t a, uint64_t b) {
    if (FIRST)
        asm volatile("wgmma.mma_async.sync.aligned.m64n256k16.f32.bf16.bf16 {%0,%1,%2,%3,%4,%5,%6,%7,%8,%9,%10,%11,%12,%13,%14,%15,%16,%17,%18,%19,%20,%21,%22,%23,%24,%25,%26,%27,%28,%29,%30,%31,%32,%33,%34,%35,%36,%37,%38,%39,%40,%41,%42,%43,%44,%45,%46,%47,%48,%49,%50,%51,%52,%53,%54,%55,%56,%57,%58,%59,%60,%61,%62,%63,%64,%65,%66,%67,%68,%69,%70,%71,%72,%73,%74,%75,%76,%77,%78,%79,%80,%81,%82,%83,%84,%85,%86,%87,%88,%89,%90,%91,%92,%93,%94,%95,%96,%97,%98,%99,%100,%101,%102,%103,%104,%105,%106,%107,%108,%109,%110,%111,%112,%113,%114,%115,%116,%117,%118,%119,%120,%121,%122,%123,%124,%125,%126,%127}, %128, %129, 0, 1, 1, 1, 0;"
            : "=f"(d[0]), "=f"(d[1]), "=f"(d[2]), "=f"(d[3]), "=f"(d[4]), "=f"(d[5]), "=f"(d[6]), "=f"(d[7]), "=f"(d[8]), "=f"(d[9]), "=f"(d[10]), "=f"(d[11]), "=f"(d[12]), "=f"(d[13]), "=f"(d[14]), "=f"(d[15]), "=f"(d[16]), "=f"(d[17]), "=f"(d[18]), "=f"(d[19]), "=f"(d[20]), "=f"(d[21]), "=f"(d[22]), "=f"(d[23]), "=f"(d[24]), "=f"(d[25]), "=f"(d[26]), "=f"(d[27]), "=f"(d[28]), "=f"(d[29]), "=f"(d[30]), "=f"(d[31]), "=f"(d[32]), "=f"(d[33]), "=f"(d[34]), "=f"(d[35]), "=f"(d[36]), "=f"(d[37]), "=f"(d[38]), "=f"(d[39]), "=f"(d[40]), "=f"(d[41]), "=f"(d[42]), "=f"(d[43]), "=f"(d[44]), "=f"(d[45]), "=f"(d[46]), "=f"(d[47]), "=f"(d[48]), "=f"(d[49]), "=f"(d[50]), "=f"(d[51]), "=f"(d[52]), "=f"(d[53]), "=f"(d[54]), "=f"(d[55]), "=f"(d[56]), "=f"(d[57]), "=f"(d[58]), "=f"(d[59]), "=f"(d[60]), "=f"(d[61]), "=f"(d[62]), "=f"(d[63]), "=f"(d[64]), "=f"(d[65]), "=f"(d[66]), "=f"(d[67]), "=f"(d[68]), "=f"(d[69]), "=f"(d[70]), "=f"(d[71]), "=f"(d[72]), "=f"(d[73]), "=f"(d[74]), "=f"(d[75]), "=f"(d[76]), "=f"(d[77]), "=f"(d[78]), "=f"(d[79]), "=f"(d[80]), "=f"(d[81]), "=f"(d[82]), "=f"(d[83]), "=f"(d[84]), "=f"(d[85]), "=f"(d[86]), "=f"(d[87]), "=f"(d[88]), "=f"(d[89]), "=f"(d[90]), "=f"(d[91]), "=f"(d[92]), "=f"(d[93]), "=f"(d[94]), "=f"(d[95]), "=f"(d[96]), "=f"(d[97]), "=f"(d[98]), "=f"(d[99]), "=f"(d[100]), "=f"(d[101]), "=f"(d[102]), "=f"(d[103]), "=f"(d[104]), "=f"(d[105]), "=f"(d[106]), "=f"(d[107]), "=f"(d[108]), "=f"(d[109]), "=f"(d[110]), "=f"(d[111]), "=f"(d[112]), "=f"(d[113]), "=f"(d[114]), "=f"(d[115]), "=f"(d[116]), "=f"(d[117]), "=f"(d[118]), "=f"(d[119]), "=f"(d[120]), "=f"(d[121]), "=f"(d[122]), "=f"(d[123]), "=f"(d[124]), "=f"(d[125]), "=f"(d[126]), "=f"(d[127]) : "l"(a), "l"(b));
    else
        asm volatile("wgmma.mma_async.sync.aligned.m64n256k16.f32.bf16.bf16 {%0,%1,%2,%3,%4,%5,%6,%7,%8,%9,%10,%11,%12,%13,%14,%15,%16,%17,%18,%19,%20,%21,%22,%23,%24,%25,%26,%27,%28,%29,%30,%31,%32,%33,%34,%35,%36,%37,%38,%39,%40,%41,%42,%43,%44,%45,%46,%47,%48,%49,%50,%51,%52,%53,%54,%55,%56,%57,%58,%59,%60,%61,%62,%63,%64,%65,%66,%67,%68,%69,%70,%71,%72,%73,%74,%75,%76,%77,%78,%79,%80,%81,%82,%83,%84,%85,%86,%87,%88,%89,%90,%91,%92,%93,%94,%95,%96,%97,%98,%99,%100,%101,%102,%103,%104,%105,%106,%107,%108,%109,%110,%111,%112,%113,%114,%115,%116,%117,%118,%119,%120,%121,%122,%123,%124,%125,%126,%127}, %128, %129, 1, 1, 1, 1, 0;"
            : "+f"(d[0]), "+f"(d[1]), "+f"(d[2]), "+f"(d[3]), "+f"(d[4]), "+f"(d[5]), "+f"(d[6]), "+f"(d[7]), "+f"(d[8]), "+f"(d[9]), "+f"(d[10]), "+f"(d[11]), "+f"(d[12]), "+f"(d[13]), "+f"(d[14]), "+f"(d[15]), "+f"(d[16]), "+f"(d[17]), "+f"(d[18]), "+f"(d[19]), "+f"(d[20]), "+f"(d[21]), "+f"(d[22]), "+f"(d[23]), "+f"(d[24]), "+f"(d[25]), "+f"(d[26]), "+f"(d[27]), "+f"(d[28]), "+f"(d[29]), "+f"(d[30]), "+f"(d[31]), "+f"(d[32]), "+f"(d[33]), "+f"(d[34]), "+f"(d[35]), "+f"(d[36]), "+f"(d[37]), "+f"(d[38]), "+f"(d[39]), "+f"(d[40]), "+f"(d[41]), "+f"(d[42]), "+f"(d[43]), "+f"(d[44]), "+f"(d[45]), "+f"(d[46]), "+f"(d[47]), "+f"(d[48]), "+f"(d[49]), "+f"(d[50]), "+f"(d[51]), "+f"(d[52]), "+f"(d[53]), "+f"(d[54]), "+f"(d[55]), "+f"(d[56]), "+f"(d[57]), "+f"(d[58]), "+f"(d[59]), "+f"(d[60]), "+f"(d[61]), "+f"(d[62]), "+f"(d[63]), "+f"(d[64]), "+f"(d[65]), "+f"(d[66]), "+f"(d[67]), "+f"(d[68]), "+f"(d[69]), "+f"(d[70]), "+f"(d[71]), "+f"(d[72]), "+f"(d[73]), "+f"(d[74]), "+f"(d[75]), "+f"(d[76]), "+f"(d[77]), "+f"(d[78]), "+f"(d[79]), "+f"(d[80]), "+f"(d[81]), "+f"(d[82]), "+f"(d[83]), "+f"(d[84]), "+f"(d[85]), "+f"(d[86]), "+f"(d[87]), "+f"(d[88]), "+f"(d[89]), "+f"(d[90]), "+f"(d[91]), "+f"(d[92]), "+f"(d[93]), "+f"(d[94]), "+f"(d[95]), "+f"(d[96]), "+f"(d[97]), "+f"(d[98]), "+f"(d[99]), "+f"(d[100]), "+f"(d[101]), "+f"(d[102]), "+f"(d[103]), "+f"(d[104]), "+f"(d[105]), "+f"(d[106]), "+f"(d[107]), "+f"(d[108]), "+f"(d[109]), "+f"(d[110]), "+f"(d[111]), "+f"(d[112]), "+f"(d[113]), "+f"(d[114]), "+f"(d[115]), "+f"(d[116]), "+f"(d[117]), "+f"(d[118]), "+f"(d[119]), "+f"(d[120]), "+f"(d[121]), "+f"(d[122]), "+f"(d[123]), "+f"(d[124]), "+f"(d[125]), "+f"(d[126]), "+f"(d[127]) : "l"(a), "l"(b));
}
template <bool FIRST>
DEVI void wgmma_n128_ss(float* d, uint64_t a, uint64_t b) {
    if (FIRST)
        asm volatile("wgmma.mma_async.sync.aligned.m64n128k16.f32.bf16.bf16 {%0,%1,%2,%3,%4,%5,%6,%7,%8,%9,%10,%11,%12,%13,%14,%15,%16,%17,%18,%19,%20,%21,%22,%23,%24,%25,%26,%27,%28,%29,%30,%31,%32,%33,%34,%35,%36,%37,%38,%39,%40,%41,%42,%43,%44,%45,%46,%47,%48,%49,%50,%51,%52,%53,%54,%55,%56,%57,%58,%59,%60,%61,%62,%63}, %64, %65, 0, 1, 1, 1, 0;"
            : "=f"(d[0]), "=f"(d[1]), "=f"(d[2]), "=f"(d[3]), "=f"(d[4]), "=f"(d[5]), "=f"(d[6]), "=f"(d[7]), "=f"(d[8]), "=f"(d[9]), "=f"(d[10]), "=f"(d[11]), "=f"(d[12]), "=f"(d[13]), "=f"(d[14]), "=f"(d[15]), "=f"(d[16]), "=f"(d[17]), "=f"(d[18]), "=f"(d[19]), "=f"(d[20]), "=f"(d[21]), "=f"(d[22]), "=f"(d[23]), "=f"(d[24]), "=f"(d[25]), "=f"(d[26]), "=f"(d[27]), "=f"(d[28]), "=f"(d[29]), "=f"(d[30]), "=f"(d[31]), "=f"(d[32]), "=f"(d[33]), "=f"(d[34]), "=f"(d[35]), "=f"(d[36]), "=f"(d[37]), "=f"(d[38]), "=f"(d[39]), "=f"(d[40]), "=f"(d[41]), "=f"(d[42]), "=f"(d[43]), "=f"(d[44]), "=f"(d[45]), "=f"(d[46]), "=f"(d[47]), "=f"(d[48]), "=f"(d[49]), "=f"(d[50]), "=f"(d[51]), "=f"(d[52]), "=f"(d[53]), "=f"(d[54]), "=f"(d[55]), "=f"(d[56]), "=f"(d[57]), "=f"(d[58]), "=f"(d[59]), "=f"(d[60]), "=f"(d[61]), "=f"(d[62]), "=f"(d[63]) : "l"(a), "l"(b));
    else
        asm volatile("wgmma.mma_async.sync.aligned.m64n128k16.f32.bf16.bf16 {%0,%1,%2,%3,%4,%5,%6,%7,%8,%9,%10,%11,%12,%13,%14,%15,%16,%17,%18,%19,%20,%21,%22,%23,%24,%25,%26,%27,%28,%29,%30,%31,%32,%33,%34,%35,%36,%37,%38,%39,%40,%41,%42,%43,%44,%45,%46,%47,%48,%49,%50,%51,%52,%53,%54,%55,%56,%57,%58,%59,%60,%61,%62,%63}, %64, %65, 1, 1, 1, 1, 0;"
            : "+f"(d[0]), "+f"(d[1]), "+f"(d[2]), "+f"(d[3]), "+f"(d[4]), "+f"(d[5]), "+f"(d[6]), "+f"(d[7]), "+f"(d[8]), "+f"(d[9]), "+f"(d[10]), "+f"(d[11]), "+f"(d[12]), "+f"(d[13]), "+f"(d[14]), "+f"(d[15]), "+f"(d[16]), "+f"(d[17]), "+f"(d[18]), "+f"(d[19]), "+f"(d[20]), "+f"(d[21]), "+f"(d[22]), "+f"(d[23]), "+f"(d[24]), "+f"(d[25]), "+f"(d[26]), "+f"(d[27]), "+f"(d[28]), "+f"(d[29]), "+f"(d[30]), "+f"(d[31]), "+f"(d[32]), "+f"(d[33]), "+f"(d[34]), "+f"(d[35]), "+f"(d[36]), "+f"(d[37]), "+f"(d[38]), "+f"(d[39]), "+f"(d[40]), "+f"(d[41]), "+f"(d[42]), "+f"(d[43]), "+f"(d[44]), "+f"(d[45]), "+f"(d[46]), "+f"(d[47]), "+f"(d[48]), "+f"(d[49]), "+f"(d[50]), "+f"(d[51]), "+f"(d[52]), "+f"(d[53]), "+f"(d[54]), "+f"(d[55]), "+f"(d[56]), "+f"(d[57]), "+f"(d[58]), "+f"(d[59]), "+f"(d[60]), "+f"(d[61]), "+f"(d[62]), "+f"(d[63]) : "l"(a), "l"(b));
}

DEVI void mma16816(float* d, const uint32_t* a, uint32_t b0, uint32_t b1) {
    asm volatile("mma.sync.aligned.m16n8k16.row.col.f32.bf16.bf16.f32 {%0,%1,%2,%3}, {%4,%5,%6,%7}, {%8,%9}, {%0,%1,%2,%3};"
                 : "+f"(d[0]), "+f"(d[1]), "+f"(d[2]), "+f"(d[3])
                 : "r"(a[0]), "r"(a[1]), "r"(a[2]), "r"(a[3]), "r"(b0), "r"(b1));
}
DEVI void mma1688(float* d, uint32_t a0, uint32_t a1, uint32_t b0) {
    asm volatile("mma.sync.aligned.m16n8k8.row.col.f32.bf16.bf16.f32 {%0,%1,%2,%3}, {%4,%5}, {%6}, {%0,%1,%2,%3};"
                 : "+f"(d[0]), "+f"(d[1]), "+f"(d[2]), "+f"(d[3]) : "r"(a0), "r"(a1), "r"(b0));
}
DEVI void ldsm4(uint32_t* r, uint32_t addr) {
    asm volatile("ldmatrix.sync.aligned.m8n8.x4.shared.b16 {%0,%1,%2,%3}, [%4];"
                 : "=r"(r[0]), "=r"(r[1]), "=r"(r[2]), "=r"(r[3]) : "r"(addr) : "memory");
}
DEVI void ldsm4t(uint32_t* r, uint32_t addr) {
    asm volatile("ldmatrix.sync.aligned.m8n8.x4.trans.shared.b16 {%0,%1,%2,%3}, [%4];"
                 : "=r"(r[0]), "=r"(r[1]), "=r"(r[2]), "=r"(r[3]) : "r"(addr) : "memory");
}
DEVI void ldsm2(uint32_t* r, uint32_t addr) {
    asm volatile("ldmatrix.sync.aligned.m8n8.x2.shared.b16 {%0,%1}, [%2];" : "=r"(r[0]), "=r"(r[1]) : "r"(addr) : "memory");
}
DEVI void ldsm1t(uint32_t& r, uint32_t addr) {
    asm volatile("ldmatrix.sync.aligned.m8n8.x1.trans.shared.b16 {%0}, [%1];" : "=r"(r) : "r"(addr) : "memory");
}
DEVI void stsm4(uint32_t addr, uint32_t r0, uint32_t r1, uint32_t r2, uint32_t r3) {
    asm volatile("stmatrix.sync.aligned.m8n8.x4.shared.b16 [%0], {%1,%2,%3,%4};" :: "r"(addr), "r"(r0), "r"(r1), "r"(r2), "r"(r3) : "memory");
}
DEVI void stsm4t(uint32_t addr, uint32_t r0, uint32_t r1, uint32_t r2, uint32_t r3) {
    asm volatile("stmatrix.sync.aligned.m8n8.x4.trans.shared.b16 [%0], {%1,%2,%3,%4};" :: "r"(addr), "r"(r0), "r"(r1), "r"(r2), "r"(r3) : "memory");
}
DEVI uint32_t movm_t(uint32_t a) {
    uint32_t d; asm volatile("movmatrix.sync.aligned.m8n8.trans.b16 %0, %1;" : "=r"(d) : "r"(a)); return d;
}
DEVI uint32_t pack_bf16(float lo, float hi) {
    uint32_t r; asm("cvt.rn.bf16x2.f32 %0, %1, %2;" : "=r"(r) : "f"(hi), "f"(lo)); return r;
}
DEVI float ex2(float x) { float y; asm("ex2.approx.ftz.f32 %0, %1;" : "=f"(y) : "f"(x)); return y; }

DEVI uint4 ld_rlx4(const void* p) {
    uint4 v;
    asm volatile("ld.relaxed.gpu.global.v4.u32 {%0,%1,%2,%3}, [%4];" : "=r"(v.x), "=r"(v.y), "=r"(v.z), "=r"(v.w) : "l"(p) : "memory");
    return v;
}
DEVI void ld_rlx4f(float* d, const void* p) {
    asm volatile("ld.relaxed.gpu.global.v4.f32 {%0,%1,%2,%3}, [%4];" : "=f"(d[0]), "=f"(d[1]), "=f"(d[2]), "=f"(d[3]) : "l"(p) : "memory");
}
DEVI bool all_nzf(const float* d) { return __float_as_uint(d[0]) && __float_as_uint(d[1]) && __float_as_uint(d[2]) && __float_as_uint(d[3]); }
DEVI void sts128f(uint32_t addr, const float* d) {
    asm volatile("st.shared.v4.f32 [%0], {%1,%2,%3,%4};" :: "r"(addr), "f"(d[0]), "f"(d[1]), "f"(d[2]), "f"(d[3]) : "memory");
}
DEVI void st_rlx4(void* p, uint32_t a, uint32_t b, uint32_t c, uint32_t d) {
    asm volatile("st.relaxed.gpu.global.v4.u32 [%0], {%1,%2,%3,%4};" :: "l"(p), "r"(a), "r"(b), "r"(c), "r"(d) : "memory");
}
DEVI void st_rlx(void* p, uint32_t v) { asm volatile("st.relaxed.gpu.global.u32 [%0], %1;" :: "l"(p), "r"(v) : "memory"); }
DEVI void sts128(uint32_t addr, uint4 v) {
    asm volatile("st.shared.v4.u32 [%0], {%1,%2,%3,%4};" :: "r"(addr), "r"(v.x), "r"(v.y), "r"(v.z), "r"(v.w) : "memory");
}
DEVI void sts64(uint32_t addr, uint32_t a, uint32_t b) { asm volatile("st.shared.v2.u32 [%0], {%1,%2};" :: "r"(addr), "r"(a), "r"(b) : "memory"); }
DEVI void sts32(uint32_t addr, uint32_t v) { asm volatile("st.shared.u32 [%0], %1;" :: "r"(addr), "r"(v) : "memory"); }
DEVI uint4 lds128(uint32_t addr) {
    uint4 v; asm volatile("ld.shared.v4.u32 {%0,%1,%2,%3}, [%4];" : "=r"(v.x), "=r"(v.y), "=r"(v.z), "=r"(v.w) : "r"(addr) : "memory"); return v;
}
DEVI float2 lds64f(uint32_t addr) {
    float2 v; asm volatile("ld.shared.v2.f32 {%0,%1}, [%2];" : "=f"(v.x), "=f"(v.y) : "r"(addr) : "memory"); return v;
}
DEVI void cp_async16(uint32_t dst, const void* src) {
    asm volatile("cp.async.cg.shared.global [%0], [%1], 16;" :: "r"(dst), "l"(src) : "memory");
}
DEVI void cp_async_commit() { asm volatile("cp.async.commit_group;" ::: "memory"); }
DEVI void cp_async_wait0() { asm volatile("cp.async.wait_group 0;" ::: "memory"); }
DEVI uint32_t lds32(uint32_t addr) { uint32_t v; asm volatile("ld.shared.u32 %0, [%1];" : "=r"(v) : "r"(addr) : "memory"); return v; }
DEVI float rcp_fast(float x) { float y; asm("rcp.approx.ftz.f32 %0, %1;" : "=f"(y) : "f"(x)); return y; }
DEVI bool all_nz(const uint4& v) { return v.x && v.y && v.z && v.w; }
DEVI uint32_t mapa(uint32_t addr, uint32_t rank) {
    uint32_t r; asm("mapa.shared::cluster.u32 %0, %1, %2;" : "=r"(r) : "r"(addr), "r"(rank)); return r;
}
DEVI void st_async32(uint32_t dst, uint32_t a, uint32_t bar) {
    asm volatile("st.async.weak.shared::cluster.mbarrier::complete_tx::bytes.b32 [%0], %1, [%2];" :: "r"(dst), "r"(a), "r"(bar) : "memory");
}
DEVI void st_async64(uint32_t dst, uint32_t a, uint32_t b, uint32_t bar) {
    asm volatile("st.async.weak.shared::cluster.mbarrier::complete_tx::bytes.v2.b32 [%0], {%1,%2}, [%3];"
                 :: "r"(dst), "r"(a), "r"(b), "r"(bar) : "memory");
}

DEVI void st_async128(uint32_t dst, uint32_t a, uint32_t b, uint32_t c, uint32_t d, uint32_t bar) {
    asm volatile("st.async.weak.shared::cluster.mbarrier::complete_tx::bytes.v4.b32 [%0], {%1,%2,%3,%4}, [%5];"
                 :: "r"(dst), "r"(a), "r"(b), "r"(c), "r"(d), "r"(bar) : "memory");
}

DEVI uint32_t b_addr(uint32_t sb, int row, int which, int chunk) { const int l = 3 * row + which; return sb + l * 128 + ((chunk ^ (l & 7)) * 16); }
DEVI void battn_warp(uint32_t st, uint32_t so, int i0, int par, int head, int hh, int mt, int lane) {
    const int gq = lane >> 2, t = lane & 3;
    float s[3][4];
#pragma unroll
    for (int n = 0; n < 3; n++) { s[n][0] = s[n][1] = s[n][2] = s[n][3] = 0.f; }
    const int arow = 16 * mt + (lane & 7) + ((lane >> 3) & 1) * 8;
#pragma unroll
    for (int ks = 0; ks < 2; ks++) {
        uint32_t a[4], b[4], b2[2];
        ldsm4(a, b_addr(st, 8 + arow, 0, hh * 4 + ks * 2 + (lane >> 4)));
        const int brow = 16 * mt + (lane >> 4) * 8 + (lane & 7);
        ldsm4(b, b_addr(st, brow, 1, hh * 4 + ks * 2 + ((lane >> 3) & 1)));
        const int crow = 16 * mt + 16 + (lane & 7);
        ldsm2(b2, b_addr(st, crow, 1, hh * 4 + ks * 2 + ((lane >> 3) & 1)));
        mma16816(s[0], a, b[0], b[1]);
        mma16816(s[1], a, b[2], b[3]);
        mma16816(s[2], a, b2[0], b2[1]);
    }
    float m0 = -INFINITY, m1 = -INFINITY;
#pragma unroll
    for (int n = 0; n < 3; n++) {
#pragma unroll
        for (int c = 0; c < 2; c++) {
            const int dj = 8 * n - 8 + 2 * t + c;
            const bool ex = i0 + 16 * mt + dj >= 0;
            if (!(ex && gq - dj >= 0 && gq - dj <= 7)) s[n][c] = -INFINITY;
            if (!(ex && gq + 8 - dj >= 0 && gq + 8 - dj <= 7)) s[n][2 + c] = -INFINITY;
            m0 = fmaxf(m0, s[n][c]); m1 = fmaxf(m1, s[n][2 + c]);
        }
    }
    m0 = fmaxf(m0, __shfl_xor_sync(0xffffffffu, m0, 1)); m0 = fmaxf(m0, __shfl_xor_sync(0xffffffffu, m0, 2));
    m1 = fmaxf(m1, __shfl_xor_sync(0xffffffffu, m1, 1)); m1 = fmaxf(m1, __shfl_xor_sync(0xffffffffu, m1, 2));
    constexpr float C = 0.17677669529663687f * 1.4426950408889634f;
    float l0 = 0.f, l1 = 0.f;
    uint32_t p[3][2];
#pragma unroll
    for (int n = 0; n < 3; n++) {
        const float e0 = ex2((s[n][0] - m0) * C), e1 = ex2((s[n][1] - m0) * C), e2 = ex2((s[n][2] - m1) * C), e3 = ex2((s[n][3] - m1) * C);
        l0 += e0 + e1; l1 += e2 + e3;
        p[n][0] = pack_bf16(e0, e1); p[n][1] = pack_bf16(e2, e3);
    }
    l0 += __shfl_xor_sync(0xffffffffu, l0, 1); l0 += __shfl_xor_sync(0xffffffffu, l0, 2);
    l1 += __shfl_xor_sync(0xffffffffu, l1, 1); l1 += __shfl_xor_sync(0xffffffffu, l1, 2);
    const float i0f = rcp_fast(l0), i1f = rcp_fast(l1);
    float o[4][4];
#pragma unroll
    for (int n = 0; n < 4; n++) { o[n][0] = o[n][1] = o[n][2] = o[n][3] = 0.f; }
    {
        const uint32_t a0[4] = {p[0][0], p[0][1], p[1][0], p[1][1]}, a1[4] = {p[2][0], p[2][1], 0u, 0u};
#pragma unroll
        for (int n = 0; n < 4; n += 2) {
            uint32_t b[4], b2[4];
            const int vrow = 16 * mt + ((lane >> 3) & 1) * 8 + (lane & 7);
            ldsm4t(b, b_addr(st, vrow, 2, hh * 4 + n + (lane >> 4)));
            const int wrow = 16 * mt + 16 + (lane & 7);
            ldsm4t(b2, b_addr(st, wrow, 2, hh * 4 + n + (lane >> 4)));
            mma16816(o[n], a0, b[0], b[1]);
            mma16816(o[n + 1], a0, b[2], b[3]);
            mma16816(o[n], a1, b2[0], 0u);
            mma16816(o[n + 1], a1, b2[2], 0u);
        }
    }
    {
        const int row = (lane & 7) + ((lane >> 3) & 1) * 8;
#pragma unroll
        for (int n = 0; n < 4; n += 2)
            stsm4(so + row * 64 + (((n + (lane >> 4)) ^ ((row >> 1) & 3)) * 16),
                  pack_bf16(o[n][0] * i0f, o[n][1] * i0f), pack_bf16(o[n][2] * i1f, o[n][3] * i1f),
                  pack_bf16(o[n + 1][0] * i0f, o[n + 1][1] * i0f), pack_bf16(o[n + 1][2] * i1f, o[n + 1][3] * i1f));
    }
    __syncwarp();
#pragma unroll
    for (int i = 0; i < 2; i++) {
        const int idx = lane + i * 32, row = idx >> 2, ch = idx & 3;
        const uint4 v = lds128(so + row * 64 + ((ch ^ ((row >> 1) & 3)) * 16));
        *(uint4*)(g_bo + (size_t)(2 * (i0 + 16 * mt + row) + par) * 1024 + head * 32 + ch * 8) = v;
    }
    __syncwarp();
}

constexpr float SCALE_LOG2E = 0.08838834764831845f * 1.4426950408889634f;

constexpr int P_STAGES = 4, P_STAGE = 16384 + 32768;
constexpr int PS_STG = P_STAGES * P_STAGE;
constexpr int PS_BAR = PS_STG + 32768;
constexpr int P_SMEM = PS_BAR + 256;
static_assert(P_SMEM <= 232448, "smem");
enum { K_Q, K_B1, K_B3, K_A4, K_QH, K_A3, K_SK, K_B2, K_END };
struct PList { int n, nworker; int4 run[16]; };
struct PTask { int kind, a, b, c; };
DEVI PTask p_decode(const PList& pl, int id) {
    for (int i = 0; i < pl.n; i++) {
        const int4 r = pl.run[i];
        if (id < r.w) {
            const int j = id - r.z;
            if (r.x == K_Q || r.x == K_QH) return {r.x, j & 31, r.y + (j >> 5), 0};
            if (r.x == K_B1) return {r.x, j % 24, r.y + j / 24, 0};
            if (r.x == K_B2) return {r.x, 0, r.y + j, 0};
            if (r.x == K_SK) return {r.x, (j / P_SPLIT) & 7, r.y + j / (8 * P_SPLIT), j % P_SPLIT};
            return {r.x, j & 7, r.y + (j >> 3), 0};
        }
    }
    return {K_END, 0, 0, 0};
}
DEVI void wait_count(const unsigned* p, unsigned target) {
    int n = 0;
    while (true) {
        unsigned v; asm volatile("ld.acquire.gpu.global.u32 %0, [%1];" : "=r"(v) : "l"(p) : "memory");
        if ((int)(v - target) >= 0) break;
        __nanosleep(100);
        if (++n > SPIN_LIMIT) TRAP(0x10000000u | ((unsigned)(size_t)p & 0xFFFFu));
    }
}
DEVI void wait_count_warp(const unsigned* p, unsigned target) {
    int n = 0;
    while (true) {
        unsigned v; asm volatile("ld.acquire.gpu.global.u32 %0, [%1];" : "=r"(v) : "l"(p) : "memory");
        if (__all_sync(0xffffffffu, (int)(v - target) >= 0)) break;
        __nanosleep(100);
        if (++n > SPIN_LIMIT) TRAP(0x10000000u | ((unsigned)(size_t)p & 0xFFFFu));
    }
}
DEVI void signal_count(unsigned* p) { __threadfence(); atomicAdd(p, 1u); }

struct PMaps { CUtensorMap wq, bw, bwo, wo, x, bx, bo, ox, cb, cout, cq, b40; PList list; };
constexpr int PB_F = PS_BAR, PB_E = PB_F + 32, PB_TF = PB_F + 64, PB_TE = PB_F + 80, PB_S = PB_F + 96;
constexpr int PS_T = PB_F + 112, PS_SIG = PS_T + 32, PS_SK = PS_SIG + 16;

struct POut { const CUtensorMap* map; int col, tok, cnt; bool blocked; };
DEVI void p_store(const uint32_t* pk, const POut& o, int c, uint32_t stg, int warp, int lane_, int barid, bool elected) {
    const int lane = (int)opaque((uint32_t)lane_);
    const int mi = lane >> 3, r = lane & 7;
    const uint32_t buf = stg + (c & 1) * 8192;
    if (elected) asm volatile("cp.async.bulk.wait_group.read 1;" ::: "memory");
    nbar_sync(barid, 128);
    if (o.blocked) {
#pragma unroll
        for (int j = 0; j < 8; j += 2)
            stsm4(buf + (j + (mi >> 1)) * 1024 + (warp * 16 + (mi & 1) * 8 + r) * 16, pk[2 * j], pk[2 * j + 1], pk[2 * j + 2], pk[2 * j + 3]);
    } else {
#pragma unroll
        for (int j = 0; j < 8; j += 2)
            stsm4t(buf + (8 * (j + (mi >> 1)) + r) * 128 + ((2 * warp + (mi & 1)) ^ r) * 16, pk[2 * j], pk[2 * j + 1], pk[2 * j + 2], pk[2 * j + 3]);
    }
    fence_proxy_async();
    nbar_sync(barid, 128);
    if (elected) {
        if (o.blocked)
            asm volatile("cp.async.bulk.tensor.4d.global.shared::cta.bulk_group [%0, {%2, %3, %4, %5}], [%1];"
                         :: "l"(o.map), "r"(buf), "r"(0), "r"((o.col >> 5) & 2), "r"((o.col >> 7) * 4), "r"((o.tok >> 5) + 2 * c) : "memory");
        else tma_store_2d(o.map, buf, o.col, o.tok + c * 64);
        bulk_commit();
    }
}
DEVI void p_signal(uint32_t sb, int g, int cnt, int& nsig) {
    sts32(sb + PS_SIG + g * 8 + (nsig & 1) * 4, (uint32_t)cnt);
    mbar_arrive(sb + PB_S + g * 8);
    nsig++;
}
template <int BN, bool FIRST>
DEVI void p_kblock(float* d, uint32_t sb, int g, int it, bool elected) {
    const int st = it % P_STAGES;
    mbar_wait(sb + PB_F + st * 8, (it / P_STAGES) & 1);
    const uint32_t a = sb + st * P_STAGE;
    const uint64_t da = mk_desc(a + g * 8192, 16, 1024, 1), db = mk_desc(a + 16384, 16, 1024, 1);
    wg_fence();
#pragma unroll
    for (int kk = 0; kk < 4; kk++) {
        if (BN == 256) { if (FIRST && kk == 0) wgmma_n256_ss<true>(d, da, db); else wgmma_n256_ss<false>(d, da + (uint64_t)(kk * 128), db + (uint64_t)(kk * 2)); }
        else           { if (FIRST && kk == 0) wgmma_n128_ss<true>(d, da, db); else wgmma_n128_ss<false>(d, da + (uint64_t)(kk * 128), db + (uint64_t)(kk * 2)); }
    }
    wg_commit();
    if (!FIRST) {
        wg_wait<1>();
        if (elected) mbar_arrive(sb + PB_E + ((it - 1) % P_STAGES) * 8);
    }
}

DEVI int post_claim(const PMaps& mp, unsigned E) {
    const int id = (int)(atomicAdd(&g_qctr, 1u) - (E - 1) * (unsigned)(mp.list.run[mp.list.n - 1].w + mp.list.nworker));
    const PTask tk = p_decode(mp.list, id);
    if (tk.kind == K_B2) {
        wait_count(&g_cnt[C_B1 + (tk.b >> 2)], 48 * E);
        if ((tk.b & 3) == 0 && tk.b > 0) wait_count(&g_cnt[C_B1 + (tk.b >> 2) - 1], 48 * E);
    } else if (tk.kind == K_B3) wait_count(&g_cnt[C_B2 + tk.b], 8 * E);
    else if (tk.kind == K_A4) wait_count(&g_prog[2 * tk.b + 1], 128 * E);
    else if (tk.kind == K_A3 || tk.kind == K_SK) wait_count(&g_prog[tk.b], 128 * E);
    if (tk.kind != K_Q && tk.kind != K_QH && tk.kind != K_B1) asm volatile("fence.proxy.async;" ::: "memory");
    return id;
}
DEVI void post_producer(const PMaps& mp, uint32_t sb, unsigned E, int id) {
    const uint32_t bF = sb + PB_F, bE = sb + PB_E;
    int it = 0;
    for (int i = 0;; i++) {
        mbar_wait(sb + PB_TE + (i & 1) * 8, ((i >> 1) & 1) ^ 1);
        if (i > 0) id = post_claim(mp, E);
        const PTask tk = p_decode(mp.list, id);
        sts128(sb + PS_T + (i & 1) * 16, make_uint4((uint32_t)tk.kind | ((uint32_t)id << 8), (uint32_t)tk.a, (uint32_t)tk.b, (uint32_t)tk.c));
        mbar_arrive(sb + PB_TF + (i & 1) * 8);
        if (tk.kind == K_END) break;
        if (tk.kind == K_B2) {
            const int i0 = tk.b * 32;
            for (int j = 0; j < 16; j++, it++) {
                const int st = it % P_STAGES;
                mbar_wait(bE + st * 8, ((it / P_STAGES) & 1) ^ 1);
                const uint32_t a = sb + st * P_STAGE, bar = bF + st * 8;
                mbar_expect_tx(bar, 2 * 15360);
                for (int u = 0; u < 2; u++)
                    asm volatile("cp.async.bulk.tensor.4d.shared::cluster.global.mbarrier::complete_tx::bytes [%0], [%1, {%3, %4, %5, %6}], [%2];"
                                 :: "r"(a + u * 15360), "l"(&mp.b40), "r"(bar), "r"(j * 64), "r"(0), "r"(u), "r"(i0 - 8) : "memory");
            }
            continue;
        }
        const bool qk = tk.kind == K_Q || tk.kind == K_QH, ak = tk.kind == K_A4 || tk.kind == K_A3 || tk.kind == K_SK, wide = tk.kind <= K_A4;
        const CUtensorMap* tw = tk.kind == K_B1 ? &mp.bw : (qk ? &mp.wq : &mp.bwo);
        const CUtensorMap* tx = tk.kind == K_B1 ? &mp.bx : (qk ? &mp.x : (ak ? &mp.ox : &mp.bo));
        const int nk = tk.kind == K_A3 || tk.kind == K_A4 ? HD / 64 : (tk.kind == K_SK ? HD / 64 / P_SPLIT : DM / 64), kb0 = tk.c * (HD / 64 / P_SPLIT);
        for (int kb = kb0; kb < kb0 + nk; kb++, it++) {
            const int st = it % P_STAGES;
            mbar_wait(bE + st * 8, ((it / P_STAGES) & 1) ^ 1);
            const uint32_t a = sb + st * P_STAGE, bar = bF + st * 8;
            mbar_expect_tx(bar, wide ? P_STAGE : 32768);
            if (ak) {
                tma_load_wo(a, &mp.wo, tk.a * 128, kb * 2, bar);
                tma_load_wo(a + 8192, &mp.wo, tk.a * 128 + 64, kb * 2, bar);
            } else {
                tma_load_2d(a, tw, tk.a * 128, kb * 64, bar);
                tma_load_2d(a + 8192, tw, tk.a * 128 + 64, kb * 64, bar);
            }
            tma_load_2d(a + 16384, tx, kb * 64, tk.b * (wide ? 256 : 128), bar);
            if (wide) tma_load_2d(a + 32768, tx, kb * 64, tk.b * 256 + 128, bar);
        }
    }
    __threadfence();
    if (atomicAdd(&g_done, 1u) == E * mp.list.nworker - 1) { __threadfence(); *(volatile unsigned*)&g_epoch = E; }
}
DEVI void post_helper(uint32_t sb, int g) {
    for (int n = 0;; n++) {
        mbar_wait_sleepy(sb + PB_S + g * 8, n & 1);
        const int cnt = (int)lds32(sb + PS_SIG + g * 8 + (n & 1) * 4);
        if (cnt < 0) break;
        signal_count(&g_cnt[cnt]);
    }
}
DEVI void post_consumer(const PMaps& mp, uint32_t sb, int g, int warp) {
    const int barid = 1 + g, tid = threadIdx.x, lane = tid & 31;
    const bool elected = (tid & 127) == 0;
    const uint32_t stg = sb + PS_STG + g * 16384;
    int it = 0, nsig = 0;
    uint32_t pk[64];
    POut out;
    bool pend = false;
#pragma unroll
    for (int i = 0; i < 64; i++) pk[i] = 0u;
    for (int i = 0;; i++) {
        const uint32_t bTF = sb + PB_TF + (i & 1) * 8;
        if (pend) {
            uint32_t now;
            asm volatile("{.reg .pred p, q; mbarrier.test_wait.parity.shared::cta.b64 p, [%1], %2; bar.red.and.pred q, %3, 128, p; selp.u32 %0, 1, 0, q;}"
                         : "=r"(now) : "r"(bTF), "r"((i >> 1) & 1), "r"(barid) : "memory");
            if (!now || (lds32(sb + PS_T + (i & 1) * 16) & 255u) > K_A4) {
#pragma unroll
                for (int c = 0; c < 4; c++) p_store(pk + 16 * c, out, c, stg, warp, lane, barid, elected);
                if (elected && out.cnt != C_NONE) { bulk_wait_all(); p_signal(sb, g, out.cnt, nsig); }
                pend = false;
            }
        }
        mbar_wait(bTF, (i >> 1) & 1);
        const uint4 tw = lds128(sb + PS_T + (i & 1) * 16);
        mbar_arrive(sb + PB_TE + (i & 1) * 8);
        const PTask tk = {(int)(tw.x & 255u), (int)tw.y, (int)tw.z, (int)tw.w};
        if (tk.kind == K_END) break;
        if (tk.kind <= K_A4) {
            float d[128];
            const int nk = tk.kind == K_A4 ? HD / 64 : DM / 64;
            p_kblock<256, true>(d, sb, g, it, elected);
            if (pend) p_store(pk, out, 0, stg, warp, lane, barid, elected);
#pragma unroll
            for (int c = 1; c < 4; c++) {
                p_kblock<256, false>(d, sb, g, it + c, elected);
                if (pend) p_store(pk + 16 * c, out, c, stg, warp, lane, barid, elected);
            }
#pragma unroll 1
            for (int kb = 4; kb < nk; kb++) {
                p_kblock<256, false>(d, sb, g, it + kb, elected);
                if (kb == 6 && pend && elected && out.cnt != C_NONE) { bulk_wait_all(); p_signal(sb, g, out.cnt, nsig); }
            }
            it += nk;
            wg_wait<0>();
            reg_fence<128>(d);
            if (elected) mbar_arrive(sb + PB_E + ((it - 1) % P_STAGES) * 8);
#pragma unroll
            for (int j = 0; j < 64; j++) pk[j] = pack_bf16(d[2 * j], d[2 * j + 1]);
            out.map = tk.kind == K_Q ? &mp.cq : (tk.kind == K_B1 ? &mp.cb : &mp.cout);
            out.col = tk.a * 128 + g * 64 + (tk.kind == K_B3 ? DM : 0);
            out.tok = tk.b * 256;
            out.cnt = tk.kind == K_Q ? C_Q + tk.b : (tk.kind == K_B1 ? C_B1 + tk.b : C_NONE);
            out.blocked = tk.kind == K_Q;
            pend = true;
        } else if (tk.kind == K_B2) {
            if (elected) bulk_wait_all();
            nbar_sync(barid, 128);
#pragma unroll 1
            for (int j = 0; j < 16; j++, it++) {
                const int st = it % P_STAGES;
                mbar_wait(sb + PB_F + st * 8, (it / P_STAGES) & 1);
                const uint32_t a = sb + st * P_STAGE + g * 15360;
                battn_warp(a, stg + warp * 1024, tk.b * 32, g, j * 2 + (warp >> 1), warp >> 1, warp & 1, (int)opaque((uint32_t)lane));
                nbar_sync(barid, 128);
                if (elected) mbar_arrive(sb + PB_E + st * 8);
            }
            if (elected) p_signal(sb, g, C_B2 + (tk.b >> 2), nsig);
#pragma unroll
            for (int j = 0; j < 64; j++) pk[j] = 0u;
        } else {
            float d[64];
            const int nk = tk.kind == K_A3 ? HD / 64 : (tk.kind == K_SK ? HD / 64 / P_SPLIT : DM / 64);
            p_kblock<128, true>(d, sb, g, it, elected);
#pragma unroll 1
            for (int kb = 1; kb < nk; kb++) p_kblock<128, false>(d, sb, g, it + kb, elected);
            it += nk;
            wg_wait<0>();
            reg_fence<64>(d);
            if (elected) mbar_arrive(sb + PB_E + ((it - 1) % P_STAGES) * 8);
            bool finish = true;
            if (tk.kind == K_SK) {
                const int tile = ((tk.b - (16 - P_NSK)) * 8 + tk.a);
                uint4* const base = g_skp + (size_t)(tile * P_SPLIT * 2 + g) * 1024 + (tid & 127);
#pragma unroll
                for (int j = 0; j < 8; j++)
                    base[tk.c * 2048 + j * 128] = make_uint4(pack_bf16(d[8 * j], d[8 * j + 1]), pack_bf16(d[8 * j + 2], d[8 * j + 3]),
                                                             pack_bf16(d[8 * j + 4], d[8 * j + 5]), pack_bf16(d[8 * j + 6], d[8 * j + 7]));
                nbar_sync(barid, 128);
                if (elected) {
                    unsigned old;
                    asm volatile("atom.acq_rel.gpu.global.add.u32 %0, [%1], 1;" : "=r"(old) : "l"(&g_cnt_sk[tile * 2 + g]) : "memory");
                    sts32(sb + PS_SK + g * 4, old % P_SPLIT);
                }
                nbar_sync(barid, 128);
                finish = lds32(sb + PS_SK + g * 4) == P_SPLIT - 1;
                if (finish) {
#pragma unroll 1
                    for (int q = 1; q < P_SPLIT; q += 2) {
                        uint4 v[16];
#pragma unroll
                        for (int j = 0; j < 16; j++)
                            v[j] = j < 8 || q + 1 < P_SPLIT ? __ldcg(base + ((tk.c + q + (j >> 3)) % P_SPLIT) * 2048 + (j & 7) * 128) : make_uint4(0u, 0u, 0u, 0u);
#pragma unroll
                        for (int j = 0; j < 16; j++) {
                            float* e = d + 8 * (j & 7);
                            e[0] += __uint_as_float(v[j].x << 16); e[1] += __uint_as_float(v[j].x & 0xFFFF0000u);
                            e[2] += __uint_as_float(v[j].y << 16); e[3] += __uint_as_float(v[j].y & 0xFFFF0000u);
                            e[4] += __uint_as_float(v[j].z << 16); e[5] += __uint_as_float(v[j].z & 0xFFFF0000u);
                            e[6] += __uint_as_float(v[j].w << 16); e[7] += __uint_as_float(v[j].w & 0xFFFF0000u);
                        }
                    }
                }
                nbar_sync(barid, 128);
            }
            if (finish) {
                const POut o = {tk.kind == K_QH ? &mp.cq : &mp.cout, tk.a * 128 + g * 64, tk.b * 128, 0, tk.kind == K_QH};
                uint32_t q[32];
#pragma unroll
                for (int j = 0; j < 32; j++) q[j] = pack_bf16(d[2 * j], d[2 * j + 1]);
                p_store(q, o, 0, stg, warp, lane, barid, elected);
                p_store(q + 16, o, 1, stg, warp, lane, barid, elected);
                if (elected && tk.kind == K_QH) { bulk_wait_all(); p_signal(sb, g, tk.b == 0 ? C_QH : C_Q, nsig); }
            }
#pragma unroll
            for (int j = 0; j < 64; j++) pk[j] = 0u;
        }
    }
    if (elected) { bulk_wait_all(); p_signal(sb, g, -1, nsig); }
}
DEVI void post_init(uint32_t sb) {
    for (int i = 0; i < P_STAGES; i++) { mbar_init(sb + PB_F + i * 8, 1); mbar_init(sb + PB_E + i * 8, 2); }
    for (int i = 0; i < 2; i++) { mbar_init(sb + PB_TF + i * 8, 1); mbar_init(sb + PB_TE + i * 8, 256); mbar_init(sb + PB_S + i * 8, 1); }
    fence_mbar_init();
}

constexpr unsigned long long R_TORD_PACK = 0xf5ea4937dc6b8120ull;
__host__ __device__ constexpr int r_tord(int pos) { return (int)((R_TORD_PACK >> (4 * pos)) & 15ull); }
__host__ __device__ constexpr int r_tinv(int T) { for (int p = 0; p < 16; p++) if (r_tord(p) == T) return p; return 0; }
__host__ __device__ constexpr bool r_pos_ss(int pos) { return pos % 3 == 2; }
__host__ __device__ constexpr int r_ss(int pos) { return pos / 3; }
__host__ __device__ constexpr int r_rs(int pos) { return pos - pos / 3; }
constexpr int R_NRS = 11, R_NSS = 5;
constexpr int R_G1 = 9;
#define REG_KB 232
#define TA_LATE 0
#define WO_REL 0
constexpr int X_SLOTS = 4;
constexpr int X_NST = 8;

constexpr int RS_WSS  = 0;
constexpr int RS_WO   = RS_WSS + R_NSS * 16384;
constexpr int RS_MEM  = RS_WO + 5 * 16384;
constexpr int RS_O    = RS_MEM + 16384;
constexpr int RS_SX   = RS_O + 2048;
constexpr int RS_BAR  = RS_SX + 2048;
constexpr int RS_TAIL = RS_BAR + 1024;
constexpr int RS_WO5  = RS_TAIL;
constexpr int RS_K    = RS_WO5 + 16384;
constexpr int RS_V    = RS_K + 10240;
constexpr int RS_Q    = RS_V + 10240;
constexpr int RS_QX   = RS_Q + 2048;
constexpr int RS_QEND = RS_QX + 8192;
constexpr int RS_X    = RS_TAIL;
constexpr int X_PITCH = X_SLOTS * 4096;
constexpr int RS_XD   = RS_X + 2 * X_PITCH;
constexpr int RS_WX   = RS_XD + 8192;
constexpr int RS_KEND = RS_WX + 4096;
constexpr int RS_EV   = RS_BAR + 256;
constexpr int R_SMEM  = RS_KEND > RS_QEND ? RS_KEND : RS_QEND;
static_assert(R_SMEM <= 232448 && P_SMEM <= R_SMEM, "smem");
static_assert(RS_TAIL % 1024 == 0 && RS_MEM % 1024 == 0, "alignment");

constexpr int RB_G = RS_BAR, RB_WO = RS_BAR + 16, RB_K = RS_BAR + 24, RB_V = RS_BAR + 32, RB_KV = RS_BAR + 40, RB_QX = RS_BAR + 48, RB_O = RS_BAR + 56;
constexpr int RB_ATT = RS_BAR + 64, RB_W = RS_BAR + 72, RB_SF = RS_BAR + 80, RB_SE = RB_SF + 40, RB_XF = RB_SE + 40;
constexpr int RB_T = RB_XF + 64, RS_INV = RS_SX + 1024;
static_assert(RB_T + 8 <= RS_EV, "barriers");
constexpr uint32_t SB0 = 1024;
__host__ __device__ constexpr uint32_t cdesc(uint32_t off, uint32_t lbo) { return ((SB0 + off) >> 4) | ((lbo >> 4) << 16); }
#define SCHED_FENCE() __syncwarp()
constexpr int NB_BIG = 1, NB_Q = 2, NB_AUX = 3, NB_WO = 4, NB_XS = 5, NB_WG = 6, NB_PAIR = 8;

DEVI int tid_now() { int t; asm volatile("mov.u32 %0, %%tid.x;" : "=r"(t)); return t; }
DEVI uint32_t a_frag_off(int lane, int warp) { return (uint32_t)((((lane >> 4) * 8 + (lane & 7)) * 128) + (((2 * warp + ((lane >> 3) & 1)) ^ (lane & 7)) * 16)); }
DEVI uint32_t b_frag_off(int lane) { return (uint32_t)((lane & 3) * 64 + (((lane >> 2) * 8) ^ ((lane & 2) * 16))); }
DEVI void lds_b(uint32_t* b, uint32_t a) {
    asm volatile("ld.shared.v2.u32 {%0,%1}, [%2];" : "=r"(b[0]), "=r"(b[1]) : "r"(a) : "memory");
    asm volatile("ld.shared.v2.u32 {%0,%1}, [%2];" : "=r"(b[2]), "=r"(b[3]) : "r"(a + 256) : "memory");
}
DEVI uint32_t clk32() { unsigned long long c; asm volatile("mov.u64 %0, %%clock64;" : "=l"(c)); return (uint32_t)c; }
DEVI bool elect_one() {
    uint32_t e; asm volatile("{.reg .pred p; elect.sync _|p, 0xffffffff; selp.u32 %0, 1, 0, p;}" : "=r"(e)); return e;
}

__host__ __device__ constexpr int x_pair(int j) { return j == 0 || j > 3 ? j : (j == 3 ? 1 : j + 1); }
DEVI void x_load(uint32_t sb, int seg, int j, int g, const CUtensorMap* tmX) {
    const uint32_t bar = sb + RB_XF + g * 8;
    mbar_expect_tx(bar, 4096);
    tma_load_3d(sb + RS_X + g * X_PITCH + (j % X_SLOTS) * 4096, tmX, g * 32, seg * 32, x_pair(j) * 2, bar);
}
DEVI void x_refill(uint32_t sb, int seg, int j, int g, int warp, const CUtensorMap* tmX) {
    const int sn = j + X_SLOTS < X_NST ? seg : seg + 1;
    if (warp == (j & 3) && sn < NSEG) {
        if (elect_one()) x_load(sb, sn, (j + X_SLOTS) % X_NST, g, tmX);
    }
}
template <int H>
DEVI void x_half(float* xa, const uint32_t* w, uint32_t sb, int seg, int g0, int warp, const CUtensorMap* tmX) {
    wg_fence();
#pragma unroll
    for (int grp = 0; grp < 4; grp++) {
        const int g = (int)opaque((uint32_t)g0);
        const uint32_t dW0 = cdesc(RS_WSS, 16) + g * 768, dW1 = cdesc(RS_WSS + 8192, 16) - g * 256;
#pragma unroll
        for (int i = 0; i < 8; i++) {
            const bool last = H == 1 && grp >= 2;
            const int j = last ? 6 + (i >> 2) : 4 * H + grp, q = last ? 2 * (i & 3) + (grp == 2) : i;
            const int pos = r_tinv(2 * x_pair(j) + (q >> 2)), kk = (q >> 1) & 1, mt = q & 1;
            const uint32_t db = cdesc(RS_X + (j % X_SLOTS) * 4096, 16) + g * (X_PITCH >> 4) + (q >> 2) * 128 + kk * 2;
            if (j == 0 && q < 2)   wgmma_n32_rs_first(xa + 16 * mt, &w[((r_rs(pos) * 2 + kk) * 2 + mt) * 4], db);
            else if (j == 0 && q == 3) wgmma_n32_ss(xa + 16, cdesc(RS_WX, 16) + g * 128, db);
            else if (r_pos_ss(pos)) wgmma_n32_ss(xa + 16 * mt, (mt ? dW1 : dW0) + r_ss(pos) * 1024 + kk * 128, db);
            else                   wgmma_n32_rs(xa + 16 * mt, &w[((r_rs(pos) * 2 + kk) * 2 + mt) * 4], db);
        }
        wg_commit();
    }
    const int g = (int)opaque((uint32_t)g0);
    wg_wait<3>(); x_refill(sb, seg, 4 * H, g, warp, tmX);
    wg_wait<2>(); x_refill(sb, seg, 4 * H + 1, g, warp, tmX);
    wg_wait<1>();
    if (H == 0) {
        x_refill(sb, seg, 2, g, warp, tmX);
        wg_wait<0>(); reg_fence<32>(xa); x_refill(sb, seg, 3, g, warp, tmX);
    } else reg_fence<16>(xa + 16);
}
DEVI void x_finish(float* xa, uint32_t sb, int seg, int g, int warp, int lane, const CUtensorMap* tmX) {
    const uint32_t d = sb + RS_XD + (lane >> 4) * 2048 + warp * 256 + (lane & 15) * 16;
#pragma unroll
    for (int i = 0; i < 2; i++) {
        const float* x = xa + 16 + 8 * i;
        sts128(d + (g ^ 1) * 1024 + i * 4096, make_uint4(pack_bf16(x[0], x[1]), pack_bf16(x[2], x[3]), pack_bf16(x[4], x[5]), pack_bf16(x[6], x[7])));
    }
    nbar_sync(NB_PAIR + warp, 64);
    float y[16];
#pragma unroll
    for (int i = 0; i < 2; i++) {
        const uint4 v = lds128(d + g * 1024 + i * 4096);
        const uint32_t u[4] = {v.x, v.y, v.z, v.w};
#pragma unroll
        for (int j = 0; j < 4; j++) { y[8 * i + 2 * j] = __uint_as_float(u[j] << 16); y[8 * i + 2 * j + 1] = __uint_as_float(u[j] & 0xFFFF0000u); }
    }
    reg_fence<16>(y);
    wg_wait<0>();
    reg_fence<16>(xa);
    uint32_t p[8];
#pragma unroll
    for (int j = 0; j < 8; j++) p[j] = pack_bf16(xa[2 * j] + y[2 * j], xa[2 * j + 1] + y[2 * j + 1]);
    __syncwarp();
    stsm4(d + g * 1024, p[0], p[1], p[2], p[3]);
    stsm4(d + g * 1024 + 4096, p[4], p[5], p[6], p[7]);
    nbar_arrive(NB_XS, 256 + 32);
    x_refill(sb, seg, X_NST - 2, g, warp, tmX);
    x_refill(sb, seg, X_NST - 1, g, warp, tmX);
}
DEVI void x_send(uint32_t sb, int seg, uint32_t rank, int vdelay) {
    mbar_wait(sb + RB_ATT, (seg - 1) & 1);
    nbar_sync(NB_XS, 256 + 32);
    if (rank == 2) { const uint32_t t = clk32() + vdelay; while ((int)(clk32() - t) < 0) { } }
    if (elect_one()) {
        fence_proxy_async();
        bulk_copy_s2c(mapa(sb + (rank == 1 ? RS_K : RS_V) + 2048, 0), sb + RS_XD, 8192, mapa(sb + (rank == 1 ? RB_KV : RB_V), 0));
    }
    __syncwarp();
}

template <bool XP>
DEVI void mem_pass(float* c0, float* c1, const uint32_t* w, uint32_t sb, uint32_t aA0, uint32_t aB, int g, int warp, int s) {
    const uint32_t aA1 = aA0 + 8192 - g * 16384, par = (s - 1) & 1;
    uint32_t a[16], b[2][4], e[4];
    float d0[4], d1[4];
    if (XP) ldsm4t(e, aA0 + opaque((RS_WX - RS_WSS) - g * (8192 + 2048)));
#pragma unroll
    for (int q = 0; q < 4; q++) ldsm4t(a + 4 * q, ((q & 1) ? aA1 : aA0) + (q >> 1) * 2048);
#pragma unroll
    for (int i = 0; i < 4; i++) { c0[i] = 0.f; c1[i] = 0.f; d0[i] = 0.f; d1[i] = 0.f; }
    EV(EV_BIG0, s, 0);
    mbar_wait(sb + RB_G, par);
    EV(EV_BIG0, s, 1);
    lds_b(b[0], aB + r_tord(0) * 1024);
    bool in = false;
#pragma unroll
    for (int pos = 0; pos < 16; pos++) {
        if (pos + 1 < 16) {
            if (pos + 1 == R_G1) { if (!in) mbar_wait(sb + RB_G + 8, par); EV(EV_BIG0, s, 2); }
            lds_b(b[(pos + 1) & 1], aB + r_tord(pos + 1) * 1024);
        }
        if (pos + 2 == R_G1) in = mbar_try(sb + RB_G + 8, par);
        if (XP && pos == 12) in = s == NSEG - 1 || mbar_try(sb + RB_XF + g * 8, 0);
        if (XP && pos == 14) { if (!in) mbar_wait(sb + RB_XF + g * 8, 0); in = mbar_try(sb + RB_ATT, par); }
        const uint32_t* bb = b[pos & 1];
        const uint32_t* aa = r_pos_ss(pos) ? a : &w[r_rs(pos) * 16];
        mma16816(c1, aa + 4, bb[0], bb[1]);
        mma16816(d1, XP && pos == 0 ? e : aa + 12, bb[2], bb[3]);
        mma16816(c0, aa, bb[0], bb[1]);
        mma16816(d0, aa + 8, bb[2], bb[3]);
        if (r_pos_ss(pos) && pos + 3 < 16) {
#pragma unroll
            for (int q = 0; q < 4; q++) ldsm4t(a + 4 * q, ((q & 1) ? aA1 : aA0) + (r_ss(pos) + 1) * 16384 + (q >> 1) * 2048);
        }
        SCHED_FENCE();
    }
    if (XP && !in) mbar_wait(sb + RB_ATT, par);
#pragma unroll
    for (int i = 0; i < 4; i++) { c1[i] += d1[i]; c0[i] += d0[i]; }
}

DEVI uint32_t k_frag_off(int lane) { return (uint32_t)((((lane >> 3) & 1) * 16 + (lane >> 4) * 8 + (lane & 7)) * 16); }
DEVI uint32_t v_frag_off(int lane) { return (uint32_t)(((lane >> 3) & 1) * 2048 + ((lane >> 4) * 8 + (lane & 7)) * 16); }
DEVI void pv_pair(float (*o)[4], const uint32_t* p, const uint32_t* v) {
#pragma unroll
    for (int n = 0; n < 4; n++) mma16816(o[n], p, v[2 * n], v[2 * n + 1]);
}
DEVI void pv_single(float (*o)[4], const uint32_t* p, const uint32_t* v) {
#pragma unroll
    for (int n = 0; n < 4; n++) mma1688(o[n], p[0], p[1], v[n]);
}
DEVI float inv_sum4(float l) {
    l += __shfl_xor_sync(0xffffffffu, l, 1);
    l += __shfl_xor_sync(0xffffffffu, l, 2);
    return rcp_fast(l);
}

DEVI void s_tile(const uint32_t* qa, const uint32_t* k, float& s0, float& s1) {
    float c[4][4];
#pragma unroll
    for (int q = 0; q < 4; q++) { c[q][0] = c[q][1] = c[q][2] = c[q][3] = 0.f; }
#pragma unroll
    for (int q = 0; q < 4; q++) {
        mma16816(c[2 * (q & 1)], qa + 4 * q, k[4 * q], k[4 * q + 1]);
        mma16816(c[2 * (q & 1) + 1], qa + 4 * q, k[4 * q + 2], k[4 * q + 3]);
    }
    s0 = (c[0][0] + c[1][2]) + (c[2][0] + c[3][2]);
    s1 = (c[0][1] + c[1][3]) + (c[2][1] + c[3][3]);
}
DEVI void mem_scores(uint32_t sb, int s, int warp, int lane) {
    const uint32_t ka = sb + RS_K + k_frag_off(lane) + (1 + warp) * 2048;
    uint32_t qa[16], kx[16];
    const bool in = mbar_try(sb + RB_KV, s & 1);
    nbar_sync(NB_Q, 256);
#pragma unroll
    for (int q = 0; q < 4; q++) ldsm4t(qa + 4 * q, sb + RS_Q + q * 512 + lane * 16);
    if (!in) mbar_wait(sb + RB_KV, s & 1);
#pragma unroll
    for (int q = 0; q < 4; q++) ldsm4t(kx + 4 * q, ka + q * 512);
    SCHED_FENCE();
    float s0, s1;
    s_tile(qa, kx, s0, s1);
    asm volatile("st.shared.v2.f32 [%0], {%1,%2};" :: "r"(sb + RS_SX + warp * 256 + lane * 8), "f"(s0), "f"(s1) : "memory");
    nbar_arrive(NB_XS, 256);
}
DEVI void mem_attn(uint32_t sb, int s, int warp, int lane) {
    const uint32_t ka = sb + RS_K + k_frag_off(lane), va = sb + RS_V + warp * 512;
    const uint32_t dst = sb + RS_O + warp * 512 + (lane & 3) * 128 + (lane >> 2) * 16;
    [[maybe_unused]] constexpr int g = 0;
    uint32_t qa[16], vx[16];
    float sc[10];
    nbar_sync(NB_Q, 256);
    EV(EV_BIG0 && lds32(sb + RS_Q) != 0x12345678u, s, 8);
#pragma unroll
    for (int q = 0; q < 4; q++) ldsm4t(qa + 4 * q, sb + RS_Q + q * 512 + lane * 16);
    mbar_wait(sb + RB_K, s & 1);
    EV(EV_BIG0, s, 9);
    {
        uint32_t km[16];
#pragma unroll
        for (int q = 0; q < 4; q++) ldsm4t(km + 4 * q, ka + q * 512);
        nbar_sync(NB_XS, 256);
        s_tile(qa, km, sc[0], sc[1]);
    }
#pragma unroll
    for (int n = 0; n < 4; n++) { const float2 v = lds64f(sb + RS_SX + n * 256 + lane * 8); sc[2 + 2 * n] = v.x; sc[3 + 2 * n] = v.y; }
    const bool v_in = mbar_try(sb + RB_V, s & 1);
    float m = fmaxf(fmaxf(fmaxf(sc[2], sc[3]), fmaxf(sc[4], sc[5])), fmaxf(fmaxf(sc[6], sc[7]), fmaxf(sc[8], sc[9])));
    m = fmaxf(m, fmaxf(sc[0], sc[1]));
    m = fmaxf(fmaxf(m, __shfl_xor_sync(0xffffffffu, m, 1)), fmaxf(__shfl_xor_sync(0xffffffffu, m, 2), __shfl_xor_sync(0xffffffffu, m, 3)));
    EV(warp == 0 && m != 1.2345e30f && elect_one(), s, 5);
    if (!v_in) mbar_wait(sb + RB_V, s & 1);
    EV(warp == 0 && elect_one(), s, 13);
    uint32_t vm[4], p[10];
#pragma unroll
    for (int q = 3; q >= 0; q--) ldsm4(vx + 4 * q, va + 2048 + (q >> 1) * 4096 + (q & 1) * 256 + v_frag_off(lane));
    ldsm4(vm, va + lane * 16);
    SCHED_FENCE();
    const float nm = -m * SCALE_LOG2E;
    float l = 0.f;
#pragma unroll
    for (int n = 4; n >= 0; n--) {
        const float e0 = ex2(fmaf(sc[2 * n], SCALE_LOG2E, nm)), e1 = ex2(fmaf(sc[2 * n + 1], SCALE_LOG2E, nm));
        l += e0 + e1;
        p[2 * n] = pack_bf16(e0, e1); p[2 * n + 1] = __float_as_uint(e0);
    }
    float o[4][4];
#pragma unroll
    for (int n = 0; n < 4; n++) { o[n][0] = o[n][1] = o[n][2] = o[n][3] = 0.f; }
    pv_pair(o, p + 6, vx + 8);
    pv_pair(o, p + 2, vx);
    pv_single(o, p, vm);
    l = (l + __shfl_xor_sync(0xffffffffu, l, 1)) + (__shfl_xor_sync(0xffffffffu, l, 2) + __shfl_xor_sync(0xffffffffu, l, 3));
    const uint4 u = make_uint4(pack_bf16(o[0][0], o[0][1]), pack_bf16(o[1][0], o[1][1]), pack_bf16(o[2][0], o[2][1]), pack_bf16(o[3][0], o[3][1]));
    st_async128(mapa(dst, 1), u.x, u.y, u.z, u.w, mapa(sb + RB_O, 1));
    st_async128(mapa(dst, 2), u.x, u.y, u.z, u.w, mapa(sb + RB_O, 2));
    const uint32_t dl = sb + RS_INV + (lane & 3) * 32 + (lane & 28);
    asm volatile("st.async.weak.shared::cluster.mbarrier::complete_tx::bytes.b32 [%0], %1, [%2];"
                 :: "r"(mapa(dl, 1 + (warp & 1))), "r"(__float_as_uint(l)), "r"(mapa(sb + RB_O, 1 + (warp & 1))) : "memory");
    sts128(dst, u);
    sts32(dl, __float_as_uint(l));
    __syncwarp();
    if (elect_one()) mbar_arrive(sb + RB_O);
    EV(warp == 0 && elect_one(), s, 15);
}

DEVI void ta_scores(float* c, uint32_t sb, int seg, int cw, int lane) {
    const int mt = cw >= 3, n = cw - 3 * mt;
    const uint32_t qa = sb + RS_QX + (2 * mt + ((lane >> 3) & 1)) * 2048 + ((lane >> 4) * 8 + (lane & 7)) * 16;
    const uint32_t ka = sb + RS_K + n * 2048 + lane * 16;
    float d[4] = {0.f, 0.f, 0.f, 0.f};
    c[0] = c[1] = c[2] = c[3] = 0.f;
    mbar_wait(sb + RB_QX, seg & 1);
    if (n == 0) mbar_wait(sb + RB_K, seg & 1);
#pragma unroll
    for (int j = 0; j < 4; j++) {
        uint32_t a0[4], a1[4], b[4];
        ldsm4t(a0, qa + j * 512);
        ldsm4t(b, ka + j * 512);
        ldsm4t(a1, qa + j * 512 + 256);
        mma16816(c, a0, b[0], b[1]);
        mma16816(d, a1, b[2], b[3]);
    }
    const int over = 8 * (n - 1) + 2 * (lane & 3) - 16 * mt - (lane >> 2);
    c[0] = over > 0 ? -INFINITY : c[0] + d[0];
    c[1] = over >= 0 ? -INFINITY : c[1] + d[1];
    c[2] = over > 8 ? -INFINITY : c[2] + d[2];
    c[3] = over >= 8 ? -INFINITY : c[3] + d[3];
}
DEVI void ta_output(uint32_t sb, int seg, int head, int mt, int j, int lane) {
    const uint32_t sa = sb + RS_QX + mt * 1536 + lane * 16;
    float sc[5][4];
#pragma unroll
    for (int n = 0; n < 5; n++) {
        uint4 v = make_uint4(0xFF800000u, 0xFF800000u, 0xFF800000u, 0xFF800000u);
        if (n < 2 || n == 4 || mt) v = lds128(sa + (n == 4 ? 1024 + mt * 1024 : n * 512));
        sc[n][0] = __uint_as_float(v.x); sc[n][1] = __uint_as_float(v.y); sc[n][2] = __uint_as_float(v.z); sc[n][3] = __uint_as_float(v.w);
    }
    float m0 = -INFINITY, m1 = -INFINITY;
#pragma unroll
    for (int n = 0; n < 5; n++) { m0 = fmaxf(m0, fmaxf(sc[n][0], sc[n][1])); m1 = fmaxf(m1, fmaxf(sc[n][2], sc[n][3])); }
    m0 = fmaxf(m0, __shfl_xor_sync(0xffffffffu, m0, 1)); m1 = fmaxf(m1, __shfl_xor_sync(0xffffffffu, m1, 1));
    m0 = fmaxf(m0, __shfl_xor_sync(0xffffffffu, m0, 2)); m1 = fmaxf(m1, __shfl_xor_sync(0xffffffffu, m1, 2));
    m0 *= -SCALE_LOG2E; m1 *= -SCALE_LOG2E;
    float l0 = 0.f, l1 = 0.f;
    uint32_t p[10];
#pragma unroll
    for (int n = 0; n < 5; n++) {
        const float e0 = ex2(fmaf(sc[n][0], SCALE_LOG2E, m0)), e1 = ex2(fmaf(sc[n][1], SCALE_LOG2E, m0));
        const float e2 = ex2(fmaf(sc[n][2], SCALE_LOG2E, m1)), e3 = ex2(fmaf(sc[n][3], SCALE_LOG2E, m1));
        l0 += e0 + e1; l1 += e2 + e3;
        p[2 * n] = pack_bf16(e0, e1); p[2 * n + 1] = pack_bf16(e2, e3);
    }
    const float i0 = inv_sum4(l0), i1 = inv_sum4(l1);
    mbar_wait(sb + RB_V, seg & 1);
    const uint32_t vb = sb + RS_V + j * 512;
    float o[4][4];
#pragma unroll
    for (int n = 0; n < 4; n++) { o[n][0] = o[n][1] = o[n][2] = o[n][3] = 0.f; }
    uint32_t v[8];
    ldsm4(v, vb + v_frag_off(lane)); ldsm4(v + 4, vb + v_frag_off(lane) + 256);
    pv_pair(o, p, v);
    SCHED_FENCE();
    ldsm4(v, vb + 4096 + v_frag_off(lane)); ldsm4(v + 4, vb + 4096 + v_frag_off(lane) + 256);
    pv_pair(o, p + 4, v);
    SCHED_FENCE();
    ldsm4(v, vb + 4096 + mt * 4096 + lane * 16);
    pv_single(o, p + 8, v);
    bf16* dst = g_ox + (uint32_t)((seg * 32 + mt * 16 + (lane >> 2)) * HD + head * DH + j * 32 + (lane & 3) * 8);
    asm volatile("st.global.v4.u32 [%0], {%1,%2,%3,%4};" :: "l"(dst), "r"(pack_bf16(o[0][0] * i0, o[0][1] * i0)), "r"(pack_bf16(o[1][0] * i0, o[1][1] * i0)),
                 "r"(pack_bf16(o[2][0] * i0, o[2][1] * i0)), "r"(pack_bf16(o[3][0] * i0, o[3][1] * i0)) : "memory");
    asm volatile("st.global.v4.u32 [%0], {%1,%2,%3,%4};" :: "l"(dst + 8 * HD), "r"(pack_bf16(o[0][2] * i1, o[0][3] * i1)), "r"(pack_bf16(o[1][2] * i1, o[1][3] * i1)),
                 "r"(pack_bf16(o[2][2] * i1, o[2][3] * i1)), "r"(pack_bf16(o[3][2] * i1, o[3][3] * i1)) : "memory");
}

template <bool XP>
DEVI void big_main(const uint32_t* w, const uint32_t sb, const int g, const int warp, const uint32_t rank, const int head,
                   const CUtensorMap* tmX, const bf16* xg, const unsigned E) {
    float xa[32];
    const uint32_t aB = __shfl_sync(0xffffffffu, sb + RS_MEM + (g * 32 + (tid_now() & 31)) * 16, tid_now() & 31);
#define lane0 ((int)(opaque(aB) >> 4) & 31)
    const uint32_t aA0 = sb + RS_WSS + g * (8192 + 4096) + a_frag_off(lane0, warp);
    const uint32_t aBf = sb + RS_MEM + g * 512 + b_frag_off(lane0);
    if constexpr (XP) {
        mbar_wait(sb + RB_XF + g * 8, 0);
        x_half<0>(xa, w, sb, 0, g, warp, tmX);
        mbar_wait(sb + RB_XF + g * 8, 1);
        x_half<1>(xa, w, sb, 0, g, warp, tmX);
        x_finish(xa, sb, 0, g, warp, lane0, tmX);
    }
    nbar_sync(NB_BIG, 256);
    for (int s = 0; s < NSEG; s++) {
        float c0[4], c1[4];
        mem_pass<XP>(c0, c1, w, sb, aA0, aBf, g, warp, s);
        EV(EV_BIG0 && c0[0] != 1.2345e30f, s, 3);
        const uint32_t xs = aB + (RS_O - RS_MEM) + (warp - g) * 512;
        sts128f(xs + g * 2048, c1);
        auto combine = [&]() {
            const uint32_t d = sb + (XP ? (rank == 1 ? RS_K : RS_V) : RS_Q) + (g * 4 + warp) * 256 + lane0 * 4;
            const uint32_t rbar = XP ? mapa(sb + (rank == 1 ? RB_K : RB_V), 0) : 0u;
            nbar_sync(NB_PAIR + warp, 64);
            const uint4 v = lds128(xs + (g ^ 1) * 2048);
            const uint32_t p0 = pack_bf16(c0[0] + __uint_as_float(v.x), c0[1] + __uint_as_float(v.y));
            const uint32_t p1 = pack_bf16(c0[2] + __uint_as_float(v.z), c0[3] + __uint_as_float(v.w));
            if constexpr (XP) { st_async32(mapa(d, 0), p0, rbar); st_async32(mapa(d + 128, 0), p1, rbar); }
            else { sts32(d, p0); sts32(d + 128, p1); }
            EV(EV_BIG0, s, 4);
        };
        combine();
        if constexpr (XP) {
            if (s == NSEG - 1) break;
            x_half<0>(xa, w, sb, s + 1, g, warp, tmX);
            EV(EV_BIG0, s, 5);
            EVCAL(s);
            mbar_wait(sb + RB_XF + g * 8, 1);
            nbar_sync(NB_WO, 384);
            EV(EV_BIG0 && lds32(sb + RS_O) != 0x12345678u, s, 6);
            x_half<1>(xa, w, sb, s + 1, g, warp, tmX);
            EV(EV_BIG0, s, 7);
            x_finish(xa, sb, s + 1, g, warp, lane0, tmX);
        } else {
            if (g == 0) {
                if (s < NSEG - 1) mem_attn(sb, s, warp, lane0);
            } else {
                if (s < NSEG - 1) mem_scores(sb, s, warp, lane0); else mbar_wait(sb + RB_KV, s & 1);
                if (s == 0 && warp == 0) {
                    wait_count_warp(&g_cnt[C_QH], 64 * E);
                    if (elect_one()) {
                        asm volatile("fence.proxy.async;" ::: "memory");
                        mbar_expect_tx(sb + RB_QX, 8192);
                        bulk_load(sb + RS_QX, g_qx + (size_t)head * 4096, 8192, sb + RB_QX);
                    }
                    __syncwarp();
                }
                if (TA_LATE && s < NSEG - 1) mbar_wait(sb + RB_O, s & 1);
                float sc[8];
                const int t2 = warp == 3 ? 3 : (warp + 1) % 3;
                ta_scores(sc, sb, s, 4 + warp, lane0);
                ta_scores(sc + 4, sb, s, t2, lane0);
                nbar_sync(NB_WG + 1, 128);
                sts128f(aB + (RS_QX - RS_MEM) + (3 + warp) * 512, sc);
                sts128f(aB + (RS_QX - RS_MEM) + (t2 - 1) * 512, sc + 4);
            }
            EVCAL(s);
            if (s < NSEG - 1) nbar_sync(NB_WO, 384); else nbar_sync(NB_BIG, 256);
            EV(EV_BIG0 && lds32(sb + RS_O) != 0x12345678u, s, 6);
            ta_output(sb, s, head, g, warp, lane0);
            nbar_sync(NB_BIG, 256);
            EV(EV_BIG0 && lds32(sb + RS_O) != 0x12345678u, s, 7);
            if (g == 0 && warp == 0 && s + 1 < NSEG) {
                if (elect_one()) {
                    mbar_arrive_remote(mapa(sb + RB_ATT, 1));
                    mbar_arrive_remote(mapa(sb + RB_ATT, 2));
                    mbar_expect_tx(sb + RB_KV, 8192);
                    mbar_expect_tx(sb + RB_K, 2048);
                    mbar_expect_tx(sb + RB_V, 2048 + 8192);
                    mbar_arrive(sb + RB_T);
                }
                __syncwarp();
            }
        }
    }
    if constexpr (!XP) { if (tid_now() == 0) signal_count(&g_prog[(NSEG - 1) >> 2]); }
#undef lane0
}

template <int T, int K0, int K1>
DEVI void wo_part(float* acc) {
    constexpr uint32_t dWo = cdesc(T < 5 ? RS_WO + T * 16384 : RS_WO5, 16), dO = cdesc(RS_O, 128);
#pragma unroll
    for (int kk = K0; kk < K1; kk++) {
        if (kk == 0) { if (T < 3) wgmma_n8_ss_first<0>(acc, dWo, dO); else wgmma_n8_ss<0, 0>(acc, dWo, dO); }
        else wgmma_n8_ss<0, 1>(acc, dWo + kk * 128, dO + kk * 16);
    }
    wg_commit();
}
DEVI void red3(uint8_t* p, uint32_t a, uint32_t b, uint32_t c, uint32_t one) {
    asm volatile("red.relaxed.gpu.global.add.noftz.v4.bf16x2 [%0], {%1,%2,%3,%4};" :: "l"(p), "r"(a), "r"(b), "r"(c), "r"(one) : "memory");
}
constexpr int ACC_CH = 3 * 16 * 1024;
template <bool Q>
DEVI void wo_phase(uint32_t sb, int s, int warp, uint8_t* p, uint32_t ainv, int gap) {
    float a0[4], a1[4], a2[4];
    fence_proxy_async();
    const float2 iv = lds64f(ainv);
    SCHED_FENCE();
    const float i0 = rcp_fast(iv.x), i1 = rcp_fast(iv.y);
#define WORD(a, h) pack_bf16(a[2 * h] * i0, a[2 * h + 1] * i1)
    wg_fence();
    wo_part<0, 0, 8>(a0); wo_part<1, 0, 8>(a1); wo_part<2, 0, 8>(a2);
    if (!Q && WO_REL == 4) nbar_arrive(NB_WO, 384);
    wg_wait<1>(); reg_fence<4>(a0); reg_fence<4>(a1);
    if (!Q && WO_REL == 3) nbar_arrive(NB_WO, 384);
    red3(p, WORD(a0, 0), WORD(a0, 1), WORD(a1, 0), 0x3F80u);
    SCHED_FENCE();
    EV(warp == 0 && elect_one(), s, 11);
    wg_wait<0>(); reg_fence<4>(a2);
    if (!Q && WO_REL == 2) nbar_arrive(NB_WO, 384);
    red3(p + ACC_CH, WORD(a2, 0), WORD(a2, 1), WORD(a1, 1), 0x3F80u);
    SCHED_FENCE();
    if (Q || WO_REL < 2) { const uint32_t t = clk32() + gap; while ((int)(clk32() - t) < 0) { } }
    wg_fence();
    wo_part<3, 0, 8>(a0); wo_part<4, 0, 8>(a1);
    if (Q) {
        wo_part<5, 0, 8>(a2);
        wg_wait<1>(); reg_fence<4>(a0); reg_fence<4>(a1);
        red3(p + 2 * ACC_CH, WORD(a0, 0), WORD(a0, 1), WORD(a1, 0), 0x3F80u);
        SCHED_FENCE();
        wg_wait<0>(); reg_fence<4>(a2);
        red3(p + 3 * ACC_CH, WORD(a2, 0), WORD(a2, 1), WORD(a1, 1), 0x3F80u);
        nbar_arrive(NB_WO, 384);
    } else {
        wg_wait<1>();
        nbar_arrive(NB_WO, 384);
        wg_wait<0>(); reg_fence<4>(a0); reg_fence<4>(a1);
        red3(p + 2 * ACC_CH, WORD(a0, 0), WORD(a0, 1), WORD(a1, 0), 0x3F80u);
        red3(p + 3 * ACC_CH, 0u, 0u, WORD(a1, 1), 0x3F80u);
    }
#undef WORD
}
template <bool SEND>
DEVI void unit_put(uint32_t d, uint32_t x0, uint32_t x1, uint32_t x2, uint32_t x3, uint32_t bar, uint32_t nxt) {
    const uint32_t u0 = __byte_perm(x0, x1, 0x5410), u1 = __byte_perm(x2, x3, 0x5410), u2 = __byte_perm(x0, x1, 0x7632), u3 = __byte_perm(x2, x3, 0x7632);
    if (SEND) st_async128(mapa(d, nxt), u0, u1, u2, u3, mapa(bar, nxt));
    sts128(d, make_uint4(u0, u1, u2, u3));
}
template <bool SEND, int R>
DEVI void stage_round(uint32_t sb, int s, uint32_t rr, uint32_t nxt, int warp, const uint8_t* src, uint32_t col, uint32_t gate, uint32_t bytes) {
    uint4 v[4];
    while ((int)(clk32() - gate) < 0) { }
    EV(elect_one(), s, 16 + 2 * R + (warp & 1) + (warp & 2) * 50);
#pragma unroll
    for (int j = 0; j < 4; j++) v[j] = ld_rlx4(src + R * 2 * ACC_CH + j * 1024);
    const uint32_t bar = sb + RB_G + 8 * R, c0 = col + R * 3072;
    int n = 0;
    while (!__all_sync(0xffffffffu, v[0].w == 0x4200u && v[1].w == 0x4200u && v[2].w == 0x4200u && v[3].w == 0x4200u)) {
#pragma unroll
        for (int j = 0; j < 4; j++) v[j] = ld_rlx4(src + R * 2 * ACC_CH + j * 1024);
        if (++n > SPIN_LIMIT) TRAP(0x20000000u | (s << 8) | warp);
    }
    EV(elect_one(), s, 24 + 2 * R + (warp & 1) + (warp & 2) * 50);
    if (R == 0 || rr == 0 || !(warp & 1)) {
        unit_put<SEND>(c0 + (warp & 1) * 2048, v[0].x, v[1].x, v[2].x, v[3].x, bar, nxt);
        unit_put<SEND>((c0 ^ 160) + (warp & 1) * 2048, v[0].y, v[1].y, v[2].y, v[3].y, bar, nxt);
    }
    unit_put<SEND>((c0 ^ ((warp & 1) * 160)) + 1024, v[0].z, v[1].z, v[2].z, v[3].z, bar, nxt);
    __syncwarp();
    if (elect_one()) mbar_expect_tx(bar, bytes);
    EV(elect_one(), s, 20 + 2 * R + (warp & 1) + (warp & 2) * 50);
    SCHED_FENCE();
}
DEVI void wo_permute(uint32_t a, int n) {
    const uint32_t flip = (a >> 3) & 16;
#pragma unroll 2
    for (int i = 0; i < n; i++, a += 4096) {
        const uint4 v = lds128(a ^ flip), u = lds128(a ^ flip ^ 16);
        sts128(a ^ flip, make_uint4(__byte_perm(v.x, v.y, 0x5410), __byte_perm(v.x, v.y, 0x7632), __byte_perm(u.x, u.y, 0x5410), __byte_perm(u.x, u.y, 0x7632)));
        sts128(a ^ flip ^ 16, make_uint4(__byte_perm(v.z, v.w, 0x5410), __byte_perm(v.z, v.w, 0x7632), __byte_perm(u.z, u.w, 0x5410), __byte_perm(u.z, u.w, 0x7632)));
    }
}
DEVI uint32_t acc_clear(int slot, int idx, uint32_t lo) {
    uint8_t* p = g_acc + (uint32_t)(slot * 128 + idx * 3072 + (lo < 3072 ? lo : lo - 1024));
    st_rlx4(p, 0u, 0u, 0u, 0u);
    uint32_t z; asm volatile("ld.relaxed.gpu.global.u32 %0, [%1];" : "=r"(z) : "l"(p) : "memory");
    return z;
}

template <bool Q>
DEVI void aux_main(uint32_t sb, int warp, uint32_t rank, int head, const CUtensorMap* tmX, const bf16* xg, unsigned E, const int4 tune) {
    const uint32_t lo = __shfl_sync(0xffffffffu, ((tid_now() >> 3) & 3) * 1024 + (tid_now() & 7) * 16, tid_now() & 31);
    for (int s = 0; s < NSEG - 1; s++) {
        if (!Q && warp == 0 && elect_one()) mbar_expect_tx(sb + RB_O, 2048 + 256);
        __syncwarp();
        const uint32_t slot = (s & 3) * 128;
        mbar_wait(sb + RB_O, s & 1);
        EV(warp == 0 && elect_one(), s, 10);
        wo_phase<Q>(sb, s, warp, g_acc + (uint32_t)(slot + (rank * 4 + warp) * 4096 + opaque(lo)), sb + RS_INV + ((opaque(lo) >> 1) & 24), tune.z);
        SCHED_FENCE();
        const uint32_t t_o = clk32();
        EV(warp == 0 && elect_one(), s, 12);
        {
            const uint32_t l = opaque(lo), nxt = Q ? 1 : (rank == 1 ? 2 : 0), rr = warp < 2 ? rank : nxt;
            const uint8_t* src = g_acc + (uint32_t)(slot + rr * 16384 + (warp & 1) * ACC_CH + (l & 0xC00) * 4 + (l & 0x70));
            const uint32_t col = sb + RS_MEM + (rr == 0 ? 0 : rr * 5 + 1) * 1024 + ((l >> 2) & 0x300) + (l & 0x70);
            if (warp < 2) {
                stage_round<true, 0>(sb, s, rr, nxt, warp, src, col, t_o + tune.x, 1536u);
                stage_round<true, 1>(sb, s, rr, nxt, warp, src, col, t_o + tune.y, rank == 1 ? 1536u : 1024u);
            } else {
                stage_round<false, 0>(sb, s, rr, nxt, warp, src, col, t_o + tune.x, 0u);
                stage_round<false, 1>(sb, s, rr, nxt, warp, src, col, t_o + tune.y, 0u);
            }
        }
        EV(warp == 2 && elect_one(), s, 14);
        if (warp == 3) {
            if (Q) {
                mbar_wait(sb + RB_T, s & 1);
                if (s == 3) wait_count_warp(&g_cnt[C_Q], 64 * E);
                if (elect_one()) {
                    if (s == 3) asm volatile("fence.proxy.async;" ::: "memory"); else fence_proxy_async();
                    mbar_expect_tx(sb + RB_QX, 8192);
                    bulk_load(sb + RS_QX, g_qx + ((size_t)(s + 1) * NH + head) * 4096, 8192, sb + RB_QX);
                    if (head == 0) { TLOG(1400 + s, 0, gtime()); TLOG(1400 + s, 1, clock64()); }
                }
                __syncwarp();
                const bool fresh = (s & 7) == 6 && s + 2 < NSEG;
                if (fresh) wait_count_warp(&g_cnt[C_Q + ((s + 2) >> 3)], 64 * E);
                if (elect_one()) {
                    if (fresh) asm volatile("fence.proxy.async;" ::: "memory");
                    if (s + 2 < NSEG && s != 2) l2_prefetch(g_qx + ((size_t)(s + 2) * NH + head) * 4096, 8192);
                    if (s + 4 < NSEG) l2_prefetch(xg + (size_t)((s + 4) * 32 + head) * DM, 2048);
                    signal_count(&g_prog[s >> 2]);
                }
                __syncwarp();
            } else {
                const uint32_t zero = acc_clear((s + 2) & 3, 2 * head + (int)rank - 1, opaque(lo));
                mbar_wait(sb + RB_G + 8, s & 1);
                x_send(sb, s + 1, rank, tune.w);
                if (__any_sync(0xffffffffu, zero != 0u)) __trap();
            }
        }
    }
}

DEVI void load_weights(uint32_t sb, const CUtensorMap* tmW, const CUtensorMap* tmWo, int head, uint32_t rank) {
    const uint32_t bW = sb + RB_W, bSF = sb + RB_SF, bSE = sb + RB_SE;
    const int ntile = rank == 0 ? 6 : 5, tile0 = rank == 0 ? 0 : (rank == 1 ? 6 : 11);
    mbar_expect_tx(bW, R_NSS * 16384);
    mbar_expect_tx(sb + RB_WO, ntile * 16384);
    for (int pass = 0; pass < 2; pass++) {
        for (int pos = 0; pos < 16; pos++) {
            const int k = (int)((R_TORD_PACK >> (4 * pos)) & 15ull) * 64, rd = pos - pos / 3, slot = rd % 5;
            if (r_pos_ss(pos)) {
                if (pass) continue;
                const uint32_t dst = sb + RS_WSS + (pos / 3) * 16384;
                tma_load_2d(dst, tmW, head * DH, k, bW);
                tma_load_2d(dst + 8192, tmW, head * DH + 64, k, bW);
            } else if (pass == (rd >= 5)) {
                if (rd >= 5) mbar_wait(bSE + 8 * slot, ((rd / 5) - 1) & 1);
                mbar_expect_tx(bSF + 8 * slot, 16384);
                const uint32_t dst = sb + RS_WO + slot * 16384;
                tma_load_2d(dst, tmW, head * DH, k, bSF + 8 * slot);
                tma_load_2d(dst + 8192, tmW, head * DH + 64, k, bSF + 8 * slot);
            }
        }
    }
    if (rank == 0) tma_load_wo(sb + RS_WO5, tmWo, 5 * 64, head * 4, sb + RB_WO);
    for (int i = 1; i <= 5; i++) {
        const int slot = i % 5, last = slot + 10 < R_NRS ? slot + 10 : slot + 5;
        mbar_wait(bSE + 8 * slot, (last / 5) & 1);
        tma_load_wo(sb + RS_WO + slot * 16384, tmWo, (tile0 + slot) * 64, head * 4, sb + RB_WO);
    }
}
template <bool XP>
DEVI void big_prologue(uint32_t* w, uint32_t sb, int g, int warp, const bf16* __restrict__ mem0) {
    const int tid = tid_now(), lane = tid & 31;
    {
        const uint32_t* m = (const uint32_t*)(mem0 + (lane >> 2) * DM + (tid >> 5) * 16) + (lane & 3);
        uint32_t u[16];
#pragma unroll
        for (int j = 0; j < 8; j++) { u[2 * j] = m[j * 64]; u[2 * j + 1] = m[j * 64 + 4]; }
#pragma unroll
        for (int j = 0; j < 8; j++) sts64(sb + RS_MEM + ((tid >> 5) + j * 8) * 256 + b_frag_off(lane), u[2 * j], u[2 * j + 1]);
    }
    const uint32_t a0 = sb + RS_WO + g * (8192 + 4096) + a_frag_off(lane, warp), a1 = a0 + 8192 - g * 16384;
#pragma unroll
    for (int rd = 0; rd < R_NRS; rd++) {
        const int slot = rd % 5;
        mbar_wait(sb + RB_SF + 8 * slot, (rd / 5) & 1);
#pragma unroll
        for (int q = 0; q < 4; q++) {
            if (XP && rd == 0 && q == 3) {
                sts128(sb + RS_WX + g * 2048 + (tid & 127) * 16, lds128(sb + RS_WO + 8192 - g * 4096 + 2048 + (tid & 127) * 16));
                fence_proxy_async();
                nbar_sync(NB_WG + g, 128);
            } else ldsm4t(&w[rd * 16 + q * 4], ((q & 1) ? a1 : a0) + slot * 16384 + (q >> 1) * 2048);
        }
        mbar_arrive(sb + RB_SE + 8 * slot);
    }
    mbar_wait(sb + RB_W, 0);
}

#define REC_END() do { if (tid_now() == 0) TLOG(1024 + blockIdx.x, 1, gtime()); } while (0)
__global__ void __launch_bounds__(384, 1)
k_rec(const __grid_constant__ PMaps mp, const __grid_constant__ CUtensorMap tmWk, const __grid_constant__ CUtensorMap tmWv,
      const __grid_constant__ CUtensorMap tmWo, const __grid_constant__ CUtensorMap tmX, const bf16* __restrict__ mem0, const bf16* __restrict__ xg,
      int4 tq, int4 tk, int rec) {
    extern __shared__ __align__(1024) uint8_t smem_raw[];
    const uint32_t sb = smem_u32(smem_raw);
    if ((sb & 0x3FFFFu) != SB0) __trap();
    const int tid = threadIdx.x;
    const int wg = __shfl_sync(0xffffffffu, tid >> 7, 0), warp = __shfl_sync(0xffffffffu, (tid >> 5) & 3, 0);
    uint32_t rank; asm("mov.u32 %0, %%cluster_ctarank;" : "=r"(rank));
    const int head = blockIdx.x / 3;
    asm volatile("griddepcontrol.launch_dependents;");
    if (tid == 0 && rec) {
        mbar_init(sb + RB_G, 4);
        mbar_init(sb + RB_G + 8, 4);
        mbar_init(sb + RB_T, 1); mbar_init(sb + RB_WO, 1);
        mbar_init(sb + RB_K, 1); mbar_init(sb + RB_V, 1); mbar_init(sb + RB_KV, 1); mbar_init(sb + RB_QX, 1);
        mbar_init(sb + RB_O, rank == 0 ? 4 : 1); mbar_init(sb + RB_ATT, 1); mbar_init(sb + RB_W, 1);
        for (int i = 0; i < 5; i++) { mbar_init(sb + RB_SF + 8 * i, 1); mbar_init(sb + RB_SE + 8 * i, 256); }
        for (int i = 0; i < 2; i++) mbar_init(sb + RB_XF + 8 * i, X_SLOTS);
        fence_mbar_init();
        if (rank == 0) { mbar_expect_tx(sb + RB_KV, 8192); mbar_expect_tx(sb + RB_K, 2048); mbar_expect_tx(sb + RB_V, 2048 + 8192); }
    }
    __syncthreads();
    asm volatile("barrier.cluster.arrive.release.aligned;" ::: "memory");

    if (wg < 2) {
        reg_inc<REG_KB>();
        if (rank != 0) {
            uint32_t w[R_NRS * 16];
            if ((tid & 127) == 0) for (int j = 0; j < X_SLOTS; j++) x_load(sb, 0, j, wg, &tmX);
            __syncwarp();
            cluster_wait();
            big_prologue<true>(w, sb, wg, warp, mem0);
            big_main<true>(w, sb, wg, warp, rank, head, &tmX, xg, 0u);
            REC_END();
        } else if (rec) {
            uint32_t w[R_NRS * 16];
            cluster_wait();
            big_prologue<false>(w, sb, wg, warp, mem0);
            big_main<false>(w, sb, wg, warp, rank, head, &tmX, xg, *(volatile unsigned*)&g_epoch + 1);
            REC_END();
        } else cluster_wait();
        nbar_sync(0, 384);
        nbar_sync(0, 384);
        post_consumer(mp, sb, wg, warp);
    } else {
        reg_dec<504 - 2 * REG_KB>();
        if (rec) {
            if (tid == 256) {
                if (rank == 0) l2_prefetch(xg + (size_t)head * 8 * DM, 16384);
                load_weights(sb, rank == 0 ? &mp.wq : (rank == 1 ? &tmWk : &tmWv), &tmWo, head, rank);
            }
            if (warp == 3 && rank != 0) {
                const uint32_t lo = ((tid >> 3) & 3) * 1024 + (tid & 7) * 16;
                acc_clear(0, 2 * head + (int)rank - 1, lo); acc_clear(1, 2 * head + (int)rank - 1, lo);
                __threadfence();
                __syncwarp();
                if (tid == 256 + 96) atomicAdd(&g_zero, 1u);
            }
            __syncwarp();
        }
        cluster_wait();
        const unsigned E = __shfl_sync(0xffffffffu, *(volatile unsigned*)&g_epoch + 1, 0);
        if (rec) {
            if (warp == 1) wait_count_warp(&g_zero, E * 64u);
            if (warp == 3 && rank != 0) x_send(sb, 0, rank, 0);
            mbar_wait(sb + RB_WO, 0);
            wo_permute(sb + RS_WO + (tid & 127) * 32, 20);
            if (rank == 0) wo_permute(sb + RS_WO5 + (tid & 127) * 32, 4);
            fence_proxy_async();
            nbar_sync(NB_AUX, 128);
            if (rank == 0) aux_main<true>(sb, warp, rank, head, &tmX, xg, E, tq);
            else           aux_main<false>(sb, warp, rank, head, &tmX, xg, E, tk);
        }
        const int t = tid_now();
        int id = 0;
        if (t >= 288 && t < 288 + 12) asm volatile("prefetch.tensormap [%0];" :: "l"(&mp.wq + (t - 288)) : "memory");
        if (t == 256) id = post_claim(mp, E);
        __syncwarp();
        nbar_sync(0, 384);
        if (t == 256) { post_init(sb); fence_proxy_async(); }
        __syncwarp();
        nbar_sync(0, 384);
        if (t == 256) post_producer(mp, sb, E, id);
        else if (t == 288 || t == 320) post_helper(sb, warp - 1);
    }
    __syncthreads();
    asm volatile("griddepcontrol.wait;" ::: "memory");
}

typedef CUresult (*EncodeFn)(CUtensorMap*, CUtensorMapDataType, cuuint32_t, void*, const cuuint64_t*, const cuuint64_t*,
                             const cuuint32_t*, const cuuint32_t*, CUtensorMapInterleave, CUtensorMapSwizzle,
                             CUtensorMapL2promotion, CUtensorMapFloatOOBfill);

static CUtensorMap make_map(EncodeFn fn, const void* ptr, uint64_t inner, uint64_t outer, uint32_t box_inner, uint32_t box_outer) {
    CUtensorMap m;
    cuuint64_t dims[2] = {inner, outer};
    cuuint64_t strides[1] = {inner * 2};
    cuuint32_t box[2] = {box_inner, box_outer};
    cuuint32_t es[2] = {1, 1};
    fn(&m, CU_TENSOR_MAP_DATA_TYPE_BFLOAT16, 2, const_cast<void*>(ptr), dims, strides, box, es,
       CU_TENSOR_MAP_INTERLEAVE_NONE, CU_TENSOR_MAP_SWIZZLE_128B, CU_TENSOR_MAP_L2_PROMOTION_L2_256B, CU_TENSOR_MAP_FLOAT_OOB_FILL_NONE);
    return m;
}

static CUtensorMap make_wo_map(EncodeFn fn, const void* ptr, uint32_t ngrp) {
    CUtensorMap m;
    cuuint64_t dims[5] = {DM, 2, 4, 4, HD / 32};
    cuuint64_t strides[4] = {DM * 2, 8 * DM * 2, 2 * DM * 2, 32 * DM * 2};
    cuuint32_t box[5] = {64, 2, 4, 4, ngrp};
    cuuint32_t es[5] = {1, 1, 1, 1, 1};
    fn(&m, CU_TENSOR_MAP_DATA_TYPE_BFLOAT16, 5, const_cast<void*>(ptr), dims, strides, box, es,
       CU_TENSOR_MAP_INTERLEAVE_NONE, CU_TENSOR_MAP_SWIZZLE_128B, CU_TENSOR_MAP_L2_PROMOTION_L2_256B, CU_TENSOR_MAP_FLOAT_OOB_FILL_NONE);
    return m;
}

struct Maps {
    PMaps post;
    CUtensorMap wk16, wv16, wo128, x32;
};

extern "C" void kernel_launch(void* const* d_in, const int* in_sizes, int n_in, void* d_out, int out_size) {
    const bf16* A_x   = (const bf16*)d_in[0];
    const bf16* A_mem = (const bf16*)d_in[1];
    const bf16* A_Wq  = (const bf16*)d_in[2];
    const bf16* A_Wk  = (const bf16*)d_in[3];
    const bf16* A_Wv  = (const bf16*)d_in[4];
    const bf16* A_Wo  = (const bf16*)d_in[5];
    const bf16* B_x   = (const bf16*)d_in[7];
    const bf16* B_w   = (const bf16*)d_in[8];
    const bf16* B_wo  = (const bf16*)d_in[9];

    static EncodeFn fn = nullptr;
    static Maps mp;
    static const void* cached[10];
    const void* cur[10] = {A_x, A_mem, A_Wq, A_Wk, A_Wv, A_Wo, B_x, B_w, B_wo, d_out};
    bool same = fn != nullptr;
    for (int i = 0; i < 10 && same; i++) same = cached[i] == cur[i];
    if (!same) {
        if (!fn) {
            void* p = nullptr; cudaDriverEntryPointQueryResult qr;
            cudaGetDriverEntryPoint("cuTensorMapEncodeTiled", &p, cudaEnableDefault, &qr);
            fn = (EncodeFn)p;
            cudaFuncSetAttribute(k_rec, cudaFuncAttributeMaxDynamicSharedMemorySize, R_SMEM);
        }
        void *p_ox, *p_bqkv, *p_bo, *p_qx;
        cudaGetSymbolAddress(&p_qx, g_qx);
        cudaGetSymbolAddress(&p_ox, g_ox); cudaGetSymbolAddress(&p_bqkv, g_bqkv); cudaGetSymbolAddress(&p_bo, g_bo);
        mp.post.wq   = make_map(fn, A_Wq, HD, DM, 64, 64);
        mp.post.wo   = make_wo_map(fn, A_Wo, 2);
        mp.post.bw   = make_map(fn, B_w, 3 * DM, DM, 64, 64);
        mp.post.bwo  = make_map(fn, B_wo, DM, DM, 64, 64);
        mp.post.x    = make_map(fn, A_x, DM, S_TOK, 64, 128);
        mp.post.bx   = make_map(fn, B_x, DM, S_TOK, 64, 128);
        mp.post.bo   = make_map(fn, p_bo, DM, S_TOK, 64, 128);
        mp.post.ox   = make_map(fn, p_ox, HD, S_TOK, 64, 128);
        mp.post.cb   = make_map(fn, p_bqkv, 3 * DM, S_TOK, 64, 64);
        mp.post.cout = make_map(fn, d_out, 2 * DM, S_TOK, 64, 64);
        {
            cuuint64_t dims[4] = {256, 4, NH * 4, NSEG};
            cuuint64_t strides[3] = {512, 2048, NH * 8192};
            cuuint32_t box[4] = {256, 2, 4, 2};
            cuuint32_t es[4] = {1, 1, 1, 1};
            fn(&mp.post.cq, CU_TENSOR_MAP_DATA_TYPE_BFLOAT16, 4, p_qx, dims, strides, box, es,
               CU_TENSOR_MAP_INTERLEAVE_NONE, CU_TENSOR_MAP_SWIZZLE_NONE, CU_TENSOR_MAP_L2_PROMOTION_NONE, CU_TENSOR_MAP_FLOAT_OOB_FILL_NONE);
        }
        {
            int runs[48] = {K_QH, 0, 2, K_Q, 1, 7, K_B1, 0, 8, K_A4, 0, 4, K_B2, 0, 32, K_A4, 4, 2, K_B3, 0, 4, K_A3, 12, 2, K_B3, 4, 4, K_SK, 14, 2, -1};
            const int per[8] = {32, 24, 8, 8, 32, 8, 8 * P_SPLIT, 1};
            int n = 0, id = 0;
            for (; runs[3 * n] >= 0; n++) {
                mp.post.list.run[n] = make_int4(runs[3 * n], runs[3 * n + 1], id, id + runs[3 * n + 2] * per[runs[3 * n]]);
                id = mp.post.list.run[n].w;
            }
            mp.post.list.n = n;
            int dev = 0, nsm = 132;
            cudaGetDevice(&dev);
            cudaDeviceGetAttribute(&nsm, cudaDevAttrMultiProcessorCount, dev);
            mp.post.list.nworker = nsm > 96 ? nsm : 97;
        }
        {
            cuuint64_t dims[4] = {DM, 3, 2, S_TOK / 2};
            cuuint64_t strides[3] = {DM * 2, 3 * DM * 2, 3 * DM * 4};
            cuuint32_t box[4] = {64, 3, 1, 40};
            cuuint32_t es[4] = {1, 1, 1, 1};
            fn(&mp.post.b40, CU_TENSOR_MAP_DATA_TYPE_BFLOAT16, 4, p_bqkv, dims, strides, box, es,
               CU_TENSOR_MAP_INTERLEAVE_NONE, CU_TENSOR_MAP_SWIZZLE_128B, CU_TENSOR_MAP_L2_PROMOTION_L2_256B, CU_TENSOR_MAP_FLOAT_OOB_FILL_NONE);
        }
        mp.wk16 = make_map(fn, A_Wk, HD, DM, 64, 64);
        mp.wv16 = make_map(fn, A_Wv, HD, DM, 64, 64);
        mp.wo128 = make_wo_map(fn, A_Wo, 4);
        {
            cuuint64_t dims[3] = {64, S_TOK, DM / 64};
            cuuint64_t strides[2] = {DM * 2, 128};
            cuuint32_t box[3] = {32, 32, 2};
            cuuint32_t es[3] = {1, 1, 1};
            fn(&mp.x32, CU_TENSOR_MAP_DATA_TYPE_BFLOAT16, 3, const_cast<bf16*>(A_x), dims, strides, box, es,
               CU_TENSOR_MAP_INTERLEAVE_NONE, CU_TENSOR_MAP_SWIZZLE_64B, CU_TENSOR_MAP_L2_PROMOTION_L2_128B, CU_TENSOR_MAP_FLOAT_OOB_FILL_NONE);
        }
        for (int i = 0; i < 10; i++) cached[i] = cur[i];
    }

    cudaStream_t st = cudaStreamPerThread;
    int4 tq = make_int4(150, 0, 80, 350), tk = make_int4(250, 0, 80, 200);
    cudaLaunchConfig_t cfg = {};
    cfg.gridDim = dim3(96); cfg.blockDim = dim3(384); cfg.dynamicSmemBytes = R_SMEM; cfg.stream = st;
    cudaLaunchAttribute at[1];
    at[0].id = cudaLaunchAttributeClusterDimension;
    at[0].val.clusterDim.x = 3; at[0].val.clusterDim.y = 1; at[0].val.clusterDim.z = 1;
    cfg.attrs = at; cfg.numAttrs = 1;
    cudaLaunchKernelEx(&cfg, k_rec, mp.post, mp.wk16, mp.wv16, mp.wo128, mp.x32, A_mem, A_x, tq, tk, 1);
    cfg.gridDim = dim3(mp.post.list.nworker - 96);
    at[0].id = cudaLaunchAttributeProgrammaticStreamSerialization;
    at[0].val.programmaticStreamSerializationAllowed = 1;
    cudaLaunchKernelEx(&cfg, k_rec, mp.post, mp.wk16, mp.wv16, mp.wo128, mp.x32, A_mem, A_x, tq, tk, 0);
}
```

```cpp
#include <cuda_runtime.h>
#include <cuda_bf16.h>
#include <cuda.h>
#include <stdint.h>

typedef __nv_bfloat16 bf16;

constexpr int S_TOK = 2048;
constexpr int DM    = 1024;
constexpr int NH    = 32;
constexpr int DH    = 128;
constexpr int NSEG  = 64;
constexpr int HD    = NH * DH;

__device__ __align__(1024) bf16 g_qx[NSEG * NH * 4 * DH * 8];
__device__ __align__(1024) bf16 g_ox[S_TOK * HD];
__device__ __align__(1024) bf16 g_bqkv[S_TOK * 3 * DM];
__device__ __align__(1024) bf16 g_bo[S_TOK * DM];
__device__ __align__(1024) uint8_t g_acc[192 * 1024];

#define EV(cond, s, k) do {} while (0)
#define EVCAL(s) do {} while (0)

constexpr int P_NSK = 4;
__device__ unsigned g_epoch, g_qctr, g_done, g_zero;
enum { C_B1 = 0, C_B2 = 8, C_Q = 16, C_QH = 24, C_NONE = 31 };
__device__ unsigned g_cnt[32], g_prog[16], g_cnt_sk[P_NSK * 16];
#define P_SPLIT 4
__device__ __align__(1024) uint4 g_skp[P_NSK * 8 * P_SPLIT * 2 * 8 * 128];
#define TLOG(i, k, v) do {} while (0)

#define DEVI __device__ __forceinline__

DEVI uint32_t opaque(uint32_t v) { uint32_t r; asm volatile("mov.u32 %0, %1;" : "=r"(r) : "r"(v)); return r; }
DEVI uint32_t smem_u32(const void* p) { return (uint32_t)__cvta_generic_to_shared(p); }

#define TRAP(code) __trap()
constexpr int SPIN_LIMIT = 1 << 22;
#define MBAR_HINT_NS 20000u
constexpr int SPIN_LIMIT_MBAR = 1 << 17;

DEVI void mbar_init(uint32_t bar, uint32_t cnt) { asm volatile("mbarrier.init.shared::cta.b64 [%0], %1;" :: "r"(bar), "r"(cnt)); }
DEVI void mbar_expect_tx(uint32_t bar, uint32_t bytes) {
    asm volatile("mbarrier.arrive.expect_tx.shared::cta.b64 _, [%0], %1;" :: "r"(bar), "r"(bytes) : "memory");
}
DEVI void mbar_arrive(uint32_t bar) { asm volatile("mbarrier.arrive.shared::cta.b64 _, [%0];" :: "r"(bar) : "memory"); }
DEVI bool mbar_try(uint32_t bar, uint32_t parity) {
    uint32_t ok;
    asm volatile("{.reg .pred p; mbarrier.try_wait.parity.shared::cta.b64 p, [%1], %2; selp.u32 %0, 1, 0, p;}"
                 : "=r"(ok) : "r"(bar), "r"(parity) : "memory");
    return ok;
}
DEVI bool mbar_try_cluster(uint32_t bar, uint32_t parity) {
    uint32_t ok;
    asm volatile("{.reg .pred p; mbarrier.try_wait.parity.acquire.cluster.shared::cta.b64 p, [%1], %2; selp.u32 %0, 1, 0, p;}"
                 : "=r"(ok) : "r"(bar), "r"(parity) : "memory");
    return ok;
}
DEVI bool mbar_try_hint(uint32_t bar, uint32_t parity) {
    uint32_t ok;
    asm volatile("{.reg .pred p; mbarrier.try_wait.parity.shared::cta.b64 p, [%1], %2, %3; selp.u32 %0, 1, 0, p;}"
                 : "=r"(ok) : "r"(bar), "r"(parity), "r"(MBAR_HINT_NS) : "memory");
    return ok;
}
DEVI void mbar_wait(uint32_t bar, uint32_t parity) {
    int n = 0;
    while (!mbar_try(bar, parity)) { if (++n > SPIN_LIMIT) TRAP(bar | (parity << 31)); }
}
DEVI void mbar_wait_sleepy(uint32_t bar, uint32_t parity) {
    int n = 0;
    while (!mbar_try_hint(bar, parity)) { if (++n > SPIN_LIMIT_MBAR) __trap(); }
}
DEVI void mbar_wait_cluster(uint32_t bar, uint32_t parity) {
    int n = 0;
    while (!mbar_try_cluster(bar, parity)) { if (++n > SPIN_LIMIT) __trap(); }
}
DEVI void mbar_spin(uint32_t bar, uint32_t parity) {
    uint32_t ok; int n = 0;
    do {
        asm volatile("{.reg .pred p; mbarrier.test_wait.parity.shared::cta.b64 p, [%1], %2; selp.u32 %0, 1, 0, p;}"
                     : "=r"(ok) : "r"(bar), "r"(parity) : "memory");
        if (++n > SPIN_LIMIT) __trap();
    } while (!ok);
}
DEVI void fence_mbar_init() { asm volatile("fence.mbarrier_init.release.cluster;" ::: "memory"); }
DEVI void fence_proxy_async() { asm volatile("fence.proxy.async.shared::cta;" ::: "memory"); }
DEVI void cluster_sync() {
    asm volatile("barrier.cluster.arrive.release.aligned;\n barrier.cluster.wait.acquire.aligned;" ::: "memory");
}
DEVI void fence_proxy_global() { asm volatile("fence.proxy.async.global;" ::: "memory"); }
DEVI void cluster_wait() { asm volatile("barrier.cluster.wait.acquire.aligned;" ::: "memory"); }
DEVI void nbar_sync(int id, int n) { asm volatile("bar.sync %0, %1;" :: "r"(id), "r"(n) : "memory"); }
DEVI void nbar_arrive(int id, int n) { asm volatile("bar.arrive %0, %1;" :: "r"(id), "r"(n) : "memory"); }

DEVI void tma_load_2d(uint32_t dst, const CUtensorMap* map, int x, int y, uint32_t bar) {
    asm volatile("cp.async.bulk.tensor.2d.shared::cluster.global.mbarrier::complete_tx::bytes [%0], [%1, {%3, %4}], [%2];"
                 :: "r"(dst), "l"(map), "r"(bar), "r"(x), "r"(y) : "memory");
}
DEVI void tma_load_3d(uint32_t dst, const CUtensorMap* map, int x, int y, int z, uint32_t bar) {
    asm volatile("cp.async.bulk.tensor.3d.shared::cluster.global.mbarrier::complete_tx::bytes [%0], [%1, {%3, %4, %5}], [%2];"
                 :: "r"(dst), "l"(map), "r"(bar), "r"(x), "r"(y), "r"(z) : "memory");
}
DEVI void tma_load_wo(uint32_t dst, const CUtensorMap* map, int col, int k32, uint32_t bar) {
    asm volatile("cp.async.bulk.tensor.5d.shared::cluster.global.mbarrier::complete_tx::bytes [%0], [%1, {%3, %5, %5, %5, %4}], [%2];"
                 :: "r"(dst), "l"(map), "r"(bar), "r"(col), "r"(k32), "r"(0) : "memory");
}
DEVI void tma_store_2d(const CUtensorMap* map, uint32_t src, int x, int y) {
    asm volatile("cp.async.bulk.tensor.2d.global.shared::cta.bulk_group [%0, {%2, %3}], [%1];"
                 :: "l"(map), "r"(src), "r"(x), "r"(y) : "memory");
}
DEVI void bulk_load(uint32_t dst, const void* src, uint32_t bytes, uint32_t bar) {
    asm volatile("cp.async.bulk.shared::cluster.global.mbarrier::complete_tx::bytes [%0], [%1], %2, [%3];"
                 :: "r"(dst), "l"(src), "r"(bytes), "r"(bar) : "memory");
}
DEVI void tma_load_2d_mc(uint32_t dst, const CUtensorMap* map, int x, int y, uint32_t bar, uint16_t mask) {
    asm volatile("cp.async.bulk.tensor.2d.shared::cluster.global.mbarrier::complete_tx::bytes.multicast::cluster [%0], [%1, {%3, %4}], [%2], %5;"
                 :: "r"(dst), "l"(map), "r"(bar), "r"(x), "r"(y), "h"(mask) : "memory");
}
DEVI void bulk_copy_s2c(uint32_t dst_cluster, uint32_t src, uint32_t bytes, uint32_t bar_cluster) {
    asm volatile("cp.async.bulk.shared::cluster.shared::cta.mbarrier::complete_tx::bytes [%0], [%1], %2, [%3];"
                 :: "r"(dst_cluster), "r"(src), "r"(bytes), "r"(bar_cluster) : "memory");
}
DEVI void bulk_store(void* dst, uint32_t src, uint32_t bytes) {
    asm volatile("cp.async.bulk.global.shared::cta.bulk_group [%0], [%1], %2;" :: "l"(dst), "r"(src), "r"(bytes) : "memory");
}
DEVI void bulk_wait_read() { asm volatile("cp.async.bulk.wait_group.read 0;" ::: "memory"); }
DEVI void mbar_arrive_remote(uint32_t bar_cluster) {
    asm volatile("mbarrier.arrive.shared::cluster.b64 _, [%0];" :: "r"(bar_cluster) : "memory");
}
DEVI void mbar_expect_tx_remote(uint32_t bar_cluster, uint32_t bytes) {
    asm volatile("mbarrier.arrive.expect_tx.shared::cluster.b64 _, [%0], %1;" :: "r"(bar_cluster), "r"(bytes) : "memory");
}
DEVI void l2_prefetch(const void* p, uint32_t bytes) {
    asm volatile("cp.async.bulk.prefetch.L2.global [%0], %1;" :: "l"(p), "r"(bytes) : "memory");
}
DEVI void bulk_commit() { asm volatile("cp.async.bulk.commit_group;" ::: "memory"); }
DEVI void bulk_wait_all() { asm volatile("cp.async.bulk.wait_group 0;" ::: "memory"); }

DEVI void wg_fence() { asm volatile("wgmma.fence.sync.aligned;" ::: "memory"); }
DEVI void wg_commit() { asm volatile("wgmma.commit_group.sync.aligned;" ::: "memory"); }
template <int N> DEVI void wg_wait() { asm volatile("wgmma.wait_group.sync.aligned %0;" :: "n"(N) : "memory"); }

template <int R> DEVI void reg_dec() { asm volatile("setmaxnreg.dec.sync.aligned.u32 %0;" :: "n"(R)); }
template <int R> DEVI void reg_inc() { asm volatile("setmaxnreg.inc.sync.aligned.u32 %0;" :: "n"(R)); }

DEVI uint64_t mk_desc(uint32_t addr, uint32_t lbo, uint32_t sbo, uint32_t sw) {
    return (uint64_t)((addr & 0x3FFFF) >> 4) | ((uint64_t)(lbo >> 4) << 16) | ((uint64_t)(sbo >> 4) << 32) | ((uint64_t)sw << 62);
}

DEVI uint32_t desc_lo(uint32_t addr, uint32_t lbo) { return ((addr & 0x3FFFF) >> 4) | ((lbo >> 4) << 16); }
constexpr uint32_t DHI_SW128 = (1024u >> 4) | (1u << 30);
constexpr uint32_t DHI_SW64  = (512u >> 4) | (2u << 30);
constexpr uint32_t DHI_NONE  = (128u >> 4);

template <int TB, int SCALE_D>
DEVI void wgmma_n8_ss(float* d, uint32_t alo, uint32_t blo) {
    asm volatile("{.reg .b64 da, db; mov.b64 da, {%4, %6}; mov.b64 db, {%5, %7};\n"
                 "wgmma.mma_async.sync.aligned.m64n8k16.f32.bf16.bf16 {%0,%1,%2,%3}, da, db, %8, 1, 1, 1, %9;}"
                 : "+f"(d[0]), "+f"(d[1]), "+f"(d[2]), "+f"(d[3])
                 : "r"(alo), "r"(blo), "n"(DHI_SW128), "n"(DHI_NONE), "n"(SCALE_D), "n"(TB));
}

template <int TB>
DEVI void wgmma_n8_ss_first(float* d, uint32_t alo, uint32_t blo) {
    asm volatile("{.reg .b64 da, db; mov.b64 da, {%4, %6}; mov.b64 db, {%5, %7};\n"
                 "wgmma.mma_async.sync.aligned.m64n8k16.f32.bf16.bf16 {%0,%1,%2,%3}, da, db, 0, 1, 1, 1, %8;}"
                 : "=f"(d[0]), "=f"(d[1]), "=f"(d[2]), "=f"(d[3])
                 : "r"(alo), "r"(blo), "n"(DHI_SW128), "n"(DHI_NONE), "n"(TB));
}
DEVI void wgmma_n32_rs_first(float* d, const uint32_t* a, uint32_t blo) {
    asm volatile("{.reg .b64 db; mov.b64 db, {%20, %21};\n"
                 "wgmma.mma_async.sync.aligned.m64n32k16.f32.bf16.bf16 {%0,%1,%2,%3,%4,%5,%6,%7,%8,%9,%10,%11,%12,%13,%14,%15}, "
                 "{%16,%17,%18,%19}, db, 0, 1, 1, 0;}"
                 : "=f"(d[0]), "=f"(d[1]), "=f"(d[2]), "=f"(d[3]), "=f"(d[4]), "=f"(d[5]), "=f"(d[6]), "=f"(d[7]),
                   "=f"(d[8]), "=f"(d[9]), "=f"(d[10]), "=f"(d[11]), "=f"(d[12]), "=f"(d[13]), "=f"(d[14]), "=f"(d[15])
                 : "r"(a[0]), "r"(a[1]), "r"(a[2]), "r"(a[3]), "r"(blo), "n"(DHI_SW64));
}
template <int N> DEVI void reg_fence(float* d) {
#pragma unroll
    for (int i = 0; i < N; i++) asm volatile("" : "+f"(d[i]) :: "memory");
}
DEVI void wgmma_n32_rs(float* d, const uint32_t* a, uint32_t blo) {
    asm volatile("{.reg .b64 db; mov.b64 db, {%20, %21};\n"
                 "wgmma.mma_async.sync.aligned.m64n32k16.f32.bf16.bf16 {%0,%1,%2,%3,%4,%5,%6,%7,%8,%9,%10,%11,%12,%13,%14,%15}, "
                 "{%16,%17,%18,%19}, db, 1, 1, 1, 0;}"
                 : "+f"(d[0]), "+f"(d[1]), "+f"(d[2]), "+f"(d[3]), "+f"(d[4]), "+f"(d[5]), "+f"(d[6]), "+f"(d[7]),
                   "+f"(d[8]), "+f"(d[9]), "+f"(d[10]), "+f"(d[11]), "+f"(d[12]), "+f"(d[13]), "+f"(d[14]), "+f"(d[15])
                 : "r"(a[0]), "r"(a[1]), "r"(a[2]), "r"(a[3]), "r"(blo), "n"(DHI_SW64));
}
DEVI void wgmma_n32_ss(float* d, uint32_t alo, uint32_t blo) {
    asm volatile("{.reg .b64 da, db; mov.b64 da, {%16, %18}; mov.b64 db, {%17, %19};\n"
                 "wgmma.mma_async.sync.aligned.m64n32k16.f32.bf16.bf16 {%0,%1,%2,%3,%4,%5,%6,%7,%8,%9,%10,%11,%12,%13,%14,%15}, "
                 "da, db, 1, 1, 1, 1, 0;}"
                 : "+f"(d[0]), "+f"(d[1]), "+f"(d[2]), "+f"(d[3]), "+f"(d[4]), "+f"(d[5]), "+f"(d[6]), "+f"(d[7]),
                   "+f"(d[8]), "+f"(d[9]), "+f"(d[10]), "+f"(d[11]), "+f"(d[12]), "+f"(d[13]), "+f"(d[14]), "+f"(d[15])
                 : "r"(alo), "r"(blo), "n"(DHI_SW128), "n"(DHI_SW64));
}

template <bool FIRST>
DEVI void wgmma_n256_ss(float* d, uint64_t a, uint64_t b) {
    if (FIRST)
        asm volatile("wgmma.mma_async.sync.aligned.m64n256k16.f32.bf16.bf16 {%0,%1,%2,%3,%4,%5,%6,%7,%8,%9,%10,%11,%12,%13,%14,%15,%16,%17,%18,%19,%20,%21,%22,%23,%24,%25,%26,%27,%28,%29,%30,%31,%32,%33,%34,%35,%36,%37,%38,%39,%40,%41,%42,%43,%44,%45,%46,%47,%48,%49,%50,%51,%52,%53,%54,%55,%56,%57,%58,%59,%60,%61,%62,%63,%64,%65,%66,%67,%68,%69,%70,%71,%72,%73,%74,%75,%76,%77,%78,%79,%80,%81,%82,%83,%84,%85,%86,%87,%88,%89,%90,%91,%92,%93,%94,%95,%96,%97,%98,%99,%100,%101,%102,%103,%104,%105,%106,%107,%108,%109,%110,%111,%112,%113,%114,%115,%116,%117,%118,%119,%120,%121,%122,%123,%124,%125,%126,%127}, %128, %129, 0, 1, 1, 1, 0;"
            : "=f"(d[0]), "=f"(d[1]), "=f"(d[2]), "=f"(d[3]), "=f"(d[4]), "=f"(d[5]), "=f"(d[6]), "=f"(d[7]), "=f"(d[8]), "=f"(d[9]), "=f"(d[10]), "=f"(d[11]), "=f"(d[12]), "=f"(d[13]), "=f"(d[14]), "=f"(d[15]), "=f"(d[16]), "=f"(d[17]), "=f"(d[18]), "=f"(d[19]), "=f"(d[20]), "=f"(d[21]), "=f"(d[22]), "=f"(d[23]), "=f"(d[24]), "=f"(d[25]), "=f"(d[26]), "=f"(d[27]), "=f"(d[28]), "=f"(d[29]), "=f"(d[30]), "=f"(d[31]), "=f"(d[32]), "=f"(d[33]), "=f"(d[34]), "=f"(d[35]), "=f"(d[36]), "=f"(d[37]), "=f"(d[38]), "=f"(d[39]), "=f"(d[40]), "=f"(d[41]), "=f"(d[42]), "=f"(d[43]), "=f"(d[44]), "=f"(d[45]), "=f"(d[46]), "=f"(d[47]), "=f"(d[48]), "=f"(d[49]), "=f"(d[50]), "=f"(d[51]), "=f"(d[52]), "=f"(d[53]), "=f"(d[54]), "=f"(d[55]), "=f"(d[56]), "=f"(d[57]), "=f"(d[58]), "=f"(d[59]), "=f"(d[60]), "=f"(d[61]), "=f"(d[62]), "=f"(d[63]), "=f"(d[64]), "=f"(d[65]), "=f"(d[66]), "=f"(d[67]), "=f"(d[68]), "=f"(d[69]), "=f"(d[70]), "=f"(d[71]), "=f"(d[72]), "=f"(d[73]), "=f"(d[74]), "=f"(d[75]), "=f"(d[76]), "=f"(d[77]), "=f"(d[78]), "=f"(d[79]), "=f"(d[80]), "=f"(d[81]), "=f"(d[82]), "=f"(d[83]), "=f"(d[84]), "=f"(d[85]), "=f"(d[86]), "=f"(d[87]), "=f"(d[88]), "=f"(d[89]), "=f"(d[90]), "=f"(d[91]), "=f"(d[92]), "=f"(d[93]), "=f"(d[94]), "=f"(d[95]), "=f"(d[96]), "=f"(d[97]), "=f"(d[98]), "=f"(d[99]), "=f"(d[100]), "=f"(d[101]), "=f"(d[102]), "=f"(d[103]), "=f"(d[104]), "=f"(d[105]), "=f"(d[106]), "=f"(d[107]), "=f"(d[108]), "=f"(d[109]), "=f"(d[110]), "=f"(d[111]), "=f"(d[112]), "=f"(d[113]), "=f"(d[114]), "=f"(d[115]), "=f"(d[116]), "=f"(d[117]), "=f"(d[118]), "=f"(d[119]), "=f"(d[120]), "=f"(d[121]), "=f"(d[122]), "=f"(d[123]), "=f"(d[124]), "=f"(d[125]), "=f"(d[126]), "=f"(d[127]) : "l"(a), "l"(b));
    else
        asm volatile("wgmma.mma_async.sync.aligned.m64n256k16.f32.bf16.bf16 {%0,%1,%2,%3,%4,%5,%6,%7,%8,%9,%10,%11,%12,%13,%14,%15,%16,%17,%18,%19,%20,%21,%22,%23,%24,%25,%26,%27,%28,%29,%30,%31,%32,%33,%34,%35,%36,%37,%38,%39,%40,%41,%42,%43,%44,%45,%46,%47,%48,%49,%50,%51,%52,%53,%54,%55,%56,%57,%58,%59,%60,%61,%62,%63,%64,%65,%66,%67,%68,%69,%70,%71,%72,%73,%74,%75,%76,%77,%78,%79,%80,%81,%82,%83,%84,%85,%86,%87,%88,%89,%90,%91,%92,%93,%94,%95,%96,%97,%98,%99,%100,%101,%102,%103,%104,%105,%106,%107,%108,%109,%110,%111,%112,%113,%114,%115,%116,%117,%118,%119,%120,%121,%122,%123,%124,%125,%126,%127}, %128, %129, 1, 1, 1, 1, 0;"
            : "+f"(d[0]), "+f"(d[1]), "+f"(d[2]), "+f"(d[3]), "+f"(d[4]), "+f"(d[5]), "+f"(d[6]), "+f"(d[7]), "+f"(d[8]), "+f"(d[9]), "+f"(d[10]), "+f"(d[11]), "+f"(d[12]), "+f"(d[13]), "+f"(d[14]), "+f"(d[15]), "+f"(d[16]), "+f"(d[17]), "+f"(d[18]), "+f"(d[19]), "+f"(d[20]), "+f"(d[21]), "+f"(d[22]), "+f"(d[23]), "+f"(d[24]), "+f"(d[25]), "+f"(d[26]), "+f"(d[27]), "+f"(d[28]), "+f"(d[29]), "+f"(d[30]), "+f"(d[31]), "+f"(d[32]), "+f"(d[33]), "+f"(d[34]), "+f"(d[35]), "+f"(d[36]), "+f"(d[37]), "+f"(d[38]), "+f"(d[39]), "+f"(d[40]), "+f"(d[41]), "+f"(d[42]), "+f"(d[43]), "+f"(d[44]), "+f"(d[45]), "+f"(d[46]), "+f"(d[47]), "+f"(d[48]), "+f"(d[49]), "+f"(d[50]), "+f"(d[51]), "+f"(d[52]), "+f"(d[53]), "+f"(d[54]), "+f"(d[55]), "+f"(d[56]), "+f"(d[57]), "+f"(d[58]), "+f"(d[59]), "+f"(d[60]), "+f"(d[61]), "+f"(d[62]), "+f"(d[63]), "+f"(d[64]), "+f"(d[65]), "+f"(d[66]), "+f"(d[67]), "+f"(d[68]), "+f"(d[69]), "+f"(d[70]), "+f"(d[71]), "+f"(d[72]), "+f"(d[73]), "+f"(d[74]), "+f"(d[75]), "+f"(d[76]), "+f"(d[77]), "+f"(d[78]), "+f"(d[79]), "+f"(d[80]), "+f"(d[81]), "+f"(d[82]), "+f"(d[83]), "+f"(d[84]), "+f"(d[85]), "+f"(d[86]), "+f"(d[87]), "+f"(d[88]), "+f"(d[89]), "+f"(d[90]), "+f"(d[91]), "+f"(d[92]), "+f"(d[93]), "+f"(d[94]), "+f"(d[95]), "+f"(d[96]), "+f"(d[97]), "+f"(d[98]), "+f"(d[99]), "+f"(d[100]), "+f"(d[101]), "+f"(d[102]), "+f"(d[103]), "+f"(d[104]), "+f"(d[105]), "+f"(d[106]), "+f"(d[107]), "+f"(d[108]), "+f"(d[109]), "+f"(d[110]), "+f"(d[111]), "+f"(d[112]), "+f"(d[113]), "+f"(d[114]), "+f"(d[115]), "+f"(d[116]), "+f"(d[117]), "+f"(d[118]), "+f"(d[119]), "+f"(d[120]), "+f"(d[121]), "+f"(d[122]), "+f"(d[123]), "+f"(d[124]), "+f"(d[125]), "+f"(d[126]), "+f"(d[127]) : "l"(a), "l"(b));
}
template <bool FIRST>
DEVI void wgmma_n128_ss(float* d, uint64_t a, uint64_t b) {
    if (FIRST)
        asm volatile("wgmma.mma_async.sync.aligned.m64n128k16.f32.bf16.bf16 {%0,%1,%2,%3,%4,%5,%6,%7,%8,%9,%10,%11,%12,%13,%14,%15,%16,%17,%18,%19,%20,%21,%22,%23,%24,%25,%26,%27,%28,%29,%30,%31,%32,%33,%34,%35,%36,%37,%38,%39,%40,%41,%42,%43,%44,%45,%46,%47,%48,%49,%50,%51,%52,%53,%54,%55,%56,%57,%58,%59,%60,%61,%62,%63}, %64, %65, 0, 1, 1, 1, 0;"
            : "=f"(d[0]), "=f"(d[1]), "=f"(d[2]), "=f"(d[3]), "=f"(d[4]), "=f"(d[5]), "=f"(d[6]), "=f"(d[7]), "=f"(d[8]), "=f"(d[9]), "=f"(d[10]), "=f"(d[11]), "=f"(d[12]), "=f"(d[13]), "=f"(d[14]), "=f"(d[15]), "=f"(d[16]), "=f"(d[17]), "=f"(d[18]), "=f"(d[19]), "=f"(d[20]), "=f"(d[21]), "=f"(d[22]), "=f"(d[23]), "=f"(d[24]), "=f"(d[25]), "=f"(d[26]), "=f"(d[27]), "=f"(d[28]), "=f"(d[29]), "=f"(d[30]), "=f"(d[31]), "=f"(d[32]), "=f"(d[33]), "=f"(d[34]), "=f"(d[35]), "=f"(d[36]), "=f"(d[37]), "=f"(d[38]), "=f"(d[39]), "=f"(d[40]), "=f"(d[41]), "=f"(d[42]), "=f"(d[43]), "=f"(d[44]), "=f"(d[45]), "=f"(d[46]), "=f"(d[47]), "=f"(d[48]), "=f"(d[49]), "=f"(d[50]), "=f"(d[51]), "=f"(d[52]), "=f"(d[53]), "=f"(d[54]), "=f"(d[55]), "=f"(d[56]), "=f"(d[57]), "=f"(d[58]), "=f"(d[59]), "=f"(d[60]), "=f"(d[61]), "=f"(d[62]), "=f"(d[63]) : "l"(a), "l"(b));
    else
        asm volatile("wgmma.mma_async.sync.aligned.m64n128k16.f32.bf16.bf16 {%0,%1,%2,%3,%4,%5,%6,%7,%8,%9,%10,%11,%12,%13,%14,%15,%16,%17,%18,%19,%20,%21,%22,%23,%24,%25,%26,%27,%28,%29,%30,%31,%32,%33,%34,%35,%36,%37,%38,%39,%40,%41,%42,%43,%44,%45,%46,%47,%48,%49,%50,%51,%52,%53,%54,%55,%56,%57,%58,%59,%60,%61,%62,%63}, %64, %65, 1, 1, 1, 1, 0;"
            : "+f"(d[0]), "+f"(d[1]), "+f"(d[2]), "+f"(d[3]), "+f"(d[4]), "+f"(d[5]), "+f"(d[6]), "+f"(d[7]), "+f"(d[8]), "+f"(d[9]), "+f"(d[10]), "+f"(d[11]), "+f"(d[12]), "+f"(d[13]), "+f"(d[14]), "+f"(d[15]), "+f"(d[16]), "+f"(d[17]), "+f"(d[18]), "+f"(d[19]), "+f"(d[20]), "+f"(d[21]), "+f"(d[22]), "+f"(d[23]), "+f"(d[24]), "+f"(d[25]), "+f"(d[26]), "+f"(d[27]), "+f"(d[28]), "+f"(d[29]), "+f"(d[30]), "+f"(d[31]), "+f"(d[32]), "+f"(d[33]), "+f"(d[34]), "+f"(d[35]), "+f"(d[36]), "+f"(d[37]), "+f"(d[38]), "+f"(d[39]), "+f"(d[40]), "+f"(d[41]), "+f"(d[42]), "+f"(d[43]), "+f"(d[44]), "+f"(d[45]), "+f"(d[46]), "+f"(d[47]), "+f"(d[48]), "+f"(d[49]), "+f"(d[50]), "+f"(d[51]), "+f"(d[52]), "+f"(d[53]), "+f"(d[54]), "+f"(d[55]), "+f"(d[56]), "+f"(d[57]), "+f"(d[58]), "+f"(d[59]), "+f"(d[60]), "+f"(d[61]), "+f"(d[62]), "+f"(d[63]) : "l"(a), "l"(b));
}

DEVI void mma16816(float* d, const uint32_t* a, uint32_t b0, uint32_t b1) {
    asm volatile("mma.sync.aligned.m16n8k16.row.col.f32.bf16.bf16.f32 {%0,%1,%2,%3}, {%4,%5,%6,%7}, {%8,%9}, {%0,%1,%2,%3};"
                 : "+f"(d[0]), "+f"(d[1]), "+f"(d[2]), "+f"(d[3])
                 : "r"(a[0]), "r"(a[1]), "r"(a[2]), "r"(a[3]), "r"(b0), "r"(b1));
}
DEVI void mma1688(float* d, uint32_t a0, uint32_t a1, uint32_t b0) {
    asm volatile("mma.sync.aligned.m16n8k8.row.col.f32.bf16.bf16.f32 {%0,%1,%2,%3}, {%4,%5}, {%6}, {%0,%1,%2,%3};"
                 : "+f"(d[0]), "+f"(d[1]), "+f"(d[2]), "+f"(d[3]) : "r"(a0), "r"(a1), "r"(b0));
}
DEVI void ldsm4(uint32_t* r, uint32_t addr) {
    asm volatile("ldmatrix.sync.aligned.m8n8.x4.shared.b16 {%0,%1,%2,%3}, [%4];"
                 : "=r"(r[0]), "=r"(r[1]), "=r"(r[2]), "=r"(r[3]) : "r"(addr) : "memory");
}
DEVI void ldsm4t(uint32_t* r, uint32_t addr) {
    asm volatile("ldmatrix.sync.aligned.m8n8.x4.trans.shared.b16 {%0,%1,%2,%3}, [%4];"
                 : "=r"(r[0]), "=r"(r[1]), "=r"(r[2]), "=r"(r[3]) : "r"(addr) : "memory");
}
DEVI void ldsm2(uint32_t* r, uint32_t addr) {
    asm volatile("ldmatrix.sync.aligned.m8n8.x2.shared.b16 {%0,%1}, [%2];" : "=r"(r[0]), "=r"(r[1]) : "r"(addr) : "memory");
}
DEVI void ldsm1t(uint32_t& r, uint32_t addr) {
    asm volatile("ldmatrix.sync.aligned.m8n8.x1.trans.shared.b16 {%0}, [%1];" : "=r"(r) : "r"(addr) : "memory");
}
DEVI void stsm4(uint32_t addr, uint32_t r0, uint32_t r1, uint32_t r2, uint32_t r3) {
    asm volatile("stmatrix.sync.aligned.m8n8.x4.shared.b16 [%0], {%1,%2,%3,%4};" :: "r"(addr), "r"(r0), "r"(r1), "r"(r2), "r"(r3) : "memory");
}
DEVI void stsm4t(uint32_t addr, uint32_t r0, uint32_t r1, uint32_t r2, uint32_t r3) {
    asm volatile("stmatrix.sync.aligned.m8n8.x4.trans.shared.b16 [%0], {%1,%2,%3,%4};" :: "r"(addr), "r"(r0), "r"(r1), "r"(r2), "r"(r3) : "memory");
}
DEVI uint32_t movm_t(uint32_t a) {
    uint32_t d; asm volatile("movmatrix.sync.aligned.m8n8.trans.b16 %0, %1;" : "=r"(d) : "r"(a)); return d;
}
DEVI uint32_t pack_bf16(float lo, float hi) {
    uint32_t r; asm("cvt.rn.bf16x2.f32 %0, %1, %2;" : "=r"(r) : "f"(hi), "f"(lo)); return r;
}
DEVI float ex2(float x) { float y; asm("ex2.approx.ftz.f32 %0, %1;" : "=f"(y) : "f"(x)); return y; }

DEVI uint4 ld_rlx4(const void* p) {
    uint4 v;
    asm volatile("ld.relaxed.gpu.global.v4.u32 {%0,%1,%2,%3}, [%4];" : "=r"(v.x), "=r"(v.y), "=r"(v.z), "=r"(v.w) : "l"(p) : "memory");
    return v;
}
DEVI void ld_rlx4f(float* d, const void* p) {
    asm volatile("ld.relaxed.gpu.global.v4.f32 {%0,%1,%2,%3}, [%4];" : "=f"(d[0]), "=f"(d[1]), "=f"(d[2]), "=f"(d[3]) : "l"(p) : "memory");
}
DEVI bool all_nzf(const float* d) { return __float_as_uint(d[0]) && __float_as_uint(d[1]) && __float_as_uint(d[2]) && __float_as_uint(d[3]); }
DEVI void sts128f(uint32_t addr, const float* d) {
    asm volatile("st.shared.v4.f32 [%0], {%1,%2,%3,%4};" :: "r"(addr), "f"(d[0]), "f"(d[1]), "f"(d[2]), "f"(d[3]) : "memory");
}
DEVI void st_rlx4(void* p, uint32_t a, uint32_t b, uint32_t c, uint32_t d) {
    asm volatile("st.relaxed.gpu.global.v4.u32 [%0], {%1,%2,%3,%4};" :: "l"(p), "r"(a), "r"(b), "r"(c), "r"(d) : "memory");
}
DEVI void st_rlx(void* p, uint32_t v) { asm volatile("st.relaxed.gpu.global.u32 [%0], %1;" :: "l"(p), "r"(v) : "memory"); }
DEVI void sts128(uint32_t addr, uint4 v) {
    asm volatile("st.shared.v4.u32 [%0], {%1,%2,%3,%4};" :: "r"(addr), "r"(v.x), "r"(v.y), "r"(v.z), "r"(v.w) : "memory");
}
DEVI void sts64(uint32_t addr, uint32_t a, uint32_t b) { asm volatile("st.shared.v2.u32 [%0], {%1,%2};" :: "r"(addr), "r"(a), "r"(b) : "memory"); }
DEVI void sts32(uint32_t addr, uint32_t v) { asm volatile("st.shared.u32 [%0], %1;" :: "r"(addr), "r"(v) : "memory"); }
DEVI uint4 lds128(uint32_t addr) {
    uint4 v; asm volatile("ld.shared.v4.u32 {%0,%1,%2,%3}, [%4];" : "=r"(v.x), "=r"(v.y), "=r"(v.z), "=r"(v.w) : "r"(addr) : "memory"); return v;
}
DEVI float2 lds64f(uint32_t addr) {
    float2 v; asm volatile("ld.shared.v2.f32 {%0,%1}, [%2];" : "=f"(v.x), "=f"(v.y) : "r"(addr) : "memory"); return v;
}
DEVI void cp_async16(uint32_t dst, const void* src) {
    asm volatile("cp.async.cg.shared.global [%0], [%1], 16;" :: "r"(dst), "l"(src) : "memory");
}
DEVI void cp_async_commit() { asm volatile("cp.async.commit_group;" ::: "memory"); }
DEVI void cp_async_wait0() { asm volatile("cp.async.wait_group 0;" ::: "memory"); }
DEVI uint32_t lds32(uint32_t addr) { uint32_t v; asm volatile("ld.shared.u32 %0, [%1];" : "=r"(v) : "r"(addr) : "memory"); return v; }
DEVI float rcp_fast(float x) { float y; asm("rcp.approx.ftz.f32 %0, %1;" : "=f"(y) : "f"(x)); return y; }
DEVI bool all_nz(const uint4& v) { return v.x && v.y && v.z && v.w; }
DEVI uint32_t mapa(uint32_t addr, uint32_t rank) {
    uint32_t r; asm("mapa.shared::cluster.u32 %0, %1, %2;" : "=r"(r) : "r"(addr), "r"(rank)); return r;
}
DEVI void st_async32(uint32_t dst, uint32_t a, uint32_t bar) {
    asm volatile("st.async.weak.shared::cluster.mbarrier::complete_tx::bytes.b32 [%0], %1, [%2];" :: "r"(dst), "r"(a), "r"(bar) : "memory");
}
DEVI void st_async64(uint32_t dst, uint32_t a, uint32_t b, uint32_t bar) {
    asm volatile("st.async.weak.shared::cluster.mbarrier::complete_tx::bytes.v2.b32 [%0], {%1,%2}, [%3];"
                 :: "r"(dst), "r"(a), "r"(b), "r"(bar) : "memory");
}

DEVI void st_async128(uint32_t dst, uint32_t a, uint32_t b, uint32_t c, uint32_t d, uint32_t bar) {
    asm volatile("st.async.weak.shared::cluster.mbarrier::complete_tx::bytes.v4.b32 [%0], {%1,%2,%3,%4}, [%5];"
                 :: "r"(dst), "r"(a), "r"(b), "r"(c), "r"(d), "r"(bar) : "memory");
}

DEVI uint32_t b_addr(uint32_t sb, int row, int which, int chunk) { const int l = 3 * row + which; return sb + l * 128 + ((chunk ^ (l & 7)) * 16); }
DEVI void battn_warp(uint32_t st, uint32_t so, int i0, int par, int head, int hh, int mt, int lane) {
    const int gq = lane >> 2, t = lane & 3;
    float s[3][4];
#pragma unroll
    for (int n = 0; n < 3; n++) { s[n][0] = s[n][1] = s[n][2] = s[n][3] = 0.f; }
    const int arow = 16 * mt + (lane & 7) + ((lane >> 3) & 1) * 8;
#pragma unroll
    for (int ks = 0; ks < 2; ks++) {
        uint32_t a[4], b[4], b2[2];
        ldsm4(a, b_addr(st, 8 + arow, 0, hh * 4 + ks * 2 + (lane >> 4)));
        const int brow = 16 * mt + (lane >> 4) * 8 + (lane & 7);
        ldsm4(b, b_addr(st, brow, 1, hh * 4 + ks * 2 + ((lane >> 3) & 1)));
        const int crow = 16 * mt + 16 + (lane & 7);
        ldsm2(b2, b_addr(st, crow, 1, hh * 4 + ks * 2 + ((lane >> 3) & 1)));
        mma16816(s[0], a, b[0], b[1]);
        mma16816(s[1], a, b[2], b[3]);
        mma16816(s[2], a, b2[0], b2[1]);
    }
    float m0 = -INFINITY, m1 = -INFINITY;
#pragma unroll
    for (int n = 0; n < 3; n++) {
#pragma unroll
        for (int c = 0; c < 2; c++) {
            const int dj = 8 * n - 8 + 2 * t + c;
            const bool ex = i0 + 16 * mt + dj >= 0;
            if (!(ex && gq - dj >= 0 && gq - dj <= 7)) s[n][c] = -INFINITY;
            if (!(ex && gq + 8 - dj >= 0 && gq + 8 - dj <= 7)) s[n][2 + c] = -INFINITY;
            m0 = fmaxf(m0, s[n][c]); m1 = fmaxf(m1, s[n][2 + c]);
        }
    }
    m0 = fmaxf(m0, __shfl_xor_sync(0xffffffffu, m0, 1)); m0 = fmaxf(m0, __shfl_xor_sync(0xffffffffu, m0, 2));
    m1 = fmaxf(m1, __shfl_xor_sync(0xffffffffu, m1, 1)); m1 = fmaxf(m1, __shfl_xor_sync(0xffffffffu, m1, 2));
    constexpr float C = 0.17677669529663687f * 1.4426950408889634f;
    float l0 = 0.f, l1 = 0.f;
    uint32_t p[3][2];
#pragma unroll
    for (int n = 0; n < 3; n++) {
        const float e0 = ex2((s[n][0] - m0) * C), e1 = ex2((s[n][1] - m0) * C), e2 = ex2((s[n][2] - m1) * C), e3 = ex2((s[n][3] - m1) * C);
        l0 += e0 + e1; l1 += e2 + e3;
        p[n][0] = pack_bf16(e0, e1); p[n][1] = pack_bf16(e2, e3);
    }
    l0 += __shfl_xor_sync(0xffffffffu, l0, 1); l0 += __shfl_xor_sync(0xffffffffu, l0, 2);
    l1 += __shfl_xor_sync(0xffffffffu, l1, 1); l1 += __shfl_xor_sync(0xffffffffu, l1, 2);
    const float i0f = rcp_fast(l0), i1f = rcp_fast(l1);
    float o[4][4];
#pragma unroll
    for (int n = 0; n < 4; n++) { o[n][0] = o[n][1] = o[n][2] = o[n][3] = 0.f; }
    {
        const uint32_t a0[4] = {p[0][0], p[0][1], p[1][0], p[1][1]}, a1[4] = {p[2][0], p[2][1], 0u, 0u};
#pragma unroll
        for (int n = 0; n < 4; n += 2) {
            uint32_t b[4], b2[4];
            const int vrow = 16 * mt + ((lane >> 3) & 1) * 8 + (lane & 7);
            ldsm4t(b, b_addr(st, vrow, 2, hh * 4 + n + (lane >> 4)));
            const int wrow = 16 * mt + 16 + (lane & 7);
            ldsm4t(b2, b_addr(st, wrow, 2, hh * 4 + n + (lane >> 4)));
            mma16816(o[n], a0, b[0], b[1]);
            mma16816(o[n + 1], a0, b[2], b[3]);
            mma16816(o[n], a1, b2[0], 0u);
            mma16816(o[n + 1], a1, b2[2], 0u);
        }
    }
    {
        const int row = (lane & 7) + ((lane >> 3) & 1) * 8;
#pragma unroll
        for (int n = 0; n < 4; n += 2)
            stsm4(so + row * 64 + (((n + (lane >> 4)) ^ ((row >> 1) & 3)) * 16),
                  pack_bf16(o[n][0] * i0f, o[n][1] * i0f), pack_bf16(o[n][2] * i1f, o[n][3] * i1f),
                  pack_bf16(o[n + 1][0] * i0f, o[n + 1][1] * i0f), pack_bf16(o[n + 1][2] * i1f, o[n + 1][3] * i1f));
    }
    __syncwarp();
#pragma unroll
    for (int i = 0; i < 2; i++) {
        const int idx = lane + i * 32, row = idx >> 2, ch = idx & 3;
        const uint4 v = lds128(so + row * 64 + ((ch ^ ((row >> 1) & 3)) * 16));
        *(uint4*)(g_bo + (size_t)(2 * (i0 + 16 * mt + row) + par) * 1024 + head * 32 + ch * 8) = v;
    }
    __syncwarp();
}

constexpr float SCALE_LOG2E = 0.08838834764831845f * 1.4426950408889634f;

constexpr int P_STAGES = 4, P_STAGE = 16384 + 32768;
constexpr int PS_STG = P_STAGES * P_STAGE;
constexpr int PS_BAR = PS_STG + 32768;
constexpr int P_SMEM = PS_BAR + 256;
static_assert(P_SMEM <= 232448, "smem");
enum { K_Q, K_B1, K_B3, K_A4, K_QH, K_A3, K_SK, K_B2, K_END };
struct PList { int n, nworker; int4 run[16]; };
struct PTask { int kind, a, b, c; };
DEVI PTask p_decode(const PList& pl, int id) {
    for (int i = 0; i < pl.n; i++) {
        const int4 r = pl.run[i];
        if (id < r.w) {
            const int j = id - r.z;
            if (r.x == K_Q || r.x == K_QH) return {r.x, j & 31, r.y + (j >> 5), 0};
            if (r.x == K_B1) return {r.x, j % 24, r.y + j / 24, 0};
            if (r.x == K_B2) return {r.x, 0, r.y + j, 0};
            if (r.x == K_SK) return {r.x, (j / P_SPLIT) & 7, r.y + j / (8 * P_SPLIT), j % P_SPLIT};
            return {r.x, j & 7, r.y + (j >> 3), 0};
        }
    }
    return {K_END, 0, 0, 0};
}
DEVI void wait_count(const unsigned* p, unsigned target) {
    int n = 0;
    while (true) {
        unsigned v; asm volatile("ld.acquire.gpu.global.u32 %0, [%1];" : "=r"(v) : "l"(p) : "memory");
        if ((int)(v - target) >= 0) break;
        __nanosleep(100);
        if (++n > SPIN_LIMIT) TRAP(0x10000000u | ((unsigned)(size_t)p & 0xFFFFu));
    }
}
DEVI void wait_count_warp(const unsigned* p, unsigned target) {
    int n = 0;
    while (true) {
        unsigned v; asm volatile("ld.acquire.gpu.global.u32 %0, [%1];" : "=r"(v) : "l"(p) : "memory");
        if (__all_sync(0xffffffffu, (int)(v - target) >= 0)) break;
        __nanosleep(100);
        if (++n > SPIN_LIMIT) TRAP(0x10000000u | ((unsigned)(size_t)p & 0xFFFFu));
    }
}
DEVI void signal_count(unsigned* p) { __threadfence(); atomicAdd(p, 1u); }

struct PMaps { CUtensorMap wq, bw, bwo, wo, x, bx, bo, ox, cb, cout, cq, b40; PList list; };
constexpr int PB_F = PS_BAR, PB_E = PB_F + 32, PB_TF = PB_F + 64, PB_TE = PB_F + 80, PB_S = PB_F + 96;
constexpr int PS_T = PB_F + 112, PS_SIG = PS_T + 32, PS_SK = PS_SIG + 16;

struct POut { const CUtensorMap* map; int col, tok, cnt; bool blocked; };
DEVI void p_store(const uint32_t* pk, const POut& o, int c, uint32_t stg, int warp, int lane_, int barid, bool elected) {
    const int lane = (int)opaque((uint32_t)lane_);
    const int mi = lane >> 3, r = lane & 7;
    const uint32_t buf = stg + (c & 1) * 8192;
    if (elected) asm volatile("cp.async.bulk.wait_group.read 1;" ::: "memory");
    nbar_sync(barid, 128);
    if (o.blocked) {
#pragma unroll
        for (int j = 0; j < 8; j += 2)
            stsm4(buf + (j + (mi >> 1)) * 1024 + (warp * 16 + (mi & 1) * 8 + r) * 16, pk[2 * j], pk[2 * j + 1], pk[2 * j + 2], pk[2 * j + 3]);
    } else {
#pragma unroll
        for (int j = 0; j < 8; j += 2)
            stsm4t(buf + (8 * (j + (mi >> 1)) + r) * 128 + ((2 * warp + (mi & 1)) ^ r) * 16, pk[2 * j], pk[2 * j + 1], pk[2 * j + 2], pk[2 * j + 3]);
    }
    fence_proxy_async();
    nbar_sync(barid, 128);
    if (elected) {
        if (o.blocked)
            asm volatile("cp.async.bulk.tensor.4d.global.shared::cta.bulk_group [%0, {%2, %3, %4, %5}], [%1];"
                         :: "l"(o.map), "r"(buf), "r"(0), "r"((o.col >> 5) & 2), "r"((o.col >> 7) * 4), "r"((o.tok >> 5) + 2 * c) : "memory");
        else tma_store_2d(o.map, buf, o.col, o.tok + c * 64);
        bulk_commit();
    }
}
DEVI void p_signal(uint32_t sb, int g, int cnt, int& nsig) {
    sts32(sb + PS_SIG + g * 8 + (nsig & 1) * 4, (uint32_t)cnt);
    mbar_arrive(sb + PB_S + g * 8);
    nsig++;
}
template <int BN, bool FIRST>
DEVI void p_kblock(float* d, uint32_t sb, int g, int it, bool elected) {
    const int st = it % P_STAGES;
    mbar_wait(sb + PB_F + st * 8, (it / P_STAGES) & 1);
    const uint32_t a = sb + st * P_STAGE;
    const uint64_t da = mk_desc(a + g * 8192, 16, 1024, 1), db = mk_desc(a + 16384, 16, 1024, 1);
    wg_fence();
#pragma unroll
    for (int kk = 0; kk < 4; kk++) {
        if (BN == 256) { if (FIRST && kk == 0) wgmma_n256_ss<true>(d, da, db); else wgmma_n256_ss<false>(d, da + (uint64_t)(kk * 128), db + (uint64_t)(kk * 2)); }
        else           { if (FIRST && kk == 0) wgmma_n128_ss<true>(d, da, db); else wgmma_n128_ss<false>(d, da + (uint64_t)(kk * 128), db + (uint64_t)(kk * 2)); }
    }
    wg_commit();
    if (!FIRST) {
        wg_wait<1>();
        if (elected) mbar_arrive(sb + PB_E + ((it - 1) % P_STAGES) * 8);
    }
}

DEVI int post_claim(const PMaps& mp, unsigned E) {
    const int id = (int)(atomicAdd(&g_qctr, 1u) - (E - 1) * (unsigned)(mp.list.run[mp.list.n - 1].w + mp.list.nworker));
    const PTask tk = p_decode(mp.list, id);
    if (tk.kind == K_B2) {
        wait_count(&g_cnt[C_B1 + (tk.b >> 2)], 48 * E);
        if ((tk.b & 3) == 0 && tk.b > 0) wait_count(&g_cnt[C_B1 + (tk.b >> 2) - 1], 48 * E);
    } else if (tk.kind == K_B3) wait_count(&g_cnt[C_B2 + tk.b], 8 * E);
    else if (tk.kind == K_A4) wait_count(&g_prog[2 * tk.b + 1], 128 * E);
    else if (tk.kind == K_A3 || tk.kind == K_SK) wait_count(&g_prog[tk.b], 128 * E);
    if (tk.kind != K_Q && tk.kind != K_QH && tk.kind != K_B1) fence_proxy_global();
    return id;
}
DEVI void post_producer(const PMaps& mp, uint32_t sb, unsigned E, int id) {
    const uint32_t bF = sb + PB_F, bE = sb + PB_E;
    int it = 0;
    for (int i = 0;; i++) {
        mbar_wait(sb + PB_TE + (i & 1) * 8, ((i >> 1) & 1) ^ 1);
        if (i > 0) id = post_claim(mp, E);
        const PTask tk = p_decode(mp.list, id);
        sts128(sb + PS_T + (i & 1) * 16, make_uint4((uint32_t)tk.kind | ((uint32_t)id << 8), (uint32_t)tk.a, (uint32_t)tk.b, (uint32_t)tk.c));
        mbar_arrive(sb + PB_TF + (i & 1) * 8);
        if (tk.kind == K_END) break;
        if (tk.kind == K_B2) {
            const int i0 = tk.b * 32;
            for (int j = 0; j < 16; j++, it++) {
                const int st = it % P_STAGES;
                mbar_wait(bE + st * 8, ((it / P_STAGES) & 1) ^ 1);
                const uint32_t a = sb + st * P_STAGE, bar = bF + st * 8;
                mbar_expect_tx(bar, 2 * 15360);
                for (int u = 0; u < 2; u++)
                    asm volatile("cp.async.bulk.tensor.4d.shared::cluster.global.mbarrier::complete_tx::bytes [%0], [%1, {%3, %4, %5, %6}], [%2];"
                                 :: "r"(a + u * 15360), "l"(&mp.b40), "r"(bar), "r"(j * 64), "r"(0), "r"(u), "r"(i0 - 8) : "memory");
            }
            continue;
        }
        const bool qk = tk.kind == K_Q || tk.kind == K_QH, ak = tk.kind == K_A4 || tk.kind == K_A3 || tk.kind == K_SK, wide = tk.kind <= K_A4;
        const CUtensorMap* tw = tk.kind == K_B1 ? &mp.bw : (qk ? &mp.wq : &mp.bwo);
        const CUtensorMap* tx = tk.kind == K_B1 ? &mp.bx : (qk ? &mp.x : (ak ? &mp.ox : &mp.bo));
        const int nk = tk.kind == K_A3 || tk.kind == K_A4 ? HD / 64 : (tk.kind == K_SK ? HD / 64 / P_SPLIT : DM / 64), kb0 = tk.c * (HD / 64 / P_SPLIT);
        for (int kb = kb0; kb < kb0 + nk; kb++, it++) {
            const int st = it % P_STAGES;
            mbar_wait(bE + st * 8, ((it / P_STAGES) & 1) ^ 1);
            const uint32_t a = sb + st * P_STAGE, bar = bF + st * 8;
            mbar_expect_tx(bar, wide ? P_STAGE : 32768);
            if (ak) {
                tma_load_wo(a, &mp.wo, tk.a * 128, kb * 2, bar);
                tma_load_wo(a + 8192, &mp.wo, tk.a * 128 + 64, kb * 2, bar);
            } else {
                tma_load_2d(a, tw, tk.a * 128, kb * 64, bar);
                tma_load_2d(a + 8192, tw, tk.a * 128 + 64, kb * 64, bar);
            }
            tma_load_2d(a + 16384, tx, kb * 64, tk.b * (wide ? 256 : 128), bar);
            if (wide) tma_load_2d(a + 32768, tx, kb * 64, tk.b * 256 + 128, bar);
        }
    }
    __threadfence();
    if (atomicAdd(&g_done, 1u) == E * mp.list.nworker - 1) { __threadfence(); *(volatile unsigned*)&g_epoch = E; }
}
DEVI void post_helper(uint32_t sb, int g) {
    for (int n = 0;; n++) {
        mbar_wait_sleepy(sb + PB_S + g * 8, n & 1);
        const int cnt = (int)lds32(sb + PS_SIG + g * 8 + (n & 1) * 4);
        if (cnt < 0) break;
        signal_count(&g_cnt[cnt]);
    }
}
DEVI void post_consumer(const PMaps& mp, uint32_t sb, int g, int warp) {
    const int barid = 1 + g, tid = threadIdx.x, lane = tid & 31;
    const bool elected = (tid & 127) == 0;
    const uint32_t stg = sb + PS_STG + g * 16384;
    int it = 0, nsig = 0;
    uint32_t pk[64];
    POut out;
    bool pend = false;
#pragma unroll
    for (int i = 0; i < 64; i++) pk[i] = 0u;
    for (int i = 0;; i++) {
        const uint32_t bTF = sb + PB_TF + (i & 1) * 8;
        if (pend) {
            uint32_t now;
            asm volatile("{.reg .pred p, q; mbarrier.test_wait.parity.shared::cta.b64 p, [%1], %2; bar.red.and.pred q, %3, 128, p; selp.u32 %0, 1, 0, q;}"
                         : "=r"(now) : "r"(bTF), "r"((i >> 1) & 1), "r"(barid) : "memory");
            if (!now || (lds32(sb + PS_T + (i & 1) * 16) & 255u) > K_A4) {
#pragma unroll
                for (int c = 0; c < 4; c++) p_store(pk + 16 * c, out, c, stg, warp, lane, barid, elected);
                if (elected && out.cnt != C_NONE) { bulk_wait_all(); p_signal(sb, g, out.cnt, nsig); }
                pend = false;
            }
        }
        mbar_wait(bTF, (i >> 1) & 1);
        const uint4 tw = lds128(sb + PS_T + (i & 1) * 16);
        mbar_arrive(sb + PB_TE + (i & 1) * 8);
        const PTask tk = {(int)(tw.x & 255u), (int)tw.y, (int)tw.z, (int)tw.w};
        if (tk.kind == K_END) break;
        if (tk.kind <= K_A4) {
            float d[128];
            const int nk = tk.kind == K_A4 ? HD / 64 : DM / 64;
            p_kblock<256, true>(d, sb, g, it, elected);
            if (pend) p_store(pk, out, 0, stg, warp, lane, barid, elected);
#pragma unroll
            for (int c = 1; c < 4; c++) {
                p_kblock<256, false>(d, sb, g, it + c, elected);
                if (pend) p_store(pk + 16 * c, out, c, stg, warp, lane, barid, elected);
            }
#pragma unroll 1
            for (int kb = 4; kb < nk; kb++) {
                p_kblock<256, false>(d, sb, g, it + kb, elected);
                if (kb == 6 && pend && elected && out.cnt != C_NONE) { bulk_wait_all(); p_signal(sb, g, out.cnt, nsig); }
            }
            it += nk;
            wg_wait<0>();
            reg_fence<128>(d);
            if (elected) mbar_arrive(sb + PB_E + ((it - 1) % P_STAGES) * 8);
#pragma unroll
            for (int j = 0; j < 64; j++) pk[j] = pack_bf16(d[2 * j], d[2 * j + 1]);
            out.map = tk.kind == K_Q ? &mp.cq : (tk.kind == K_B1 ? &mp.cb : &mp.cout);
            out.col = tk.a * 128 + g * 64 + (tk.kind == K_B3 ? DM : 0);
            out.tok = tk.b * 256;
            out.cnt = tk.kind == K_Q ? C_Q + tk.b : (tk.kind == K_B1 ? C_B1 + tk.b : C_NONE);
            out.blocked = tk.kind == K_Q;
            pend = true;
        } else if (tk.kind == K_B2) {
            if (elected) bulk_wait_all();
            nbar_sync(barid, 128);
#pragma unroll 1
            for (int j = 0; j < 16; j++, it++) {
                const int st = it % P_STAGES;
                mbar_wait(sb + PB_F + st * 8, (it / P_STAGES) & 1);
                const uint32_t a = sb + st * P_STAGE + g * 15360;
                battn_warp(a, stg + warp * 1024, tk.b * 32, g, j * 2 + (warp >> 1), warp >> 1, warp & 1, (int)opaque((uint32_t)lane));
                nbar_sync(barid, 128);
                if (elected) mbar_arrive(sb + PB_E + st * 8);
            }
            if (elected) p_signal(sb, g, C_B2 + (tk.b >> 2), nsig);
#pragma unroll
            for (int j = 0; j < 64; j++) pk[j] = 0u;
        } else {
            float d[64];
            const int nk = tk.kind == K_A3 ? HD / 64 : (tk.kind == K_SK ? HD / 64 / P_SPLIT : DM / 64);
            p_kblock<128, true>(d, sb, g, it, elected);
#pragma unroll 1
            for (int kb = 1; kb < nk; kb++) p_kblock<128, false>(d, sb, g, it + kb, elected);
            it += nk;
            wg_wait<0>();
            reg_fence<64>(d);
            if (elected) mbar_arrive(sb + PB_E + ((it - 1) % P_STAGES) * 8);
            bool finish = true;
            if (tk.kind == K_SK) {
                const int tile = ((tk.b - (16 - P_NSK)) * 8 + tk.a);
                uint4* const base = g_skp + (size_t)(tile * P_SPLIT * 2 + g) * 1024 + (tid & 127);
#pragma unroll
                for (int j = 0; j < 8; j++)
                    base[tk.c * 2048 + j * 128] = make_uint4(pack_bf16(d[8 * j], d[8 * j + 1]), pack_bf16(d[8 * j + 2], d[8 * j + 3]),
                                                             pack_bf16(d[8 * j + 4], d[8 * j + 5]), pack_bf16(d[8 * j + 6], d[8 * j + 7]));
                nbar_sync(barid, 128);
                if (elected) {
                    unsigned old;
                    asm volatile("atom.acq_rel.gpu.global.add.u32 %0, [%1], 1;" : "=r"(old) : "l"(&g_cnt_sk[tile * 2 + g]) : "memory");
                    sts32(sb + PS_SK + g * 4, old % P_SPLIT);
                }
                nbar_sync(barid, 128);
                finish = lds32(sb + PS_SK + g * 4) == P_SPLIT - 1;
                if (finish) {
#pragma unroll 1
                    for (int q = 1; q < P_SPLIT; q += 2) {
                        uint4 v[16];
#pragma unroll
                        for (int j = 0; j < 16; j++)
                            v[j] = j < 8 || q + 1 < P_SPLIT ? __ldcg(base + ((tk.c + q + (j >> 3)) % P_SPLIT) * 2048 + (j & 7) * 128) : make_uint4(0u, 0u, 0u, 0u);
#pragma unroll
                        for (int j = 0; j < 16; j++) {
                            float* e = d + 8 * (j & 7);
                            e[0] += __uint_as_float(v[j].x << 16); e[1] += __uint_as_float(v[j].x & 0xFFFF0000u);
                            e[2] += __uint_as_float(v[j].y << 16); e[3] += __uint_as_float(v[j].y & 0xFFFF0000u);
                            e[4] += __uint_as_float(v[j].z << 16); e[5] += __uint_as_float(v[j].z & 0xFFFF0000u);
                            e[6] += __uint_as_float(v[j].w << 16); e[7] += __uint_as_float(v[j].w & 0xFFFF0000u);
                        }
                    }
                }
                nbar_sync(barid, 128);
            }
            if (finish) {
                const POut o = {tk.kind == K_QH ? &mp.cq : &mp.cout, tk.a * 128 + g * 64, tk.b * 128, 0, tk.kind == K_QH};
                uint32_t q[32];
#pragma unroll
                for (int j = 0; j < 32; j++) q[j] = pack_bf16(d[2 * j], d[2 * j + 1]);
                p_store(q, o, 0, stg, warp, lane, barid, elected);
                p_store(q + 16, o, 1, stg, warp, lane, barid, elected);
                if (elected && tk.kind == K_QH) { bulk_wait_all(); p_signal(sb, g, tk.b == 0 ? C_QH : C_Q, nsig); }
            }
#pragma unroll
            for (int j = 0; j < 64; j++) pk[j] = 0u;
        }
    }
    if (elected) { bulk_wait_all(); p_signal(sb, g, -1, nsig); }
}
DEVI void post_init(uint32_t sb) {
    for (int i = 0; i < P_STAGES; i++) { mbar_init(sb + PB_F + i * 8, 1); mbar_init(sb + PB_E + i * 8, 2); }
    for (int i = 0; i < 2; i++) { mbar_init(sb + PB_TF + i * 8, 1); mbar_init(sb + PB_TE + i * 8, 256); mbar_init(sb + PB_S + i * 8, 1); }
    fence_mbar_init();
}

constexpr unsigned long long R_TORD_PACK = 0xf5ea4937dc1826b0ull;
__host__ __device__ constexpr int r_tord(int pos) { return (int)((R_TORD_PACK >> (4 * pos)) & 15ull); }
__host__ __device__ constexpr int r_tinv(int T) { for (int p = 0; p < 16; p++) if (r_tord(p) == T) return p; return 0; }
__host__ __device__ constexpr bool r_pos_ss(int pos) { return pos % 3 == 2; }
__host__ __device__ constexpr int r_ss(int pos) { return pos / 3; }
__host__ __device__ constexpr int r_rs(int pos) { return pos - pos / 3; }
constexpr int R_NRS = 11, R_NSS = 5;
constexpr int R_G1 = 3, R_G2 = 9;
#define REG_KB 232
#define TA_LATE 0
#define WO_REL 0
constexpr int X_SLOTS = 4;
constexpr int X_NST = 8;

constexpr int RS_WSS  = 0;
constexpr int RS_WO   = RS_WSS + R_NSS * 16384;
constexpr int RS_MEM  = RS_WO + 5 * 16384;
constexpr int RS_O    = RS_MEM + 16384;
constexpr int RS_SX   = RS_O + 2048;
constexpr int RS_BAR  = RS_SX + 2048;
constexpr int RS_TAIL = RS_BAR + 1024;
constexpr int RS_WO5  = RS_TAIL;
constexpr int RS_K    = RS_WO5 + 16384;
constexpr int RS_V    = RS_K + 10240;
constexpr int RS_Q    = RS_V + 10240;
constexpr int RS_QX   = RS_Q + 2048;
constexpr int RS_QEND = RS_QX + 8192;
constexpr int RS_X    = RS_TAIL;
constexpr int X_PITCH = X_SLOTS * 4096;
constexpr int RS_XD   = RS_X + 2 * X_PITCH;
constexpr int RS_WX   = RS_XD + 8192;
constexpr int RS_KEND = RS_WX + 4096;
constexpr int RS_EV   = RS_BAR + 256;
constexpr int R_SMEM  = RS_KEND > RS_QEND ? RS_KEND : RS_QEND;
static_assert(R_SMEM <= 232448 && P_SMEM <= R_SMEM, "smem");
static_assert(RS_TAIL % 1024 == 0 && RS_MEM % 1024 == 0, "alignment");

constexpr int RB_G = RS_BAR, RB_K = RS_BAR + 24, RB_V = RS_BAR + 32, RB_KV = RS_BAR + 40, RB_QX = RS_BAR + 48, RB_O = RS_BAR + 56;
constexpr int RB_ATT = RS_BAR + 64, RB_W = RS_BAR + 72, RB_SF = RS_BAR + 80, RB_SE = RB_SF + 40, RB_XF = RB_SE + 40;
constexpr int RB_WO = RB_XF + 56, RB_T = RB_XF + 64, RS_INV = RS_SX + 1024;
static_assert(RB_T + 8 <= RS_EV, "barriers");
constexpr uint32_t SB0 = 1024;
__host__ __device__ constexpr uint32_t cdesc(uint32_t off, uint32_t lbo) { return ((SB0 + off) >> 4) | ((lbo >> 4) << 16); }
#define SCHED_FENCE() __syncwarp()
constexpr int NB_BIG = 1, NB_Q = 2, NB_AUX = 3, NB_WO = 4, NB_XS = 5, NB_WG = 6, NB_PAIR = 8;

DEVI int tid_now() { int t; asm volatile("mov.u32 %0, %%tid.x;" : "=r"(t)); return t; }
DEVI uint32_t a_frag_off(int lane, int warp) { return (uint32_t)((((lane >> 4) * 8 + (lane & 7)) * 128) + (((2 * warp + ((lane >> 3) & 1)) ^ (lane & 7)) * 16)); }
DEVI uint32_t b_frag_off(int lane) { return (uint32_t)((lane & 3) * 64 + (((lane >> 2) * 8) ^ ((lane & 2) * 16))); }
DEVI void lds_b(uint32_t* b, uint32_t a) {
    asm volatile("ld.shared.v2.u32 {%0,%1}, [%2];" : "=r"(b[0]), "=r"(b[1]) : "r"(a) : "memory");
    asm volatile("ld.shared.v2.u32 {%0,%1}, [%2];" : "=r"(b[2]), "=r"(b[3]) : "r"(a + 256) : "memory");
}
DEVI uint32_t clk32() { unsigned long long c; asm volatile("mov.u64 %0, %%clock64;" : "=l"(c)); return (uint32_t)c; }
DEVI bool elect_one() {
    uint32_t e; asm volatile("{.reg .pred p; elect.sync _|p, 0xffffffff; selp.u32 %0, 1, 0, p;}" : "=r"(e)); return e;
}

__host__ __device__ constexpr int x_pair(int j) { return j == 0 || j > 3 ? j : (j == 3 ? 1 : j + 1); }
DEVI void x_load(uint32_t sb, int seg, int j, int g, const CUtensorMap* tmX) {
    const uint32_t bar = sb + RB_XF + g * 8;
    mbar_expect_tx(bar, 4096);
    tma_load_3d(sb + RS_X + g * X_PITCH + (j % X_SLOTS) * 4096, tmX, g * 32, seg * 32, x_pair(j) * 2, bar);
}
DEVI void x_refill(uint32_t sb, int seg, int j, int g, int warp, const CUtensorMap* tmX) {
    const int sn = j + X_SLOTS < X_NST ? seg : seg + 1;
    if (warp == (j & 3) && sn < NSEG) {
        if (elect_one()) x_load(sb, sn, (j + X_SLOTS) % X_NST, g, tmX);
    }
}
template <int H>
DEVI void x_half(float* xa, const uint32_t* w, uint32_t sb, int seg, int g0, int warp, const CUtensorMap* tmX) {
    wg_fence();
#pragma unroll
    for (int grp = 0; grp < 4; grp++) {
        const int g = (int)opaque((uint32_t)g0);
        const uint32_t dW0 = cdesc(RS_WSS, 16) + g * 768, dW1 = cdesc(RS_WSS + 8192, 16) - g * 256;
#pragma unroll
        for (int i = 0; i < 8; i++) {
            const bool last = H == 1 && grp >= 2;
            const int j = last ? 6 + (i >> 2) : 4 * H + grp, q = last ? 2 * (i & 3) + (grp == 2) : i;
            const int pos = r_tinv(2 * x_pair(j) + (q >> 2)), kk = (q >> 1) & 1, mt = q & 1;
            const uint32_t db = cdesc(RS_X + (j % X_SLOTS) * 4096, 16) + g * (X_PITCH >> 4) + (q >> 2) * 128 + kk * 2;
            if (j == 0 && q < 2)   wgmma_n32_rs_first(xa + 16 * mt, &w[((r_rs(pos) * 2 + kk) * 2 + mt) * 4], db);
            else if (j == 0 && q == 3) wgmma_n32_ss(xa + 16, cdesc(RS_WX, 16) + g * 128, db);
            else if (r_pos_ss(pos)) wgmma_n32_ss(xa + 16 * mt, (mt ? dW1 : dW0) + r_ss(pos) * 1024 + kk * 128, db);
            else                   wgmma_n32_rs(xa + 16 * mt, &w[((r_rs(pos) * 2 + kk) * 2 + mt) * 4], db);
        }
        wg_commit();
    }
    const int g = (int)opaque((uint32_t)g0);
    wg_wait<3>(); x_refill(sb, seg, 4 * H, g, warp, tmX);
    wg_wait<2>(); x_refill(sb, seg, 4 * H + 1, g, warp, tmX);
    wg_wait<1>();
    if (H == 0) {
        x_refill(sb, seg, 2, g, warp, tmX);
        wg_wait<0>(); reg_fence<32>(xa); x_refill(sb, seg, 3, g, warp, tmX);
    } else reg_fence<16>(xa + 16);
}
DEVI void x_finish(float* xa, uint32_t sb, int seg, int g, int warp, int lane, const CUtensorMap* tmX) {
    const uint32_t d = sb + RS_XD + (lane >> 4) * 2048 + warp * 256 + (lane & 15) * 16;
#pragma unroll
    for (int i = 0; i < 2; i++) {
        const float* x = xa + 16 + 8 * i;
        sts128(d + (g ^ 1) * 1024 + i * 4096, make_uint4(pack_bf16(x[0], x[1]), pack_bf16(x[2], x[3]), pack_bf16(x[4], x[5]), pack_bf16(x[6], x[7])));
    }
    nbar_sync(NB_PAIR + warp, 64);
    float y[16];
#pragma unroll
    for (int i = 0; i < 2; i++) {
        const uint4 v = lds128(d + g * 1024 + i * 4096);
        const uint32_t u[4] = {v.x, v.y, v.z, v.w};
#pragma unroll
        for (int j = 0; j < 4; j++) { y[8 * i + 2 * j] = __uint_as_float(u[j] << 16); y[8 * i + 2 * j + 1] = __uint_as_float(u[j] & 0xFFFF0000u); }
    }
    reg_fence<16>(y);
    wg_wait<0>();
    reg_fence<16>(xa);
    uint32_t p[8];
#pragma unroll
    for (int j = 0; j < 8; j++) p[j] = pack_bf16(xa[2 * j] + y[2 * j], xa[2 * j + 1] + y[2 * j + 1]);
    __syncwarp();
    stsm4(d + g * 1024, p[0], p[1], p[2], p[3]);
    stsm4(d + g * 1024 + 4096, p[4], p[5], p[6], p[7]);
    nbar_arrive(NB_XS, 256 + 32);
    x_refill(sb, seg, X_NST - 2, g, warp, tmX);
    x_refill(sb, seg, X_NST - 1, g, warp, tmX);
}
DEVI void x_send(uint32_t sb, int seg, uint32_t rank, int vdelay) {
    mbar_wait(sb + RB_ATT, (seg - 1) & 1);
    nbar_sync(NB_XS, 256 + 32);
    if (rank == 2) { const uint32_t t = clk32() + vdelay; while ((int)(clk32() - t) < 0) { } }
    if (elect_one()) {
        fence_proxy_async();
        bulk_copy_s2c(mapa(sb + (rank == 1 ? RS_K : RS_V) + 2048, 0), sb + RS_XD, 8192, mapa(sb + (rank == 1 ? RB_KV : RB_V), 0));
    }
    __syncwarp();
}

template <bool XP>
DEVI void mem_pass(float* c0, float* c1, const uint32_t* w, uint32_t sb, uint32_t aA0, uint32_t aB, int g, int warp, int s) {
    const uint32_t aA1 = aA0 + 8192 - g * 16384, par = (s - 1) & 1;
    uint32_t a[16], b[2][4], e[4];
    float d0[4], d1[4];
    if (XP) ldsm4t(e, aA0 + opaque((RS_WX - RS_WSS) - g * (8192 + 2048)));
#pragma unroll
    for (int q = 0; q < 4; q++) ldsm4t(a + 4 * q, ((q & 1) ? aA1 : aA0) + (q >> 1) * 2048);
#pragma unroll
    for (int i = 0; i < 4; i++) { c0[i] = 0.f; c1[i] = 0.f; d0[i] = 0.f; d1[i] = 0.f; }
    EV(EV_BIG0, s, 0);
    mbar_wait(sb + RB_G, par);
    EV(EV_BIG0, s, 1);
    lds_b(b[0], aB + r_tord(0) * 1024);
    bool in = false;
#pragma unroll
    for (int pos = 0; pos < 16; pos++) {
        if (pos + 1 < 16) {
            if (pos + 1 == R_G1 && !in) mbar_wait(sb + RB_G + 8, par);
            if (pos + 1 == R_G2) { if (!in) mbar_wait(sb + RB_G + 16, par); EV(EV_BIG0, s, 2); }
            lds_b(b[(pos + 1) & 1], aB + r_tord(pos + 1) * 1024);
        }
        if (pos + 2 == R_G1) in = mbar_try(sb + RB_G + 8, par);
        if (pos + 2 == R_G2) in = mbar_try(sb + RB_G + 16, par);
        if (XP && pos == 12) in = s == NSEG - 1 || mbar_try(sb + RB_XF + g * 8, 0);
        if (XP && pos == 14) { if (!in) mbar_wait(sb + RB_XF + g * 8, 0); in = mbar_try(sb + RB_ATT, par); }
        const uint32_t* bb = b[pos & 1];
        const uint32_t* aa = r_pos_ss(pos) ? a : &w[r_rs(pos) * 16];
        mma16816(c1, aa + 4, bb[0], bb[1]);
        mma16816(d1, XP && pos == 0 ? e : aa + 12, bb[2], bb[3]);
        mma16816(c0, aa, bb[0], bb[1]);
        mma16816(d0, aa + 8, bb[2], bb[3]);
        if (r_pos_ss(pos) && pos + 3 < 16) {
#pragma unroll
            for (int q = 0; q < 4; q++) ldsm4t(a + 4 * q, ((q & 1) ? aA1 : aA0) + (r_ss(pos) + 1) * 16384 + (q >> 1) * 2048);
        }
        SCHED_FENCE();
    }
    if (XP && !in) mbar_wait(sb + RB_ATT, par);
#pragma unroll
    for (int i = 0; i < 4; i++) { c1[i] += d1[i]; c0[i] += d0[i]; }
}

DEVI uint32_t k_frag_off(int lane) { return (uint32_t)((((lane >> 3) & 1) * 16 + (lane >> 4) * 8 + (lane & 7)) * 16); }
DEVI uint32_t v_frag_off(int lane) { return (uint32_t)(((lane >> 3) & 1) * 2048 + ((lane >> 4) * 8 + (lane & 7)) * 16); }
DEVI void pv_pair(float (*o)[4], const uint32_t* p, const uint32_t* v) {
#pragma unroll
    for (int n = 0; n < 4; n++) mma16816(o[n], p, v[2 * n], v[2 * n + 1]);
}
DEVI void pv_single(float (*o)[4], const uint32_t* p, const uint32_t* v) {
#pragma unroll
    for (int n = 0; n < 4; n++) mma1688(o[n], p[0], p[1], v[n]);
}
DEVI float inv_sum4(float l) {
    l += __shfl_xor_sync(0xffffffffu, l, 1);
    l += __shfl_xor_sync(0xffffffffu, l, 2);
    return rcp_fast(l);
}

DEVI void s_tile(const uint32_t* qa, const uint32_t* k, float& s0, float& s1) {
    float c[4][4];
#pragma unroll
    for (int q = 0; q < 4; q++) { c[q][0] = c[q][1] = c[q][2] = c[q][3] = 0.f; }
#pragma unroll
    for (int q = 0; q < 4; q++) {
        mma16816(c[2 * (q & 1)], qa + 4 * q, k[4 * q], k[4 * q + 1]);
        mma16816(c[2 * (q & 1) + 1], qa + 4 * q, k[4 * q + 2], k[4 * q + 3]);
    }
    s0 = (c[0][0] + c[1][2]) + (c[2][0] + c[3][2]);
    s1 = (c[0][1] + c[1][3]) + (c[2][1] + c[3][3]);
}
DEVI void mem_scores(uint32_t sb, int s, int warp, int lane) {
    const uint32_t ka = sb + RS_K + k_frag_off(lane) + (1 + warp) * 2048;
    uint32_t qa[16], kx[16];
    const bool in = mbar_try(sb + RB_KV, s & 1);
    nbar_sync(NB_Q, 256);
#pragma unroll
    for (int q = 0; q < 4; q++) ldsm4t(qa + 4 * q, sb + RS_Q + q * 512 + lane * 16);
    if (!in) mbar_wait(sb + RB_KV, s & 1);
#pragma unroll
    for (int q = 0; q < 4; q++) ldsm4t(kx + 4 * q, ka + q * 512);
    SCHED_FENCE();
    float s0, s1;
    s_tile(qa, kx, s0, s1);
    asm volatile("st.shared.v2.f32 [%0], {%1,%2};" :: "r"(sb + RS_SX + warp * 256 + lane * 8), "f"(s0), "f"(s1) : "memory");
    nbar_arrive(NB_XS, 256);
}
DEVI void mem_attn(uint32_t sb, int s, int warp, int lane) {
    const uint32_t ka = sb + RS_K + k_frag_off(lane), va = sb + RS_V + warp * 512;
    const uint32_t dst = sb + RS_O + warp * 512 + (lane & 3) * 128 + (lane >> 2) * 16;
    [[maybe_unused]] constexpr int g = 0;
    uint32_t qa[16], vx[16];
    float sc[10];
    nbar_sync(NB_Q, 256);
    EV(EV_BIG0 && lds32(sb + RS_Q) != 0x12345678u, s, 8);
#pragma unroll
    for (int q = 0; q < 4; q++) ldsm4t(qa + 4 * q, sb + RS_Q + q * 512 + lane * 16);
    mbar_wait(sb + RB_K, s & 1);
    EV(EV_BIG0, s, 9);
    {
        uint32_t km[16];
#pragma unroll
        for (int q = 0; q < 4; q++) ldsm4t(km + 4 * q, ka + q * 512);
        nbar_sync(NB_XS, 256);
        s_tile(qa, km, sc[0], sc[1]);
    }
#pragma unroll
    for (int n = 0; n < 4; n++) { const float2 v = lds64f(sb + RS_SX + n * 256 + lane * 8); sc[2 + 2 * n] = v.x; sc[3 + 2 * n] = v.y; }
    const bool v_in = mbar_try(sb + RB_V, s & 1);
    float m = fmaxf(fmaxf(fmaxf(sc[2], sc[3]), fmaxf(sc[4], sc[5])), fmaxf(fmaxf(sc[6], sc[7]), fmaxf(sc[8], sc[9])));
    m = fmaxf(m, fmaxf(sc[0], sc[1]));
    m = fmaxf(fmaxf(m, __shfl_xor_sync(0xffffffffu, m, 1)), fmaxf(__shfl_xor_sync(0xffffffffu, m, 2), __shfl_xor_sync(0xffffffffu, m, 3)));
    EV(warp == 0 && m != 1.2345e30f && elect_one(), s, 5);
    if (!v_in) mbar_wait(sb + RB_V, s & 1);
    EV(warp == 0 && elect_one(), s, 13);
    uint32_t vm[4], p[10];
#pragma unroll
    for (int q = 3; q >= 0; q--) ldsm4(vx + 4 * q, va + 2048 + (q >> 1) * 4096 + (q & 1) * 256 + v_frag_off(lane));
    ldsm4(vm, va + lane * 16);
    SCHED_FENCE();
    const float nm = -m * SCALE_LOG2E;
    float l = 0.f;
#pragma unroll
    for (int n = 4; n >= 0; n--) {
        const float e0 = ex2(fmaf(sc[2 * n], SCALE_LOG2E, nm)), e1 = ex2(fmaf(sc[2 * n + 1], SCALE_LOG2E, nm));
        l += e0 + e1;
        p[2 * n] = pack_bf16(e0, e1); p[2 * n + 1] = __float_as_uint(e0);
    }
    float o[4][4];
#pragma unroll
    for (int n = 0; n < 4; n++) { o[n][0] = o[n][1] = o[n][2] = o[n][3] = 0.f; }
    pv_pair(o, p + 6, vx + 8);
    pv_pair(o, p + 2, vx);
    pv_single(o, p, vm);
    l = (l + __shfl_xor_sync(0xffffffffu, l, 1)) + (__shfl_xor_sync(0xffffffffu, l, 2) + __shfl_xor_sync(0xffffffffu, l, 3));
    const uint4 u = make_uint4(pack_bf16(o[0][0], o[0][1]), pack_bf16(o[1][0], o[1][1]), pack_bf16(o[2][0], o[2][1]), pack_bf16(o[3][0], o[3][1]));
    st_async128(mapa(dst, 1), u.x, u.y, u.z, u.w, mapa(sb + RB_O, 1));
    st_async128(mapa(dst, 2), u.x, u.y, u.z, u.w, mapa(sb + RB_O, 2));
    const uint32_t dl = sb + RS_INV + (lane & 3) * 32 + (lane & 28);
    asm volatile("st.async.weak.shared::cluster.mbarrier::complete_tx::bytes.b32 [%0], %1, [%2];"
                 :: "r"(mapa(dl, 1 + (warp & 1))), "r"(__float_as_uint(l)), "r"(mapa(sb + RB_O, 1 + (warp & 1))) : "memory");
    sts128(dst, u);
    sts32(dl, __float_as_uint(l));
    __syncwarp();
    if (elect_one()) mbar_arrive(sb + RB_O);
    EV(warp == 0 && elect_one(), s, 15);
}

DEVI void ta_scores(float* c, uint32_t sb, int seg, int cw, int lane) {
    const int mt = cw >= 3, n = cw - 3 * mt;
    const uint32_t qa = sb + RS_QX + (2 * mt + ((lane >> 3) & 1)) * 2048 + ((lane >> 4) * 8 + (lane & 7)) * 16;
    const uint32_t ka = sb + RS_K + n * 2048 + lane * 16;
    float d[4] = {0.f, 0.f, 0.f, 0.f};
    c[0] = c[1] = c[2] = c[3] = 0.f;
    mbar_wait(sb + RB_QX, seg & 1);
    if (n == 0) mbar_wait(sb + RB_K, seg & 1);
#pragma unroll
    for (int j = 0; j < 4; j++) {
        uint32_t a0[4], a1[4], b[4];
        ldsm4t(a0, qa + j * 512);
        ldsm4t(b, ka + j * 512);
        ldsm4t(a1, qa + j * 512 + 256);
        mma16816(c, a0, b[0], b[1]);
        mma16816(d, a1, b[2], b[3]);
    }
    const int over = 8 * (n - 1) + 2 * (lane & 3) - 16 * mt - (lane >> 2);
    c[0] = over > 0 ? -INFINITY : c[0] + d[0];
    c[1] = over >= 0 ? -INFINITY : c[1] + d[1];
    c[2] = over > 8 ? -INFINITY : c[2] + d[2];
    c[3] = over >= 8 ? -INFINITY : c[3] + d[3];
}
DEVI void ta_output(uint32_t sb, int seg, int head, int mt, int j, int lane) {
    const uint32_t sa = sb + RS_QX + mt * 1536 + lane * 16;
    float sc[5][4];
#pragma unroll
    for (int n = 0; n < 5; n++) {
        uint4 v = make_uint4(0xFF800000u, 0xFF800000u, 0xFF800000u, 0xFF800000u);
        if (n < 2 || n == 4 || mt) v = lds128(sa + (n == 4 ? 1024 + mt * 1024 : n * 512));
        sc[n][0] = __uint_as_float(v.x); sc[n][1] = __uint_as_float(v.y); sc[n][2] = __uint_as_float(v.z); sc[n][3] = __uint_as_float(v.w);
    }
    float m0 = -INFINITY, m1 = -INFINITY;
#pragma unroll
    for (int n = 0; n < 5; n++) { m0 = fmaxf(m0, fmaxf(sc[n][0], sc[n][1])); m1 = fmaxf(m1, fmaxf(sc[n][2], sc[n][3])); }
    m0 = fmaxf(m0, __shfl_xor_sync(0xffffffffu, m0, 1)); m1 = fmaxf(m1, __shfl_xor_sync(0xffffffffu, m1, 1));
    m0 = fmaxf(m0, __shfl_xor_sync(0xffffffffu, m0, 2)); m1 = fmaxf(m1, __shfl_xor_sync(0xffffffffu, m1, 2));
    m0 *= -SCALE_LOG2E; m1 *= -SCALE_LOG2E;
    float l0 = 0.f, l1 = 0.f;
    uint32_t p[10];
#pragma unroll
    for (int n = 0; n < 5; n++) {
        const float e0 = ex2(fmaf(sc[n][0], SCALE_LOG2E, m0)), e1 = ex2(fmaf(sc[n][1], SCALE_LOG2E, m0));
        const float e2 = ex2(fmaf(sc[n][2], SCALE_LOG2E, m1)), e3 = ex2(fmaf(sc[n][3], SCALE_LOG2E, m1));
        l0 += e0 + e1; l1 += e2 + e3;
        p[2 * n] = pack_bf16(e0, e1); p[2 * n + 1] = pack_bf16(e2, e3);
    }
    const float i0 = inv_sum4(l0), i1 = inv_sum4(l1);
    mbar_wait(sb + RB_V, seg & 1);
    const uint32_t vb = sb + RS_V + j * 512;
    float o[4][4];
#pragma unroll
    for (int n = 0; n < 4; n++) { o[n][0] = o[n][1] = o[n][2] = o[n][3] = 0.f; }
    uint32_t v[8];
    ldsm4(v, vb + v_frag_off(lane)); ldsm4(v + 4, vb + v_frag_off(lane) + 256);
    pv_pair(o, p, v);
    SCHED_FENCE();
    ldsm4(v, vb + 4096 + v_frag_off(lane)); ldsm4(v + 4, vb + 4096 + v_frag_off(lane) + 256);
    pv_pair(o, p + 4, v);
    SCHED_FENCE();
    ldsm4(v, vb + 4096 + mt * 4096 + lane * 16);
    pv_single(o, p + 8, v);
    bf16* dst = g_ox + (uint32_t)((seg * 32 + mt * 16 + (lane >> 2)) * HD + head * DH + j * 32 + (lane & 3) * 8);
    asm volatile("st.global.v4.u32 [%0], {%1,%2,%3,%4};" :: "l"(dst), "r"(pack_bf16(o[0][0] * i0, o[0][1] * i0)), "r"(pack_bf16(o[1][0] * i0, o[1][1] * i0)),
                 "r"(pack_bf16(o[2][0] * i0, o[2][1] * i0)), "r"(pack_bf16(o[3][0] * i0, o[3][1] * i0)) : "memory");
    asm volatile("st.global.v4.u32 [%0], {%1,%2,%3,%4};" :: "l"(dst + 8 * HD), "r"(pack_bf16(o[0][2] * i1, o[0][3] * i1)), "r"(pack_bf16(o[1][2] * i1, o[1][3] * i1)),
                 "r"(pack_bf16(o[2][2] * i1, o[2][3] * i1)), "r"(pack_bf16(o[3][2] * i1, o[3][3] * i1)) : "memory");
}

template <bool XP>
DEVI void big_main(const uint32_t* w, const uint32_t sb, const int g, const int warp, const uint32_t rank, const int head,
                   const CUtensorMap* tmX, const bf16* xg, const unsigned E) {
    float xa[32];
    const uint32_t aB = __shfl_sync(0xffffffffu, sb + RS_MEM + (g * 32 + (tid_now() & 31)) * 16, tid_now() & 31);
#define lane0 ((int)(opaque(aB) >> 4) & 31)
    const uint32_t aA0 = sb + RS_WSS + g * (8192 + 4096) + a_frag_off(lane0, warp);
    const uint32_t aBf = sb + RS_MEM + g * 512 + b_frag_off(lane0);
    if constexpr (XP) {
        mbar_wait(sb + RB_XF + g * 8, 0);
        x_half<0>(xa, w, sb, 0, g, warp, tmX);
        mbar_wait(sb + RB_XF + g * 8, 1);
        x_half<1>(xa, w, sb, 0, g, warp, tmX);
        x_finish(xa, sb, 0, g, warp, lane0, tmX);
    }
    nbar_sync(NB_BIG, 256);
    for (int s = 0; s < NSEG; s++) {
        float c0[4], c1[4];
        mem_pass<XP>(c0, c1, w, sb, aA0, aBf, g, warp, s);
        EV(EV_BIG0 && c0[0] != 1.2345e30f, s, 3);
        const uint32_t xs = aB + (RS_O - RS_MEM) + (warp - g) * 512;
        sts128f(xs + g * 2048, c1);
        auto combine = [&]() {
            const uint32_t d = sb + (XP ? (rank == 1 ? RS_K : RS_V) : RS_Q) + (g * 4 + warp) * 256 + lane0 * 4;
            const uint32_t rbar = XP ? mapa(sb + (rank == 1 ? RB_K : RB_V), 0) : 0u;
            nbar_sync(NB_PAIR + warp, 64);
            const uint4 v = lds128(xs + (g ^ 1) * 2048);
            const uint32_t p0 = pack_bf16(c0[0] + __uint_as_float(v.x), c0[1] + __uint_as_float(v.y));
            const uint32_t p1 = pack_bf16(c0[2] + __uint_as_float(v.z), c0[3] + __uint_as_float(v.w));
            if constexpr (XP) { st_async32(mapa(d, 0), p0, rbar); st_async32(mapa(d + 128, 0), p1, rbar); }
            else { sts32(d, p0); sts32(d + 128, p1); }
            EV(EV_BIG0, s, 4);
        };
        combine();
        if constexpr (XP) {
            if (s == NSEG - 1) break;
            x_half<0>(xa, w, sb, s + 1, g, warp, tmX);
            EV(EV_BIG0, s, 5);
            EVCAL(s);
            mbar_wait(sb + RB_XF + g * 8, 1);
            nbar_sync(NB_WO, 384);
            EV(EV_BIG0 && lds32(sb + RS_O) != 0x12345678u, s, 6);
            x_half<1>(xa, w, sb, s + 1, g, warp, tmX);
            EV(EV_BIG0, s, 7);
            x_finish(xa, sb, s + 1, g, warp, lane0, tmX);
        } else {
            if (g == 0) {
                if (s < NSEG - 1) mem_attn(sb, s, warp, lane0);
            } else {
                if (s < NSEG - 1) mem_scores(sb, s, warp, lane0); else mbar_wait(sb + RB_KV, s & 1);
                if (s == 0 && warp == 0) {
                    wait_count_warp(&g_cnt[C_QH], 64 * E);
                    if (elect_one()) {
                        fence_proxy_global();
                        mbar_expect_tx(sb + RB_QX, 8192);
                        bulk_load(sb + RS_QX, g_qx + (size_t)head * 4096, 8192, sb + RB_QX);
                    }
                    __syncwarp();
                }
                if (TA_LATE && s < NSEG - 1) mbar_wait(sb + RB_O, s & 1);
                float sc[8];
                const int t2 = warp == 3 ? 3 : (warp + 1) % 3;
                ta_scores(sc, sb, s, 4 + warp, lane0);
                ta_scores(sc + 4, sb, s, t2, lane0);
                nbar_sync(NB_WG + 1, 128);
                sts128f(aB + (RS_QX - RS_MEM) + (3 + warp) * 512, sc);
                sts128f(aB + (RS_QX - RS_MEM) + (t2 - 1) * 512, sc + 4);
            }
            EVCAL(s);
            if (s < NSEG - 1) nbar_sync(NB_WO, 384); else nbar_sync(NB_BIG, 256);
            EV(EV_BIG0 && lds32(sb + RS_O) != 0x12345678u, s, 6);
            ta_output(sb, s, head, g, warp, lane0);
            nbar_sync(NB_BIG, 256);
            EV(EV_BIG0 && lds32(sb + RS_O) != 0x12345678u, s, 7);
            if (g == 0 && warp == 0 && s + 1 < NSEG) {
                if (elect_one()) {
                    mbar_arrive_remote(mapa(sb + RB_ATT, 1));
                    mbar_arrive_remote(mapa(sb + RB_ATT, 2));
                    mbar_expect_tx(sb + RB_KV, 8192);
                    mbar_expect_tx(sb + RB_K, 2048);
                    mbar_expect_tx(sb + RB_V, 2048 + 8192);
                    mbar_arrive(sb + RB_T);
                }
                __syncwarp();
            }
        }
    }
    if constexpr (!XP) { if (tid_now() == 0) signal_count(&g_prog[(NSEG - 1) >> 2]); }
#undef lane0
}

template <int T, int K0, int K1>
DEVI void wo_part(float* acc) {
    constexpr uint32_t dWo = cdesc(T < 5 ? RS_WO + T * 16384 : RS_WO5, 16), dO = cdesc(RS_O, 128);
#pragma unroll
    for (int kk = K0; kk < K1; kk++) {
        if (kk == 0) { if (T < 3) wgmma_n8_ss_first<0>(acc, dWo, dO); else wgmma_n8_ss<0, 0>(acc, dWo, dO); }
        else wgmma_n8_ss<0, 1>(acc, dWo + kk * 128, dO + kk * 16);
    }
    wg_commit();
}
DEVI void red3(uint8_t* p, uint32_t a, uint32_t b, uint32_t c, uint32_t one) {
    asm volatile("red.relaxed.gpu.global.add.noftz.v4.bf16x2 [%0], {%1,%2,%3,%4};" :: "l"(p), "r"(a), "r"(b), "r"(c), "r"(one) : "memory");
}
constexpr int ACC_CH = 3 * 16 * 1024;
template <bool Q>
DEVI void wo_phase(uint32_t sb, int s, int warp, uint8_t* p, uint32_t ainv, int gap) {
    float a0[4], a1[4], a2[4];
    fence_proxy_async();
    const float2 iv = lds64f(ainv);
    SCHED_FENCE();
    const float i0 = rcp_fast(iv.x), i1 = rcp_fast(iv.y);
#define WORD(a, h) pack_bf16(a[2 * h] * i0, a[2 * h + 1] * i1)
    wg_fence();
    wo_part<0, 0, 8>(a0); wo_part<1, 0, 8>(a1); wo_part<2, 0, 8>(a2);
    if (!Q && WO_REL == 4) nbar_arrive(NB_WO, 384);
    wg_wait<1>(); reg_fence<4>(a0); reg_fence<4>(a1);
    if (!Q && WO_REL == 3) nbar_arrive(NB_WO, 384);
    red3(p, WORD(a0, 0), WORD(a0, 1), WORD(a1, 0), 0x3F80u);
    SCHED_FENCE();
    EV(warp == 0 && elect_one(), s, 11);
    wg_wait<0>(); reg_fence<4>(a2);
    if (!Q && WO_REL == 2) nbar_arrive(NB_WO, 384);
    red3(p + ACC_CH, WORD(a2, 0), WORD(a2, 1), WORD(a1, 1), 0x3F80u);
    SCHED_FENCE();
    if (Q || WO_REL < 2) { const uint32_t t = clk32() + gap; while ((int)(clk32() - t) < 0) { } }
    wg_fence();
    wo_part<3, 0, 8>(a0); wo_part<4, 0, 8>(a1);
    if (Q) {
        wo_part<5, 0, 8>(a2);
        wg_wait<1>(); reg_fence<4>(a0); reg_fence<4>(a1);
        red3(p + 2 * ACC_CH, WORD(a0, 0), WORD(a0, 1), WORD(a1, 0), 0x3F80u);
        SCHED_FENCE();
        wg_wait<0>(); reg_fence<4>(a2);
        red3(p + 3 * ACC_CH, WORD(a2, 0), WORD(a2, 1), WORD(a1, 1), 0x3F80u);
        nbar_arrive(NB_WO, 384);
    } else {
        wg_wait<1>();
        nbar_arrive(NB_WO, 384);
        wg_wait<0>(); reg_fence<4>(a0); reg_fence<4>(a1);
        red3(p + 2 * ACC_CH, WORD(a0, 0), WORD(a0, 1), WORD(a1, 0), 0x3F80u);
        red3(p + 3 * ACC_CH, 0u, 0u, WORD(a1, 1), 0x3F80u);
    }
#undef WORD
}
DEVI void unit_pack(uint32_t* u, uint32_t x0, uint32_t x1, uint32_t x2, uint32_t x3) {
    u[0] = __byte_perm(x0, x1, 0x5410); u[1] = __byte_perm(x2, x3, 0x5410); u[2] = __byte_perm(x0, x1, 0x7632); u[3] = __byte_perm(x2, x3, 0x7632);
}
DEVI void unit_send(uint32_t d, const uint32_t* u, uint32_t bar, uint32_t r1, uint32_t r2) {
    st_async128(mapa(d, r1), u[0], u[1], u[2], u[3], mapa(bar, r1));
    st_async128(mapa(d, r2), u[0], u[1], u[2], u[3], mapa(bar, r2));
}
template <bool Q>
DEVI void stage_sums(uint32_t sb, int s, uint32_t rank, int warp, const uint8_t* src, uint32_t l, uint32_t gate) {
    uint4 v[4];
    while ((int)(clk32() - gate) < 0) { }
    EV(elect_one(), s, 16 + warp);
#pragma unroll
    for (int j = 0; j < 4; j++) v[j] = ld_rlx4(src + j * 1024);
    const uint32_t col = sb + RS_MEM + ((Q ? 0 : (rank == 1 ? 6 : 11)) + 3 * (warp >> 1)) * 1024 + ((l >> 2) & 0x300) + (l & 0x70);
    const uint32_t d0 = col + (warp & 1) * 2048, d1 = d0 ^ 160, d2 = (col ^ ((warp & 1) * 160)) + 1024;
    const uint32_t r1 = Q ? 1 : 0, r2 = Q ? 2 : 3 - rank, bar = sb + RB_G + 8 * (warp < 2 ? warp : 2);
    int n = 0;
    while (!__all_sync(0xffffffffu, v[0].w == 0x4200u && v[1].w == 0x4200u && v[2].w == 0x4200u && v[3].w == 0x4200u)) {
#pragma unroll
        for (int j = 0; j < 4; j++) v[j] = ld_rlx4(src + j * 1024);
        if (++n > SPIN_LIMIT) TRAP(0x20000000u | (s << 8) | warp);
    }
    EV(elect_one(), s, 24 + warp);
    uint32_t u[12];
    unit_pack(u + 8, v[0].z, v[1].z, v[2].z, v[3].z);
    unit_send(d2, u + 8, bar, r1, r2);
    if (Q || warp < 3) {
        unit_pack(u, v[0].x, v[1].x, v[2].x, v[3].x);
        unit_pack(u + 4, v[0].y, v[1].y, v[2].y, v[3].y);
        unit_send(d0, u, bar, r1, r2);
        unit_send(d1, u + 4, bar, r1, r2);
        sts128(d0, make_uint4(u[0], u[1], u[2], u[3]));
        sts128(d1, make_uint4(u[4], u[5], u[6], u[7]));
    }
    sts128(d2, make_uint4(u[8], u[9], u[10], u[11]));
    __syncwarp();
    if (elect_one()) mbar_expect_tx(bar, warp < 2 ? 3072u : (warp == 3 ? 0u : (Q ? 4096u : 5120u)));
    EV(elect_one(), s, 20 + warp);
}
DEVI void wo_permute(uint32_t a, int n) {
    const uint32_t flip = (a >> 3) & 16;
#pragma unroll 2
    for (int i = 0; i < n; i++, a += 4096) {
        const uint4 v = lds128(a ^ flip), u = lds128(a ^ flip ^ 16);
        sts128(a ^ flip, make_uint4(__byte_perm(v.x, v.y, 0x5410), __byte_perm(v.x, v.y, 0x7632), __byte_perm(u.x, u.y, 0x5410), __byte_perm(u.x, u.y, 0x7632)));
        sts128(a ^ flip ^ 16, make_uint4(__byte_perm(v.z, v.w, 0x5410), __byte_perm(v.z, v.w, 0x7632), __byte_perm(u.z, u.w, 0x5410), __byte_perm(u.z, u.w, 0x7632)));
    }
}
DEVI uint32_t acc_clear(int slot, int idx, uint32_t lo) {
    uint8_t* p = g_acc + (uint32_t)(slot * 128 + idx * 3072 + (lo < 3072 ? lo : lo - 1024));
    st_rlx4(p, 0u, 0u, 0u, 0u);
    uint32_t z; asm volatile("ld.relaxed.gpu.global.u32 %0, [%1];" : "=r"(z) : "l"(p) : "memory");
    return z;
}

template <bool Q>
DEVI void aux_main(uint32_t sb, int warp, uint32_t rank, int head, const CUtensorMap* tmX, const bf16* xg, unsigned E, const int delay, const int gap, const int vdelay) {
    const uint32_t lo = __shfl_sync(0xffffffffu, ((tid_now() >> 3) & 3) * 1024 + (tid_now() & 7) * 16, tid_now() & 31);
    for (int s = 0; s < NSEG - 1; s++) {
        if (!Q && warp == 0 && elect_one()) mbar_expect_tx(sb + RB_O, 2048 + 256);
        __syncwarp();
        const uint32_t slot = (s & 3) * 128;
        mbar_wait(sb + RB_O, s & 1);
        EV(warp == 0 && elect_one(), s, 10);
        wo_phase<Q>(sb, s, warp, g_acc + (uint32_t)(slot + (rank * 4 + warp) * 4096 + opaque(lo)), sb + RS_INV + ((opaque(lo) >> 1) & 24), gap);
        SCHED_FENCE();
        const uint32_t t_o = clk32();
        EV(warp == 0 && elect_one(), s, 12);
        {
            const uint32_t l = opaque(lo);
            stage_sums<Q>(sb, s, rank, warp, g_acc + (uint32_t)(slot + rank * 16384 + warp * ACC_CH + (l & 0xC00) * 4 + (l & 0x70)), l, t_o + delay);
        }
        EV(warp == 2 && elect_one(), s, 14);
        if (warp == 3) {
            if (Q) {
                mbar_wait(sb + RB_T, s & 1);
                if (s == 3) wait_count_warp(&g_cnt[C_Q], 64 * E);
                if (elect_one()) {
                    if (s == 3) fence_proxy_global();
                    fence_proxy_async();
                    mbar_expect_tx(sb + RB_QX, 8192);
                    bulk_load(sb + RS_QX, g_qx + ((size_t)(s + 1) * NH + head) * 4096, 8192, sb + RB_QX);
                    if (head == 0) { TLOG(1400 + s, 0, gtime()); TLOG(1400 + s, 1, clock64()); }
                }
                __syncwarp();
                const bool fresh = (s & 7) == 6 && s + 2 < NSEG;
                if (fresh) wait_count_warp(&g_cnt[C_Q + ((s + 2) >> 3)], 64 * E);
                if (elect_one()) {
                    if (fresh) fence_proxy_global();
                    if (s + 2 < NSEG && s != 2) l2_prefetch(g_qx + ((size_t)(s + 2) * NH + head) * 4096, 8192);
                    if (s + 4 < NSEG) l2_prefetch(xg + (size_t)((s + 4) * 32 + head) * DM, 2048);
                    signal_count(&g_prog[s >> 2]);
                }
                __syncwarp();
            } else {
                const uint32_t zero = acc_clear((s + 2) & 3, 2 * head + (int)rank - 1, opaque(lo));
                mbar_wait(sb + RB_G + 16, s & 1);
                x_send(sb, s + 1, rank, vdelay);
                if (__any_sync(0xffffffffu, zero != 0u)) __trap();
            }
        }
    }
}

DEVI void load_weights(uint32_t sb, const CUtensorMap* tmW, const CUtensorMap* tmWo, int head, uint32_t rank) {
    const uint32_t bW = sb + RB_W, bSF = sb + RB_SF, bSE = sb + RB_SE;
    const int ntile = rank == 0 ? 6 : 5, tile0 = rank == 0 ? 0 : (rank == 1 ? 6 : 11);
    mbar_expect_tx(bW, R_NSS * 16384);
    mbar_expect_tx(sb + RB_WO, ntile * 16384);
    for (int pass = 0; pass < 2; pass++) {
        for (int pos = 0; pos < 16; pos++) {
            const int k = (int)((R_TORD_PACK >> (4 * pos)) & 15ull) * 64, rd = pos - pos / 3, slot = rd % 5;
            if (r_pos_ss(pos)) {
                if (pass) continue;
                const uint32_t dst = sb + RS_WSS + (pos / 3) * 16384;
                tma_load_2d(dst, tmW, head * DH, k, bW);
                tma_load_2d(dst + 8192, tmW, head * DH + 64, k, bW);
            } else if (pass == (rd >= 5)) {
                if (rd >= 5) mbar_wait(bSE + 8 * slot, ((rd / 5) - 1) & 1);
                mbar_expect_tx(bSF + 8 * slot, 16384);
                const uint32_t dst = sb + RS_WO + slot * 16384;
                tma_load_2d(dst, tmW, head * DH, k, bSF + 8 * slot);
                tma_load_2d(dst + 8192, tmW, head * DH + 64, k, bSF + 8 * slot);
            }
        }
    }
    if (rank == 0) tma_load_wo(sb + RS_WO5, tmWo, 5 * 64, head * 4, sb + RB_WO);
    for (int i = 1; i <= 5; i++) {
        const int slot = i % 5, last = slot + 10 < R_NRS ? slot + 10 : slot + 5;
        mbar_wait(bSE + 8 * slot, (last / 5) & 1);
        tma_load_wo(sb + RS_WO + slot * 16384, tmWo, (tile0 + slot) * 64, head * 4, sb + RB_WO);
    }
}
template <bool XP>
DEVI void big_prologue(uint32_t* w, uint32_t sb, int g, int warp, const bf16* __restrict__ mem0) {
    const int tid = tid_now(), lane = tid & 31;
    {
        const uint32_t* m = (const uint32_t*)(mem0 + (lane >> 2) * DM + (tid >> 5) * 16) + (lane & 3);
        uint32_t u[16];
#pragma unroll
        for (int j = 0; j < 8; j++) { u[2 * j] = m[j * 64]; u[2 * j + 1] = m[j * 64 + 4]; }
#pragma unroll
        for (int j = 0; j < 8; j++) sts64(sb + RS_MEM + ((tid >> 5) + j * 8) * 256 + b_frag_off(lane), u[2 * j], u[2 * j + 1]);
    }
    const uint32_t a0 = sb + RS_WO + g * (8192 + 4096) + a_frag_off(lane, warp), a1 = a0 + 8192 - g * 16384;
#pragma unroll
    for (int rd = 0; rd < R_NRS; rd++) {
        const int slot = rd % 5;
        mbar_wait(sb + RB_SF + 8 * slot, (rd / 5) & 1);
#pragma unroll
        for (int q = 0; q < 4; q++) {
            if (XP && rd == 0 && q == 3) {
                sts128(sb + RS_WX + g * 2048 + (tid & 127) * 16, lds128(sb + RS_WO + 8192 - g * 4096 + 2048 + (tid & 127) * 16));
                fence_proxy_async();
                nbar_sync(NB_WG + g, 128);
            } else ldsm4t(&w[rd * 16 + q * 4], ((q & 1) ? a1 : a0) + slot * 16384 + (q >> 1) * 2048);
        }
        mbar_arrive(sb + RB_SE + 8 * slot);
    }
    mbar_wait(sb + RB_W, 0);
}

#define REC_END() do { if (tid_now() == 0) TLOG(1024 + blockIdx.x, 1, gtime()); } while (0)
__global__ void __launch_bounds__(384, 1)
k_rec(const __grid_constant__ PMaps mp, const __grid_constant__ CUtensorMap tmWk, const __grid_constant__ CUtensorMap tmWv,
      const __grid_constant__ CUtensorMap tmWo, const __grid_constant__ CUtensorMap tmX, const bf16* __restrict__ mem0, const bf16* __restrict__ xg,
      int4 tq, int4 tk, int rec) {
    extern __shared__ __align__(1024) uint8_t smem_raw[];
    const uint32_t sb = smem_u32(smem_raw);
    if ((sb & 0x3FFFFu) != SB0) __trap();
    const int tid = threadIdx.x;
    const int wg = __shfl_sync(0xffffffffu, tid >> 7, 0), warp = __shfl_sync(0xffffffffu, (tid >> 5) & 3, 0);
    uint32_t rank; asm("mov.u32 %0, %%cluster_ctarank;" : "=r"(rank));
    const int head = blockIdx.x / 3;
    asm volatile("griddepcontrol.launch_dependents;");
    if (tid == 0 && rec) {
        mbar_init(sb + RB_G, 1);
        mbar_init(sb + RB_G + 8, 1);
        mbar_init(sb + RB_G + 16, 2);
        mbar_init(sb + RB_T, 1); mbar_init(sb + RB_WO, 1);
        mbar_init(sb + RB_K, 1); mbar_init(sb + RB_V, 1); mbar_init(sb + RB_KV, 1); mbar_init(sb + RB_QX, 1);
        mbar_init(sb + RB_O, rank == 0 ? 4 : 1); mbar_init(sb + RB_ATT, 1); mbar_init(sb + RB_W, 1);
        for (int i = 0; i < 5; i++) { mbar_init(sb + RB_SF + 8 * i, 1); mbar_init(sb + RB_SE + 8 * i, 256); }
        for (int i = 0; i < 2; i++) mbar_init(sb + RB_XF + 8 * i, X_SLOTS);
        fence_mbar_init();
        if (rank == 0) { mbar_expect_tx(sb + RB_KV, 8192); mbar_expect_tx(sb + RB_K, 2048); mbar_expect_tx(sb + RB_V, 2048 + 8192); }
    }
    __syncthreads();
    asm volatile("barrier.cluster.arrive.release.aligned;" ::: "memory");

    if (wg < 2) {
        reg_inc<REG_KB>();
        if (rank != 0) {
            uint32_t w[R_NRS * 16];
            if ((tid & 127) == 0) for (int j = 0; j < X_SLOTS; j++) x_load(sb, 0, j, wg, &tmX);
            __syncwarp();
            cluster_wait();
            big_prologue<true>(w, sb, wg, warp, mem0);
            big_main<true>(w, sb, wg, warp, rank, head, &tmX, xg, 0u);
            REC_END();
        } else if (rec) {
            uint32_t w[R_NRS * 16];
            cluster_wait();
            big_prologue<false>(w, sb, wg, warp, mem0);
            big_main<false>(w, sb, wg, warp, rank, head, &tmX, xg, *(volatile unsigned*)&g_epoch + 1);
            REC_END();
        } else cluster_wait();
        nbar_sync(0, 384);
        nbar_sync(0, 384);
        post_consumer(mp, sb, wg, warp);
    } else {
        reg_dec<504 - 2 * REG_KB>();
        if (rec) {
            if (tid == 256) {
                if (rank == 0) l2_prefetch(xg + (size_t)head * 8 * DM, 16384);
                load_weights(sb, rank == 0 ? &mp.wq : (rank == 1 ? &tmWk : &tmWv), &tmWo, head, rank);
            }
            if (warp == 3 && rank != 0) {
                const uint32_t lo = ((tid >> 3) & 3) * 1024 + (tid & 7) * 16;
                acc_clear(0, 2 * head + (int)rank - 1, lo); acc_clear(1, 2 * head + (int)rank - 1, lo);
                __threadfence();
                __syncwarp();
                if (tid == 256 + 96) atomicAdd(&g_zero, 1u);
            }
            __syncwarp();
        }
        cluster_wait();
        const unsigned E = __shfl_sync(0xffffffffu, *(volatile unsigned*)&g_epoch + 1, 0);
        if (rec) {
            if (warp == 1) wait_count_warp(&g_zero, E * 64u);
            if (warp == 3 && rank != 0) x_send(sb, 0, rank, 0);
            mbar_wait(sb + RB_WO, 0);
            wo_permute(sb + RS_WO + (tid & 127) * 32, 20);
            if (rank == 0) wo_permute(sb + RS_WO5 + (tid & 127) * 32, 4);
            fence_proxy_async();
            nbar_sync(NB_AUX, 128);
            if (rank == 0) aux_main<true>(sb, warp, rank, head, &tmX, xg, E, warp == 0 ? tq.x : (warp == 1 ? tq.y : tq.z), tq.w, 0);
            else           aux_main<false>(sb, warp, rank, head, &tmX, xg, E, warp == 0 ? tk.x : (warp == 1 ? tk.y : tk.z), tq.w, tk.w);
        }
        const int t = tid_now();
        int id = 0;
        if (t >= 288 && t < 288 + 12) asm volatile("prefetch.tensormap [%0];" :: "l"(&mp.wq + (t - 288)) : "memory");
        if (t == 256) id = post_claim(mp, E);
        __syncwarp();
        nbar_sync(0, 384);
        if (t == 256) { post_init(sb); fence_proxy_async(); }
        __syncwarp();
        nbar_sync(0, 384);
        if (t == 256) post_producer(mp, sb, E, id);
        else if (t == 288 || t == 320) post_helper(sb, warp - 1);
    }
    __syncthreads();
    asm volatile("griddepcontrol.wait;" ::: "memory");
}

typedef CUresult (*EncodeFn)(CUtensorMap*, CUtensorMapDataType, cuuint32_t, void*, const cuuint64_t*, const cuuint64_t*,
                             const cuuint32_t*, const cuuint32_t*, CUtensorMapInterleave, CUtensorMapSwizzle,
                             CUtensorMapL2promotion, CUtensorMapFloatOOBfill);

static CUtensorMap make_map(EncodeFn fn, const void* ptr, uint64_t inner, uint64_t outer, uint32_t box_inner, uint32_t box_outer) {
    CUtensorMap m;
    cuuint64_t dims[2] = {inner, outer};
    cuuint64_t strides[1] = {inner * 2};
    cuuint32_t box[2] = {box_inner, box_outer};
    cuuint32_t es[2] = {1, 1};
    fn(&m, CU_TENSOR_MAP_DATA_TYPE_BFLOAT16, 2, const_cast<void*>(ptr), dims, strides, box, es,
       CU_TENSOR_MAP_INTERLEAVE_NONE, CU_TENSOR_MAP_SWIZZLE_128B, CU_TENSOR_MAP_L2_PROMOTION_L2_256B, CU_TENSOR_MAP_FLOAT_OOB_FILL_NONE);
    return m;
}

static CUtensorMap make_wo_map(EncodeFn fn, const void* ptr, uint32_t ngrp) {
    CUtensorMap m;
    cuuint64_t dims[5] = {DM, 2, 4, 4, HD / 32};
    cuuint64_t strides[4] = {DM * 2, 8 * DM * 2, 2 * DM * 2, 32 * DM * 2};
    cuuint32_t box[5] = {64, 2, 4, 4, ngrp};
    cuuint32_t es[5] = {1, 1, 1, 1, 1};
    fn(&m, CU_TENSOR_MAP_DATA_TYPE_BFLOAT16, 5, const_cast<void*>(ptr), dims, strides, box, es,
       CU_TENSOR_MAP_INTERLEAVE_NONE, CU_TENSOR_MAP_SWIZZLE_128B, CU_TENSOR_MAP_L2_PROMOTION_L2_256B, CU_TENSOR_MAP_FLOAT_OOB_FILL_NONE);
    return m;
}

struct Maps {
    PMaps post;
    CUtensorMap wk16, wv16, wo128, x32;
};

extern "C" void kernel_launch(void* const* d_in, const int* in_sizes, int n_in, void* d_out, int out_size) {
    const bf16* A_x   = (const bf16*)d_in[0];
    const bf16* A_mem = (const bf16*)d_in[1];
    const bf16* A_Wq  = (const bf16*)d_in[2];
    const bf16* A_Wk  = (const bf16*)d_in[3];
    const bf16* A_Wv  = (const bf16*)d_in[4];
    const bf16* A_Wo  = (const bf16*)d_in[5];
    const bf16* B_x   = (const bf16*)d_in[7];
    const bf16* B_w   = (const bf16*)d_in[8];
    const bf16* B_wo  = (const bf16*)d_in[9];

    static EncodeFn fn = nullptr;
    static Maps mp;
    static const void* cached[10];
    const void* cur[10] = {A_x, A_mem, A_Wq, A_Wk, A_Wv, A_Wo, B_x, B_w, B_wo, d_out};
    bool same = fn != nullptr;
    for (int i = 0; i < 10 && same; i++) same = cached[i] == cur[i];
    if (!same) {
        if (!fn) {
            void* p = nullptr; cudaDriverEntryPointQueryResult qr;
            cudaGetDriverEntryPoint("cuTensorMapEncodeTiled", &p, cudaEnableDefault, &qr);
            fn = (EncodeFn)p;
            cudaFuncSetAttribute(k_rec, cudaFuncAttributeMaxDynamicSharedMemorySize, R_SMEM);
        }
        void *p_ox, *p_bqkv, *p_bo, *p_qx;
        cudaGetSymbolAddress(&p_qx, g_qx);
        cudaGetSymbolAddress(&p_ox, g_ox); cudaGetSymbolAddress(&p_bqkv, g_bqkv); cudaGetSymbolAddress(&p_bo, g_bo);
        mp.post.wq   = make_map(fn, A_Wq, HD, DM, 64, 64);
        mp.post.wo   = make_wo_map(fn, A_Wo, 2);
        mp.post.bw   = make_map(fn, B_w, 3 * DM, DM, 64, 64);
        mp.post.bwo  = make_map(fn, B_wo, DM, DM, 64, 64);
        mp.post.x    = make_map(fn, A_x, DM, S_TOK, 64, 128);
        mp.post.bx   = make_map(fn, B_x, DM, S_TOK, 64, 128);
        mp.post.bo   = make_map(fn, p_bo, DM, S_TOK, 64, 128);
        mp.post.ox   = make_map(fn, p_ox, HD, S_TOK, 64, 128);
        mp.post.cb   = make_map(fn, p_bqkv, 3 * DM, S_TOK, 64, 64);
        mp.post.cout = make_map(fn, d_out, 2 * DM, S_TOK, 64, 64);
        {
            cuuint64_t dims[4] = {256, 4, NH * 4, NSEG};
            cuuint64_t strides[3] = {512, 2048, NH * 8192};
            cuuint32_t box[4] = {256, 2, 4, 2};
            cuuint32_t es[4] = {1, 1, 1, 1};
            fn(&mp.post.cq, CU_TENSOR_MAP_DATA_TYPE_BFLOAT16, 4, p_qx, dims, strides, box, es,
               CU_TENSOR_MAP_INTERLEAVE_NONE, CU_TENSOR_MAP_SWIZZLE_NONE, CU_TENSOR_MAP_L2_PROMOTION_NONE, CU_TENSOR_MAP_FLOAT_OOB_FILL_NONE);
        }
        {
            int runs[48] = {K_QH, 0, 2, K_Q, 1, 7, K_B1, 0, 8, K_A4, 0, 4, K_B2, 0, 32, K_A4, 4, 2, K_B3, 0, 4, K_A3, 12, 2, K_B3, 4, 4, K_SK, 14, 2, -1};
            const int per[8] = {32, 24, 8, 8, 32, 8, 8 * P_SPLIT, 1};
            int n = 0, id = 0;
            for (; runs[3 * n] >= 0; n++) {
                mp.post.list.run[n] = make_int4(runs[3 * n], runs[3 * n + 1], id, id + runs[3 * n + 2] * per[runs[3 * n]]);
                id = mp.post.list.run[n].w;
            }
            mp.post.list.n = n;
            int dev = 0, nsm = 132;
            cudaGetDevice(&dev);
            cudaDeviceGetAttribute(&nsm, cudaDevAttrMultiProcessorCount, dev);
            mp.post.list.nworker = nsm > 96 ? nsm : 97;
        }
        {
            cuuint64_t dims[4] = {DM, 3, 2, S_TOK / 2};
            cuuint64_t strides[3] = {DM * 2, 3 * DM * 2, 3 * DM * 4};
            cuuint32_t box[4] = {64, 3, 1, 40};
            cuuint32_t es[4] = {1, 1, 1, 1};
            fn(&mp.post.b40, CU_TENSOR_MAP_DATA_TYPE_BFLOAT16, 4, p_bqkv, dims, strides, box, es,
               CU_TENSOR_MAP_INTERLEAVE_NONE, CU_TENSOR_MAP_SWIZZLE_128B, CU_TENSOR_MAP_L2_PROMOTION_L2_256B, CU_TENSOR_MAP_FLOAT_OOB_FILL_NONE);
        }
        mp.wk16 = make_map(fn, A_Wk, HD, DM, 64, 64);
        mp.wv16 = make_map(fn, A_Wv, HD, DM, 64, 64);
        mp.wo128 = make_wo_map(fn, A_Wo, 4);
        {
            cuuint64_t dims[3] = {64, S_TOK, DM / 64};
            cuuint64_t strides[2] = {DM * 2, 128};
            cuuint32_t box[3] = {32, 32, 2};
            cuuint32_t es[3] = {1, 1, 1};
            fn(&mp.x32, CU_TENSOR_MAP_DATA_TYPE_BFLOAT16, 3, const_cast<bf16*>(A_x), dims, strides, box, es,
               CU_TENSOR_MAP_INTERLEAVE_NONE, CU_TENSOR_MAP_SWIZZLE_64B, CU_TENSOR_MAP_L2_PROMOTION_L2_128B, CU_TENSOR_MAP_FLOAT_OOB_FILL_NONE);
        }
        for (int i = 0; i < 10; i++) cached[i] = cur[i];
    }

    cudaStream_t st = cudaStreamPerThread;
    int4 tq = make_int4(0, 150, 600, 80), tk = make_int4(100, 250, 650, 200);
    cudaLaunchConfig_t cfg = {};
    cfg.gridDim = dim3(96); cfg.blockDim = dim3(384); cfg.dynamicSmemBytes = R_SMEM; cfg.stream = st;
    cudaLaunchAttribute at[1];
    at[0].id = cudaLaunchAttributeClusterDimension;
    at[0].val.clusterDim.x = 3; at[0].val.clusterDim.y = 1; at[0].val.clusterDim.z = 1;
    cfg.attrs = at; cfg.numAttrs = 1;
    cudaLaunchKernelEx(&cfg, k_rec, mp.post, mp.wk16, mp.wv16, mp.wo128, mp.x32, A_mem, A_x, tq, tk, 1);
    cfg.gridDim = dim3(mp.post.list.nworker - 96);
    at[0].id = cudaLaunchAttributeProgrammaticStreamSerialization;
    at[0].val.programmaticStreamSerializationAllowed = 1;
    cudaLaunchKernelEx(&cfg, k_rec, mp.post, mp.wk16, mp.wv16, mp.wo128, mp.x32, A_mem, A_x, tq, tk, 0);
}
```

```cpp
#include <cuda_runtime.h>
#include <cuda_bf16.h>
#include <cuda.h>
#include <stdint.h>

typedef __nv_bfloat16 bf16;

constexpr int S_TOK = 2048;
constexpr int DM    = 1024;
constexpr int NH    = 32;
constexpr int DH    = 128;
constexpr int NSEG  = 64;
constexpr int HD    = NH * DH;

__device__ __align__(1024) bf16 g_qx[NSEG * NH * 4 * DH * 8];
__device__ __align__(1024) bf16 g_ox[S_TOK * HD];
__device__ __align__(1024) bf16 g_bqkv[S_TOK * 3 * DM];
__device__ __align__(1024) bf16 g_bo[S_TOK * DM];
__device__ __align__(1024) uint8_t g_acc[192 * 1024];

#define EV(cond, s, k) do {} while (0)
#define EVCAL(s) do {} while (0)

constexpr int P_NSK = 4;
__device__ unsigned g_epoch, g_qctr, g_done, g_zero;
enum { C_B1 = 0, C_B2 = 8, C_Q = 16, C_QH = 24, C_NONE = 31 };
__device__ unsigned g_cnt[32], g_prog[16], g_cnt_sk[P_NSK * 16];
#define P_SPLIT 4
__device__ __align__(1024) uint4 g_skp[P_NSK * 8 * P_SPLIT * 2 * 8 * 128];
#define TLOG(i, k, v) do {} while (0)

#define DEVI __device__ __forceinline__

DEVI uint32_t opaque(uint32_t v) { uint32_t r; asm volatile("mov.u32 %0, %1;" : "=r"(r) : "r"(v)); return r; }
DEVI uint32_t smem_u32(const void* p) { return (uint32_t)__cvta_generic_to_shared(p); }

#define TRAP(code) __trap()
constexpr int SPIN_LIMIT = 1 << 22;
#define MBAR_HINT_NS 20000u
constexpr int SPIN_LIMIT_MBAR = 1 << 17;

DEVI void mbar_init(uint32_t bar, uint32_t cnt) { asm volatile("mbarrier.init.shared::cta.b64 [%0], %1;" :: "r"(bar), "r"(cnt)); }
DEVI void mbar_expect_tx(uint32_t bar, uint32_t bytes) {
    asm volatile("mbarrier.arrive.expect_tx.shared::cta.b64 _, [%0], %1;" :: "r"(bar), "r"(bytes) : "memory");
}
DEVI void mbar_arrive(uint32_t bar) { asm volatile("mbarrier.arrive.shared::cta.b64 _, [%0];" :: "r"(bar) : "memory"); }
DEVI bool mbar_try(uint32_t bar, uint32_t parity) {
    uint32_t ok;
    asm volatile("{.reg .pred p; mbarrier.try_wait.parity.shared::cta.b64 p, [%1], %2; selp.u32 %0, 1, 0, p;}"
                 : "=r"(ok) : "r"(bar), "r"(parity) : "memory");
    return ok;
}
DEVI bool mbar_try_cluster(uint32_t bar, uint32_t parity) {
    uint32_t ok;
    asm volatile("{.reg .pred p; mbarrier.try_wait.parity.acquire.cluster.shared::cta.b64 p, [%1], %2; selp.u32 %0, 1, 0, p;}"
                 : "=r"(ok) : "r"(bar), "r"(parity) : "memory");
    return ok;
}
DEVI bool mbar_try_hint(uint32_t bar, uint32_t parity) {
    uint32_t ok;
    asm volatile("{.reg .pred p; mbarrier.try_wait.parity.shared::cta.b64 p, [%1], %2, %3; selp.u32 %0, 1, 0, p;}"
                 : "=r"(ok) : "r"(bar), "r"(parity), "r"(MBAR_HINT_NS) : "memory");
    return ok;
}
DEVI void mbar_wait(uint32_t bar, uint32_t parity) {
    int n = 0;
    while (!mbar_try(bar, parity)) { if (++n > SPIN_LIMIT) TRAP(bar | (parity << 31)); }
}
DEVI void mbar_wait_sleepy(uint32_t bar, uint32_t parity) {
    int n = 0;
    while (!mbar_try_hint(bar, parity)) { if (++n > SPIN_LIMIT_MBAR) __trap(); }
}
DEVI void mbar_wait_cluster(uint32_t bar, uint32_t parity) {
    int n = 0;
    while (!mbar_try_cluster(bar, parity)) { if (++n > SPIN_LIMIT) __trap(); }
}
DEVI void mbar_spin(uint32_t bar, uint32_t parity) {
    uint32_t ok; int n = 0;
    do {
        asm volatile("{.reg .pred p; mbarrier.test_wait.parity.shared::cta.b64 p, [%1], %2; selp.u32 %0, 1, 0, p;}"
                     : "=r"(ok) : "r"(bar), "r"(parity) : "memory");
        if (++n > SPIN_LIMIT) __trap();
    } while (!ok);
}
DEVI void fence_mbar_init() { asm volatile("fence.mbarrier_init.release.cluster;" ::: "memory"); }
DEVI void fence_proxy_async() { asm volatile("fence.proxy.async.shared::cta;" ::: "memory"); }
DEVI void cluster_sync() {
    asm volatile("barrier.cluster.arrive.release.aligned;\n barrier.cluster.wait.acquire.aligned;" ::: "memory");
}
DEVI void fence_proxy_global() { asm volatile("fence.proxy.async.global;" ::: "memory"); }
DEVI void cluster_wait() { asm volatile("barrier.cluster.wait.acquire.aligned;" ::: "memory"); }
DEVI void nbar_sync(int id, int n) { asm volatile("bar.sync %0, %1;" :: "r"(id), "r"(n) : "memory"); }
DEVI void nbar_arrive(int id, int n) { asm volatile("bar.arrive %0, %1;" :: "r"(id), "r"(n) : "memory"); }

DEVI void tma_load_2d(uint32_t dst, const CUtensorMap* map, int x, int y, uint32_t bar) {
    asm volatile("cp.async.bulk.tensor.2d.shared::cluster.global.mbarrier::complete_tx::bytes [%0], [%1, {%3, %4}], [%2];"
                 :: "r"(dst), "l"(map), "r"(bar), "r"(x), "r"(y) : "memory");
}
DEVI void tma_load_3d(uint32_t dst, const CUtensorMap* map, int x, int y, int z, uint32_t bar) {
    asm volatile("cp.async.bulk.tensor.3d.shared::cluster.global.mbarrier::complete_tx::bytes [%0], [%1, {%3, %4, %5}], [%2];"
                 :: "r"(dst), "l"(map), "r"(bar), "r"(x), "r"(y), "r"(z) : "memory");
}
DEVI void tma_load_wo(uint32_t dst, const CUtensorMap* map, int col, int k32, uint32_t bar) {
    asm volatile("cp.async.bulk.tensor.5d.shared::cluster.global.mbarrier::complete_tx::bytes [%0], [%1, {%3, %5, %5, %5, %4}], [%2];"
                 :: "r"(dst), "l"(map), "r"(bar), "r"(col), "r"(k32), "r"(0) : "memory");
}
DEVI void tma_store_2d(const CUtensorMap* map, uint32_t src, int x, int y) {
    asm volatile("cp.async.bulk.tensor.2d.global.shared::cta.bulk_group [%0, {%2, %3}], [%1];"
                 :: "l"(map), "r"(src), "r"(x), "r"(y) : "memory");
}
DEVI void bulk_load(uint32_t dst, const void* src, uint32_t bytes, uint32_t bar) {
    asm volatile("cp.async.bulk.shared::cluster.global.mbarrier::complete_tx::bytes [%0], [%1], %2, [%3];"
                 :: "r"(dst), "l"(src), "r"(bytes), "r"(bar) : "memory");
}
DEVI void tma_load_2d_mc(uint32_t dst, const CUtensorMap* map, int x, int y, uint32_t bar, uint16_t mask) {
    asm volatile("cp.async.bulk.tensor.2d.shared::cluster.global.mbarrier::complete_tx::bytes.multicast::cluster [%0], [%1, {%3, %4}], [%2], %5;"
                 :: "r"(dst), "l"(map), "r"(bar), "r"(x), "r"(y), "h"(mask) : "memory");
}
DEVI void bulk_copy_s2c(uint32_t dst_cluster, uint32_t src, uint32_t bytes, uint32_t bar_cluster) {
    asm volatile("cp.async.bulk.shared::cluster.shared::cta.mbarrier::complete_tx::bytes [%0], [%1], %2, [%3];"
                 :: "r"(dst_cluster), "r"(src), "r"(bytes), "r"(bar_cluster) : "memory");
}
DEVI void bulk_store(void* dst, uint32_t src, uint32_t bytes) {
    asm volatile("cp.async.bulk.global.shared::cta.bulk_group [%0], [%1], %2;" :: "l"(dst), "r"(src), "r"(bytes) : "memory");
}
DEVI void bulk_wait_read() { asm volatile("cp.async.bulk.wait_group.read 0;" ::: "memory"); }
DEVI void mbar_arrive_remote(uint32_t bar_cluster) {
    asm volatile("mbarrier.arrive.shared::cluster.b64 _, [%0];" :: "r"(bar_cluster) : "memory");
}
DEVI void mbar_expect_tx_remote(uint32_t bar_cluster, uint32_t bytes) {
    asm volatile("mbarrier.arrive.expect_tx.shared::cluster.b64 _, [%0], %1;" :: "r"(bar_cluster), "r"(bytes) : "memory");
}
DEVI void l2_prefetch(const void* p, uint32_t bytes) {
    asm volatile("cp.async.bulk.prefetch.L2.global [%0], %1;" :: "l"(p), "r"(bytes) : "memory");
}
DEVI void bulk_commit() { asm volatile("cp.async.bulk.commit_group;" ::: "memory"); }
DEVI void bulk_wait_all() { asm volatile("cp.async.bulk.wait_group 0;" ::: "memory"); }

DEVI void wg_fence() { asm volatile("wgmma.fence.sync.aligned;" ::: "memory"); }
DEVI void wg_commit() { asm volatile("wgmma.commit_group.sync.aligned;" ::: "memory"); }
template <int N> DEVI void wg_wait() { asm volatile("wgmma.wait_group.sync.aligned %0;" :: "n"(N) : "memory"); }

template <int R> DEVI void reg_dec() { asm volatile("setmaxnreg.dec.sync.aligned.u32 %0;" :: "n"(R)); }
template <int R> DEVI void reg_inc() { asm volatile("setmaxnreg.inc.sync.aligned.u32 %0;" :: "n"(R)); }

DEVI uint64_t mk_desc(uint32_t addr, uint32_t lbo, uint32_t sbo, uint32_t sw) {
    return (uint64_t)((addr & 0x3FFFF) >> 4) | ((uint64_t)(lbo >> 4) << 16) | ((uint64_t)(sbo >> 4) << 32) | ((uint64_t)sw << 62);
}

DEVI uint32_t desc_lo(uint32_t addr, uint32_t lbo) { return ((addr & 0x3FFFF) >> 4) | ((lbo >> 4) << 16); }
constexpr uint32_t DHI_SW128 = (1024u >> 4) | (1u << 30);
constexpr uint32_t DHI_SW64  = (512u >> 4) | (2u << 30);
constexpr uint32_t DHI_NONE  = (128u >> 4);

template <int TB, int SCALE_D>
DEVI void wgmma_n8_ss(float* d, uint32_t alo, uint32_t blo) {
    asm volatile("{.reg .b64 da, db; mov.b64 da, {%4, %6}; mov.b64 db, {%5, %7};\n"
                 "wgmma.mma_async.sync.aligned.m64n8k16.f32.bf16.bf16 {%0,%1,%2,%3}, da, db, %8, 1, 1, 1, %9;}"
                 : "+f"(d[0]), "+f"(d[1]), "+f"(d[2]), "+f"(d[3])
                 : "r"(alo), "r"(blo), "n"(DHI_SW128), "n"(DHI_NONE), "n"(SCALE_D), "n"(TB));
}

template <int TB>
DEVI void wgmma_n8_ss_first(float* d, uint32_t alo, uint32_t blo) {
    asm volatile("{.reg .b64 da, db; mov.b64 da, {%4, %6}; mov.b64 db, {%5, %7};\n"
                 "wgmma.mma_async.sync.aligned.m64n8k16.f32.bf16.bf16 {%0,%1,%2,%3}, da, db, 0, 1, 1, 1, %8;}"
                 : "=f"(d[0]), "=f"(d[1]), "=f"(d[2]), "=f"(d[3])
                 : "r"(alo), "r"(blo), "n"(DHI_SW128), "n"(DHI_NONE), "n"(TB));
}
DEVI void wgmma_n32_rs_first(float* d, const uint32_t* a, uint32_t blo) {
    asm volatile("{.reg .b64 db; mov.b64 db, {%20, %21};\n"
                 "wgmma.mma_async.sync.aligned.m64n32k16.f32.bf16.bf16 {%0,%1,%2,%3,%4,%5,%6,%7,%8,%9,%10,%11,%12,%13,%14,%15}, "
                 "{%16,%17,%18,%19}, db, 0, 1, 1, 0;}"
                 : "=f"(d[0]), "=f"(d[1]), "=f"(d[2]), "=f"(d[3]), "=f"(d[4]), "=f"(d[5]), "=f"(d[6]), "=f"(d[7]),
                   "=f"(d[8]), "=f"(d[9]), "=f"(d[10]), "=f"(d[11]), "=f"(d[12]), "=f"(d[13]), "=f"(d[14]), "=f"(d[15])
                 : "r"(a[0]), "r"(a[1]), "r"(a[2]), "r"(a[3]), "r"(blo), "n"(DHI_SW64));
}
template <int N> DEVI void reg_fence(float* d) {
#pragma unroll
    for (int i = 0; i < N; i++) asm volatile("" : "+f"(d[i]) :: "memory");
}
DEVI void wgmma_n32_rs(float* d, const uint32_t* a, uint32_t blo) {
    asm volatile("{.reg .b64 db; mov.b64 db, {%20, %21};\n"
                 "wgmma.mma_async.sync.aligned.m64n32k16.f32.bf16.bf16 {%0,%1,%2,%3,%4,%5,%6,%7,%8,%9,%10,%11,%12,%13,%14,%15}, "
                 "{%16,%17,%18,%19}, db, 1, 1, 1, 0;}"
                 : "+f"(d[0]), "+f"(d[1]), "+f"(d[2]), "+f"(d[3]), "+f"(d[4]), "+f"(d[5]), "+f"(d[6]), "+f"(d[7]),
                   "+f"(d[8]), "+f"(d[9]), "+f"(d[10]), "+f"(d[11]), "+f"(d[12]), "+f"(d[13]), "+f"(d[14]), "+f"(d[15])
                 : "r"(a[0]), "r"(a[1]), "r"(a[2]), "r"(a[3]), "r"(blo), "n"(DHI_SW64));
}
DEVI void wgmma_n32_ss(float* d, uint32_t alo, uint32_t blo) {
    asm volatile("{.reg .b64 da, db; mov.b64 da, {%16, %18}; mov.b64 db, {%17, %19};\n"
                 "wgmma.mma_async.sync.aligned.m64n32k16.f32.bf16.bf16 {%0,%1,%2,%3,%4,%5,%6,%7,%8,%9,%10,%11,%12,%13,%14,%15}, "
                 "da, db, 1, 1, 1, 1, 0;}"
                 : "+f"(d[0]), "+f"(d[1]), "+f"(d[2]), "+f"(d[3]), "+f"(d[4]), "+f"(d[5]), "+f"(d[6]), "+f"(d[7]),
                   "+f"(d[8]), "+f"(d[9]), "+f"(d[10]), "+f"(d[11]), "+f"(d[12]), "+f"(d[13]), "+f"(d[14]), "+f"(d[15])
                 : "r"(alo), "r"(blo), "n"(DHI_SW128), "n"(DHI_SW64));
}

template <bool FIRST>
DEVI void wgmma_n256_ss(float* d, uint64_t a, uint64_t b) {
    if (FIRST)
        asm volatile("wgmma.mma_async.sync.aligned.m64n256k16.f32.bf16.bf16 {%0,%1,%2,%3,%4,%5,%6,%7,%8,%9,%10,%11,%12,%13,%14,%15,%16,%17,%18,%19,%20,%21,%22,%23,%24,%25,%26,%27,%28,%29,%30,%31,%32,%33,%34,%35,%36,%37,%38,%39,%40,%41,%42,%43,%44,%45,%46,%47,%48,%49,%50,%51,%52,%53,%54,%55,%56,%57,%58,%59,%60,%61,%62,%63,%64,%65,%66,%67,%68,%69,%70,%71,%72,%73,%74,%75,%76,%77,%78,%79,%80,%81,%82,%83,%84,%85,%86,%87,%88,%89,%90,%91,%92,%93,%94,%95,%96,%97,%98,%99,%100,%101,%102,%103,%104,%105,%106,%107,%108,%109,%110,%111,%112,%113,%114,%115,%116,%117,%118,%119,%120,%121,%122,%123,%124,%125,%126,%127}, %128, %129, 0, 1, 1, 1, 0;"
            : "=f"(d[0]), "=f"(d[1]), "=f"(d[2]), "=f"(d[3]), "=f"(d[4]), "=f"(d[5]), "=f"(d[6]), "=f"(d[7]), "=f"(d[8]), "=f"(d[9]), "=f"(d[10]), "=f"(d[11]), "=f"(d[12]), "=f"(d[13]), "=f"(d[14]), "=f"(d[15]), "=f"(d[16]), "=f"(d[17]), "=f"(d[18]), "=f"(d[19]), "=f"(d[20]), "=f"(d[21]), "=f"(d[22]), "=f"(d[23]), "=f"(d[24]), "=f"(d[25]), "=f"(d[26]), "=f"(d[27]), "=f"(d[28]), "=f"(d[29]), "=f"(d[30]), "=f"(d[31]), "=f"(d[32]), "=f"(d[33]), "=f"(d[34]), "=f"(d[35]), "=f"(d[36]), "=f"(d[37]), "=f"(d[38]), "=f"(d[39]), "=f"(d[40]), "=f"(d[41]), "=f"(d[42]), "=f"(d[43]), "=f"(d[44]), "=f"(d[45]), "=f"(d[46]), "=f"(d[47]), "=f"(d[48]), "=f"(d[49]), "=f"(d[50]), "=f"(d[51]), "=f"(d[52]), "=f"(d[53]), "=f"(d[54]), "=f"(d[55]), "=f"(d[56]), "=f"(d[57]), "=f"(d[58]), "=f"(d[59]), "=f"(d[60]), "=f"(d[61]), "=f"(d[62]), "=f"(d[63]), "=f"(d[64]), "=f"(d[65]), "=f"(d[66]), "=f"(d[67]), "=f"(d[68]), "=f"(d[69]), "=f"(d[70]), "=f"(d[71]), "=f"(d[72]), "=f"(d[73]), "=f"(d[74]), "=f"(d[75]), "=f"(d[76]), "=f"(d[77]), "=f"(d[78]), "=f"(d[79]), "=f"(d[80]), "=f"(d[81]), "=f"(d[82]), "=f"(d[83]), "=f"(d[84]), "=f"(d[85]), "=f"(d[86]), "=f"(d[87]), "=f"(d[88]), "=f"(d[89]), "=f"(d[90]), "=f"(d[91]), "=f"(d[92]), "=f"(d[93]), "=f"(d[94]), "=f"(d[95]), "=f"(d[96]), "=f"(d[97]), "=f"(d[98]), "=f"(d[99]), "=f"(d[100]), "=f"(d[101]), "=f"(d[102]), "=f"(d[103]), "=f"(d[104]), "=f"(d[105]), "=f"(d[106]), "=f"(d[107]), "=f"(d[108]), "=f"(d[109]), "=f"(d[110]), "=f"(d[111]), "=f"(d[112]), "=f"(d[113]), "=f"(d[114]), "=f"(d[115]), "=f"(d[116]), "=f"(d[117]), "=f"(d[118]), "=f"(d[119]), "=f"(d[120]), "=f"(d[121]), "=f"(d[122]), "=f"(d[123]), "=f"(d[124]), "=f"(d[125]), "=f"(d[126]), "=f"(d[127]) : "l"(a), "l"(b));
    else
        asm volatile("wgmma.mma_async.sync.aligned.m64n256k16.f32.bf16.bf16 {%0,%1,%2,%3,%4,%5,%6,%7,%8,%9,%10,%11,%12,%13,%14,%15,%16,%17,%18,%19,%20,%21,%22,%23,%24,%25,%26,%27,%28,%29,%30,%31,%32,%33,%34,%35,%36,%37,%38,%39,%40,%41,%42,%43,%44,%45,%46,%47,%48,%49,%50,%51,%52,%53,%54,%55,%56,%57,%58,%59,%60,%61,%62,%63,%64,%65,%66,%67,%68,%69,%70,%71,%72,%73,%74,%75,%76,%77,%78,%79,%80,%81,%82,%83,%84,%85,%86,%87,%88,%89,%90,%91,%92,%93,%94,%95,%96,%97,%98,%99,%100,%101,%102,%103,%104,%105,%106,%107,%108,%109,%110,%111,%112,%113,%114,%115,%116,%117,%118,%119,%120,%121,%122,%123,%124,%125,%126,%127}, %128, %129, 1, 1, 1, 1, 0;"
            : "+f"(d[0]), "+f"(d[1]), "+f"(d[2]), "+f"(d[3]), "+f"(d[4]), "+f"(d[5]), "+f"(d[6]), "+f"(d[7]), "+f"(d[8]), "+f"(d[9]), "+f"(d[10]), "+f"(d[11]), "+f"(d[12]), "+f"(d[13]), "+f"(d[14]), "+f"(d[15]), "+f"(d[16]), "+f"(d[17]), "+f"(d[18]), "+f"(d[19]), "+f"(d[20]), "+f"(d[21]), "+f"(d[22]), "+f"(d[23]), "+f"(d[24]), "+f"(d[25]), "+f"(d[26]), "+f"(d[27]), "+f"(d[28]), "+f"(d[29]), "+f"(d[30]), "+f"(d[31]), "+f"(d[32]), "+f"(d[33]), "+f"(d[34]), "+f"(d[35]), "+f"(d[36]), "+f"(d[37]), "+f"(d[38]), "+f"(d[39]), "+f"(d[40]), "+f"(d[41]), "+f"(d[42]), "+f"(d[43]), "+f"(d[44]), "+f"(d[45]), "+f"(d[46]), "+f"(d[47]), "+f"(d[48]), "+f"(d[49]), "+f"(d[50]), "+f"(d[51]), "+f"(d[52]), "+f"(d[53]), "+f"(d[54]), "+f"(d[55]), "+f"(d[56]), "+f"(d[57]), "+f"(d[58]), "+f"(d[59]), "+f"(d[60]), "+f"(d[61]), "+f"(d[62]), "+f"(d[63]), "+f"(d[64]), "+f"(d[65]), "+f"(d[66]), "+f"(d[67]), "+f"(d[68]), "+f"(d[69]), "+f"(d[70]), "+f"(d[71]), "+f"(d[72]), "+f"(d[73]), "+f"(d[74]), "+f"(d[75]), "+f"(d[76]), "+f"(d[77]), "+f"(d[78]), "+f"(d[79]), "+f"(d[80]), "+f"(d[81]), "+f"(d[82]), "+f"(d[83]), "+f"(d[84]), "+f"(d[85]), "+f"(d[86]), "+f"(d[87]), "+f"(d[88]), "+f"(d[89]), "+f"(d[90]), "+f"(d[91]), "+f"(d[92]), "+f"(d[93]), "+f"(d[94]), "+f"(d[95]), "+f"(d[96]), "+f"(d[97]), "+f"(d[98]), "+f"(d[99]), "+f"(d[100]), "+f"(d[101]), "+f"(d[102]), "+f"(d[103]), "+f"(d[104]), "+f"(d[105]), "+f"(d[106]), "+f"(d[107]), "+f"(d[108]), "+f"(d[109]), "+f"(d[110]), "+f"(d[111]), "+f"(d[112]), "+f"(d[113]), "+f"(d[114]), "+f"(d[115]), "+f"(d[116]), "+f"(d[117]), "+f"(d[118]), "+f"(d[119]), "+f"(d[120]), "+f"(d[121]), "+f"(d[122]), "+f"(d[123]), "+f"(d[124]), "+f"(d[125]), "+f"(d[126]), "+f"(d[127]) : "l"(a), "l"(b));
}
template <bool FIRST>
DEVI void wgmma_n128_ss(float* d, uint64_t a, uint64_t b) {
    if (FIRST)
        asm volatile("wgmma.mma_async.sync.aligned.m64n128k16.f32.bf16.bf16 {%0,%1,%2,%3,%4,%5,%6,%7,%8,%9,%10,%11,%12,%13,%14,%15,%16,%17,%18,%19,%20,%21,%22,%23,%24,%25,%26,%27,%28,%29,%30,%31,%32,%33,%34,%35,%36,%37,%38,%39,%40,%41,%42,%43,%44,%45,%46,%47,%48,%49,%50,%51,%52,%53,%54,%55,%56,%57,%58,%59,%60,%61,%62,%63}, %64, %65, 0, 1, 1, 1, 0;"
            : "=f"(d[0]), "=f"(d[1]), "=f"(d[2]), "=f"(d[3]), "=f"(d[4]), "=f"(d[5]), "=f"(d[6]), "=f"(d[7]), "=f"(d[8]), "=f"(d[9]), "=f"(d[10]), "=f"(d[11]), "=f"(d[12]), "=f"(d[13]), "=f"(d[14]), "=f"(d[15]), "=f"(d[16]), "=f"(d[17]), "=f"(d[18]), "=f"(d[19]), "=f"(d[20]), "=f"(d[21]), "=f"(d[22]), "=f"(d[23]), "=f"(d[24]), "=f"(d[25]), "=f"(d[26]), "=f"(d[27]), "=f"(d[28]), "=f"(d[29]), "=f"(d[30]), "=f"(d[31]), "=f"(d[32]), "=f"(d[33]), "=f"(d[34]), "=f"(d[35]), "=f"(d[36]), "=f"(d[37]), "=f"(d[38]), "=f"(d[39]), "=f"(d[40]), "=f"(d[41]), "=f"(d[42]), "=f"(d[43]), "=f"(d[44]), "=f"(d[45]), "=f"(d[46]), "=f"(d[47]), "=f"(d[48]), "=f"(d[49]), "=f"(d[50]), "=f"(d[51]), "=f"(d[52]), "=f"(d[53]), "=f"(d[54]), "=f"(d[55]), "=f"(d[56]), "=f"(d[57]), "=f"(d[58]), "=f"(d[59]), "=f"(d[60]), "=f"(d[61]), "=f"(d[62]), "=f"(d[63]) : "l"(a), "l"(b));
    else
        asm volatile("wgmma.mma_async.sync.aligned.m64n128k16.f32.bf16.bf16 {%0,%1,%2,%3,%4,%5,%6,%7,%8,%9,%10,%11,%12,%13,%14,%15,%16,%17,%18,%19,%20,%21,%22,%23,%24,%25,%26,%27,%28,%29,%30,%31,%32,%33,%34,%35,%36,%37,%38,%39,%40,%41,%42,%43,%44,%45,%46,%47,%48,%49,%50,%51,%52,%53,%54,%55,%56,%57,%58,%59,%60,%61,%62,%63}, %64, %65, 1, 1, 1, 1, 0;"
            : "+f"(d[0]), "+f"(d[1]), "+f"(d[2]), "+f"(d[3]), "+f"(d[4]), "+f"(d[5]), "+f"(d[6]), "+f"(d[7]), "+f"(d[8]), "+f"(d[9]), "+f"(d[10]), "+f"(d[11]), "+f"(d[12]), "+f"(d[13]), "+f"(d[14]), "+f"(d[15]), "+f"(d[16]), "+f"(d[17]), "+f"(d[18]), "+f"(d[19]), "+f"(d[20]), "+f"(d[21]), "+f"(d[22]), "+f"(d[23]), "+f"(d[24]), "+f"(d[25]), "+f"(d[26]), "+f"(d[27]), "+f"(d[28]), "+f"(d[29]), "+f"(d[30]), "+f"(d[31]), "+f"(d[32]), "+f"(d[33]), "+f"(d[34]), "+f"(d[35]), "+f"(d[36]), "+f"(d[37]), "+f"(d[38]), "+f"(d[39]), "+f"(d[40]), "+f"(d[41]), "+f"(d[42]), "+f"(d[43]), "+f"(d[44]), "+f"(d[45]), "+f"(d[46]), "+f"(d[47]), "+f"(d[48]), "+f"(d[49]), "+f"(d[50]), "+f"(d[51]), "+f"(d[52]), "+f"(d[53]), "+f"(d[54]), "+f"(d[55]), "+f"(d[56]), "+f"(d[57]), "+f"(d[58]), "+f"(d[59]), "+f"(d[60]), "+f"(d[61]), "+f"(d[62]), "+f"(d[63]) : "l"(a), "l"(b));
}

DEVI void mma16816(float* d, const uint32_t* a, uint32_t b0, uint32_t b1) {
    asm volatile("mma.sync.aligned.m16n8k16.row.col.f32.bf16.bf16.f32 {%0,%1,%2,%3}, {%4,%5,%6,%7}, {%8,%9}, {%0,%1,%2,%3};"
                 : "+f"(d[0]), "+f"(d[1]), "+f"(d[2]), "+f"(d[3])
                 : "r"(a[0]), "r"(a[1]), "r"(a[2]), "r"(a[3]), "r"(b0), "r"(b1));
}
DEVI void mma1688(float* d, uint32_t a0, uint32_t a1, uint32_t b0) {
    asm volatile("mma.sync.aligned.m16n8k8.row.col.f32.bf16.bf16.f32 {%0,%1,%2,%3}, {%4,%5}, {%6}, {%0,%1,%2,%3};"
                 : "+f"(d[0]), "+f"(d[1]), "+f"(d[2]), "+f"(d[3]) : "r"(a0), "r"(a1), "r"(b0));
}
DEVI void ldsm4(uint32_t* r, uint32_t addr) {
    asm volatile("ldmatrix.sync.aligned.m8n8.x4.shared.b16 {%0,%1,%2,%3}, [%4];"
                 : "=r"(r[0]), "=r"(r[1]), "=r"(r[2]), "=r"(r[3]) : "r"(addr) : "memory");
}
DEVI void ldsm4t(uint32_t* r, uint32_t addr) {
    asm volatile("ldmatrix.sync.aligned.m8n8.x4.trans.shared.b16 {%0,%1,%2,%3}, [%4];"
                 : "=r"(r[0]), "=r"(r[1]), "=r"(r[2]), "=r"(r[3]) : "r"(addr) : "memory");
}
DEVI void ldsm2(uint32_t* r, uint32_t addr) {
    asm volatile("ldmatrix.sync.aligned.m8n8.x2.shared.b16 {%0,%1}, [%2];" : "=r"(r[0]), "=r"(r[1]) : "r"(addr) : "memory");
}
DEVI void ldsm1t(uint32_t& r, uint32_t addr) {
    asm volatile("ldmatrix.sync.aligned.m8n8.x1.trans.shared.b16 {%0}, [%1];" : "=r"(r) : "r"(addr) : "memory");
}
DEVI void stsm4(uint32_t addr, uint32_t r0, uint32_t r1, uint32_t r2, uint32_t r3) {
    asm volatile("stmatrix.sync.aligned.m8n8.x4.shared.b16 [%0], {%1,%2,%3,%4};" :: "r"(addr), "r"(r0), "r"(r1), "r"(r2), "r"(r3) : "memory");
}
DEVI void stsm4t(uint32_t addr, uint32_t r0, uint32_t r1, uint32_t r2, uint32_t r3) {
    asm volatile("stmatrix.sync.aligned.m8n8.x4.trans.shared.b16 [%0], {%1,%2,%3,%4};" :: "r"(addr), "r"(r0), "r"(r1), "r"(r2), "r"(r3) : "memory");
}
DEVI uint32_t movm_t(uint32_t a) {
    uint32_t d; asm volatile("movmatrix.sync.aligned.m8n8.trans.b16 %0, %1;" : "=r"(d) : "r"(a)); return d;
}
DEVI uint32_t pack_bf16(float lo, float hi) {
    uint32_t r; asm("cvt.rn.bf16x2.f32 %0, %1, %2;" : "=r"(r) : "f"(hi), "f"(lo)); return r;
}
DEVI float ex2(float x) { float y; asm("ex2.approx.ftz.f32 %0, %1;" : "=f"(y) : "f"(x)); return y; }

DEVI uint4 ld_rlx4(const void* p) {
    uint4 v;
    asm volatile("ld.relaxed.gpu.global.v4.u32 {%0,%1,%2,%3}, [%4];" : "=r"(v.x), "=r"(v.y), "=r"(v.z), "=r"(v.w) : "l"(p) : "memory");
    return v;
}
DEVI void ld_rlx4f(float* d, const void* p) {
    asm volatile("ld.relaxed.gpu.global.v4.f32 {%0,%1,%2,%3}, [%4];" : "=f"(d[0]), "=f"(d[1]), "=f"(d[2]), "=f"(d[3]) : "l"(p) : "memory");
}
DEVI bool all_nzf(const float* d) { return __float_as_uint(d[0]) && __float_as_uint(d[1]) && __float_as_uint(d[2]) && __float_as_uint(d[3]); }
DEVI void sts128f(uint32_t addr, const float* d) {
    asm volatile("st.shared.v4.f32 [%0], {%1,%2,%3,%4};" :: "r"(addr), "f"(d[0]), "f"(d[1]), "f"(d[2]), "f"(d[3]) : "memory");
}
DEVI void st_rlx4(void* p, uint32_t a, uint32_t b, uint32_t c, uint32_t d) {
    asm volatile("st.relaxed.gpu.global.v4.u32 [%0], {%1,%2,%3,%4};" :: "l"(p), "r"(a), "r"(b), "r"(c), "r"(d) : "memory");
}
DEVI void st_rlx(void* p, uint32_t v) { asm volatile("st.relaxed.gpu.global.u32 [%0], %1;" :: "l"(p), "r"(v) : "memory"); }
DEVI void sts128(uint32_t addr, uint4 v) {
    asm volatile("st.shared.v4.u32 [%0], {%1,%2,%3,%4};" :: "r"(addr), "r"(v.x), "r"(v.y), "r"(v.z), "r"(v.w) : "memory");
}
DEVI void sts64(uint32_t addr, uint32_t a, uint32_t b) { asm volatile("st.shared.v2.u32 [%0], {%1,%2};" :: "r"(addr), "r"(a), "r"(b) : "memory"); }
DEVI void sts32(uint32_t addr, uint32_t v) { asm volatile("st.shared.u32 [%0], %1;" :: "r"(addr), "r"(v) : "memory"); }
DEVI uint4 lds128(uint32_t addr) {
    uint4 v; asm volatile("ld.shared.v4.u32 {%0,%1,%2,%3}, [%4];" : "=r"(v.x), "=r"(v.y), "=r"(v.z), "=r"(v.w) : "r"(addr) : "memory"); return v;
}
DEVI float2 lds64f(uint32_t addr) {
    float2 v; asm volatile("ld.shared.v2.f32 {%0,%1}, [%2];" : "=f"(v.x), "=f"(v.y) : "r"(addr) : "memory"); return v;
}
DEVI void cp_async16(uint32_t dst, const void* src) {
    asm volatile("cp.async.cg.shared.global [%0], [%1], 16;" :: "r"(dst), "l"(src) : "memory");
}
DEVI void cp_async_commit() { asm volatile("cp.async.commit_group;" ::: "memory"); }
DEVI void cp_async_wait0() { asm volatile("cp.async.wait_group 0;" ::: "memory"); }
DEVI uint32_t lds32(uint32_t addr) { uint32_t v; asm volatile("ld.shared.u32 %0, [%1];" : "=r"(v) : "r"(addr) : "memory"); return v; }
DEVI float rcp_fast(float x) { float y; asm("rcp.approx.ftz.f32 %0, %1;" : "=f"(y) : "f"(x)); return y; }
DEVI bool all_nz(const uint4& v) { return v.x && v.y && v.z && v.w; }
DEVI uint32_t mapa(uint32_t addr, uint32_t rank) {
    uint32_t r; asm("mapa.shared::cluster.u32 %0, %1, %2;" : "=r"(r) : "r"(addr), "r"(rank)); return r;
}
DEVI void st_async32(uint32_t dst, uint32_t a, uint32_t bar) {
    asm volatile("st.async.weak.shared::cluster.mbarrier::complete_tx::bytes.b32 [%0], %1, [%2];" :: "r"(dst), "r"(a), "r"(bar) : "memory");
}
DEVI void st_async64(uint32_t dst, uint32_t a, uint32_t b, uint32_t bar) {
    asm volatile("st.async.weak.shared::cluster.mbarrier::complete_tx::bytes.v2.b32 [%0], {%1,%2}, [%3];"
                 :: "r"(dst), "r"(a), "r"(b), "r"(bar) : "memory");
}

DEVI void st_async128(uint32_t dst, uint32_t a, uint32_t b, uint32_t c, uint32_t d, uint32_t bar) {
    asm volatile("st.async.weak.shared::cluster.mbarrier::complete_tx::bytes.v4.b32 [%0], {%1,%2,%3,%4}, [%5];"
                 :: "r"(dst), "r"(a), "r"(b), "r"(c), "r"(d), "r"(bar) : "memory");
}

DEVI uint32_t b_addr(uint32_t sb, int row, int which, int chunk) { const int l = 3 * row + which; return sb + l * 128 + ((chunk ^ (l & 7)) * 16); }
DEVI void battn_warp(uint32_t st, uint32_t so, int i0, int par, int head, int hh, int mt, int lane) {
    const int gq = lane >> 2, t = lane & 3;
    float s[3][4];
#pragma unroll
    for (int n = 0; n < 3; n++) { s[n][0] = s[n][1] = s[n][2] = s[n][3] = 0.f; }
    const int arow = 16 * mt + (lane & 7) + ((lane >> 3) & 1) * 8;
#pragma unroll
    for (int ks = 0; ks < 2; ks++) {
        uint32_t a[4], b[4], b2[2];
        ldsm4(a, b_addr(st, 8 + arow, 0, hh * 4 + ks * 2 + (lane >> 4)));
        const int brow = 16 * mt + (lane >> 4) * 8 + (lane & 7);
        ldsm4(b, b_addr(st, brow, 1, hh * 4 + ks * 2 + ((lane >> 3) & 1)));
        const int crow = 16 * mt + 16 + (lane & 7);
        ldsm2(b2, b_addr(st, crow, 1, hh * 4 + ks * 2 + ((lane >> 3) & 1)));
        mma16816(s[0], a, b[0], b[1]);
        mma16816(s[1], a, b[2], b[3]);
        mma16816(s[2], a, b2[0], b2[1]);
    }
    float m0 = -INFINITY, m1 = -INFINITY;
#pragma unroll
    for (int n = 0; n < 3; n++) {
#pragma unroll
        for (int c = 0; c < 2; c++) {
            const int dj = 8 * n - 8 + 2 * t + c;
            const bool ex = i0 + 16 * mt + dj >= 0;
            if (!(ex && gq - dj >= 0 && gq - dj <= 7)) s[n][c] = -INFINITY;
            if (!(ex && gq + 8 - dj >= 0 && gq + 8 - dj <= 7)) s[n][2 + c] = -INFINITY;
            m0 = fmaxf(m0, s[n][c]); m1 = fmaxf(m1, s[n][2 + c]);
        }
    }
    m0 = fmaxf(m0, __shfl_xor_sync(0xffffffffu, m0, 1)); m0 = fmaxf(m0, __shfl_xor_sync(0xffffffffu, m0, 2));
    m1 = fmaxf(m1, __shfl_xor_sync(0xffffffffu, m1, 1)); m1 = fmaxf(m1, __shfl_xor_sync(0xffffffffu, m1, 2));
    constexpr float C = 0.17677669529663687f * 1.4426950408889634f;
    float l0 = 0.f, l1 = 0.f;
    uint32_t p[3][2];
#pragma unroll
    for (int n = 0; n < 3; n++) {
        const float e0 = ex2((s[n][0] - m0) * C), e1 = ex2((s[n][1] - m0) * C), e2 = ex2((s[n][2] - m1) * C), e3 = ex2((s[n][3] - m1) * C);
        l0 += e0 + e1; l1 += e2 + e3;
        p[n][0] = pack_bf16(e0, e1); p[n][1] = pack_bf16(e2, e3);
    }
    l0 += __shfl_xor_sync(0xffffffffu, l0, 1); l0 += __shfl_xor_sync(0xffffffffu, l0, 2);
    l1 += __shfl_xor_sync(0xffffffffu, l1, 1); l1 += __shfl_xor_sync(0xffffffffu, l1, 2);
    const float i0f = rcp_fast(l0), i1f = rcp_fast(l1);
    float o[4][4];
#pragma unroll
    for (int n = 0; n < 4; n++) { o[n][0] = o[n][1] = o[n][2] = o[n][3] = 0.f; }
    {
        const uint32_t a0[4] = {p[0][0], p[0][1], p[1][0], p[1][1]}, a1[4] = {p[2][0], p[2][1], 0u, 0u};
#pragma unroll
        for (int n = 0; n < 4; n += 2) {
            uint32_t b[4], b2[4];
            const int vrow = 16 * mt + ((lane >> 3) & 1) * 8 + (lane & 7);
            ldsm4t(b, b_addr(st, vrow, 2, hh * 4 + n + (lane >> 4)));
            const int wrow = 16 * mt + 16 + (lane & 7);
            ldsm4t(b2, b_addr(st, wrow, 2, hh * 4 + n + (lane >> 4)));
            mma16816(o[n], a0, b[0], b[1]);
            mma16816(o[n + 1], a0, b[2], b[3]);
            mma16816(o[n], a1, b2[0], 0u);
            mma16816(o[n + 1], a1, b2[2], 0u);
        }
    }
    {
        const int row = (lane & 7) + ((lane >> 3) & 1) * 8;
#pragma unroll
        for (int n = 0; n < 4; n += 2)
            stsm4(so + row * 64 + (((n + (lane >> 4)) ^ ((row >> 1) & 3)) * 16),
                  pack_bf16(o[n][0] * i0f, o[n][1] * i0f), pack_bf16(o[n][2] * i1f, o[n][3] * i1f),
                  pack_bf16(o[n + 1][0] * i0f, o[n + 1][1] * i0f), pack_bf16(o[n + 1][2] * i1f, o[n + 1][3] * i1f));
    }
    __syncwarp();
#pragma unroll
    for (int i = 0; i < 2; i++) {
        const int idx = lane + i * 32, row = idx >> 2, ch = idx & 3;
        const uint4 v = lds128(so + row * 64 + ((ch ^ ((row >> 1) & 3)) * 16));
        *(uint4*)(g_bo + (size_t)(2 * (i0 + 16 * mt + row) + par) * 1024 + head * 32 + ch * 8) = v;
    }
    __syncwarp();
}

constexpr float SCALE_LOG2E = 0.08838834764831845f * 1.4426950408889634f;

constexpr int P_STAGES = 4, P_STAGE = 16384 + 32768;
constexpr int PS_STG = P_STAGES * P_STAGE;
constexpr int PS_BAR = PS_STG + 32768;
constexpr int P_SMEM = PS_BAR + 256;
static_assert(P_SMEM <= 232448, "smem");
enum { K_Q, K_B1, K_B3, K_A4, K_QH, K_A3, K_SK, K_B2, K_END };
struct PList { int n, nworker; int4 run[16]; };
struct PTask { int kind, a, b, c; };
DEVI PTask p_decode(const PList& pl, int id) {
    for (int i = 0; i < pl.n; i++) {
        const int4 r = pl.run[i];
        if (id < r.w) {
            const int j = id - r.z;
            if (r.x == K_Q || r.x == K_QH) return {r.x, j & 31, r.y + (j >> 5), 0};
            if (r.x == K_B1) return {r.x, j % 24, r.y + j / 24, 0};
            if (r.x == K_B2) return {r.x, 0, r.y + j, 0};
            if (r.x == K_SK) return {r.x, (j / P_SPLIT) & 7, r.y + j / (8 * P_SPLIT), j % P_SPLIT};
            return {r.x, j & 7, r.y + (j >> 3), 0};
        }
    }
    return {K_END, 0, 0, 0};
}
DEVI void wait_count(const unsigned* p, unsigned target) {
    int n = 0;
    while (true) {
        unsigned v; asm volatile("ld.acquire.gpu.global.u32 %0, [%1];" : "=r"(v) : "l"(p) : "memory");
        if ((int)(v - target) >= 0) break;
        __nanosleep(100);
        if (++n > SPIN_LIMIT) TRAP(0x10000000u | ((unsigned)(size_t)p & 0xFFFFu));
    }
}
DEVI void wait_count_warp(const unsigned* p, unsigned target) {
    int n = 0;
    while (true) {
        unsigned v; asm volatile("ld.acquire.gpu.global.u32 %0, [%1];" : "=r"(v) : "l"(p) : "memory");
        if (__all_sync(0xffffffffu, (int)(v - target) >= 0)) break;
        __nanosleep(100);
        if (++n > SPIN_LIMIT) TRAP(0x10000000u | ((unsigned)(size_t)p & 0xFFFFu));
    }
}
DEVI void signal_count(unsigned* p) { __threadfence(); atomicAdd(p, 1u); }

struct PMaps { CUtensorMap wq, bw, bwo, wo, x, bx, bo, ox, cb, cout, cq, b40; PList list; };
constexpr int PB_F = PS_BAR, PB_E = PB_F + 32, PB_TF = PB_F + 64, PB_TE = PB_F + 80, PB_S = PB_F + 96;
constexpr int PS_T = PB_F + 112, PS_SIG = PS_T + 32, PS_SK = PS_SIG + 16;

struct POut { const CUtensorMap* map; int col, tok, cnt; bool blocked; };
DEVI void p_store(const uint32_t* pk, const POut& o, int c, uint32_t stg, int warp, int lane_, int barid, bool elected) {
    const int lane = (int)opaque((uint32_t)lane_);
    const int mi = lane >> 3, r = lane & 7;
    const uint32_t buf = stg + (c & 1) * 8192;
    if (elected) asm volatile("cp.async.bulk.wait_group.read 1;" ::: "memory");
    nbar_sync(barid, 128);
    if (o.blocked) {
#pragma unroll
        for (int j = 0; j < 8; j += 2)
            stsm4(buf + (j + (mi >> 1)) * 1024 + (warp * 16 + (mi & 1) * 8 + r) * 16, pk[2 * j], pk[2 * j + 1], pk[2 * j + 2], pk[2 * j + 3]);
    } else {
#pragma unroll
        for (int j = 0; j < 8; j += 2)
            stsm4t(buf + (8 * (j + (mi >> 1)) + r) * 128 + ((2 * warp + (mi & 1)) ^ r) * 16, pk[2 * j], pk[2 * j + 1], pk[2 * j + 2], pk[2 * j + 3]);
    }
    fence_proxy_async();
    nbar_sync(barid, 128);
    if (elected) {
        if (o.blocked)
            asm volatile("cp.async.bulk.tensor.4d.global.shared::cta.bulk_group [%0, {%2, %3, %4, %5}], [%1];"
                         :: "l"(o.map), "r"(buf), "r"(0), "r"((o.col >> 5) & 2), "r"((o.col >> 7) * 4), "r"((o.tok >> 5) + 2 * c) : "memory");
        else tma_store_2d(o.map, buf, o.col, o.tok + c * 64);
        bulk_commit();
    }
}
DEVI void p_signal(uint32_t sb, int g, int cnt, int& nsig) {
    sts32(sb + PS_SIG + g * 8 + (nsig & 1) * 4, (uint32_t)cnt);
    mbar_arrive(sb + PB_S + g * 8);
    nsig++;
}
template <int BN, bool FIRST>
DEVI void p_kblock(float* d, uint32_t sb, int g, int it, bool elected) {
    const int st = it % P_STAGES;
    mbar_wait(sb + PB_F + st * 8, (it / P_STAGES) & 1);
    const uint32_t a = sb + st * P_STAGE;
    const uint64_t da = mk_desc(a + g * 8192, 16, 1024, 1), db = mk_desc(a + 16384, 16, 1024, 1);
    wg_fence();
#pragma unroll
    for (int kk = 0; kk < 4; kk++) {
        if (BN == 256) { if (FIRST && kk == 0) wgmma_n256_ss<true>(d, da, db); else wgmma_n256_ss<false>(d, da + (uint64_t)(kk * 128), db + (uint64_t)(kk * 2)); }
        else           { if (FIRST && kk == 0) wgmma_n128_ss<true>(d, da, db); else wgmma_n128_ss<false>(d, da + (uint64_t)(kk * 128), db + (uint64_t)(kk * 2)); }
    }
    wg_commit();
    if (!FIRST) {
        wg_wait<1>();
        if (elected) mbar_arrive(sb + PB_E + ((it - 1) % P_STAGES) * 8);
    }
}

DEVI int post_claim(const PMaps& mp, unsigned E) {
    const int id = (int)(atomicAdd(&g_qctr, 1u) - (E - 1) * (unsigned)(mp.list.run[mp.list.n - 1].w + mp.list.nworker));
    const PTask tk = p_decode(mp.list, id);
    if (tk.kind == K_B2) {
        wait_count(&g_cnt[C_B1 + (tk.b >> 2)], 48 * E);
        if ((tk.b & 3) == 0 && tk.b > 0) wait_count(&g_cnt[C_B1 + (tk.b >> 2) - 1], 48 * E);
    } else if (tk.kind == K_B3) wait_count(&g_cnt[C_B2 + tk.b], 8 * E);
    else if (tk.kind == K_A4) wait_count(&g_prog[2 * tk.b + 1], 128 * E);
    else if (tk.kind == K_A3 || tk.kind == K_SK) wait_count(&g_prog[tk.b], 128 * E);
    if (tk.kind != K_Q && tk.kind != K_QH && tk.kind != K_B1) fence_proxy_global();
    return id;
}
DEVI void post_producer(const PMaps& mp, uint32_t sb, unsigned E, int id) {
    const uint32_t bF = sb + PB_F, bE = sb + PB_E;
    int it = 0;
    for (int i = 0;; i++) {
        mbar_wait(sb + PB_TE + (i & 1) * 8, ((i >> 1) & 1) ^ 1);
        if (i > 0) id = post_claim(mp, E);
        const PTask tk = p_decode(mp.list, id);
        sts128(sb + PS_T + (i & 1) * 16, make_uint4((uint32_t)tk.kind | ((uint32_t)id << 8), (uint32_t)tk.a, (uint32_t)tk.b, (uint32_t)tk.c));
        mbar_arrive(sb + PB_TF + (i & 1) * 8);
        if (tk.kind == K_END) break;
        if (tk.kind == K_B2) {
            const int i0 = tk.b * 32;
            for (int j = 0; j < 16; j++, it++) {
                const int st = it % P_STAGES;
                mbar_wait(bE + st * 8, ((it / P_STAGES) & 1) ^ 1);
                const uint32_t a = sb + st * P_STAGE, bar = bF + st * 8;
                mbar_expect_tx(bar, 2 * 15360);
                for (int u = 0; u < 2; u++)
                    asm volatile("cp.async.bulk.tensor.4d.shared::cluster.global.mbarrier::complete_tx::bytes [%0], [%1, {%3, %4, %5, %6}], [%2];"
                                 :: "r"(a + u * 15360), "l"(&mp.b40), "r"(bar), "r"(j * 64), "r"(0), "r"(u), "r"(i0 - 8) : "memory");
            }
            continue;
        }
        const bool qk = tk.kind == K_Q || tk.kind == K_QH, ak = tk.kind == K_A4 || tk.kind == K_A3 || tk.kind == K_SK, wide = tk.kind <= K_A4;
        const CUtensorMap* tw = tk.kind == K_B1 ? &mp.bw : (qk ? &mp.wq : &mp.bwo);
        const CUtensorMap* tx = tk.kind == K_B1 ? &mp.bx : (qk ? &mp.x : (ak ? &mp.ox : &mp.bo));
        const int nk = tk.kind == K_A3 || tk.kind == K_A4 ? HD / 64 : (tk.kind == K_SK ? HD / 64 / P_SPLIT : DM / 64), kb0 = tk.c * (HD / 64 / P_SPLIT);
        for (int kb = kb0; kb < kb0 + nk; kb++, it++) {
            const int st = it % P_STAGES;
            mbar_wait(bE + st * 8, ((it / P_STAGES) & 1) ^ 1);
            const uint32_t a = sb + st * P_STAGE, bar = bF + st * 8;
            mbar_expect_tx(bar, wide ? P_STAGE : 32768);
            if (ak) {
                tma_load_wo(a, &mp.wo, tk.a * 128, kb * 2, bar);
                tma_load_wo(a + 8192, &mp.wo, tk.a * 128 + 64, kb * 2, bar);
            } else {
                tma_load_2d(a, tw, tk.a * 128, kb * 64, bar);
                tma_load_2d(a + 8192, tw, tk.a * 128 + 64, kb * 64, bar);
            }
            tma_load_2d(a + 16384, tx, kb * 64, tk.b * (wide ? 256 : 128), bar);
            if (wide) tma_load_2d(a + 32768, tx, kb * 64, tk.b * 256 + 128, bar);
        }
    }
    __threadfence();
    if (atomicAdd(&g_done, 1u) == E * mp.list.nworker - 1) { __threadfence(); *(volatile unsigned*)&g_epoch = E; }
}
DEVI void post_helper(uint32_t sb, int g) {
    for (int n = 0;; n++) {
        mbar_wait_sleepy(sb + PB_S + g * 8, n & 1);
        const int cnt = (int)lds32(sb + PS_SIG + g * 8 + (n & 1) * 4);
        if (cnt < 0) break;
        signal_count(&g_cnt[cnt]);
    }
}
DEVI void post_consumer(const PMaps& mp, uint32_t sb, int g, int warp) {
    const int barid = 1 + g, tid = threadIdx.x, lane = tid & 31;
    const bool elected = (tid & 127) == 0;
    const uint32_t stg = sb + PS_STG + g * 16384;
    int it = 0, nsig = 0;
    uint32_t pk[64];
    POut out;
    bool pend = false;
#pragma unroll
    for (int i = 0; i < 64; i++) pk[i] = 0u;
    for (int i = 0;; i++) {
        const uint32_t bTF = sb + PB_TF + (i & 1) * 8;
        if (pend) {
            uint32_t now;
            asm volatile("{.reg .pred p, q; mbarrier.test_wait.parity.shared::cta.b64 p, [%1], %2; bar.red.and.pred q, %3, 128, p; selp.u32 %0, 1, 0, q;}"
                         : "=r"(now) : "r"(bTF), "r"((i >> 1) & 1), "r"(barid) : "memory");
            if (!now || (lds32(sb + PS_T + (i & 1) * 16) & 255u) > K_A4) {
#pragma unroll
                for (int c = 0; c < 4; c++) p_store(pk + 16 * c, out, c, stg, warp, lane, barid, elected);
                if (elected && out.cnt != C_NONE) { bulk_wait_all(); p_signal(sb, g, out.cnt, nsig); }
                pend = false;
            }
        }
        mbar_wait(bTF, (i >> 1) & 1);
        const uint4 tw = lds128(sb + PS_T + (i & 1) * 16);
        mbar_arrive(sb + PB_TE + (i & 1) * 8);
        const PTask tk = {(int)(tw.x & 255u), (int)tw.y, (int)tw.z, (int)tw.w};
        if (tk.kind == K_END) break;
        if (tk.kind <= K_A4) {
            float d[128];
            const int nk = tk.kind == K_A4 ? HD / 64 : DM / 64;
            p_kblock<256, true>(d, sb, g, it, elected);
            if (pend) p_store(pk, out, 0, stg, warp, lane, barid, elected);
#pragma unroll
            for (int c = 1; c < 4; c++) {
                p_kblock<256, false>(d, sb, g, it + c, elected);
                if (pend) p_store(pk + 16 * c, out, c, stg, warp, lane, barid, elected);
            }
#pragma unroll 1
            for (int kb = 4; kb < nk; kb++) {
                p_kblock<256, false>(d, sb, g, it + kb, elected);
                if (kb == 6 && pend && elected && out.cnt != C_NONE) { bulk_wait_all(); p_signal(sb, g, out.cnt, nsig); }
            }
            it += nk;
            wg_wait<0>();
            reg_fence<128>(d);
            if (elected) mbar_arrive(sb + PB_E + ((it - 1) % P_STAGES) * 8);
#pragma unroll
            for (int j = 0; j < 64; j++) pk[j] = pack_bf16(d[2 * j], d[2 * j + 1]);
            out.map = tk.kind == K_Q ? &mp.cq : (tk.kind == K_B1 ? &mp.cb : &mp.cout);
            out.col = tk.a * 128 + g * 64 + (tk.kind == K_B3 ? DM : 0);
            out.tok = tk.b * 256;
            out.cnt = tk.kind == K_Q ? C_Q + tk.b : (tk.kind == K_B1 ? C_B1 + tk.b : C_NONE);
            out.blocked = tk.kind == K_Q;
            pend = true;
        } else if (tk.kind == K_B2) {
            if (elected) bulk_wait_all();
            nbar_sync(barid, 128);
#pragma unroll 1
            for (int j = 0; j < 16; j++, it++) {
                const int st = it % P_STAGES;
                mbar_wait(sb + PB_F + st * 8, (it / P_STAGES) & 1);
                const uint32_t a = sb + st * P_STAGE + g * 15360;
                battn_warp(a, stg + warp * 1024, tk.b * 32, g, j * 2 + (warp >> 1), warp >> 1, warp & 1, (int)opaque((uint32_t)lane));
                nbar_sync(barid, 128);
                if (elected) mbar_arrive(sb + PB_E + st * 8);
            }
            if (elected) p_signal(sb, g, C_B2 + (tk.b >> 2), nsig);
#pragma unroll
            for (int j = 0; j < 64; j++) pk[j] = 0u;
        } else {
            float d[64];
            const int nk = tk.kind == K_A3 ? HD / 64 : (tk.kind == K_SK ? HD / 64 / P_SPLIT : DM / 64);
            p_kblock<128, true>(d, sb, g, it, elected);
#pragma unroll 1
            for (int kb = 1; kb < nk; kb++) p_kblock<128, false>(d, sb, g, it + kb, elected);
            it += nk;
            wg_wait<0>();
            reg_fence<64>(d);
            if (elected) mbar_arrive(sb + PB_E + ((it - 1) % P_STAGES) * 8);
            bool finish = true;
            if (tk.kind == K_SK) {
                const int tile = ((tk.b - (16 - P_NSK)) * 8 + tk.a);
                uint4* const base = g_skp + (size_t)(tile * P_SPLIT * 2 + g) * 1024 + (tid & 127);
#pragma unroll
                for (int j = 0; j < 8; j++)
                    base[tk.c * 2048 + j * 128] = make_uint4(pack_bf16(d[8 * j], d[8 * j + 1]), pack_bf16(d[8 * j + 2], d[8 * j + 3]),
                                                             pack_bf16(d[8 * j + 4], d[8 * j + 5]), pack_bf16(d[8 * j + 6], d[8 * j + 7]));
                nbar_sync(barid, 128);
                if (elected) {
                    unsigned old;
                    asm volatile("atom.acq_rel.gpu.global.add.u32 %0, [%1], 1;" : "=r"(old) : "l"(&g_cnt_sk[tile * 2 + g]) : "memory");
                    sts32(sb + PS_SK + g * 4, old % P_SPLIT);
                }
                nbar_sync(barid, 128);
                finish = lds32(sb + PS_SK + g * 4) == P_SPLIT - 1;
                if (finish) {
#pragma unroll 1
                    for (int q = 1; q < P_SPLIT; q += 2) {
                        uint4 v[16];
#pragma unroll
                        for (int j = 0; j < 16; j++)
                            v[j] = j < 8 || q + 1 < P_SPLIT ? __ldcg(base + ((tk.c + q + (j >> 3)) % P_SPLIT) * 2048 + (j & 7) * 128) : make_uint4(0u, 0u, 0u, 0u);
#pragma unroll
                        for (int j = 0; j < 16; j++) {
                            float* e = d + 8 * (j & 7);
                            e[0] += __uint_as_float(v[j].x << 16); e[1] += __uint_as_float(v[j].x & 0xFFFF0000u);
                            e[2] += __uint_as_float(v[j].y << 16); e[3] += __uint_as_float(v[j].y & 0xFFFF0000u);
                            e[4] += __uint_as_float(v[j].z << 16); e[5] += __uint_as_float(v[j].z & 0xFFFF0000u);
                            e[6] += __uint_as_float(v[j].w << 16); e[7] += __uint_as_float(v[j].w & 0xFFFF0000u);
                        }
                    }
                }
                nbar_sync(barid, 128);
            }
            if (finish) {
                const POut o = {tk.kind == K_QH ? &mp.cq : &mp.cout, tk.a * 128 + g * 64, tk.b * 128, 0, tk.kind == K_QH};
                uint32_t q[32];
#pragma unroll
                for (int j = 0; j < 32; j++) q[j] = pack_bf16(d[2 * j], d[2 * j + 1]);
                p_store(q, o, 0, stg, warp, lane, barid, elected);
                p_store(q + 16, o, 1, stg, warp, lane, barid, elected);
                if (elected && tk.kind == K_QH) { bulk_wait_all(); p_signal(sb, g, tk.b == 0 ? C_QH : C_Q, nsig); }
            }
#pragma unroll
            for (int j = 0; j < 64; j++) pk[j] = 0u;
        }
    }
    if (elected) { bulk_wait_all(); p_signal(sb, g, -1, nsig); }
}
DEVI void post_init(uint32_t sb) {
    for (int i = 0; i < P_STAGES; i++) { mbar_init(sb + PB_F + i * 8, 1); mbar_init(sb + PB_E + i * 8, 2); }
    for (int i = 0; i < 2; i++) { mbar_init(sb + PB_TF + i * 8, 1); mbar_init(sb + PB_TE + i * 8, 256); mbar_init(sb + PB_S + i * 8, 1); }
    fence_mbar_init();
}

constexpr unsigned long long R_TORD_PACK = 0xf5ea4937dc1826b0ull;
__host__ __device__ constexpr int r_tord(int pos) { return (int)((R_TORD_PACK >> (4 * pos)) & 15ull); }
__host__ __device__ constexpr int r_tinv(int T) { for (int p = 0; p < 16; p++) if (r_tord(p) == T) return p; return 0; }
__host__ __device__ constexpr bool r_pos_ss(int pos) { return pos % 3 == 2; }
__host__ __device__ constexpr int r_ss(int pos) { return pos / 3; }
__host__ __device__ constexpr int r_rs(int pos) { return pos - pos / 3; }
constexpr int R_NRS = 11, R_NSS = 5;
constexpr int R_G1 = 3, R_G2 = 9;
#define REG_KB 232
#define A_PRE 4
#define WO_REL 0
constexpr int X_SLOTS = 4;
constexpr int X_NST = 8;

constexpr int RS_WSS  = 0;
constexpr int RS_WO   = RS_WSS + R_NSS * 16384;
constexpr int RS_MEM  = RS_WO + 5 * 16384;
constexpr int RS_O    = RS_MEM + 16384;
constexpr int RS_SX   = RS_O + 2048;
constexpr int RS_BAR  = RS_SX + 2048;
constexpr int RS_TAIL = RS_BAR + 1024;
constexpr int RS_WO5  = RS_TAIL;
constexpr int RS_K    = RS_WO5 + 16384;
constexpr int RS_V    = RS_K + 10240;
constexpr int RS_Q    = RS_V + 10240;
constexpr int RS_QX   = RS_Q + 2048;
constexpr int RS_QEND = RS_QX + 8192;
constexpr int RS_X    = RS_TAIL;
constexpr int X_PITCH = X_SLOTS * 4096;
constexpr int RS_XD   = RS_X + 2 * X_PITCH;
constexpr int RS_WX   = RS_XD + 8192;
constexpr int RS_KEND = RS_WX + 4096;
constexpr int RS_EV   = RS_BAR + 256;
constexpr int R_SMEM  = RS_KEND > RS_QEND ? RS_KEND : RS_QEND;
static_assert(R_SMEM <= 232448 && P_SMEM <= R_SMEM, "smem");
static_assert(RS_TAIL % 1024 == 0 && RS_MEM % 1024 == 0, "alignment");

constexpr int RB_G = RS_BAR, RB_K = RS_BAR + 24, RB_V = RS_BAR + 32, RB_KV = RS_BAR + 40, RB_QX = RS_BAR + 48, RB_O = RS_BAR + 56;
constexpr int RB_ATT = RS_BAR + 64, RB_W = RS_BAR + 72, RB_SF = RS_BAR + 80, RB_SE = RB_SF + 40, RB_XF = RB_SE + 40;
constexpr int RB_WO = RB_XF + 56, RB_T = RB_XF + 64, RS_INV = RS_SX + 1024;
static_assert(RB_T + 8 <= RS_EV, "barriers");
constexpr uint32_t SB0 = 1024;
__host__ __device__ constexpr uint32_t cdesc(uint32_t off, uint32_t lbo) { return ((SB0 + off) >> 4) | ((lbo >> 4) << 16); }
#define SCHED_FENCE() __syncwarp()
constexpr int NB_BIG = 1, NB_Q = 2, NB_AUX = 3, NB_WO = 4, NB_XS = 5, NB_WG = 6, NB_PAIR = 8;

DEVI int tid_now() { int t; asm volatile("mov.u32 %0, %%tid.x;" : "=r"(t)); return t; }
DEVI uint32_t a_frag_off(int lane, int warp) { return (uint32_t)((((lane >> 4) * 8 + (lane & 7)) * 128) + (((2 * warp + ((lane >> 3) & 1)) ^ (lane & 7)) * 16)); }
DEVI uint32_t b_frag_off(int lane) { return (uint32_t)((lane & 3) * 64 + (((lane >> 2) * 8) ^ ((lane & 2) * 16))); }
DEVI void lds_b(uint32_t* b, uint32_t a) {
    asm volatile("ld.shared.v2.u32 {%0,%1}, [%2];" : "=r"(b[0]), "=r"(b[1]) : "r"(a) : "memory");
    asm volatile("ld.shared.v2.u32 {%0,%1}, [%2];" : "=r"(b[2]), "=r"(b[3]) : "r"(a + 256) : "memory");
}
DEVI uint32_t clk32() { unsigned long long c; asm volatile("mov.u64 %0, %%clock64;" : "=l"(c)); return (uint32_t)c; }
DEVI bool elect_one() {
    uint32_t e; asm volatile("{.reg .pred p; elect.sync _|p, 0xffffffff; selp.u32 %0, 1, 0, p;}" : "=r"(e)); return e;
}

__host__ __device__ constexpr int x_pair(int j) { return j == 0 || j > 3 ? j : (j == 3 ? 1 : j + 1); }
DEVI void x_load(uint32_t sb, int seg, int j, int g, const CUtensorMap* tmX) {
    const uint32_t bar = sb + RB_XF + g * 8;
    mbar_expect_tx(bar, 4096);
    tma_load_3d(sb + RS_X + g * X_PITCH + (j % X_SLOTS) * 4096, tmX, g * 32, seg * 32, x_pair(j) * 2, bar);
}
DEVI void x_refill(uint32_t sb, int seg, int j, int g, int warp, const CUtensorMap* tmX) {
    const int sn = j + X_SLOTS < X_NST ? seg : seg + 1;
    if (warp == (j & 3) && sn < NSEG) {
        if (elect_one()) x_load(sb, sn, (j + X_SLOTS) % X_NST, g, tmX);
    }
}
template <int H>
DEVI void x_half(float* xa, uint32_t* a, uint32_t aA0, const uint32_t* w, uint32_t sb, int seg, int g0, int warp, const CUtensorMap* tmX) {
    wg_fence();
#pragma unroll
    for (int grp = 0; grp < 4; grp++) {
        const int g = (int)opaque((uint32_t)g0);
        const uint32_t dW0 = cdesc(RS_WSS, 16) + g * 768, dW1 = cdesc(RS_WSS + 8192, 16) - g * 256;
#pragma unroll
        for (int i = 0; i < 8; i++) {
            const bool last = H == 1 && grp >= 2;
            const int j = last ? 6 + (i >> 2) : 4 * H + grp, q = last ? 2 * (i & 3) + (grp == 2) : i;
            const int pos = r_tinv(2 * x_pair(j) + (q >> 2)), kk = (q >> 1) & 1, mt = q & 1;
            const uint32_t db = cdesc(RS_X + (j % X_SLOTS) * 4096, 16) + g * (X_PITCH >> 4) + (q >> 2) * 128 + kk * 2;
            if (j == 0 && q < 2)   wgmma_n32_rs_first(xa + 16 * mt, &w[((r_rs(pos) * 2 + kk) * 2 + mt) * 4], db);
            else if (j == 0 && q == 3) wgmma_n32_ss(xa + 16, cdesc(RS_WX, 16) + g * 128, db);
            else if (r_pos_ss(pos)) wgmma_n32_ss(xa + 16 * mt, (mt ? dW1 : dW0) + r_ss(pos) * 1024 + kk * 128, db);
            else                   wgmma_n32_rs(xa + 16 * mt, &w[((r_rs(pos) * 2 + kk) * 2 + mt) * 4], db);
        }
        wg_commit();
    }
    const int g = (int)opaque((uint32_t)g0);
    if (H == 1) {
#pragma unroll
        for (int q = 0; q < A_PRE; q++) ldsm4t(a + 4 * q, aA0 + (q & 1) * (8192 - g * 16384) + (q >> 1) * 2048);
    }
    wg_wait<3>(); x_refill(sb, seg, 4 * H, g, warp, tmX);
    wg_wait<2>(); x_refill(sb, seg, 4 * H + 1, g, warp, tmX);
    wg_wait<1>();
    if (H == 0) {
        x_refill(sb, seg, 2, g, warp, tmX);
        wg_wait<0>(); reg_fence<32>(xa); x_refill(sb, seg, 3, g, warp, tmX);
    } else reg_fence<16>(xa + 16);
}
DEVI void x_finish(float* xa, uint32_t sb, int seg, int g, int warp, int lane, const CUtensorMap* tmX) {
    const uint32_t d = sb + RS_XD + (lane >> 4) * 2048 + warp * 256 + (lane & 15) * 16;
#pragma unroll
    for (int i = 0; i < 2; i++) {
        const float* x = xa + 16 + 8 * i;
        sts128(d + (g ^ 1) * 1024 + i * 4096, make_uint4(pack_bf16(x[0], x[1]), pack_bf16(x[2], x[3]), pack_bf16(x[4], x[5]), pack_bf16(x[6], x[7])));
    }
    nbar_sync(NB_PAIR + warp, 64);
    float y[16];
#pragma unroll
    for (int i = 0; i < 2; i++) {
        const uint4 v = lds128(d + g * 1024 + i * 4096);
        const uint32_t u[4] = {v.x, v.y, v.z, v.w};
#pragma unroll
        for (int j = 0; j < 4; j++) { y[8 * i + 2 * j] = __uint_as_float(u[j] << 16); y[8 * i + 2 * j + 1] = __uint_as_float(u[j] & 0xFFFF0000u); }
    }
    reg_fence<16>(y);
    wg_wait<0>();
    reg_fence<16>(xa);
    uint32_t p[8];
#pragma unroll
    for (int j = 0; j < 8; j++) p[j] = pack_bf16(xa[2 * j] + y[2 * j], xa[2 * j + 1] + y[2 * j + 1]);
    __syncwarp();
    stsm4(d + g * 1024, p[0], p[1], p[2], p[3]);
    stsm4(d + g * 1024 + 4096, p[4], p[5], p[6], p[7]);
    nbar_arrive(NB_XS, 256 + 32);
    x_refill(sb, seg, X_NST - 2, g, warp, tmX);
    x_refill(sb, seg, X_NST - 1, g, warp, tmX);
}
DEVI void x_send(uint32_t sb, int seg, uint32_t rank, int vdelay) {
    mbar_wait(sb + RB_ATT, (seg - 1) & 1);
    nbar_sync(NB_XS, 256 + 32);
    if (rank == 2) { const uint32_t t = clk32() + vdelay; while ((int)(clk32() - t) < 0) { } }
    if (elect_one()) {
        fence_proxy_async();
        bulk_copy_s2c(mapa(sb + (rank == 1 ? RS_K : RS_V) + 2048, 0), sb + RS_XD, 8192, mapa(sb + (rank == 1 ? RB_KV : RB_V), 0));
    }
    __syncwarp();
}

template <bool XP>
DEVI void mem_pass(float* c0, float* c1, uint32_t* a, const uint32_t* w, uint32_t sb, uint32_t aA0, uint32_t aB, int g, int warp, int s) {
    const uint32_t aA1 = aA0 + 8192 - g * 16384, par = (s - 1) & 1;
    uint32_t b[2][4], e[4];
    float d0[4], d1[4];
    if (XP) ldsm4t(e, aA0 + opaque((RS_WX - RS_WSS) - g * (8192 + 2048)));
#pragma unroll
    for (int q = XP ? A_PRE : 0; q < 4; q++) ldsm4t(a + 4 * q, ((q & 1) ? aA1 : aA0) + (q >> 1) * 2048);
#pragma unroll
    for (int i = 0; i < 4; i++) { c0[i] = 0.f; c1[i] = 0.f; d0[i] = 0.f; d1[i] = 0.f; }
    EV(EV_BIG0, s, 0);
    mbar_wait(sb + RB_G, par);
    EV(EV_BIG0, s, 1);
    lds_b(b[0], aB + r_tord(0) * 1024);
    bool in = false;
#pragma unroll
    for (int pos = 0; pos < 16; pos++) {
        if (pos + 1 < 16) {
            if (pos + 1 == R_G1 && !in) mbar_wait(sb + RB_G + 8, par);
            if (pos + 1 == R_G2) { if (!in) mbar_wait(sb + RB_G + 16, par); EV(EV_BIG0, s, 2); }
            lds_b(b[(pos + 1) & 1], aB + r_tord(pos + 1) * 1024);
        }
        if (pos + 2 == R_G1) in = mbar_try(sb + RB_G + 8, par);
        if (pos + 2 == R_G2) in = mbar_try(sb + RB_G + 16, par);
        if (XP && pos == 12) in = s == NSEG - 1 || mbar_try(sb + RB_XF + g * 8, 0);
        if (XP && pos == 14) { if (!in) mbar_wait(sb + RB_XF + g * 8, 0); in = mbar_try(sb + RB_ATT, par); }
        const uint32_t* bb = b[pos & 1];
        const uint32_t* aa = r_pos_ss(pos) ? a : &w[r_rs(pos) * 16];
        mma16816(c1, aa + 4, bb[0], bb[1]);
        mma16816(d1, XP && pos == 0 ? e : aa + 12, bb[2], bb[3]);
        mma16816(c0, aa, bb[0], bb[1]);
        mma16816(d0, aa + 8, bb[2], bb[3]);
        if (r_pos_ss(pos) && pos + 3 < 16) {
#pragma unroll
            for (int q = 0; q < 4; q++) ldsm4t(a + 4 * q, ((q & 1) ? aA1 : aA0) + (r_ss(pos) + 1) * 16384 + (q >> 1) * 2048);
        }
        SCHED_FENCE();
    }
    if (XP && !in) mbar_wait(sb + RB_ATT, par);
#pragma unroll
    for (int i = 0; i < 4; i++) { c1[i] += d1[i]; c0[i] += d0[i]; }
}

DEVI uint32_t k_frag_off(int lane) { return (uint32_t)((((lane >> 3) & 1) * 16 + (lane >> 4) * 8 + (lane & 7)) * 16); }
DEVI uint32_t v_frag_off(int lane) { return (uint32_t)(((lane >> 3) & 1) * 2048 + ((lane >> 4) * 8 + (lane & 7)) * 16); }
DEVI void pv_pair(float (*o)[4], const uint32_t* p, const uint32_t* v) {
#pragma unroll
    for (int n = 0; n < 4; n++) mma16816(o[n], p, v[2 * n], v[2 * n + 1]);
}
DEVI void pv_single(float (*o)[4], const uint32_t* p, const uint32_t* v) {
#pragma unroll
    for (int n = 0; n < 4; n++) mma1688(o[n], p[0], p[1], v[n]);
}
DEVI void s_tile(const uint32_t* qa, const uint32_t* k, float& s0, float& s1) {
    float c[4][4];
#pragma unroll
    for (int q = 0; q < 4; q++) { c[q][0] = c[q][1] = c[q][2] = c[q][3] = 0.f; }
#pragma unroll
    for (int q = 0; q < 4; q++) {
        mma16816(c[2 * (q & 1)], qa + 4 * q, k[4 * q], k[4 * q + 1]);
        mma16816(c[2 * (q & 1) + 1], qa + 4 * q, k[4 * q + 2], k[4 * q + 3]);
    }
    s0 = (c[0][0] + c[1][2]) + (c[2][0] + c[3][2]);
    s1 = (c[0][1] + c[1][3]) + (c[2][1] + c[3][3]);
}
DEVI void mem_scores(uint32_t sb, int s, int warp, int lane) {
    const uint32_t ka = sb + RS_K + k_frag_off(lane) + (1 + warp) * 2048;
    uint32_t qa[16], kx[16];
    const bool in = mbar_try(sb + RB_KV, s & 1);
    nbar_sync(NB_Q, 256);
#pragma unroll
    for (int q = 0; q < 4; q++) ldsm4t(qa + 4 * q, sb + RS_Q + q * 512 + lane * 16);
    if (!in) mbar_wait(sb + RB_KV, s & 1);
#pragma unroll
    for (int q = 0; q < 4; q++) ldsm4t(kx + 4 * q, ka + q * 512);
    SCHED_FENCE();
    float s0, s1;
    s_tile(qa, kx, s0, s1);
    asm volatile("st.shared.v2.f32 [%0], {%1,%2};" :: "r"(sb + RS_SX + warp * 256 + lane * 8), "f"(s0), "f"(s1) : "memory");
    nbar_arrive(NB_XS, 256);
}
DEVI void mem_attn(uint32_t sb, int s, int warp, int lane) {
    const uint32_t ka = sb + RS_K + k_frag_off(lane), va = sb + RS_V + warp * 512;
    const uint32_t dst = sb + RS_O + warp * 512 + (lane & 3) * 128 + (lane >> 2) * 16;
    [[maybe_unused]] constexpr int g = 0;
    uint32_t qa[16], vx[16];
    float sc[10];
    nbar_sync(NB_Q, 256);
    EV(EV_BIG0 && lds32(sb + RS_Q) != 0x12345678u, s, 8);
#pragma unroll
    for (int q = 0; q < 4; q++) ldsm4t(qa + 4 * q, sb + RS_Q + q * 512 + lane * 16);
    mbar_wait(sb + RB_K, s & 1);
    EV(EV_BIG0, s, 9);
    {
        uint32_t km[16];
#pragma unroll
        for (int q = 0; q < 4; q++) ldsm4t(km + 4 * q, ka + q * 512);
        nbar_sync(NB_XS, 256);
        s_tile(qa, km, sc[0], sc[1]);
    }
#pragma unroll
    for (int n = 0; n < 4; n++) { const float2 v = lds64f(sb + RS_SX + n * 256 + lane * 8); sc[2 + 2 * n] = v.x; sc[3 + 2 * n] = v.y; }
    const bool v_in = mbar_try(sb + RB_V, s & 1);
    float m = fmaxf(fmaxf(fmaxf(sc[2], sc[3]), fmaxf(sc[4], sc[5])), fmaxf(fmaxf(sc[6], sc[7]), fmaxf(sc[8], sc[9])));
    m = fmaxf(m, fmaxf(sc[0], sc[1]));
    m = fmaxf(fmaxf(m, __shfl_xor_sync(0xffffffffu, m, 1)), fmaxf(__shfl_xor_sync(0xffffffffu, m, 2), __shfl_xor_sync(0xffffffffu, m, 3)));
    EV(warp == 0 && m != 1.2345e30f && elect_one(), s, 5);
    if (!v_in) mbar_wait(sb + RB_V, s & 1);
    EV(warp == 0 && elect_one(), s, 13);
    uint32_t vm[4], p[10];
#pragma unroll
    for (int q = 3; q >= 0; q--) ldsm4(vx + 4 * q, va + 2048 + (q >> 1) * 4096 + (q & 1) * 256 + v_frag_off(lane));
    ldsm4(vm, va + lane * 16);
    SCHED_FENCE();
    const float nm = -m * SCALE_LOG2E;
    float l = 0.f;
#pragma unroll
    for (int n = 4; n >= 0; n--) {
        const float e0 = ex2(fmaf(sc[2 * n], SCALE_LOG2E, nm)), e1 = ex2(fmaf(sc[2 * n + 1], SCALE_LOG2E, nm));
        l += e0 + e1;
        p[2 * n] = pack_bf16(e0, e1); p[2 * n + 1] = __float_as_uint(e0);
    }
    float o[4][4];
#pragma unroll
    for (int n = 0; n < 4; n++) { o[n][0] = o[n][1] = o[n][2] = o[n][3] = 0.f; }
    pv_pair(o, p + 6, vx + 8);
    pv_pair(o, p + 2, vx);
    pv_single(o, p, vm);
    l = (l + __shfl_xor_sync(0xffffffffu, l, 1)) + (__shfl_xor_sync(0xffffffffu, l, 2) + __shfl_xor_sync(0xffffffffu, l, 3));
    const uint4 u = make_uint4(pack_bf16(o[0][0], o[0][1]), pack_bf16(o[1][0], o[1][1]), pack_bf16(o[2][0], o[2][1]), pack_bf16(o[3][0], o[3][1]));
    st_async128(mapa(dst, 1), u.x, u.y, u.z, u.w, mapa(sb + RB_O, 1));
    st_async128(mapa(dst, 2), u.x, u.y, u.z, u.w, mapa(sb + RB_O, 2));
    const uint32_t dl = sb + RS_INV + (lane & 3) * 32 + (lane & 28);
    asm volatile("st.async.weak.shared::cluster.mbarrier::complete_tx::bytes.b32 [%0], %1, [%2];"
                 :: "r"(mapa(dl, 1 + (warp & 1))), "r"(__float_as_uint(l)), "r"(mapa(sb + RB_O, 1 + (warp & 1))) : "memory");
    sts128(dst, u);
    sts32(dl, __float_as_uint(l));
    __syncwarp();
    if (elect_one()) mbar_arrive(sb + RB_O);
    EV(warp == 0 && elect_one(), s, 15);
}

DEVI void ta_mask(float* c, int cw, int lane) {
    const int mt = cw >= 3, over = 8 * (cw - 3 * mt - 1) + 2 * (lane & 3) - 16 * mt - (lane >> 2);
    if (over > 0) c[0] = -INFINITY;
    if (over >= 0) c[1] = -INFINITY;
    if (over > 8) c[2] = -INFINITY;
    if (over >= 8) c[3] = -INFINITY;
}
DEVI void ta_scores(uint32_t sb, int seg, int warp, int lane) {
    const int tx = warp == 3 ? 0 : (warp == 2 ? 1 : 4 + 2 * warp), ty = warp == 3 ? 3 : tx + 1;
    const uint32_t qa = sb + RS_QX + ((warp < 2 ? 2 : 0) + ((lane >> 3) & 1)) * 2048 + ((lane >> 4) * 8 + (lane & 7)) * 16;
    const uint32_t ka = sb + RS_K + (warp < 2 ? tx - 3 : tx) * 2048 + lane * 16;
    float x[4] = {0.f, 0.f, 0.f, 0.f}, y[4] = {0.f, 0.f, 0.f, 0.f};
    mbar_wait(sb + RB_QX, seg & 1);
    if (warp < 3) {
#pragma unroll
        for (int j = 0; j < 4; j++) {
            uint32_t a0[4], a1[4], bx[4], by[4];
            ldsm4t(a0, qa + j * 512); ldsm4t(bx, ka + j * 512); ldsm4t(by, ka + 2048 + j * 512); ldsm4t(a1, qa + j * 512 + 256);
            mma16816(x, a0, bx[0], bx[1]); mma16816(y, a0, by[0], by[1]);
            mma16816(x, a1, bx[2], bx[3]); mma16816(y, a1, by[2], by[3]);
        }
        ta_mask(x, tx, lane); ta_mask(y, ty, lane);
    } else {
        mbar_wait(sb + RB_K, seg & 1);
#pragma unroll
        for (int j = 0; j < 4; j++) {
            uint32_t a0[4], a1[4], a2[4], a3[4], b[4];
            ldsm4t(a0, qa + j * 512); ldsm4t(b, ka + j * 512); ldsm4t(a2, qa + 4096 + j * 512);
            ldsm4t(a1, qa + j * 512 + 256); ldsm4t(a3, qa + 4096 + j * 512 + 256);
            mma16816(x, a0, b[0], b[1]); mma16816(y, a2, b[0], b[1]);
            mma16816(x, a1, b[2], b[3]); mma16816(y, a3, b[2], b[3]);
        }
    }
    nbar_sync(NB_WG + 1, 128);
    asm volatile("st.shared.v2.f32 [%0], {%1,%2};" :: "r"(sb + RS_QX + 4096 + tx * 256 + lane * 8), "f"(fmaxf(x[0], x[1])), "f"(fmaxf(x[2], x[3])) : "memory");
    asm volatile("st.shared.v2.f32 [%0], {%1,%2};" :: "r"(sb + RS_QX + 4096 + ty * 256 + lane * 8), "f"(fmaxf(y[0], y[1])), "f"(fmaxf(y[2], y[3])) : "memory");
    nbar_sync(NB_WG + 1, 128);
    float m[4] = {-INFINITY, -INFINITY, -INFINITY, -INFINITY};
#pragma unroll
    for (int n = 0; n < 8; n++) {
        if (n < 3 ? warp >= 2 : warp != 2) {
            const float2 v = lds64f(sb + RS_QX + 4096 + n * 256 + lane * 8);
            m[n < 3 ? 0 : 2] = fmaxf(m[n < 3 ? 0 : 2], v.x); m[n < 3 ? 1 : 3] = fmaxf(m[n < 3 ? 1 : 3], v.y);
        }
    }
#pragma unroll
    for (int o = 1; o < 4; o <<= 1) {
#pragma unroll
        for (int i = 0; i < 4; i++) m[i] = fmaxf(m[i], __shfl_xor_sync(0xffffffffu, m[i], o));
    }
    const float x0 = (warp < 2 ? m[2] : m[0]) * -SCALE_LOG2E, x1 = (warp < 2 ? m[3] : m[1]) * -SCALE_LOG2E;
    const float y0 = (warp == 2 ? m[0] : m[2]) * -SCALE_LOG2E, y1 = (warp == 2 ? m[1] : m[3]) * -SCALE_LOG2E;
    sts64(sb + RS_QX + tx * 256 + lane * 8, pack_bf16(ex2(fmaf(x[0], SCALE_LOG2E, x0)), ex2(fmaf(x[1], SCALE_LOG2E, x0))),
                                            pack_bf16(ex2(fmaf(x[2], SCALE_LOG2E, x1)), ex2(fmaf(x[3], SCALE_LOG2E, x1))));
    sts64(sb + RS_QX + ty * 256 + lane * 8, pack_bf16(ex2(fmaf(y[0], SCALE_LOG2E, y0)), ex2(fmaf(y[1], SCALE_LOG2E, y0))),
                                            pack_bf16(ex2(fmaf(y[2], SCALE_LOG2E, y1)), ex2(fmaf(y[3], SCALE_LOG2E, y1))));
}
template <int MT>
DEVI void ta_output(uint32_t sb, int seg, int head, int j, int lane) {
    const uint32_t pa = sb + RS_QX + MT * 768 + lane * 8, vb = sb + RS_V + j * 512;
    uint32_t p[6 + 4 * MT], v[12 + 8 * MT];
#pragma unroll
    for (int n = 0; n < 3 + 2 * MT; n++)
        asm volatile("ld.shared.v2.u32 {%0,%1}, [%2];" : "=r"(p[2 * n]), "=r"(p[2 * n + 1]) : "r"(pa + n * 256) : "memory");
#pragma unroll
    for (int q = 0; q < 2 + 2 * MT; q++) ldsm4(v + 4 * q, vb + (q >> 1) * 4096 + (q & 1) * 256 + v_frag_off(lane));
    ldsm4(v + 8 + 8 * MT, vb + 4096 + MT * 4096 + lane * 16);
    float o[4][4], l[4] = {0.f, 0.f, 0.f, 0.f};
#pragma unroll
    for (int n = 0; n < 4; n++) { o[n][0] = o[n][1] = o[n][2] = o[n][3] = 0.f; }
    mma16816(l, p, 0x3F803F80u, 0x3F803F80u);
    pv_pair(o, p, v);
    if (MT) { mma16816(l, p + 4, 0x3F803F80u, 0x3F803F80u); pv_pair(o, p + 4, v + 8); }
    mma1688(l, p[4 + 4 * MT], p[5 + 4 * MT], 0x3F803F80u);
    pv_single(o, p + 4 + 4 * MT, v + 8 + 8 * MT);
    const float i0 = rcp_fast(l[0]), i1 = rcp_fast(l[2]);
    bf16* dst = g_ox + (uint32_t)((seg * 32 + MT * 16 + (lane >> 2)) * HD + head * DH + j * 32 + (lane & 3) * 8);
    asm volatile("st.global.v4.u32 [%0], {%1,%2,%3,%4};" :: "l"(dst), "r"(pack_bf16(o[0][0] * i0, o[0][1] * i0)), "r"(pack_bf16(o[1][0] * i0, o[1][1] * i0)),
                 "r"(pack_bf16(o[2][0] * i0, o[2][1] * i0)), "r"(pack_bf16(o[3][0] * i0, o[3][1] * i0)) : "memory");
    asm volatile("st.global.v4.u32 [%0], {%1,%2,%3,%4};" :: "l"(dst + 8 * HD), "r"(pack_bf16(o[0][2] * i1, o[0][3] * i1)), "r"(pack_bf16(o[1][2] * i1, o[1][3] * i1)),
                 "r"(pack_bf16(o[2][2] * i1, o[2][3] * i1)), "r"(pack_bf16(o[3][2] * i1, o[3][3] * i1)) : "memory");
}

template <bool XP>
DEVI void big_main(const uint32_t* w, const uint32_t sb, const int g, const int warp, const uint32_t rank, const int head,
                   const CUtensorMap* tmX, const bf16* xg, const unsigned E) {
    float xa[32];
    uint32_t a[16];
    const uint32_t aB = __shfl_sync(0xffffffffu, sb + RS_MEM + (g * 32 + (tid_now() & 31)) * 16, tid_now() & 31);
#define lane0 ((int)(opaque(aB) >> 4) & 31)
    const uint32_t aA0 = sb + RS_WSS + g * (8192 + 4096) + a_frag_off(lane0, warp);
    const uint32_t aBf = sb + RS_MEM + g * 512 + b_frag_off(lane0);
    if constexpr (XP) {
        mbar_wait(sb + RB_XF + g * 8, 0);
        x_half<0>(xa, a, aA0, w, sb, 0, g, warp, tmX);
        mbar_wait(sb + RB_XF + g * 8, 1);
        x_half<1>(xa, a, aA0, w, sb, 0, g, warp, tmX);
        x_finish(xa, sb, 0, g, warp, lane0, tmX);
    }
    nbar_sync(NB_BIG, 256);
    for (int s = 0; s < NSEG; s++) {
        float c0[4], c1[4];
        mem_pass<XP>(c0, c1, a, w, sb, aA0, aBf, g, warp, s);
        EV(EV_BIG0 && c0[0] != 1.2345e30f, s, 3);
        const uint32_t xs = aB + (RS_O - RS_MEM) + (warp - g) * 512;
        sts128f(xs + g * 2048, c1);
        auto combine = [&]() {
            const uint32_t d = sb + (XP ? (rank == 1 ? RS_K : RS_V) : RS_Q) + (g * 4 + warp) * 256 + lane0 * 4;
            const uint32_t rbar = XP ? mapa(sb + (rank == 1 ? RB_K : RB_V), 0) : 0u;
            nbar_sync(NB_PAIR + warp, 64);
            const uint4 v = lds128(xs + (g ^ 1) * 2048);
            const uint32_t p0 = pack_bf16(c0[0] + __uint_as_float(v.x), c0[1] + __uint_as_float(v.y));
            const uint32_t p1 = pack_bf16(c0[2] + __uint_as_float(v.z), c0[3] + __uint_as_float(v.w));
            if constexpr (XP) { st_async32(mapa(d, 0), p0, rbar); st_async32(mapa(d + 128, 0), p1, rbar); }
            else { sts32(d, p0); sts32(d + 128, p1); }
            EV(EV_BIG0, s, 4);
        };
        combine();
        if constexpr (XP) {
            if (s == NSEG - 1) break;
            x_half<0>(xa, a, aA0, w, sb, s + 1, g, warp, tmX);
            EV(EV_BIG0, s, 5);
            EVCAL(s);
            mbar_wait(sb + RB_XF + g * 8, 1);
            nbar_sync(NB_WO, 384);
            EV(EV_BIG0 && lds32(sb + RS_O) != 0x12345678u, s, 6);
            x_half<1>(xa, a, aA0, w, sb, s + 1, g, warp, tmX);
            EV(EV_BIG0, s, 7);
            x_finish(xa, sb, s + 1, g, warp, lane0, tmX);
        } else {
            if (g == 0) {
                if (s < NSEG - 1) mem_attn(sb, s, warp, lane0);
            } else {
                if (s < NSEG - 1) mem_scores(sb, s, warp, lane0); else mbar_wait(sb + RB_KV, s & 1);
                if (s == 0 && warp == 0) {
                    wait_count_warp(&g_cnt[C_QH], 64 * E);
                    if (elect_one()) {
                        fence_proxy_global();
                        mbar_expect_tx(sb + RB_QX, 8192);
                        bulk_load(sb + RS_QX, g_qx + (size_t)head * 4096, 8192, sb + RB_QX);
                    }
                    __syncwarp();
                }
                ta_scores(sb, s, warp, lane0);
            }
            EVCAL(s);
            mbar_wait(sb + RB_V, s & 1);
            if (s < NSEG - 1) nbar_sync(NB_WO, 384); else nbar_sync(NB_BIG, 256);
            EV(EV_BIG0 && lds32(sb + RS_O) != 0x12345678u, s, 6);
            if (g == 0) ta_output<0>(sb, s, head, warp, lane0); else ta_output<1>(sb, s, head, warp, lane0);
            nbar_sync(NB_BIG, 256);
            EV(EV_BIG0 && lds32(sb + RS_O) != 0x12345678u, s, 7);
            if (g == 0 && warp == 0 && s + 1 < NSEG) {
                if (elect_one()) {
                    mbar_arrive_remote(mapa(sb + RB_ATT, 1));
                    mbar_arrive_remote(mapa(sb + RB_ATT, 2));
                    mbar_expect_tx(sb + RB_KV, 8192);
                    mbar_expect_tx(sb + RB_K, 2048);
                    mbar_expect_tx(sb + RB_V, 2048 + 8192);
                    mbar_arrive(sb + RB_T);
                }
                __syncwarp();
            }
        }
    }
    if constexpr (!XP) { if (tid_now() == 0) signal_count(&g_prog[(NSEG - 1) >> 2]); }
#undef lane0
}

template <int T, int K0, int K1>
DEVI void wo_part(float* acc) {
    constexpr uint32_t dWo = cdesc(T < 5 ? RS_WO + T * 16384 : RS_WO5, 16), dO = cdesc(RS_O, 128);
#pragma unroll
    for (int kk = K0; kk < K1; kk++) {
        if (kk == 0) { if (T < 3) wgmma_n8_ss_first<0>(acc, dWo, dO); else wgmma_n8_ss<0, 0>(acc, dWo, dO); }
        else wgmma_n8_ss<0, 1>(acc, dWo + kk * 128, dO + kk * 16);
    }
    wg_commit();
}
DEVI void red3(uint8_t* p, uint32_t a, uint32_t b, uint32_t c, uint32_t one) {
    asm volatile("red.relaxed.gpu.global.add.noftz.v4.bf16x2 [%0], {%1,%2,%3,%4};" :: "l"(p), "r"(a), "r"(b), "r"(c), "r"(one) : "memory");
}
constexpr int ACC_CH = 3 * 16 * 1024;
template <bool Q>
DEVI void wo_phase(uint32_t sb, int s, int warp, uint8_t* p, uint32_t ainv, int gap) {
    float a0[4], a1[4], a2[4];
    fence_proxy_async();
    const float2 iv = lds64f(ainv);
    SCHED_FENCE();
    const float i0 = rcp_fast(iv.x), i1 = rcp_fast(iv.y);
#define WORD(a, h) pack_bf16(a[2 * h] * i0, a[2 * h + 1] * i1)
    wg_fence();
    wo_part<0, 0, 8>(a0); wo_part<1, 0, 8>(a1); wo_part<2, 0, 8>(a2);
    if (!Q && WO_REL == 4) nbar_arrive(NB_WO, 384);
    wg_wait<1>(); reg_fence<4>(a0); reg_fence<4>(a1);
    if (!Q && WO_REL == 3) nbar_arrive(NB_WO, 384);
    red3(p, WORD(a0, 0), WORD(a0, 1), WORD(a1, 0), 0x3F80u);
    SCHED_FENCE();
    EV(warp == 0 && elect_one(), s, 11);
    wg_wait<0>(); reg_fence<4>(a2);
    if (!Q && WO_REL == 2) nbar_arrive(NB_WO, 384);
    red3(p + ACC_CH, WORD(a2, 0), WORD(a2, 1), WORD(a1, 1), 0x3F80u);
    SCHED_FENCE();
    if (Q || WO_REL < 2) { const uint32_t t = clk32() + gap; while ((int)(clk32() - t) < 0) { } }
    wg_fence();
    wo_part<3, 0, 8>(a0); wo_part<4, 0, 8>(a1);
    if (Q) {
        wo_part<5, 0, 8>(a2);
        wg_wait<1>(); reg_fence<4>(a0); reg_fence<4>(a1);
        red3(p + 2 * ACC_CH, WORD(a0, 0), WORD(a0, 1), WORD(a1, 0), 0x3F80u);
        SCHED_FENCE();
        wg_wait<0>(); reg_fence<4>(a2);
        red3(p + 3 * ACC_CH, WORD(a2, 0), WORD(a2, 1), WORD(a1, 1), 0x3F80u);
        nbar_arrive(NB_WO, 384);
    } else {
        wg_wait<1>();
        nbar_arrive(NB_WO, 384);
        wg_wait<0>(); reg_fence<4>(a0); reg_fence<4>(a1);
        red3(p + 2 * ACC_CH, WORD(a0, 0), WORD(a0, 1), WORD(a1, 0), 0x3F80u);
        red3(p + 3 * ACC_CH, 0u, 0u, WORD(a1, 1), 0x3F80u);
    }
#undef WORD
}
DEVI void unit_pack(uint32_t* u, uint32_t x0, uint32_t x1, uint32_t x2, uint32_t x3) {
    u[0] = __byte_perm(x0, x1, 0x5410); u[1] = __byte_perm(x2, x3, 0x5410); u[2] = __byte_perm(x0, x1, 0x7632); u[3] = __byte_perm(x2, x3, 0x7632);
}
DEVI void unit_send(uint32_t d, const uint32_t* u, uint32_t bar, uint32_t r1, uint32_t r2) {
    st_async128(mapa(d, r1), u[0], u[1], u[2], u[3], mapa(bar, r1));
    st_async128(mapa(d, r2), u[0], u[1], u[2], u[3], mapa(bar, r2));
}
template <bool Q>
DEVI void stage_sums(uint32_t sb, int s, uint32_t rank, int warp, const uint8_t* src, uint32_t l, uint32_t gate) {
    uint4 v[4];
    while ((int)(clk32() - gate) < 0) { }
    EV(elect_one(), s, 16 + warp);
#pragma unroll
    for (int j = 0; j < 4; j++) v[j] = ld_rlx4(src + j * 1024);
    const uint32_t col = sb + RS_MEM + ((Q ? 0 : (rank == 1 ? 6 : 11)) + 3 * (warp >> 1)) * 1024 + ((l >> 2) & 0x300) + (l & 0x70);
    const uint32_t d0 = col + (warp & 1) * 2048, d1 = d0 ^ 160, d2 = (col ^ ((warp & 1) * 160)) + 1024;
    const uint32_t r1 = Q ? 1 : 0, r2 = Q ? 2 : 3 - rank, bar = sb + RB_G + 8 * (warp < 2 ? warp : 2);
    int n = 0;
    while (!__all_sync(0xffffffffu, v[0].w == 0x4200u && v[1].w == 0x4200u && v[2].w == 0x4200u && v[3].w == 0x4200u)) {
#pragma unroll
        for (int j = 0; j < 4; j++) v[j] = ld_rlx4(src + j * 1024);
        if (++n > SPIN_LIMIT) TRAP(0x20000000u | (s << 8) | warp);
    }
    EV(elect_one(), s, 24 + warp);
    uint32_t u[12];
    unit_pack(u + 8, v[0].z, v[1].z, v[2].z, v[3].z);
    unit_send(d2, u + 8, bar, r1, r2);
    if (Q || warp < 3) {
        unit_pack(u, v[0].x, v[1].x, v[2].x, v[3].x);
        unit_pack(u + 4, v[0].y, v[1].y, v[2].y, v[3].y);
        unit_send(d0, u, bar, r1, r2);
        unit_send(d1, u + 4, bar, r1, r2);
        sts128(d0, make_uint4(u[0], u[1], u[2], u[3]));
        sts128(d1, make_uint4(u[4], u[5], u[6], u[7]));
    }
    sts128(d2, make_uint4(u[8], u[9], u[10], u[11]));
    __syncwarp();
    if (elect_one()) mbar_expect_tx(bar, warp < 2 ? 3072u : (warp == 3 ? 0u : (Q ? 4096u : 5120u)));
    EV(elect_one(), s, 20 + warp);
}
DEVI void wo_permute(uint32_t a, int n) {
    const uint32_t flip = (a >> 3) & 16;
#pragma unroll 2
    for (int i = 0; i < n; i++, a += 4096) {
        const uint4 v = lds128(a ^ flip), u = lds128(a ^ flip ^ 16);
        sts128(a ^ flip, make_uint4(__byte_perm(v.x, v.y, 0x5410), __byte_perm(v.x, v.y, 0x7632), __byte_perm(u.x, u.y, 0x5410), __byte_perm(u.x, u.y, 0x7632)));
        sts128(a ^ flip ^ 16, make_uint4(__byte_perm(v.z, v.w, 0x5410), __byte_perm(v.z, v.w, 0x7632), __byte_perm(u.z, u.w, 0x5410), __byte_perm(u.z, u.w, 0x7632)));
    }
}
DEVI uint32_t acc_clear(int slot, int idx, uint32_t lo) {
    uint8_t* p = g_acc + (uint32_t)(slot * 128 + idx * 3072 + (lo < 3072 ? lo : lo - 1024));
    st_rlx4(p, 0u, 0u, 0u, 0u);
    uint32_t z; asm volatile("ld.relaxed.gpu.global.u32 %0, [%1];" : "=r"(z) : "l"(p) : "memory");
    return z;
}

template <bool Q>
DEVI void aux_main(uint32_t sb, int warp, uint32_t rank, int head, const CUtensorMap* tmX, const bf16* xg, unsigned E, const int delay, const int gap, const int vdelay) {
    const uint32_t lo = __shfl_sync(0xffffffffu, ((tid_now() >> 3) & 3) * 1024 + (tid_now() & 7) * 16, tid_now() & 31);
    for (int s = 0; s < NSEG - 1; s++) {
        if (!Q && warp == 0 && elect_one()) mbar_expect_tx(sb + RB_O, 2048 + 256);
        __syncwarp();
        const uint32_t slot = (s & 3) * 128;
        mbar_wait(sb + RB_O, s & 1);
        EV(warp == 0 && elect_one(), s, 10);
        wo_phase<Q>(sb, s, warp, g_acc + (uint32_t)(slot + (rank * 4 + warp) * 4096 + opaque(lo)), sb + RS_INV + ((opaque(lo) >> 1) & 24), gap);
        SCHED_FENCE();
        const uint32_t t_o = clk32();
        EV(warp == 0 && elect_one(), s, 12);
        {
            const uint32_t l = opaque(lo);
            stage_sums<Q>(sb, s, rank, warp, g_acc + (uint32_t)(slot + rank * 16384 + warp * ACC_CH + (l & 0xC00) * 4 + (l & 0x70)), l, t_o + delay);
        }
        EV(warp == 2 && elect_one(), s, 14);
        if (warp == 3) {
            if (Q) {
                mbar_wait(sb + RB_T, s & 1);
                if (s == 3) wait_count_warp(&g_cnt[C_Q], 64 * E);
                if (elect_one()) {
                    if (s == 3) fence_proxy_global();
                    fence_proxy_async();
                    mbar_expect_tx(sb + RB_QX, 8192);
                    bulk_load(sb + RS_QX, g_qx + ((size_t)(s + 1) * NH + head) * 4096, 8192, sb + RB_QX);
                    if (head == 0) { TLOG(1400 + s, 0, gtime()); TLOG(1400 + s, 1, clock64()); }
                }
                __syncwarp();
                const bool fresh = (s & 7) == 6 && s + 2 < NSEG;
                if (fresh) wait_count_warp(&g_cnt[C_Q + ((s + 2) >> 3)], 64 * E);
                if (elect_one()) {
                    if (fresh) fence_proxy_global();
                    if (s + 2 < NSEG && s != 2) l2_prefetch(g_qx + ((size_t)(s + 2) * NH + head) * 4096, 8192);
                    if (s + 4 < NSEG) l2_prefetch(xg + (size_t)((s + 4) * 32 + head) * DM, 2048);
                    signal_count(&g_prog[s >> 2]);
                }
                __syncwarp();
            } else {
                const uint32_t zero = acc_clear((s + 2) & 3, 2 * head + (int)rank - 1, opaque(lo));
                mbar_wait(sb + RB_G + 16, s & 1);
                x_send(sb, s + 1, rank, vdelay);
                if (__any_sync(0xffffffffu, zero != 0u)) __trap();
            }
        }
    }
}

DEVI void load_weights(uint32_t sb, const CUtensorMap* tmW, const CUtensorMap* tmWo, int head, uint32_t rank) {
    const uint32_t bW = sb + RB_W, bSF = sb + RB_SF, bSE = sb + RB_SE;
    const int ntile = rank == 0 ? 6 : 5, tile0 = rank == 0 ? 0 : (rank == 1 ? 6 : 11);
    mbar_expect_tx(bW, R_NSS * 16384);
    mbar_expect_tx(sb + RB_WO, ntile * 16384);
    for (int pass = 0; pass < 2; pass++) {
        for (int pos = 0; pos < 16; pos++) {
            const int k = (int)((R_TORD_PACK >> (4 * pos)) & 15ull) * 64, rd = pos - pos / 3, slot = rd % 5;
            if (r_pos_ss(pos)) {
                if (pass) continue;
                const uint32_t dst = sb + RS_WSS + (pos / 3) * 16384;
                tma_load_2d(dst, tmW, head * DH, k, bW);
                tma_load_2d(dst + 8192, tmW, head * DH + 64, k, bW);
            } else if (pass == (rd >= 5)) {
                if (rd >= 5) mbar_wait(bSE + 8 * slot, ((rd / 5) - 1) & 1);
                mbar_expect_tx(bSF + 8 * slot, 16384);
                const uint32_t dst = sb + RS_WO + slot * 16384;
                tma_load_2d(dst, tmW, head * DH, k, bSF + 8 * slot);
                tma_load_2d(dst + 8192, tmW, head * DH + 64, k, bSF + 8 * slot);
            }
        }
    }
    if (rank == 0) tma_load_wo(sb + RS_WO5, tmWo, 5 * 64, head * 4, sb + RB_WO);
    for (int i = 1; i <= 5; i++) {
        const int slot = i % 5, last = slot + 10 < R_NRS ? slot + 10 : slot + 5;
        mbar_wait(bSE + 8 * slot, (last / 5) & 1);
        tma_load_wo(sb + RS_WO + slot * 16384, tmWo, (tile0 + slot) * 64, head * 4, sb + RB_WO);
    }
}
template <bool XP>
DEVI void big_prologue(uint32_t* w, uint32_t sb, int g, int warp, const bf16* __restrict__ mem0) {
    const int tid = tid_now(), lane = tid & 31;
    {
        const uint32_t* m = (const uint32_t*)(mem0 + (lane >> 2) * DM + (tid >> 5) * 16) + (lane & 3);
        uint32_t u[16];
#pragma unroll
        for (int j = 0; j < 8; j++) { u[2 * j] = m[j * 64]; u[2 * j + 1] = m[j * 64 + 4]; }
#pragma unroll
        for (int j = 0; j < 8; j++) sts64(sb + RS_MEM + ((tid >> 5) + j * 8) * 256 + b_frag_off(lane), u[2 * j], u[2 * j + 1]);
    }
    const uint32_t a0 = sb + RS_WO + g * (8192 + 4096) + a_frag_off(lane, warp), a1 = a0 + 8192 - g * 16384;
#pragma unroll
    for (int rd = 0; rd < R_NRS; rd++) {
        const int slot = rd % 5;
        mbar_wait(sb + RB_SF + 8 * slot, (rd / 5) & 1);
#pragma unroll
        for (int q = 0; q < 4; q++) {
            if (XP && rd == 0 && q == 3) {
                sts128(sb + RS_WX + g * 2048 + (tid & 127) * 16, lds128(sb + RS_WO + 8192 - g * 4096 + 2048 + (tid & 127) * 16));
                fence_proxy_async();
                nbar_sync(NB_WG + g, 128);
            } else ldsm4t(&w[rd * 16 + q * 4], ((q & 1) ? a1 : a0) + slot * 16384 + (q >> 1) * 2048);
        }
        mbar_arrive(sb + RB_SE + 8 * slot);
    }
    mbar_wait(sb + RB_W, 0);
}

#define REC_END() do { if (tid_now() == 0) TLOG(1024 + blockIdx.x, 1, gtime()); } while (0)
__global__ void __launch_bounds__(384, 1)
k_rec(const __grid_constant__ PMaps mp, const __grid_constant__ CUtensorMap tmWk, const __grid_constant__ CUtensorMap tmWv,
      const __grid_constant__ CUtensorMap tmWo, const __grid_constant__ CUtensorMap tmX, const bf16* __restrict__ mem0, const bf16* __restrict__ xg,
      int4 tq, int4 tk, int rec) {
    extern __shared__ __align__(1024) uint8_t smem_raw[];
    const uint32_t sb = smem_u32(smem_raw);
    if ((sb & 0x3FFFFu) != SB0) __trap();
    const int tid = threadIdx.x;
    const int wg = __shfl_sync(0xffffffffu, tid >> 7, 0), warp = __shfl_sync(0xffffffffu, (tid >> 5) & 3, 0);
    uint32_t rank; asm("mov.u32 %0, %%cluster_ctarank;" : "=r"(rank));
    const int head = blockIdx.x / 3;
    asm volatile("griddepcontrol.launch_dependents;");
    if (tid == 0 && rec) {
        mbar_init(sb + RB_G, 1);
        mbar_init(sb + RB_G + 8, 1);
        mbar_init(sb + RB_G + 16, 2);
        mbar_init(sb + RB_T, 1); mbar_init(sb + RB_WO, 1);
        mbar_init(sb + RB_K, 1); mbar_init(sb + RB_V, 1); mbar_init(sb + RB_KV, 1); mbar_init(sb + RB_QX, 1);
        mbar_init(sb + RB_O, rank == 0 ? 4 : 1); mbar_init(sb + RB_ATT, 1); mbar_init(sb + RB_W, 1);
        for (int i = 0; i < 5; i++) { mbar_init(sb + RB_SF + 8 * i, 1); mbar_init(sb + RB_SE + 8 * i, 256); }
        for (int i = 0; i < 2; i++) mbar_init(sb + RB_XF + 8 * i, X_SLOTS);
        fence_mbar_init();
        if (rank == 0) { mbar_expect_tx(sb + RB_KV, 8192); mbar_expect_tx(sb + RB_K, 2048); mbar_expect_tx(sb + RB_V, 2048 + 8192); }
    }
    __syncthreads();
    asm volatile("barrier.cluster.arrive.release.aligned;" ::: "memory");

    if (wg < 2) {
        reg_inc<REG_KB>();
        if (rank != 0) {
            uint32_t w[R_NRS * 16];
            if ((tid & 127) == 0) for (int j = 0; j < X_SLOTS; j++) x_load(sb, 0, j, wg, &tmX);
            __syncwarp();
            cluster_wait();
            big_prologue<true>(w, sb, wg, warp, mem0);
            big_main<true>(w, sb, wg, warp, rank, head, &tmX, xg, 0u);
            REC_END();
        } else if (rec) {
            uint32_t w[R_NRS * 16];
            cluster_wait();
            big_prologue<false>(w, sb, wg, warp, mem0);
            big_main<false>(w, sb, wg, warp, rank, head, &tmX, xg, *(volatile unsigned*)&g_epoch + 1);
            REC_END();
        } else cluster_wait();
        nbar_sync(0, 384);
        nbar_sync(0, 384);
        post_consumer(mp, sb, wg, warp);
    } else {
        reg_dec<504 - 2 * REG_KB>();
        if (rec) {
            if (tid == 256) {
                if (rank == 0) l2_prefetch(xg + (size_t)head * 8 * DM, 16384);
                load_weights(sb, rank == 0 ? &mp.wq : (rank == 1 ? &tmWk : &tmWv), &tmWo, head, rank);
            }
            if (warp == 3 && rank != 0) {
                const uint32_t lo = ((tid >> 3) & 3) * 1024 + (tid & 7) * 16;
                acc_clear(0, 2 * head + (int)rank - 1, lo); acc_clear(1, 2 * head + (int)rank - 1, lo);
                __threadfence();
                __syncwarp();
                if (tid == 256 + 96) atomicAdd(&g_zero, 1u);
            }
            __syncwarp();
        }
        cluster_wait();
        const unsigned E = __shfl_sync(0xffffffffu, *(volatile unsigned*)&g_epoch + 1, 0);
        if (rec) {
            if (warp == 1) wait_count_warp(&g_zero, E * 64u);
            if (warp == 3 && rank != 0) x_send(sb, 0, rank, 0);
            mbar_wait(sb + RB_WO, 0);
            wo_permute(sb + RS_WO + (tid & 127) * 32, 20);
            if (rank == 0) wo_permute(sb + RS_WO5 + (tid & 127) * 32, 4);
            fence_proxy_async();
            nbar_sync(NB_AUX, 128);
            if (rank == 0) aux_main<true>(sb, warp, rank, head, &tmX, xg, E, warp == 0 ? tq.x : (warp == 1 ? tq.y : tq.z), tq.w, 0);
            else           aux_main<false>(sb, warp, rank, head, &tmX, xg, E, warp == 0 ? tk.x : (warp == 1 ? tk.y : tk.z), tq.w, tk.w);
        }
        const int t = tid_now();
        int id = 0;
        if (t >= 288 && t < 288 + 12) asm volatile("prefetch.tensormap [%0];" :: "l"(&mp.wq + (t - 288)) : "memory");
        if (t == 256) id = post_claim(mp, E);
        __syncwarp();
        nbar_sync(0, 384);
        if (t == 256) { post_init(sb); fence_proxy_async(); }
        __syncwarp();
        nbar_sync(0, 384);
        if (t == 256) post_producer(mp, sb, E, id);
        else if (t == 288 || t == 320) post_helper(sb, warp - 1);
    }
    __syncthreads();
    asm volatile("griddepcontrol.wait;" ::: "memory");
}

typedef CUresult (*EncodeFn)(CUtensorMap*, CUtensorMapDataType, cuuint32_t, void*, const cuuint64_t*, const cuuint64_t*,
                             const cuuint32_t*, const cuuint32_t*, CUtensorMapInterleave, CUtensorMapSwizzle,
                             CUtensorMapL2promotion, CUtensorMapFloatOOBfill);

static CUtensorMap make_map(EncodeFn fn, const void* ptr, uint64_t inner, uint64_t outer, uint32_t box_inner, uint32_t box_outer) {
    CUtensorMap m;
    cuuint64_t dims[2] = {inner, outer};
    cuuint64_t strides[1] = {inner * 2};
    cuuint32_t box[2] = {box_inner, box_outer};
    cuuint32_t es[2] = {1, 1};
    fn(&m, CU_TENSOR_MAP_DATA_TYPE_BFLOAT16, 2, const_cast<void*>(ptr), dims, strides, box, es,
       CU_TENSOR_MAP_INTERLEAVE_NONE, CU_TENSOR_MAP_SWIZZLE_128B, CU_TENSOR_MAP_L2_PROMOTION_L2_256B, CU_TENSOR_MAP_FLOAT_OOB_FILL_NONE);
    return m;
}

static CUtensorMap make_wo_map(EncodeFn fn, const void* ptr, uint32_t ngrp) {
    CUtensorMap m;
    cuuint64_t dims[5] = {DM, 2, 4, 4, HD / 32};
    cuuint64_t strides[4] = {DM * 2, 8 * DM * 2, 2 * DM * 2, 32 * DM * 2};
    cuuint32_t box[5] = {64, 2, 4, 4, ngrp};
    cuuint32_t es[5] = {1, 1, 1, 1, 1};
    fn(&m, CU_TENSOR_MAP_DATA_TYPE_BFLOAT16, 5, const_cast<void*>(ptr), dims, strides, box, es,
       CU_TENSOR_MAP_INTERLEAVE_NONE, CU_TENSOR_MAP_SWIZZLE_128B, CU_TENSOR_MAP_L2_PROMOTION_L2_256B, CU_TENSOR_MAP_FLOAT_OOB_FILL_NONE);
    return m;
}

struct Maps {
    PMaps post;
    CUtensorMap wk16, wv16, wo128, x32;
};

extern "C" void kernel_launch(void* const* d_in, const int* in_sizes, int n_in, void* d_out, int out_size) {
    const bf16* A_x   = (const bf16*)d_in[0];
    const bf16* A_mem = (const bf16*)d_in[1];
    const bf16* A_Wq  = (const bf16*)d_in[2];
    const bf16* A_Wk  = (const bf16*)d_in[3];
    const bf16* A_Wv  = (const bf16*)d_in[4];
    const bf16* A_Wo  = (const bf16*)d_in[5];
    const bf16* B_x   = (const bf16*)d_in[7];
    const bf16* B_w   = (const bf16*)d_in[8];
    const bf16* B_wo  = (const bf16*)d_in[9];

    static EncodeFn fn = nullptr;
    static Maps mp;
    static const void* cached[10];
    const void* cur[10] = {A_x, A_mem, A_Wq, A_Wk, A_Wv, A_Wo, B_x, B_w, B_wo, d_out};
    bool same = fn != nullptr;
    for (int i = 0; i < 10 && same; i++) same = cached[i] == cur[i];
    if (!same) {
        if (!fn) {
            void* p = nullptr; cudaDriverEntryPointQueryResult qr;
            cudaGetDriverEntryPoint("cuTensorMapEncodeTiled", &p, cudaEnableDefault, &qr);
            fn = (EncodeFn)p;
            cudaFuncSetAttribute(k_rec, cudaFuncAttributeMaxDynamicSharedMemorySize, R_SMEM);
        }
        void *p_ox, *p_bqkv, *p_bo, *p_qx;
        cudaGetSymbolAddress(&p_qx, g_qx);
        cudaGetSymbolAddress(&p_ox, g_ox); cudaGetSymbolAddress(&p_bqkv, g_bqkv); cudaGetSymbolAddress(&p_bo, g_bo);
        mp.post.wq   = make_map(fn, A_Wq, HD, DM, 64, 64);
        mp.post.wo   = make_wo_map(fn, A_Wo, 2);
        mp.post.bw   = make_map(fn, B_w, 3 * DM, DM, 64, 64);
        mp.post.bwo  = make_map(fn, B_wo, DM, DM, 64, 64);
        mp.post.x    = make_map(fn, A_x, DM, S_TOK, 64, 128);
        mp.post.bx   = make_map(fn, B_x, DM, S_TOK, 64, 128);
        mp.post.bo   = make_map(fn, p_bo, DM, S_TOK, 64, 128);
        mp.post.ox   = make_map(fn, p_ox, HD, S_TOK, 64, 128);
        mp.post.cb   = make_map(fn, p_bqkv, 3 * DM, S_TOK, 64, 64);
        mp.post.cout = make_map(fn, d_out, 2 * DM, S_TOK, 64, 64);
        {
            cuuint64_t dims[4] = {256, 4, NH * 4, NSEG};
            cuuint64_t strides[3] = {512, 2048, NH * 8192};
            cuuint32_t box[4] = {256, 2, 4, 2};
            cuuint32_t es[4] = {1, 1, 1, 1};
            fn(&mp.post.cq, CU_TENSOR_MAP_DATA_TYPE_BFLOAT16, 4, p_qx, dims, strides, box, es,
               CU_TENSOR_MAP_INTERLEAVE_NONE, CU_TENSOR_MAP_SWIZZLE_NONE, CU_TENSOR_MAP_L2_PROMOTION_NONE, CU_TENSOR_MAP_FLOAT_OOB_FILL_NONE);
        }
        {
            int runs[48] = {K_QH, 0, 2, K_Q, 1, 7, K_B1, 0, 8, K_A4, 0, 4, K_B2, 0, 32, K_A4, 4, 2, K_B3, 0, 4, K_A3, 12, 2, K_B3, 4, 4, K_SK, 14, 2, -1};
            const int per[8] = {32, 24, 8, 8, 32, 8, 8 * P_SPLIT, 1};
            int n = 0, id = 0;
            for (; runs[3 * n] >= 0; n++) {
                mp.post.list.run[n] = make_int4(runs[3 * n], runs[3 * n + 1], id, id + runs[3 * n + 2] * per[runs[3 * n]]);
                id = mp.post.list.run[n].w;
            }
            mp.post.list.n = n;
            int dev = 0, nsm = 132;
            cudaGetDevice(&dev);
            cudaDeviceGetAttribute(&nsm, cudaDevAttrMultiProcessorCount, dev);
            mp.post.list.nworker = nsm > 96 ? nsm : 97;
        }
        {
            cuuint64_t dims[4] = {DM, 3, 2, S_TOK / 2};
            cuuint64_t strides[3] = {DM * 2, 3 * DM * 2, 3 * DM * 4};
            cuuint32_t box[4] = {64, 3, 1, 40};
            cuuint32_t es[4] = {1, 1, 1, 1};
            fn(&mp.post.b40, CU_TENSOR_MAP_DATA_TYPE_BFLOAT16, 4, p_bqkv, dims, strides, box, es,
               CU_TENSOR_MAP_INTERLEAVE_NONE, CU_TENSOR_MAP_SWIZZLE_128B, CU_TENSOR_MAP_L2_PROMOTION_L2_256B, CU_TENSOR_MAP_FLOAT_OOB_FILL_NONE);
        }
        mp.wk16 = make_map(fn, A_Wk, HD, DM, 64, 64);
        mp.wv16 = make_map(fn, A_Wv, HD, DM, 64, 64);
        mp.wo128 = make_wo_map(fn, A_Wo, 4);
        {
            cuuint64_t dims[3] = {64, S_TOK, DM / 64};
            cuuint64_t strides[2] = {DM * 2, 128};
            cuuint32_t box[3] = {32, 32, 2};
            cuuint32_t es[3] = {1, 1, 1};
            fn(&mp.x32, CU_TENSOR_MAP_DATA_TYPE_BFLOAT16, 3, const_cast<bf16*>(A_x), dims, strides, box, es,
               CU_TENSOR_MAP_INTERLEAVE_NONE, CU_TENSOR_MAP_SWIZZLE_64B, CU_TENSOR_MAP_L2_PROMOTION_L2_128B, CU_TENSOR_MAP_FLOAT_OOB_FILL_NONE);
        }
        for (int i = 0; i < 10; i++) cached[i] = cur[i];
    }

    cudaStream_t st = cudaStreamPerThread;
    int4 tq = make_int4(50, 150, 750, 80), tk = make_int4(100, 250, 750, 200);
    cudaLaunchConfig_t cfg = {};
    cfg.gridDim = dim3(96); cfg.blockDim = dim3(384); cfg.dynamicSmemBytes = R_SMEM; cfg.stream = st;
    cudaLaunchAttribute at[1];
    at[0].id = cudaLaunchAttributeClusterDimension;
    at[0].val.clusterDim.x = 3; at[0].val.clusterDim.y = 1; at[0].val.clusterDim.z = 1;
    cfg.attrs = at; cfg.numAttrs = 1;
    cudaLaunchKernelEx(&cfg, k_rec, mp.post, mp.wk16, mp.wv16, mp.wo128, mp.x32, A_mem, A_x, tq, tk, 1);
    cfg.gridDim = dim3(mp.post.list.nworker - 96);
    at[0].id = cudaLaunchAttributeProgrammaticStreamSerialization;
    at[0].val.programmaticStreamSerializationAllowed = 1;
    cudaLaunchKernelEx(&cfg, k_rec, mp.post, mp.wk16, mp.wv16, mp.wo128, mp.x32, A_mem, A_x, tq, tk, 0);
}
```

```cpp
#include <cuda_runtime.h>
#include <cuda_bf16.h>
#include <cuda.h>
#include <stdint.h>

typedef __nv_bfloat16 bf16;

constexpr int S_TOK = 2048;
constexpr int DM    = 1024;
constexpr int NH    = 32;
constexpr int DH    = 128;
constexpr int NSEG  = 64;
constexpr int HD    = NH * DH;

__device__ __align__(1024) bf16 g_qx[NSEG * NH * 4 * DH * 8];
__device__ __align__(1024) bf16 g_ox[S_TOK * HD];
__device__ __align__(1024) bf16 g_bqkv[S_TOK * 3 * DM];
__device__ __align__(1024) bf16 g_bo[S_TOK * DM];
__device__ __align__(1024) uint8_t g_acc[192 * 1024];

#define EV(cond, s, k) do {} while (0)
#define EVCAL(s) do {} while (0)

constexpr int P_NSK = 4;
__device__ unsigned g_epoch, g_qctr, g_done, g_zero;
enum { C_B1 = 0, C_B2 = 8, C_Q = 16, C_QH = 24, C_NONE = 31 };
__device__ unsigned g_cnt[32], g_prog[16], g_cnt_sk[P_NSK * 16];
#define P_SPLIT 4
__device__ __align__(1024) uint4 g_skp[P_NSK * 8 * P_SPLIT * 2 * 8 * 128];
#define TLOG(i, k, v) do {} while (0)

#define DEVI __device__ __forceinline__

DEVI uint32_t opaque(uint32_t v) { uint32_t r; asm volatile("mov.u32 %0, %1;" : "=r"(r) : "r"(v)); return r; }
DEVI uint32_t smem_u32(const void* p) { return (uint32_t)__cvta_generic_to_shared(p); }

#define TRAP(code) __trap()
constexpr int SPIN_LIMIT = 1 << 22;
#define MBAR_HINT_NS 20000u
constexpr int SPIN_LIMIT_MBAR = 1 << 17;

DEVI void mbar_init(uint32_t bar, uint32_t cnt) { asm volatile("mbarrier.init.shared::cta.b64 [%0], %1;" :: "r"(bar), "r"(cnt)); }
DEVI void mbar_expect_tx(uint32_t bar, uint32_t bytes) {
    asm volatile("mbarrier.arrive.expect_tx.shared::cta.b64 _, [%0], %1;" :: "r"(bar), "r"(bytes) : "memory");
}
DEVI void mbar_arrive(uint32_t bar) { asm volatile("mbarrier.arrive.shared::cta.b64 _, [%0];" :: "r"(bar) : "memory"); }
DEVI bool mbar_try(uint32_t bar, uint32_t parity) {
    uint32_t ok;
    asm volatile("{.reg .pred p; mbarrier.try_wait.parity.shared::cta.b64 p, [%1], %2; selp.u32 %0, 1, 0, p;}"
                 : "=r"(ok) : "r"(bar), "r"(parity) : "memory");
    return ok;
}
DEVI bool mbar_try_cluster(uint32_t bar, uint32_t parity) {
    uint32_t ok;
    asm volatile("{.reg .pred p; mbarrier.try_wait.parity.acquire.cluster.shared::cta.b64 p, [%1], %2; selp.u32 %0, 1, 0, p;}"
                 : "=r"(ok) : "r"(bar), "r"(parity) : "memory");
    return ok;
}
DEVI bool mbar_try_hint(uint32_t bar, uint32_t parity) {
    uint32_t ok;
    asm volatile("{.reg .pred p; mbarrier.try_wait.parity.shared::cta.b64 p, [%1], %2, %3; selp.u32 %0, 1, 0, p;}"
                 : "=r"(ok) : "r"(bar), "r"(parity), "r"(MBAR_HINT_NS) : "memory");
    return ok;
}
DEVI void mbar_wait(uint32_t bar, uint32_t parity) {
    int n = 0;
    while (!mbar_try(bar, parity)) { if (++n > SPIN_LIMIT) TRAP(bar | (parity << 31)); }
}
DEVI void mbar_wait_sleepy(uint32_t bar, uint32_t parity) {
    int n = 0;
    while (!mbar_try_hint(bar, parity)) { if (++n > SPIN_LIMIT_MBAR) __trap(); }
}
DEVI void mbar_wait_cluster(uint32_t bar, uint32_t parity) {
    int n = 0;
    while (!mbar_try_cluster(bar, parity)) { if (++n > SPIN_LIMIT) __trap(); }
}
DEVI void mbar_spin(uint32_t bar, uint32_t parity) {
    uint32_t ok; int n = 0;
    do {
        asm volatile("{.reg .pred p; mbarrier.test_wait.parity.shared::cta.b64 p, [%1], %2; selp.u32 %0, 1, 0, p;}"
                     : "=r"(ok) : "r"(bar), "r"(parity) : "memory");
        if (++n > SPIN_LIMIT) __trap();
    } while (!ok);
}
DEVI void fence_mbar_init() { asm volatile("fence.mbarrier_init.release.cluster;" ::: "memory"); }
DEVI void fence_proxy_async() { asm volatile("fence.proxy.async.shared::cta;" ::: "memory"); }
DEVI void cluster_sync() {
    asm volatile("barrier.cluster.arrive.release.aligned;\n barrier.cluster.wait.acquire.aligned;" ::: "memory");
}
DEVI bool elect_one() {
    uint32_t e; asm volatile("{.reg .pred p; elect.sync _|p, 0xffffffff; selp.u32 %0, 1, 0, p;}" : "=r"(e)); return e;
}
DEVI void fence_proxy_global() { asm volatile("fence.proxy.async.global;" ::: "memory"); }
DEVI void cluster_wait() { asm volatile("barrier.cluster.wait.acquire.aligned;" ::: "memory"); }
DEVI void nbar_sync(int id, int n) { asm volatile("bar.sync %0, %1;" :: "r"(id), "r"(n) : "memory"); }
DEVI void nbar_arrive(int id, int n) { asm volatile("bar.arrive %0, %1;" :: "r"(id), "r"(n) : "memory"); }

DEVI void tma_load_2d(uint32_t dst, const CUtensorMap* map, int x, int y, uint32_t bar) {
    asm volatile("cp.async.bulk.tensor.2d.shared::cluster.global.mbarrier::complete_tx::bytes [%0], [%1, {%3, %4}], [%2];"
                 :: "r"(dst), "l"(map), "r"(bar), "r"(x), "r"(y) : "memory");
}
DEVI void tma_load_3d(uint32_t dst, const CUtensorMap* map, int x, int y, int z, uint32_t bar) {
    asm volatile("cp.async.bulk.tensor.3d.shared::cluster.global.mbarrier::complete_tx::bytes [%0], [%1, {%3, %4, %5}], [%2];"
                 :: "r"(dst), "l"(map), "r"(bar), "r"(x), "r"(y), "r"(z) : "memory");
}
DEVI void tma_load_wo(uint32_t dst, const CUtensorMap* map, int col, int k32, uint32_t bar) {
    asm volatile("cp.async.bulk.tensor.5d.shared::cluster.global.mbarrier::complete_tx::bytes [%0], [%1, {%3, %5, %5, %5, %4}], [%2];"
                 :: "r"(dst), "l"(map), "r"(bar), "r"(col), "r"(k32), "r"(0) : "memory");
}
DEVI void tma_store_2d(const CUtensorMap* map, uint32_t src, int x, int y) {
    asm volatile("cp.async.bulk.tensor.2d.global.shared::cta.bulk_group [%0, {%2, %3}], [%1];"
                 :: "l"(map), "r"(src), "r"(x), "r"(y) : "memory");
}
DEVI void bulk_load(uint32_t dst, const void* src, uint32_t bytes, uint32_t bar) {
    asm volatile("cp.async.bulk.shared::cluster.global.mbarrier::complete_tx::bytes [%0], [%1], %2, [%3];"
                 :: "r"(dst), "l"(src), "r"(bytes), "r"(bar) : "memory");
}
DEVI void tma_load_2d_mc(uint32_t dst, const CUtensorMap* map, int x, int y, uint32_t bar, uint16_t mask) {
    asm volatile("cp.async.bulk.tensor.2d.shared::cluster.global.mbarrier::complete_tx::bytes.multicast::cluster [%0], [%1, {%3, %4}], [%2], %5;"
                 :: "r"(dst), "l"(map), "r"(bar), "r"(x), "r"(y), "h"(mask) : "memory");
}
DEVI void bulk_copy_s2c(uint32_t dst_cluster, uint32_t src, uint32_t bytes, uint32_t bar_cluster) {
    asm volatile("cp.async.bulk.shared::cluster.shared::cta.mbarrier::complete_tx::bytes [%0], [%1], %2, [%3];"
                 :: "r"(dst_cluster), "r"(src), "r"(bytes), "r"(bar_cluster) : "memory");
}
DEVI void bulk_store(void* dst, uint32_t src, uint32_t bytes) {
    asm volatile("cp.async.bulk.global.shared::cta.bulk_group [%0], [%1], %2;" :: "l"(dst), "r"(src), "r"(bytes) : "memory");
}
DEVI void bulk_wait_read() { asm volatile("cp.async.bulk.wait_group.read 0;" ::: "memory"); }
DEVI void mbar_arrive_remote(uint32_t bar_cluster) {
    asm volatile("mbarrier.arrive.shared::cluster.b64 _, [%0];" :: "r"(bar_cluster) : "memory");
}
DEVI void mbar_expect_tx_remote(uint32_t bar_cluster, uint32_t bytes) {
    asm volatile("mbarrier.arrive.expect_tx.shared::cluster.b64 _, [%0], %1;" :: "r"(bar_cluster), "r"(bytes) : "memory");
}
DEVI void l2_prefetch(const void* p, uint32_t bytes) {
    asm volatile("cp.async.bulk.prefetch.L2.global [%0], %1;" :: "l"(p), "r"(bytes) : "memory");
}
DEVI void bulk_commit() { asm volatile("cp.async.bulk.commit_group;" ::: "memory"); }
DEVI void bulk_wait_all() { asm volatile("cp.async.bulk.wait_group 0;" ::: "memory"); }

DEVI void wg_fence() { asm volatile("wgmma.fence.sync.aligned;" ::: "memory"); }
DEVI void wg_commit() { asm volatile("wgmma.commit_group.sync.aligned;" ::: "memory"); }
template <int N> DEVI void wg_wait() { asm volatile("wgmma.wait_group.sync.aligned %0;" :: "n"(N) : "memory"); }

template <int R> DEVI void reg_dec() { asm volatile("setmaxnreg.dec.sync.aligned.u32 %0;" :: "n"(R)); }
template <int R> DEVI void reg_inc() { asm volatile("setmaxnreg.inc.sync.aligned.u32 %0;" :: "n"(R)); }

DEVI uint64_t mk_desc(uint32_t addr, uint32_t lbo, uint32_t sbo, uint32_t sw) {
    return (uint64_t)((addr & 0x3FFFF) >> 4) | ((uint64_t)(lbo >> 4) << 16) | ((uint64_t)(sbo >> 4) << 32) | ((uint64_t)sw << 62);
}

DEVI uint32_t desc_lo(uint32_t addr, uint32_t lbo) { return ((addr & 0x3FFFF) >> 4) | ((lbo >> 4) << 16); }
constexpr uint32_t DHI_SW128 = (1024u >> 4) | (1u << 30);
constexpr uint32_t DHI_SW64  = (512u >> 4) | (2u << 30);
constexpr uint32_t DHI_NONE  = (128u >> 4);

template <int TB, int SCALE_D>
DEVI void wgmma_n8_ss(float* d, uint32_t alo, uint32_t blo) {
    asm volatile("{.reg .b64 da, db; mov.b64 da, {%4, %6}; mov.b64 db, {%5, %7};\n"
                 "wgmma.mma_async.sync.aligned.m64n8k16.f32.bf16.bf16 {%0,%1,%2,%3}, da, db, %8, 1, 1, 1, %9;}"
                 : "+f"(d[0]), "+f"(d[1]), "+f"(d[2]), "+f"(d[3])
                 : "r"(alo), "r"(blo), "n"(DHI_SW128), "n"(DHI_NONE), "n"(SCALE_D), "n"(TB));
}

template <int TB>
DEVI void wgmma_n8_ss_first(float* d, uint32_t alo, uint32_t blo) {
    asm volatile("{.reg .b64 da, db; mov.b64 da, {%4, %6}; mov.b64 db, {%5, %7};\n"
                 "wgmma.mma_async.sync.aligned.m64n8k16.f32.bf16.bf16 {%0,%1,%2,%3}, da, db, 0, 1, 1, 1, %8;}"
                 : "=f"(d[0]), "=f"(d[1]), "=f"(d[2]), "=f"(d[3])
                 : "r"(alo), "r"(blo), "n"(DHI_SW128), "n"(DHI_NONE), "n"(TB));
}
DEVI void wgmma_n32_rs_first(float* d, const uint32_t* a, uint32_t blo) {
    asm volatile("{.reg .b64 db; mov.b64 db, {%20, %21};\n"
                 "wgmma.mma_async.sync.aligned.m64n32k16.f32.bf16.bf16 {%0,%1,%2,%3,%4,%5,%6,%7,%8,%9,%10,%11,%12,%13,%14,%15}, "
                 "{%16,%17,%18,%19}, db, 0, 1, 1, 0;}"
                 : "=f"(d[0]), "=f"(d[1]), "=f"(d[2]), "=f"(d[3]), "=f"(d[4]), "=f"(d[5]), "=f"(d[6]), "=f"(d[7]),
                   "=f"(d[8]), "=f"(d[9]), "=f"(d[10]), "=f"(d[11]), "=f"(d[12]), "=f"(d[13]), "=f"(d[14]), "=f"(d[15])
                 : "r"(a[0]), "r"(a[1]), "r"(a[2]), "r"(a[3]), "r"(blo), "n"(DHI_SW64));
}
template <int N> DEVI void reg_fence(float* d) {
#pragma unroll
    for (int i = 0; i < N; i++) asm volatile("" : "+f"(d[i]) :: "memory");
}
DEVI void wgmma_n32_rs(float* d, const uint32_t* a, uint32_t blo) {
    asm volatile("{.reg .b64 db; mov.b64 db, {%20, %21};\n"
                 "wgmma.mma_async.sync.aligned.m64n32k16.f32.bf16.bf16 {%0,%1,%2,%3,%4,%5,%6,%7,%8,%9,%10,%11,%12,%13,%14,%15}, "
                 "{%16,%17,%18,%19}, db, 1, 1, 1, 0;}"
                 : "+f"(d[0]), "+f"(d[1]), "+f"(d[2]), "+f"(d[3]), "+f"(d[4]), "+f"(d[5]), "+f"(d[6]), "+f"(d[7]),
                   "+f"(d[8]), "+f"(d[9]), "+f"(d[10]), "+f"(d[11]), "+f"(d[12]), "+f"(d[13]), "+f"(d[14]), "+f"(d[15])
                 : "r"(a[0]), "r"(a[1]), "r"(a[2]), "r"(a[3]), "r"(blo), "n"(DHI_SW64));
}
DEVI void wgmma_n32_ss(float* d, uint32_t alo, uint32_t blo) {
    asm volatile("{.reg .b64 da, db; mov.b64 da, {%16, %18}; mov.b64 db, {%17, %19};\n"
                 "wgmma.mma_async.sync.aligned.m64n32k16.f32.bf16.bf16 {%0,%1,%2,%3,%4,%5,%6,%7,%8,%9,%10,%11,%12,%13,%14,%15}, "
                 "da, db, 1, 1, 1, 1, 0;}"
                 : "+f"(d[0]), "+f"(d[1]), "+f"(d[2]), "+f"(d[3]), "+f"(d[4]), "+f"(d[5]), "+f"(d[6]), "+f"(d[7]),
                   "+f"(d[8]), "+f"(d[9]), "+f"(d[10]), "+f"(d[11]), "+f"(d[12]), "+f"(d[13]), "+f"(d[14]), "+f"(d[15])
                 : "r"(alo), "r"(blo), "n"(DHI_SW128), "n"(DHI_SW64));
}

template <bool FIRST>
DEVI void wgmma_n256_ss(float* d, uint64_t a, uint64_t b) {
    if (FIRST)
        asm volatile("wgmma.mma_async.sync.aligned.m64n256k16.f32.bf16.bf16 {%0,%1,%2,%3,%4,%5,%6,%7,%8,%9,%10,%11,%12,%13,%14,%15,%16,%17,%18,%19,%20,%21,%22,%23,%24,%25,%26,%27,%28,%29,%30,%31,%32,%33,%34,%35,%36,%37,%38,%39,%40,%41,%42,%43,%44,%45,%46,%47,%48,%49,%50,%51,%52,%53,%54,%55,%56,%57,%58,%59,%60,%61,%62,%63,%64,%65,%66,%67,%68,%69,%70,%71,%72,%73,%74,%75,%76,%77,%78,%79,%80,%81,%82,%83,%84,%85,%86,%87,%88,%89,%90,%91,%92,%93,%94,%95,%96,%97,%98,%99,%100,%101,%102,%103,%104,%105,%106,%107,%108,%109,%110,%111,%112,%113,%114,%115,%116,%117,%118,%119,%120,%121,%122,%123,%124,%125,%126,%127}, %128, %129, 0, 1, 1, 1, 0;"
            : "=f"(d[0]), "=f"(d[1]), "=f"(d[2]), "=f"(d[3]), "=f"(d[4]), "=f"(d[5]), "=f"(d[6]), "=f"(d[7]), "=f"(d[8]), "=f"(d[9]), "=f"(d[10]), "=f"(d[11]), "=f"(d[12]), "=f"(d[13]), "=f"(d[14]), "=f"(d[15]), "=f"(d[16]), "=f"(d[17]), "=f"(d[18]), "=f"(d[19]), "=f"(d[20]), "=f"(d[21]), "=f"(d[22]), "=f"(d[23]), "=f"(d[24]), "=f"(d[25]), "=f"(d[26]), "=f"(d[27]), "=f"(d[28]), "=f"(d[29]), "=f"(d[30]), "=f"(d[31]), "=f"(d[32]), "=f"(d[33]), "=f"(d[34]), "=f"(d[35]), "=f"(d[36]), "=f"(d[37]), "=f"(d[38]), "=f"(d[39]), "=f"(d[40]), "=f"(d[41]), "=f"(d[42]), "=f"(d[43]), "=f"(d[44]), "=f"(d[45]), "=f"(d[46]), "=f"(d[47]), "=f"(d[48]), "=f"(d[49]), "=f"(d[50]), "=f"(d[51]), "=f"(d[52]), "=f"(d[53]), "=f"(d[54]), "=f"(d[55]), "=f"(d[56]), "=f"(d[57]), "=f"(d[58]), "=f"(d[59]), "=f"(d[60]), "=f"(d[61]), "=f"(d[62]), "=f"(d[63]), "=f"(d[64]), "=f"(d[65]), "=f"(d[66]), "=f"(d[67]), "=f"(d[68]), "=f"(d[69]), "=f"(d[70]), "=f"(d[71]), "=f"(d[72]), "=f"(d[73]), "=f"(d[74]), "=f"(d[75]), "=f"(d[76]), "=f"(d[77]), "=f"(d[78]), "=f"(d[79]), "=f"(d[80]), "=f"(d[81]), "=f"(d[82]), "=f"(d[83]), "=f"(d[84]), "=f"(d[85]), "=f"(d[86]), "=f"(d[87]), "=f"(d[88]), "=f"(d[89]), "=f"(d[90]), "=f"(d[91]), "=f"(d[92]), "=f"(d[93]), "=f"(d[94]), "=f"(d[95]), "=f"(d[96]), "=f"(d[97]), "=f"(d[98]), "=f"(d[99]), "=f"(d[100]), "=f"(d[101]), "=f"(d[102]), "=f"(d[103]), "=f"(d[104]), "=f"(d[105]), "=f"(d[106]), "=f"(d[107]), "=f"(d[108]), "=f"(d[109]), "=f"(d[110]), "=f"(d[111]), "=f"(d[112]), "=f"(d[113]), "=f"(d[114]), "=f"(d[115]), "=f"(d[116]), "=f"(d[117]), "=f"(d[118]), "=f"(d[119]), "=f"(d[120]), "=f"(d[121]), "=f"(d[122]), "=f"(d[123]), "=f"(d[124]), "=f"(d[125]), "=f"(d[126]), "=f"(d[127]) : "l"(a), "l"(b));
    else
        asm volatile("wgmma.mma_async.sync.aligned.m64n256k16.f32.bf16.bf16 {%0,%1,%2,%3,%4,%5,%6,%7,%8,%9,%10,%11,%12,%13,%14,%15,%16,%17,%18,%19,%20,%21,%22,%23,%24,%25,%26,%27,%28,%29,%30,%31,%32,%33,%34,%35,%36,%37,%38,%39,%40,%41,%42,%43,%44,%45,%46,%47,%48,%49,%50,%51,%52,%53,%54,%55,%56,%57,%58,%59,%60,%61,%62,%63,%64,%65,%66,%67,%68,%69,%70,%71,%72,%73,%74,%75,%76,%77,%78,%79,%80,%81,%82,%83,%84,%85,%86,%87,%88,%89,%90,%91,%92,%93,%94,%95,%96,%97,%98,%99,%100,%101,%102,%103,%104,%105,%106,%107,%108,%109,%110,%111,%112,%113,%114,%115,%116,%117,%118,%119,%120,%121,%122,%123,%124,%125,%126,%127}, %128, %129, 1, 1, 1, 1, 0;"
            : "+f"(d[0]), "+f"(d[1]), "+f"(d[2]), "+f"(d[3]), "+f"(d[4]), "+f"(d[5]), "+f"(d[6]), "+f"(d[7]), "+f"(d[8]), "+f"(d[9]), "+f"(d[10]), "+f"(d[11]), "+f"(d[12]), "+f"(d[13]), "+f"(d[14]), "+f"(d[15]), "+f"(d[16]), "+f"(d[17]), "+f"(d[18]), "+f"(d[19]), "+f"(d[20]), "+f"(d[21]), "+f"(d[22]), "+f"(d[23]), "+f"(d[24]), "+f"(d[25]), "+f"(d[26]), "+f"(d[27]), "+f"(d[28]), "+f"(d[29]), "+f"(d[30]), "+f"(d[31]), "+f"(d[32]), "+f"(d[33]), "+f"(d[34]), "+f"(d[35]), "+f"(d[36]), "+f"(d[37]), "+f"(d[38]), "+f"(d[39]), "+f"(d[40]), "+f"(d[41]), "+f"(d[42]), "+f"(d[43]), "+f"(d[44]), "+f"(d[45]), "+f"(d[46]), "+f"(d[47]), "+f"(d[48]), "+f"(d[49]), "+f"(d[50]), "+f"(d[51]), "+f"(d[52]), "+f"(d[53]), "+f"(d[54]), "+f"(d[55]), "+f"(d[56]), "+f"(d[57]), "+f"(d[58]), "+f"(d[59]), "+f"(d[60]), "+f"(d[61]), "+f"(d[62]), "+f"(d[63]), "+f"(d[64]), "+f"(d[65]), "+f"(d[66]), "+f"(d[67]), "+f"(d[68]), "+f"(d[69]), "+f"(d[70]), "+f"(d[71]), "+f"(d[72]), "+f"(d[73]), "+f"(d[74]), "+f"(d[75]), "+f"(d[76]), "+f"(d[77]), "+f"(d[78]), "+f"(d[79]), "+f"(d[80]), "+f"(d[81]), "+f"(d[82]), "+f"(d[83]), "+f"(d[84]), "+f"(d[85]), "+f"(d[86]), "+f"(d[87]), "+f"(d[88]), "+f"(d[89]), "+f"(d[90]), "+f"(d[91]), "+f"(d[92]), "+f"(d[93]), "+f"(d[94]), "+f"(d[95]), "+f"(d[96]), "+f"(d[97]), "+f"(d[98]), "+f"(d[99]), "+f"(d[100]), "+f"(d[101]), "+f"(d[102]), "+f"(d[103]), "+f"(d[104]), "+f"(d[105]), "+f"(d[106]), "+f"(d[107]), "+f"(d[108]), "+f"(d[109]), "+f"(d[110]), "+f"(d[111]), "+f"(d[112]), "+f"(d[113]), "+f"(d[114]), "+f"(d[115]), "+f"(d[116]), "+f"(d[117]), "+f"(d[118]), "+f"(d[119]), "+f"(d[120]), "+f"(d[121]), "+f"(d[122]), "+f"(d[123]), "+f"(d[124]), "+f"(d[125]), "+f"(d[126]), "+f"(d[127]) : "l"(a), "l"(b));
}
template <bool FIRST>
DEVI void wgmma_n128_ss(float* d, uint64_t a, uint64_t b) {
    if (FIRST)
        asm volatile("wgmma.mma_async.sync.aligned.m64n128k16.f32.bf16.bf16 {%0,%1,%2,%3,%4,%5,%6,%7,%8,%9,%10,%11,%12,%13,%14,%15,%16,%17,%18,%19,%20,%21,%22,%23,%24,%25,%26,%27,%28,%29,%30,%31,%32,%33,%34,%35,%36,%37,%38,%39,%40,%41,%42,%43,%44,%45,%46,%47,%48,%49,%50,%51,%52,%53,%54,%55,%56,%57,%58,%59,%60,%61,%62,%63}, %64, %65, 0, 1, 1, 1, 0;"
            : "=f"(d[0]), "=f"(d[1]), "=f"(d[2]), "=f"(d[3]), "=f"(d[4]), "=f"(d[5]), "=f"(d[6]), "=f"(d[7]), "=f"(d[8]), "=f"(d[9]), "=f"(d[10]), "=f"(d[11]), "=f"(d[12]), "=f"(d[13]), "=f"(d[14]), "=f"(d[15]), "=f"(d[16]), "=f"(d[17]), "=f"(d[18]), "=f"(d[19]), "=f"(d[20]), "=f"(d[21]), "=f"(d[22]), "=f"(d[23]), "=f"(d[24]), "=f"(d[25]), "=f"(d[26]), "=f"(d[27]), "=f"(d[28]), "=f"(d[29]), "=f"(d[30]), "=f"(d[31]), "=f"(d[32]), "=f"(d[33]), "=f"(d[34]), "=f"(d[35]), "=f"(d[36]), "=f"(d[37]), "=f"(d[38]), "=f"(d[39]), "=f"(d[40]), "=f"(d[41]), "=f"(d[42]), "=f"(d[43]), "=f"(d[44]), "=f"(d[45]), "=f"(d[46]), "=f"(d[47]), "=f"(d[48]), "=f"(d[49]), "=f"(d[50]), "=f"(d[51]), "=f"(d[52]), "=f"(d[53]), "=f"(d[54]), "=f"(d[55]), "=f"(d[56]), "=f"(d[57]), "=f"(d[58]), "=f"(d[59]), "=f"(d[60]), "=f"(d[61]), "=f"(d[62]), "=f"(d[63]) : "l"(a), "l"(b));
    else
        asm volatile("wgmma.mma_async.sync.aligned.m64n128k16.f32.bf16.bf16 {%0,%1,%2,%3,%4,%5,%6,%7,%8,%9,%10,%11,%12,%13,%14,%15,%16,%17,%18,%19,%20,%21,%22,%23,%24,%25,%26,%27,%28,%29,%30,%31,%32,%33,%34,%35,%36,%37,%38,%39,%40,%41,%42,%43,%44,%45,%46,%47,%48,%49,%50,%51,%52,%53,%54,%55,%56,%57,%58,%59,%60,%61,%62,%63}, %64, %65, 1, 1, 1, 1, 0;"
            : "+f"(d[0]), "+f"(d[1]), "+f"(d[2]), "+f"(d[3]), "+f"(d[4]), "+f"(d[5]), "+f"(d[6]), "+f"(d[7]), "+f"(d[8]), "+f"(d[9]), "+f"(d[10]), "+f"(d[11]), "+f"(d[12]), "+f"(d[13]), "+f"(d[14]), "+f"(d[15]), "+f"(d[16]), "+f"(d[17]), "+f"(d[18]), "+f"(d[19]), "+f"(d[20]), "+f"(d[21]), "+f"(d[22]), "+f"(d[23]), "+f"(d[24]), "+f"(d[25]), "+f"(d[26]), "+f"(d[27]), "+f"(d[28]), "+f"(d[29]), "+f"(d[30]), "+f"(d[31]), "+f"(d[32]), "+f"(d[33]), "+f"(d[34]), "+f"(d[35]), "+f"(d[36]), "+f"(d[37]), "+f"(d[38]), "+f"(d[39]), "+f"(d[40]), "+f"(d[41]), "+f"(d[42]), "+f"(d[43]), "+f"(d[44]), "+f"(d[45]), "+f"(d[46]), "+f"(d[47]), "+f"(d[48]), "+f"(d[49]), "+f"(d[50]), "+f"(d[51]), "+f"(d[52]), "+f"(d[53]), "+f"(d[54]), "+f"(d[55]), "+f"(d[56]), "+f"(d[57]), "+f"(d[58]), "+f"(d[59]), "+f"(d[60]), "+f"(d[61]), "+f"(d[62]), "+f"(d[63]) : "l"(a), "l"(b));
}

DEVI void mma16816(float* d, const uint32_t* a, uint32_t b0, uint32_t b1) {
    asm volatile("mma.sync.aligned.m16n8k16.row.col.f32.bf16.bf16.f32 {%0,%1,%2,%3}, {%4,%5,%6,%7}, {%8,%9}, {%0,%1,%2,%3};"
                 : "+f"(d[0]), "+f"(d[1]), "+f"(d[2]), "+f"(d[3])
                 : "r"(a[0]), "r"(a[1]), "r"(a[2]), "r"(a[3]), "r"(b0), "r"(b1));
}
DEVI void mma1688(float* d, uint32_t a0, uint32_t a1, uint32_t b0) {
    asm volatile("mma.sync.aligned.m16n8k8.row.col.f32.bf16.bf16.f32 {%0,%1,%2,%3}, {%4,%5}, {%6}, {%0,%1,%2,%3};"
                 : "+f"(d[0]), "+f"(d[1]), "+f"(d[2]), "+f"(d[3]) : "r"(a0), "r"(a1), "r"(b0));
}
DEVI void ldsm4(uint32_t* r, uint32_t addr) {
    asm volatile("ldmatrix.sync.aligned.m8n8.x4.shared.b16 {%0,%1,%2,%3}, [%4];"
                 : "=r"(r[0]), "=r"(r[1]), "=r"(r[2]), "=r"(r[3]) : "r"(addr) : "memory");
}
DEVI void ldsm4t(uint32_t* r, uint32_t addr) {
    asm volatile("ldmatrix.sync.aligned.m8n8.x4.trans.shared.b16 {%0,%1,%2,%3}, [%4];"
                 : "=r"(r[0]), "=r"(r[1]), "=r"(r[2]), "=r"(r[3]) : "r"(addr) : "memory");
}
DEVI void ldsm2(uint32_t* r, uint32_t addr) {
    asm volatile("ldmatrix.sync.aligned.m8n8.x2.shared.b16 {%0,%1}, [%2];" : "=r"(r[0]), "=r"(r[1]) : "r"(addr) : "memory");
}
DEVI void ldsm1t(uint32_t& r, uint32_t addr) {
    asm volatile("ldmatrix.sync.aligned.m8n8.x1.trans.shared.b16 {%0}, [%1];" : "=r"(r) : "r"(addr) : "memory");
}
DEVI void stsm4(uint32_t addr, uint32_t r0, uint32_t r1, uint32_t r2, uint32_t r3) {
    asm volatile("stmatrix.sync.aligned.m8n8.x4.shared.b16 [%0], {%1,%2,%3,%4};" :: "r"(addr), "r"(r0), "r"(r1), "r"(r2), "r"(r3) : "memory");
}
DEVI void stsm4t(uint32_t addr, uint32_t r0, uint32_t r1, uint32_t r2, uint32_t r3) {
    asm volatile("stmatrix.sync.aligned.m8n8.x4.trans.shared.b16 [%0], {%1,%2,%3,%4};" :: "r"(addr), "r"(r0), "r"(r1), "r"(r2), "r"(r3) : "memory");
}
DEVI uint32_t movm_t(uint32_t a) {
    uint32_t d; asm volatile("movmatrix.sync.aligned.m8n8.trans.b16 %0, %1;" : "=r"(d) : "r"(a)); return d;
}
DEVI uint32_t pack_bf16(float lo, float hi) {
    uint32_t r; asm("cvt.rn.bf16x2.f32 %0, %1, %2;" : "=r"(r) : "f"(hi), "f"(lo)); return r;
}
DEVI float ex2(float x) { float y; asm("ex2.approx.ftz.f32 %0, %1;" : "=f"(y) : "f"(x)); return y; }

DEVI uint4 ld_rlx4(const void* p) {
    uint4 v;
    asm volatile("ld.relaxed.gpu.global.v4.u32 {%0,%1,%2,%3}, [%4];" : "=r"(v.x), "=r"(v.y), "=r"(v.z), "=r"(v.w) : "l"(p) : "memory");
    return v;
}
DEVI void ld_rlx4f(float* d, const void* p) {
    asm volatile("ld.relaxed.gpu.global.v4.f32 {%0,%1,%2,%3}, [%4];" : "=f"(d[0]), "=f"(d[1]), "=f"(d[2]), "=f"(d[3]) : "l"(p) : "memory");
}
DEVI bool all_nzf(const float* d) { return __float_as_uint(d[0]) && __float_as_uint(d[1]) && __float_as_uint(d[2]) && __float_as_uint(d[3]); }
DEVI void sts128f(uint32_t addr, const float* d) {
    asm volatile("st.shared.v4.f32 [%0], {%1,%2,%3,%4};" :: "r"(addr), "f"(d[0]), "f"(d[1]), "f"(d[2]), "f"(d[3]) : "memory");
}
DEVI void st_rlx4(void* p, uint32_t a, uint32_t b, uint32_t c, uint32_t d) {
    asm volatile("st.relaxed.gpu.global.v4.u32 [%0], {%1,%2,%3,%4};" :: "l"(p), "r"(a), "r"(b), "r"(c), "r"(d) : "memory");
}
DEVI void st_rlx(void* p, uint32_t v) { asm volatile("st.relaxed.gpu.global.u32 [%0], %1;" :: "l"(p), "r"(v) : "memory"); }
DEVI void sts128(uint32_t addr, uint4 v) {
    asm volatile("st.shared.v4.u32 [%0], {%1,%2,%3,%4};" :: "r"(addr), "r"(v.x), "r"(v.y), "r"(v.z), "r"(v.w) : "memory");
}
DEVI void sts64(uint32_t addr, uint32_t a, uint32_t b) { asm volatile("st.shared.v2.u32 [%0], {%1,%2};" :: "r"(addr), "r"(a), "r"(b) : "memory"); }
DEVI void sts32(uint32_t addr, uint32_t v) { asm volatile("st.shared.u32 [%0], %1;" :: "r"(addr), "r"(v) : "memory"); }
DEVI uint4 lds128(uint32_t addr) {
    uint4 v; asm volatile("ld.shared.v4.u32 {%0,%1,%2,%3}, [%4];" : "=r"(v.x), "=r"(v.y), "=r"(v.z), "=r"(v.w) : "r"(addr) : "memory"); return v;
}
DEVI float2 lds64f(uint32_t addr) {
    float2 v; asm volatile("ld.shared.v2.f32 {%0,%1}, [%2];" : "=f"(v.x), "=f"(v.y) : "r"(addr) : "memory"); return v;
}
DEVI void cp_async16(uint32_t dst, const void* src) {
    asm volatile("cp.async.cg.shared.global [%0], [%1], 16;" :: "r"(dst), "l"(src) : "memory");
}
DEVI void cp_async_commit() { asm volatile("cp.async.commit_group;" ::: "memory"); }
DEVI void cp_async_wait0() { asm volatile("cp.async.wait_group 0;" ::: "memory"); }
DEVI uint32_t lds32(uint32_t addr) { uint32_t v; asm volatile("ld.shared.u32 %0, [%1];" : "=r"(v) : "r"(addr) : "memory"); return v; }
DEVI float rcp_fast(float x) { float y; asm("rcp.approx.ftz.f32 %0, %1;" : "=f"(y) : "f"(x)); return y; }
DEVI bool all_nz(const uint4& v) { return v.x && v.y && v.z && v.w; }
DEVI uint32_t mapa(uint32_t addr, uint32_t rank) {
    uint32_t r; asm("mapa.shared::cluster.u32 %0, %1, %2;" : "=r"(r) : "r"(addr), "r"(rank)); return r;
}
DEVI void st_async32(uint32_t dst, uint32_t a, uint32_t bar) {
    asm volatile("st.async.weak.shared::cluster.mbarrier::complete_tx::bytes.b32 [%0], %1, [%2];" :: "r"(dst), "r"(a), "r"(bar) : "memory");
}
DEVI void st_async64(uint32_t dst, uint32_t a, uint32_t b, uint32_t bar) {
    asm volatile("st.async.weak.shared::cluster.mbarrier::complete_tx::bytes.v2.b32 [%0], {%1,%2}, [%3];"
                 :: "r"(dst), "r"(a), "r"(b), "r"(bar) : "memory");
}

DEVI void st_async128(uint32_t dst, uint32_t a, uint32_t b, uint32_t c, uint32_t d, uint32_t bar) {
    asm volatile("st.async.weak.shared::cluster.mbarrier::complete_tx::bytes.v4.b32 [%0], {%1,%2,%3,%4}, [%5];"
                 :: "r"(dst), "r"(a), "r"(b), "r"(c), "r"(d), "r"(bar) : "memory");
}

DEVI uint32_t b_addr(uint32_t sb, int row, int which, int chunk) { const int l = 3 * row + which; return sb + l * 128 + ((chunk ^ (l & 7)) * 16); }
DEVI void battn_warp(uint32_t st, uint32_t so, int i0, int par, int head, int hh, int mt, int lane) {
    const int gq = lane >> 2, t = lane & 3;
    float s[3][4];
#pragma unroll
    for (int n = 0; n < 3; n++) { s[n][0] = s[n][1] = s[n][2] = s[n][3] = 0.f; }
    const int arow = 16 * mt + (lane & 7) + ((lane >> 3) & 1) * 8;
#pragma unroll
    for (int ks = 0; ks < 2; ks++) {
        uint32_t a[4], b[4], b2[2];
        ldsm4(a, b_addr(st, 8 + arow, 0, hh * 4 + ks * 2 + (lane >> 4)));
        const int brow = 16 * mt + (lane >> 4) * 8 + (lane & 7);
        ldsm4(b, b_addr(st, brow, 1, hh * 4 + ks * 2 + ((lane >> 3) & 1)));
        const int crow = 16 * mt + 16 + (lane & 7);
        ldsm2(b2, b_addr(st, crow, 1, hh * 4 + ks * 2 + ((lane >> 3) & 1)));
        mma16816(s[0], a, b[0], b[1]);
        mma16816(s[1], a, b[2], b[3]);
        mma16816(s[2], a, b2[0], b2[1]);
    }
    float m0 = -INFINITY, m1 = -INFINITY;
#pragma unroll
    for (int n = 0; n < 3; n++) {
#pragma unroll
        for (int c = 0; c < 2; c++) {
            const int dj = 8 * n - 8 + 2 * t + c;
            const bool ex = i0 + 16 * mt + dj >= 0;
            if (!(ex && gq - dj >= 0 && gq - dj <= 7)) s[n][c] = -INFINITY;
            if (!(ex && gq + 8 - dj >= 0 && gq + 8 - dj <= 7)) s[n][2 + c] = -INFINITY;
            m0 = fmaxf(m0, s[n][c]); m1 = fmaxf(m1, s[n][2 + c]);
        }
    }
    m0 = fmaxf(m0, __shfl_xor_sync(0xffffffffu, m0, 1)); m0 = fmaxf(m0, __shfl_xor_sync(0xffffffffu, m0, 2));
    m1 = fmaxf(m1, __shfl_xor_sync(0xffffffffu, m1, 1)); m1 = fmaxf(m1, __shfl_xor_sync(0xffffffffu, m1, 2));
    constexpr float C = 0.17677669529663687f * 1.4426950408889634f;
    float l0 = 0.f, l1 = 0.f;
    uint32_t p[3][2];
#pragma unroll
    for (int n = 0; n < 3; n++) {
        const float e0 = ex2((s[n][0] - m0) * C), e1 = ex2((s[n][1] - m0) * C), e2 = ex2((s[n][2] - m1) * C), e3 = ex2((s[n][3] - m1) * C);
        l0 += e0 + e1; l1 += e2 + e3;
        p[n][0] = pack_bf16(e0, e1); p[n][1] = pack_bf16(e2, e3);
    }
    l0 += __shfl_xor_sync(0xffffffffu, l0, 1); l0 += __shfl_xor_sync(0xffffffffu, l0, 2);
    l1 += __shfl_xor_sync(0xffffffffu, l1, 1); l1 += __shfl_xor_sync(0xffffffffu, l1, 2);
    const float i0f = rcp_fast(l0), i1f = rcp_fast(l1);
    float o[4][4];
#pragma unroll
    for (int n = 0; n < 4; n++) { o[n][0] = o[n][1] = o[n][2] = o[n][3] = 0.f; }
    {
        const uint32_t a0[4] = {p[0][0], p[0][1], p[1][0], p[1][1]}, a1[4] = {p[2][0], p[2][1], 0u, 0u};
#pragma unroll
        for (int n = 0; n < 4; n += 2) {
            uint32_t b[4], b2[4];
            const int vrow = 16 * mt + ((lane >> 3) & 1) * 8 + (lane & 7);
            ldsm4t(b, b_addr(st, vrow, 2, hh * 4 + n + (lane >> 4)));
            const int wrow = 16 * mt + 16 + (lane & 7);
            ldsm4t(b2, b_addr(st, wrow, 2, hh * 4 + n + (lane >> 4)));
            mma16816(o[n], a0, b[0], b[1]);
            mma16816(o[n + 1], a0, b[2], b[3]);
            mma16816(o[n], a1, b2[0], 0u);
            mma16816(o[n + 1], a1, b2[2], 0u);
        }
    }
    {
        const int row = (lane & 7) + ((lane >> 3) & 1) * 8;
#pragma unroll
        for (int n = 0; n < 4; n += 2)
            stsm4(so + row * 64 + (((n + (lane >> 4)) ^ ((row >> 1) & 3)) * 16),
                  pack_bf16(o[n][0] * i0f, o[n][1] * i0f), pack_bf16(o[n][2] * i1f, o[n][3] * i1f),
                  pack_bf16(o[n + 1][0] * i0f, o[n + 1][1] * i0f), pack_bf16(o[n + 1][2] * i1f, o[n + 1][3] * i1f));
    }
    __syncwarp();
#pragma unroll
    for (int i = 0; i < 2; i++) {
        const int idx = lane + i * 32, row = idx >> 2, ch = idx & 3;
        const uint4 v = lds128(so + row * 64 + ((ch ^ ((row >> 1) & 3)) * 16));
        *(uint4*)(g_bo + (size_t)(2 * (i0 + 16 * mt + row) + par) * 1024 + head * 32 + ch * 8) = v;
    }
    __syncwarp();
}

constexpr float SCALE_LOG2E = 0.08838834764831845f * 1.4426950408889634f;

constexpr int P_UNITS = 12, P_STAGES = 6;
constexpr int PS_STG = P_UNITS * 16384;
constexpr int PS_BAR = PS_STG + 32768;
constexpr int P_SMEM = PS_BAR + 256;
static_assert(P_SMEM <= 232448, "smem");
enum { K_Q, K_B1, K_B3, K_A4, K_QH, K_A3, K_SK, K_B2, K_END };
struct PList { int n, nworker; int4 run[16]; };
struct PTask { int kind, a, b, c; };
DEVI PTask p_decode(const PList& pl, int id) {
    for (int i = 0; i < pl.n; i++) {
        const int4 r = pl.run[i];
        if (id < r.w) {
            const int j = id - r.z;
            if (r.x == K_Q || r.x == K_QH) return {r.x, j & 31, r.y + (j >> 5), 0};
            if (r.x == K_B1) return {r.x, j % 24, r.y + j / 24, 0};
            if (r.x == K_B2) return {r.x, 0, r.y + j, 0};
            if (r.x == K_SK) return {r.x, (j / P_SPLIT) & 7, r.y + j / (8 * P_SPLIT), j % P_SPLIT};
            return {r.x, j & 7, r.y + (j >> 3), 0};
        }
    }
    return {K_END, 0, 0, 0};
}
DEVI void wait_count(const unsigned* p, unsigned target) {
    int n = 0;
    while (true) {
        unsigned v; asm volatile("ld.acquire.gpu.global.u32 %0, [%1];" : "=r"(v) : "l"(p) : "memory");
        if ((int)(v - target) >= 0) break;
        __nanosleep(100);
        if (++n > SPIN_LIMIT) TRAP(0x10000000u | ((unsigned)(size_t)p & 0xFFFFu));
    }
}
DEVI void wait_count_warp(const unsigned* p, unsigned target) {
    int n = 0;
    while (true) {
        unsigned v; asm volatile("ld.acquire.gpu.global.u32 %0, [%1];" : "=r"(v) : "l"(p) : "memory");
        if (__all_sync(0xffffffffu, (int)(v - target) >= 0)) break;
        __nanosleep(100);
        if (++n > SPIN_LIMIT) TRAP(0x10000000u | ((unsigned)(size_t)p & 0xFFFFu));
    }
}
DEVI void signal_count(unsigned* p) { __threadfence(); atomicAdd(p, 1u); }

struct PMaps { CUtensorMap wq, bw, bwo, wo, x, bx, bo, ox, cb, cout, cq, b40; PList list; };
constexpr int PB_F = PS_BAR, PB_E = PB_F + 48, PB_TF = PB_F + 96, PB_TE = PB_F + 112, PB_S = PB_F + 128;
constexpr int PS_T = PB_F + 144, PS_SIG = PS_T + 32, PS_SK = PS_SIG + 16;

struct PRing {
    int st, ph, u;
    DEVI void next(int n) { u += n; if (u >= P_UNITS) u -= P_UNITS; if (++st == P_STAGES) { st = 0; ph ^= 1; } }
    DEVI uint32_t w(bool wide) const { return wide && u == P_UNITS - 2 ? 0u : u * 16384u; }
    DEVI uint32_t x(bool wide) const { return wide && u == P_UNITS - 2 ? u * 16384u : (u == P_UNITS - 1 ? 0u : (u + 1) * 16384u); }
};
struct POut { const CUtensorMap* map; int col, tok, cnt; bool blocked; };
DEVI void p_store(const uint32_t* pk, const POut& o, int c, uint32_t stg, int warp, int lane_, int barid, bool elected) {
    const int lane = (int)opaque((uint32_t)lane_);
    const int mi = lane >> 3, r = lane & 7;
    const uint32_t buf = stg + (c & 1) * 8192;
    if (elected) asm volatile("cp.async.bulk.wait_group.read 1;" ::: "memory");
    nbar_sync(barid, 128);
    if (o.blocked) {
#pragma unroll
        for (int j = 0; j < 8; j += 2)
            stsm4(buf + (j + (mi >> 1)) * 1024 + (warp * 16 + (mi & 1) * 8 + r) * 16, pk[2 * j], pk[2 * j + 1], pk[2 * j + 2], pk[2 * j + 3]);
    } else {
#pragma unroll
        for (int j = 0; j < 8; j += 2)
            stsm4t(buf + (8 * (j + (mi >> 1)) + r) * 128 + ((2 * warp + (mi & 1)) ^ r) * 16, pk[2 * j], pk[2 * j + 1], pk[2 * j + 2], pk[2 * j + 3]);
    }
    fence_proxy_async();
    nbar_sync(barid, 128);
    if (elected) {
        if (o.blocked)
            asm volatile("cp.async.bulk.tensor.4d.global.shared::cta.bulk_group [%0, {%2, %3, %4, %5}], [%1];"
                         :: "l"(o.map), "r"(buf), "r"(0), "r"((o.col >> 5) & 2), "r"((o.col >> 7) * 4), "r"((o.tok >> 5) + 2 * c) : "memory");
        else tma_store_2d(o.map, buf, o.col, o.tok + c * 64);
        bulk_commit();
    }
}
DEVI void p_signal(uint32_t sb, int g, int cnt, int& nsig) {
    sts32(sb + PS_SIG + g * 8 + (nsig & 1) * 4, (uint32_t)cnt);
    mbar_arrive(sb + PB_S + g * 8);
    nsig++;
}
DEVI void p_release(uint32_t sb, const PRing& r, int back, bool elected) {
    if (elected) mbar_arrive(sb + PB_E + (r.st >= back ? r.st - back : r.st - back + P_STAGES) * 8);
}
template <int BN, bool FIRST>
DEVI void p_kblock(float* d, uint32_t sb, int g, PRing& r, bool elected) {
    mbar_wait(sb + PB_F + r.st * 8, r.ph);
    const uint64_t da = mk_desc(sb + r.w(BN == 256) + g * 8192, 16, 1024, 1), db = mk_desc(sb + r.x(BN == 256), 16, 1024, 1);
    wg_fence();
#pragma unroll
    for (int kk = 0; kk < 4; kk++) {
        if (BN == 256) { if (FIRST && kk == 0) wgmma_n256_ss<true>(d, da, db); else wgmma_n256_ss<false>(d, da + (uint64_t)(kk * 128), db + (uint64_t)(kk * 2)); }
        else           { if (FIRST && kk == 0) wgmma_n128_ss<true>(d, da, db); else wgmma_n128_ss<false>(d, da + (uint64_t)(kk * 128), db + (uint64_t)(kk * 2)); }
    }
    wg_commit();
    if (!FIRST) {
        wg_wait<1>();
        p_release(sb, r, 1, elected);
    }
    r.next(BN == 256 ? 3 : 2);
}

DEVI int post_claim(const PMaps& mp, unsigned E) {
    unsigned v = 0;
    if ((threadIdx.x & 31) == 0) v = atomicAdd(&g_qctr, 1u);
    return (int)(__shfl_sync(0xffffffffu, v, 0) - (E - 1) * (unsigned)(mp.list.run[mp.list.n - 1].w + mp.list.nworker));
}
DEVI void post_producer(const PMaps& mp, uint32_t sb, unsigned E, int id) {
    PRing r = {0, 0, 0};
    int ts = 0, tp = 0, used = 0;
    uint32_t big = 0;
    auto reserve = [&](int n) {
        while (used + n > P_UNITS) {
            mbar_wait(sb + PB_E + ts * 8, tp);
            used -= 2 + ((big >> ts) & 1);
            if (++ts == P_STAGES) { ts = 0; tp ^= 1; }
        }
        used += n;
        big = (big & ~(1u << r.st)) | ((uint32_t)(n & 1) << r.st);
    };
    for (int i = 0;; i++) {
        mbar_wait(sb + PB_TE + (i & 1) * 8, ((i >> 1) & 1) ^ 1);
        if (i > 0) id = post_claim(mp, E);
        const PTask tk = p_decode(mp.list, id);
        const bool qk = tk.kind == K_Q || tk.kind == K_QH, ak = tk.kind == K_A4 || tk.kind == K_A3 || tk.kind == K_SK, wide = tk.kind <= K_A4;
        const int nk = tk.kind == K_A3 || tk.kind == K_A4 ? HD / 64 : (tk.kind == K_SK ? HD / 64 / P_SPLIT : DM / 64), kb0 = tk.c * (HD / 64 / P_SPLIT);
        const int npre = tk.kind == K_SK && (i == 0 || __any_sync(0xffffffffu, (int)(*(volatile unsigned*)&g_prog[tk.b] - 128 * E) < 0)) ? P_STAGES : 0;
        PRing rp = r;
        for (int kb = kb0; kb < kb0 + npre; kb++) {
            reserve(2);
            const uint32_t bar = sb + PB_F + r.st * 8;
            if (elect_one()) {
                mbar_expect_tx(bar, 32768);
                tma_load_wo(sb + r.w(false), &mp.wo, tk.a * 128, kb * 2, bar);
                tma_load_wo(sb + r.w(false) + 8192, &mp.wo, tk.a * 128 + 64, kb * 2, bar);
            }
            r.next(2);
        }
        if (tk.kind == K_B2) {
            wait_count_warp(&g_cnt[C_B1 + (tk.b >> 2)], 48 * E);
            if ((tk.b & 3) == 0 && tk.b > 0) wait_count_warp(&g_cnt[C_B1 + (tk.b >> 2) - 1], 48 * E);
        } else if (tk.kind == K_B3) wait_count_warp(&g_cnt[C_B2 + tk.b], 8 * E);
        else if (tk.kind == K_A4) wait_count_warp(&g_prog[2 * tk.b + 1], 128 * E);
        else if (ak) wait_count_warp(&g_prog[tk.b], 128 * E);
        fence_proxy_global();
        for (int kb = kb0; kb < kb0 + npre; kb++) {
            if (elect_one()) tma_load_2d(sb + rp.x(false), &mp.ox, kb * 64, tk.b * 128, sb + PB_F + rp.st * 8);
            rp.next(2);
        }
        if (elect_one()) {
            sts128(sb + PS_T + (i & 1) * 16, make_uint4((uint32_t)tk.kind | ((uint32_t)id << 8), (uint32_t)tk.a, (uint32_t)tk.b, (uint32_t)tk.c));
            mbar_arrive(sb + PB_TF + (i & 1) * 8);
        }
        if (tk.kind == K_END) break;
        if (tk.kind == K_B2) {
            for (int j = 0; j < 16; j++) {
                reserve(2);
                const uint32_t bar = sb + PB_F + r.st * 8;
                if (elect_one()) {
                    mbar_expect_tx(bar, 2 * 15360);
#pragma unroll
                    for (int u = 0; u < 2; u++) asm volatile("cp.async.bulk.tensor.4d.shared::cluster.global.mbarrier::complete_tx::bytes [%0], [%1, {%3, %4, %5, %6}], [%2];"
                                 :: "r"(sb + (u ? r.x(false) : r.w(false))), "l"(&mp.b40), "r"(bar), "r"(j * 64), "r"(0), "r"(u), "r"(tk.b * 32 - 8) : "memory");
                }
                r.next(2);
            }
            continue;
        }
        const CUtensorMap* tw = tk.kind == K_B1 ? &mp.bw : (qk ? &mp.wq : &mp.bwo);
        const CUtensorMap* tx = tk.kind == K_B1 ? &mp.bx : (qk ? &mp.x : (ak ? &mp.ox : &mp.bo));
        for (int kb = kb0 + npre; kb < kb0 + nk; kb++) {
            reserve(wide ? 3 : 2);
            const uint32_t aw = sb + r.w(wide), ax = sb + r.x(wide), bar = sb + PB_F + r.st * 8;
            if (elect_one()) {
                mbar_expect_tx(bar, wide ? 49152 : 32768);
                if (ak) {
                    tma_load_wo(aw, &mp.wo, tk.a * 128, kb * 2, bar);
                    tma_load_wo(aw + 8192, &mp.wo, tk.a * 128 + 64, kb * 2, bar);
                } else {
                    tma_load_2d(aw, tw, tk.a * 128, kb * 64, bar);
                    tma_load_2d(aw + 8192, tw, tk.a * 128 + 64, kb * 64, bar);
                }
                tma_load_2d(ax, tx, kb * 64, tk.b * (wide ? 256 : 128), bar);
                if (wide) tma_load_2d(ax + 16384, tx, kb * 64, tk.b * 256 + 128, bar);
            }
            r.next(wide ? 3 : 2);
        }
    }
    if (elect_one()) {
        __threadfence();
        if (atomicAdd(&g_done, 1u) == E * mp.list.nworker - 1) { __threadfence(); *(volatile unsigned*)&g_epoch = E; }
    }
}
DEVI void post_helper(uint32_t sb, int g) {
    for (int n = 0;; n++) {
        mbar_wait_sleepy(sb + PB_S + g * 8, n & 1);
        const int cnt = (int)lds32(sb + PS_SIG + g * 8 + (n & 1) * 4);
        if (cnt < 0) break;
        signal_count(&g_cnt[cnt]);
    }
}
DEVI void post_consumer(const PMaps& mp, uint32_t sb, int g, int warp) {
    const int barid = 1 + g, tid = threadIdx.x, lane = tid & 31;
    const bool elected = (tid & 127) == 0;
    const uint32_t stg = sb + PS_STG + g * 16384;
    int nsig = 0;
    PRing r = {0, 0, 0};
    uint32_t pk[64];
    POut out;
    bool pend = false;
#pragma unroll
    for (int i = 0; i < 64; i++) pk[i] = 0u;
    for (int i = 0;; i++) {
        const uint32_t bTF = sb + PB_TF + (i & 1) * 8;
        if (pend) {
            uint32_t now;
            asm volatile("{.reg .pred p, q; mbarrier.test_wait.parity.shared::cta.b64 p, [%1], %2; bar.red.and.pred q, %3, 128, p; selp.u32 %0, 1, 0, q;}"
                         : "=r"(now) : "r"(bTF), "r"((i >> 1) & 1), "r"(barid) : "memory");
            if (!now || (lds32(sb + PS_T + (i & 1) * 16) & 255u) > K_A4) {
#pragma unroll
                for (int c = 0; c < 4; c++) p_store(pk + 16 * c, out, c, stg, warp, lane, barid, elected);
                if (elected && out.cnt != C_NONE) { bulk_wait_all(); p_signal(sb, g, out.cnt, nsig); }
                pend = false;
            }
        }
        mbar_wait(bTF, (i >> 1) & 1);
        const uint4 tw = lds128(sb + PS_T + (i & 1) * 16);
        mbar_arrive(sb + PB_TE + (i & 1) * 8);
        const PTask tk = {(int)(tw.x & 255u), (int)tw.y, (int)tw.z, (int)tw.w};
        if (tk.kind == K_END) break;
        if (tk.kind <= K_A4) {
            float d[128];
            const int nk = tk.kind == K_A4 ? HD / 64 : DM / 64;
            p_kblock<256, true>(d, sb, g, r, elected);
            if (pend) p_store(pk, out, 0, stg, warp, lane, barid, elected);
#pragma unroll
            for (int c = 1; c < 4; c++) {
                p_kblock<256, false>(d, sb, g, r, elected);
                if (pend) p_store(pk + 16 * c, out, c, stg, warp, lane, barid, elected);
            }
#pragma unroll 1
            for (int kb = 4; kb < nk; kb++) {
                p_kblock<256, false>(d, sb, g, r, elected);
                if (kb == 6 && pend && elected && out.cnt != C_NONE) { bulk_wait_all(); p_signal(sb, g, out.cnt, nsig); }
            }
            wg_wait<0>();
            reg_fence<128>(d);
            p_release(sb, r, 1, elected);
#pragma unroll
            for (int j = 0; j < 64; j++) pk[j] = pack_bf16(d[2 * j], d[2 * j + 1]);
            out.map = tk.kind == K_Q ? &mp.cq : (tk.kind == K_B1 ? &mp.cb : &mp.cout);
            out.col = tk.a * 128 + g * 64 + (tk.kind == K_B3 ? DM : 0);
            out.tok = tk.b * 256;
            out.cnt = tk.kind == K_Q ? C_Q + tk.b : (tk.kind == K_B1 ? C_B1 + tk.b : C_NONE);
            out.blocked = tk.kind == K_Q;
            pend = true;
        } else if (tk.kind == K_B2) {
            if (elected) bulk_wait_all();
            nbar_sync(barid, 128);
#pragma unroll 1
            for (int j = 0; j < 16; j++) {
                mbar_wait(sb + PB_F + r.st * 8, r.ph);
                const uint32_t a = sb + (g ? r.x(false) : r.w(false));
                battn_warp(a, stg + warp * 1024, tk.b * 32, g, j * 2 + (warp >> 1), warp >> 1, warp & 1, (int)opaque((uint32_t)lane));
                nbar_sync(barid, 128);
                p_release(sb, r, 0, elected);
                r.next(2);
            }
            if (elected) p_signal(sb, g, C_B2 + (tk.b >> 2), nsig);
#pragma unroll
            for (int j = 0; j < 64; j++) pk[j] = 0u;
        } else {
            float d[64];
            const int nk = tk.kind == K_A3 ? HD / 64 : (tk.kind == K_SK ? HD / 64 / P_SPLIT : DM / 64);
            p_kblock<128, true>(d, sb, g, r, elected);
#pragma unroll 1
            for (int kb = 1; kb < nk; kb++) p_kblock<128, false>(d, sb, g, r, elected);
            wg_wait<0>();
            reg_fence<64>(d);
            p_release(sb, r, 1, elected);
            bool finish = true;
            if (tk.kind == K_SK) {
                const int tile = ((tk.b - (16 - P_NSK)) * 8 + tk.a);
                uint4* const base = g_skp + (size_t)(tile * P_SPLIT * 2 + g) * 1024 + (tid & 127);
#pragma unroll
                for (int j = 0; j < 8; j++)
                    base[tk.c * 2048 + j * 128] = make_uint4(pack_bf16(d[8 * j], d[8 * j + 1]), pack_bf16(d[8 * j + 2], d[8 * j + 3]),
                                                             pack_bf16(d[8 * j + 4], d[8 * j + 5]), pack_bf16(d[8 * j + 6], d[8 * j + 7]));
                nbar_sync(barid, 128);
                if (elected) {
                    unsigned old;
                    asm volatile("atom.acq_rel.gpu.global.add.u32 %0, [%1], 1;" : "=r"(old) : "l"(&g_cnt_sk[tile * 2 + g]) : "memory");
                    sts32(sb + PS_SK + g * 4, old % P_SPLIT);
                }
                nbar_sync(barid, 128);
                finish = lds32(sb + PS_SK + g * 4) == P_SPLIT - 1;
                if (finish) {
#pragma unroll 1
                    for (int q = 1; q < P_SPLIT; q += 4) {
                        uint4 v[32];
#pragma unroll
                        for (int j = 0; j < 32; j++)
                            v[j] = j < 24 || q + 3 < P_SPLIT ? __ldcg(base + ((tk.c + q + (j >> 3)) % P_SPLIT) * 2048 + (j & 7) * 128) : make_uint4(0u, 0u, 0u, 0u);
#pragma unroll
                        for (int j = 0; j < 32; j++) {
                            float* e = d + 8 * (j & 7);
                            e[0] += __uint_as_float(v[j].x << 16); e[1] += __uint_as_float(v[j].x & 0xFFFF0000u);
                            e[2] += __uint_as_float(v[j].y << 16); e[3] += __uint_as_float(v[j].y & 0xFFFF0000u);
                            e[4] += __uint_as_float(v[j].z << 16); e[5] += __uint_as_float(v[j].z & 0xFFFF0000u);
                            e[6] += __uint_as_float(v[j].w << 16); e[7] += __uint_as_float(v[j].w & 0xFFFF0000u);
                        }
                    }
                }
                nbar_sync(barid, 128);
            }
            if (finish) {
                const POut o = {tk.kind == K_QH ? &mp.cq : &mp.cout, tk.a * 128 + g * 64, tk.b * 128, 0, tk.kind == K_QH};
                uint32_t q[32];
#pragma unroll
                for (int j = 0; j < 32; j++) q[j] = pack_bf16(d[2 * j], d[2 * j + 1]);
                p_store(q, o, 0, stg, warp, lane, barid, elected);
                p_store(q + 16, o, 1, stg, warp, lane, barid, elected);
                if (elected && tk.kind == K_QH) { bulk_wait_all(); p_signal(sb, g, tk.b == 0 ? C_QH : C_Q, nsig); }
            }
#pragma unroll
            for (int j = 0; j < 64; j++) pk[j] = 0u;
        }
    }
    if (elected) { bulk_wait_all(); p_signal(sb, g, -1, nsig); }
}
DEVI void post_init(uint32_t sb) {
    for (int i = 0; i < P_STAGES; i++) { mbar_init(sb + PB_F + i * 8, 1); mbar_init(sb + PB_E + i * 8, 2); }
    for (int i = 0; i < 2; i++) { mbar_init(sb + PB_TF + i * 8, 1); mbar_init(sb + PB_TE + i * 8, 256); mbar_init(sb + PB_S + i * 8, 1); }
    fence_mbar_init();
}

constexpr unsigned long long R_TORD_PACK = 0xf5ea4937dc1826b0ull;
__host__ __device__ constexpr int r_tord(int pos) { return (int)((R_TORD_PACK >> (4 * pos)) & 15ull); }
__host__ __device__ constexpr int r_tinv(int T) { for (int p = 0; p < 16; p++) if (r_tord(p) == T) return p; return 0; }
__host__ __device__ constexpr bool r_pos_ss(int pos) { return pos % 3 == 2; }
__host__ __device__ constexpr int r_ss(int pos) { return pos / 3; }
__host__ __device__ constexpr int r_rs(int pos) { return pos - pos / 3; }
constexpr int R_NRS = 11, R_NSS = 5;
constexpr int R_G1 = 3, R_G2 = 9;
#define REG_KB 232
#define A_AT 2
#define A_PRE 4
#define WO_REL 0
constexpr int X_SLOTS = 4;
constexpr int X_NST = 8;

constexpr int RS_WSS  = 0;
constexpr int RS_WO   = RS_WSS + R_NSS * 16384;
constexpr int RS_MEM  = RS_WO + 5 * 16384;
constexpr int RS_O    = RS_MEM + 16384;
constexpr int RS_SX   = RS_O + 2048;
constexpr int RS_BAR  = RS_SX + 2048;
constexpr int RS_TAIL = RS_BAR + 1024;
constexpr int RS_WO5  = RS_TAIL;
constexpr int RS_K    = RS_WO5 + 16384;
constexpr int RS_V    = RS_K + 10240;
constexpr int RS_Q    = RS_V + 10240;
constexpr int RS_QX   = RS_Q + 2048;
constexpr int RS_QEND = RS_QX + 8192;
constexpr int RS_X    = RS_TAIL;
constexpr int X_PITCH = X_SLOTS * 4096;
constexpr int RS_XD   = RS_X + 2 * X_PITCH;
constexpr int RS_WX   = RS_XD + 8192;
constexpr int RS_KEND = RS_WX + 4096;
constexpr int RS_EV   = RS_BAR + 256;
constexpr int R_SMEM  = RS_KEND > RS_QEND ? RS_KEND : RS_QEND;
static_assert(R_SMEM <= 232448 && P_SMEM <= R_SMEM, "smem");
static_assert(RS_TAIL % 1024 == 0 && RS_MEM % 1024 == 0, "alignment");

constexpr int RB_G = RS_BAR, RB_K = RS_BAR + 24, RB_V = RS_BAR + 32, RB_KV = RS_BAR + 40, RB_QX = RS_BAR + 48, RB_O = RS_BAR + 56;
constexpr int RB_ATT = RS_BAR + 64, RB_W = RS_BAR + 72, RB_SF = RS_BAR + 80, RB_SE = RB_SF + 40, RB_XF = RB_SE + 40;
constexpr int RB_WO = RB_XF + 56, RB_T = RB_XF + 64, RS_INV = RS_SX + 1024;
static_assert(RB_T + 8 <= RS_EV, "barriers");
constexpr uint32_t SB0 = 1024;
__host__ __device__ constexpr uint32_t cdesc(uint32_t off, uint32_t lbo) { return ((SB0 + off) >> 4) | ((lbo >> 4) << 16); }
#define SCHED_FENCE() __syncwarp()
constexpr int NB_BIG = 1, NB_Q = 2, NB_AUX = 3, NB_WO = 4, NB_XS = 5, NB_WG = 6, NB_PAIR = 8;

DEVI int tid_now() { int t; asm volatile("mov.u32 %0, %%tid.x;" : "=r"(t)); return t; }
DEVI uint32_t a_frag_off(int lane, int warp) { return (uint32_t)((((lane >> 4) * 8 + (lane & 7)) * 128) + (((2 * warp + ((lane >> 3) & 1)) ^ (lane & 7)) * 16)); }
DEVI uint32_t b_frag_off(int lane) { return (uint32_t)((lane & 3) * 64 + (((lane >> 2) * 8) ^ ((lane & 2) * 16))); }
DEVI void lds_b(uint32_t* b, uint32_t a) {
    asm volatile("ld.shared.v2.u32 {%0,%1}, [%2];" : "=r"(b[0]), "=r"(b[1]) : "r"(a) : "memory");
    asm volatile("ld.shared.v2.u32 {%0,%1}, [%2];" : "=r"(b[2]), "=r"(b[3]) : "r"(a + 256) : "memory");
}
DEVI uint32_t clk32() { unsigned long long c; asm volatile("mov.u64 %0, %%clock64;" : "=l"(c)); return (uint32_t)c; }

__host__ __device__ constexpr int x_pair(int j) { return j == 0 || j > 3 ? j : (j == 3 ? 1 : j + 1); }
DEVI void x_load(uint32_t sb, int seg, int j, int g, const CUtensorMap* tmX) {
    const uint32_t bar = sb + RB_XF + g * 8;
    mbar_expect_tx(bar, 4096);
    tma_load_3d(sb + RS_X + g * X_PITCH + (j % X_SLOTS) * 4096, tmX, g * 32, seg * 32, x_pair(j) * 2, bar);
}
DEVI void x_refill(uint32_t sb, int seg, int j, int g, int warp, const CUtensorMap* tmX) {
    const int sn = j + X_SLOTS < X_NST ? seg : seg + 1;
    if (warp == (j & 3) && sn < NSEG) {
        if (elect_one()) x_load(sb, sn, (j + X_SLOTS) % X_NST, g, tmX);
    }
}
template <int H>
DEVI void x_half(float* xa, uint32_t* a, uint32_t aA0, const uint32_t* w, uint32_t sb, int seg, int g0, int warp, const CUtensorMap* tmX) {
    wg_fence();
#pragma unroll
    for (int grp = 0; grp < 4; grp++) {
        const int g = (int)opaque((uint32_t)g0);
        const uint32_t dW0 = cdesc(RS_WSS, 16) + g * 768, dW1 = cdesc(RS_WSS + 8192, 16) - g * 256;
#pragma unroll
        for (int i = 0; i < 8; i++) {
            const bool last = H == 1 && grp >= 2;
            const int j = last ? 6 + (i >> 2) : 4 * H + grp, q = last ? 2 * (i & 3) + (grp == 2) : i;
            const int pos = r_tinv(2 * x_pair(j) + (q >> 2)), kk = (q >> 1) & 1, mt = q & 1;
            const uint32_t db = cdesc(RS_X + (j % X_SLOTS) * 4096, 16) + g * (X_PITCH >> 4) + (q >> 2) * 128 + kk * 2;
            if (j == 0 && q < 2)   wgmma_n32_rs_first(xa + 16 * mt, &w[((r_rs(pos) * 2 + kk) * 2 + mt) * 4], db);
            else if (j == 0 && q == 3) wgmma_n32_ss(xa + 16, cdesc(RS_WX, 16) + g * 128, db);
            else if (r_pos_ss(pos)) wgmma_n32_ss(xa + 16 * mt, (mt ? dW1 : dW0) + r_ss(pos) * 1024 + kk * 128, db);
            else                   wgmma_n32_rs(xa + 16 * mt, &w[((r_rs(pos) * 2 + kk) * 2 + mt) * 4], db);
        }
        wg_commit();
    }
    const int g = (int)opaque((uint32_t)g0);
    auto prefetch = [&]() {
        SCHED_FENCE();
#pragma unroll
        for (int q = 0; q < A_PRE; q++) ldsm4t(a + 4 * q, aA0 + (q & 1) * (8192 - g * 16384) + (q >> 1) * 2048);
        SCHED_FENCE();
    };
    if (H == 1 && A_AT == 1) prefetch();
    wg_wait<3>(); x_refill(sb, seg, 4 * H, g, warp, tmX);
    if (H == 1 && A_AT == 2) prefetch();
    wg_wait<2>(); x_refill(sb, seg, 4 * H + 1, g, warp, tmX);
    if (H == 1 && A_AT == 3) prefetch();
    if (H == 0 && A_AT == 5) prefetch();
    wg_wait<1>();
    if (H == 0) {
        if (A_AT == 4) prefetch();
        x_refill(sb, seg, 2, g, warp, tmX);
        wg_wait<0>(); reg_fence<32>(xa); x_refill(sb, seg, 3, g, warp, tmX);
    } else reg_fence<16>(xa + 16);
}
DEVI void x_finish(float* xa, uint32_t sb, int seg, int g, int warp, int lane, const CUtensorMap* tmX) {
    const uint32_t d = sb + RS_XD + (lane >> 4) * 2048 + warp * 256 + (lane & 15) * 16;
#pragma unroll
    for (int i = 0; i < 2; i++) {
        const float* x = xa + 16 + 8 * i;
        sts128(d + (g ^ 1) * 1024 + i * 4096, make_uint4(pack_bf16(x[0], x[1]), pack_bf16(x[2], x[3]), pack_bf16(x[4], x[5]), pack_bf16(x[6], x[7])));
    }
    nbar_sync(NB_PAIR + warp, 64);
    float y[16];
#pragma unroll
    for (int i = 0; i < 2; i++) {
        const uint4 v = lds128(d + g * 1024 + i * 4096);
        const uint32_t u[4] = {v.x, v.y, v.z, v.w};
#pragma unroll
        for (int j = 0; j < 4; j++) { y[8 * i + 2 * j] = __uint_as_float(u[j] << 16); y[8 * i + 2 * j + 1] = __uint_as_float(u[j] & 0xFFFF0000u); }
    }
    reg_fence<16>(y);
    wg_wait<0>();
    reg_fence<16>(xa);
    uint32_t p[8];
#pragma unroll
    for (int j = 0; j < 8; j++) p[j] = pack_bf16(xa[2 * j] + y[2 * j], xa[2 * j + 1] + y[2 * j + 1]);
    __syncwarp();
    stsm4(d + g * 1024, p[0], p[1], p[2], p[3]);
    stsm4(d + g * 1024 + 4096, p[4], p[5], p[6], p[7]);
    nbar_arrive(NB_XS, 256 + 32);
    x_refill(sb, seg, X_NST - 2, g, warp, tmX);
    x_refill(sb, seg, X_NST - 1, g, warp, tmX);
}
DEVI void x_send(uint32_t sb, int seg, uint32_t rank, int vdelay) {
    mbar_wait(sb + RB_ATT, (seg - 1) & 1);
    nbar_sync(NB_XS, 256 + 32);
    if (rank == 2) { const uint32_t t = clk32() + vdelay; while ((int)(clk32() - t) < 0) { } }
    if (elect_one()) {
        fence_proxy_async();
        bulk_copy_s2c(mapa(sb + (rank == 1 ? RS_K : RS_V) + 2048, 0), sb + RS_XD, 8192, mapa(sb + (rank == 1 ? RB_KV : RB_V), 0));
    }
    __syncwarp();
}

template <bool XP>
DEVI void mem_pass(float* c0, float* c1, uint32_t* a, const uint32_t* w, uint32_t sb, uint32_t aA0, uint32_t aB, int g, int warp, int s) {
    const uint32_t aA1 = aA0 + 8192 - g * 16384, par = (s - 1) & 1;
    uint32_t b[2][4], e[4];
    float d0[4], d1[4];
    if (XP) ldsm4t(e, aA0 + opaque((RS_WX - RS_WSS) - g * (8192 + 2048)));
#pragma unroll
    for (int q = XP ? A_PRE : 0; q < 4; q++) ldsm4t(a + 4 * q, ((q & 1) ? aA1 : aA0) + (q >> 1) * 2048);
#pragma unroll
    for (int i = 0; i < 4; i++) { c0[i] = 0.f; c1[i] = 0.f; d0[i] = 0.f; d1[i] = 0.f; }
    EV(EV_BIG0, s, 0);
    mbar_wait(sb + RB_G, par);
    EV(EV_BIG0, s, 1);
    lds_b(b[0], aB + r_tord(0) * 1024);
    bool in = false;
#pragma unroll
    for (int pos = 0; pos < 16; pos++) {
        if (pos + 1 < 16) {
            if (pos + 1 == R_G1 && !in) mbar_wait(sb + RB_G + 8, par);
            if (pos + 1 == R_G2) { if (!in) mbar_wait(sb + RB_G + 16, par); EV(EV_BIG0, s, 2); }
            lds_b(b[(pos + 1) & 1], aB + r_tord(pos + 1) * 1024);
        }
        if (pos + 2 == R_G1) in = mbar_try(sb + RB_G + 8, par);
        if (pos + 2 == R_G2) in = mbar_try(sb + RB_G + 16, par);
        if (XP && pos == 12) in = s == NSEG - 1 || mbar_try(sb + RB_XF + g * 8, 0);
        if (XP && pos == 14) { if (!in) mbar_wait(sb + RB_XF + g * 8, 0); in = mbar_try(sb + RB_ATT, par); }
        const uint32_t* bb = b[pos & 1];
        const uint32_t* aa = r_pos_ss(pos) ? a : &w[r_rs(pos) * 16];
        mma16816(c1, aa + 4, bb[0], bb[1]);
        mma16816(d1, XP && pos == 0 ? e : aa + 12, bb[2], bb[3]);
        mma16816(c0, aa, bb[0], bb[1]);
        mma16816(d0, aa + 8, bb[2], bb[3]);
        if (r_pos_ss(pos) && pos + 3 < 16) {
#pragma unroll
            for (int q = 0; q < 4; q++) ldsm4t(a + 4 * q, ((q & 1) ? aA1 : aA0) + (r_ss(pos) + 1) * 16384 + (q >> 1) * 2048);
        }
        SCHED_FENCE();
    }
    if (XP && !in) mbar_wait(sb + RB_ATT, par);
#pragma unroll
    for (int i = 0; i < 4; i++) { c1[i] += d1[i]; c0[i] += d0[i]; }
}

DEVI uint32_t k_frag_off(int lane) { return (uint32_t)((((lane >> 3) & 1) * 16 + (lane >> 4) * 8 + (lane & 7)) * 16); }
DEVI uint32_t v_frag_off(int lane) { return (uint32_t)(((lane >> 3) & 1) * 2048 + ((lane >> 4) * 8 + (lane & 7)) * 16); }
DEVI void pv_pair(float (*o)[4], const uint32_t* p, const uint32_t* v) {
#pragma unroll
    for (int n = 0; n < 4; n++) mma16816(o[n], p, v[2 * n], v[2 * n + 1]);
}
DEVI void pv_single(float (*o)[4], const uint32_t* p, const uint32_t* v) {
#pragma unroll
    for (int n = 0; n < 4; n++) mma1688(o[n], p[0], p[1], v[n]);
}
DEVI void s_tile(const uint32_t* qa, const uint32_t* k, float& s0, float& s1) {
    float c[4][4];
#pragma unroll
    for (int q = 0; q < 4; q++) { c[q][0] = c[q][1] = c[q][2] = c[q][3] = 0.f; }
#pragma unroll
    for (int q = 0; q < 4; q++) {
        mma16816(c[2 * (q & 1)], qa + 4 * q, k[4 * q], k[4 * q + 1]);
        mma16816(c[2 * (q & 1) + 1], qa + 4 * q, k[4 * q + 2], k[4 * q + 3]);
    }
    s0 = (c[0][0] + c[1][2]) + (c[2][0] + c[3][2]);
    s1 = (c[0][1] + c[1][3]) + (c[2][1] + c[3][3]);
}
DEVI void mem_scores(uint32_t sb, int s, int warp, int lane) {
    const uint32_t ka = sb + RS_K + k_frag_off(lane) + (1 + warp) * 2048;
    uint32_t qa[16], kx[16];
    const bool in = mbar_try(sb + RB_KV, s & 1);
    nbar_sync(NB_Q, 256);
#pragma unroll
    for (int q = 0; q < 4; q++) ldsm4t(qa + 4 * q, sb + RS_Q + q * 512 + lane * 16);
    if (!in) mbar_wait(sb + RB_KV, s & 1);
#pragma unroll
    for (int q = 0; q < 4; q++) ldsm4t(kx + 4 * q, ka + q * 512);
    SCHED_FENCE();
    float s0, s1;
    s_tile(qa, kx, s0, s1);
    asm volatile("st.shared.v2.f32 [%0], {%1,%2};" :: "r"(sb + RS_SX + warp * 256 + lane * 8), "f"(s0), "f"(s1) : "memory");
    nbar_arrive(NB_XS, 256);
}
DEVI void mem_attn(uint32_t sb, int s, int warp, int lane) {
    const uint32_t ka = sb + RS_K + k_frag_off(lane), va = sb + RS_V + warp * 512;
    const uint32_t dst = sb + RS_O + warp * 512 + (lane & 3) * 128 + (lane >> 2) * 16;
    [[maybe_unused]] constexpr int g = 0;
    uint32_t qa[16], vx[16];
    float sc[10];
    nbar_sync(NB_Q, 256);
    EV(EV_BIG0 && lds32(sb + RS_Q) != 0x12345678u, s, 8);
#pragma unroll
    for (int q = 0; q < 4; q++) ldsm4t(qa + 4 * q, sb + RS_Q + q * 512 + lane * 16);
    mbar_wait(sb + RB_K, s & 1);
    EV(EV_BIG0, s, 9);
    {
        uint32_t km[16];
#pragma unroll
        for (int q = 0; q < 4; q++) ldsm4t(km + 4 * q, ka + q * 512);
        nbar_sync(NB_XS, 256);
        s_tile(qa, km, sc[0], sc[1]);
    }
#pragma unroll
    for (int n = 0; n < 4; n++) { const float2 v = lds64f(sb + RS_SX + n * 256 + lane * 8); sc[2 + 2 * n] = v.x; sc[3 + 2 * n] = v.y; }
    const bool v_in = mbar_try(sb + RB_V, s & 1);
    float m = fmaxf(fmaxf(fmaxf(sc[2], sc[3]), fmaxf(sc[4], sc[5])), fmaxf(fmaxf(sc[6], sc[7]), fmaxf(sc[8], sc[9])));
    m = fmaxf(m, fmaxf(sc[0], sc[1]));
    m = fmaxf(fmaxf(m, __shfl_xor_sync(0xffffffffu, m, 1)), fmaxf(__shfl_xor_sync(0xffffffffu, m, 2), __shfl_xor_sync(0xffffffffu, m, 3)));
    EV(warp == 0 && m != 1.2345e30f && elect_one(), s, 5);
    if (!v_in) mbar_wait(sb + RB_V, s & 1);
    EV(warp == 0 && elect_one(), s, 13);
    uint32_t vm[4], p[10];
#pragma unroll
    for (int q = 3; q >= 0; q--) ldsm4(vx + 4 * q, va + 2048 + (q >> 1) * 4096 + (q & 1) * 256 + v_frag_off(lane));
    ldsm4(vm, va + lane * 16);
    SCHED_FENCE();
    const float nm = -m * SCALE_LOG2E;
    float l = 0.f;
#pragma unroll
    for (int n = 4; n >= 0; n--) {
        const float e0 = ex2(fmaf(sc[2 * n], SCALE_LOG2E, nm)), e1 = ex2(fmaf(sc[2 * n + 1], SCALE_LOG2E, nm));
        l += e0 + e1;
        p[2 * n] = pack_bf16(e0, e1); p[2 * n + 1] = __float_as_uint(e0);
    }
    float o[4][4];
#pragma unroll
    for (int n = 0; n < 4; n++) { o[n][0] = o[n][1] = o[n][2] = o[n][3] = 0.f; }
    pv_pair(o, p + 6, vx + 8);
    pv_pair(o, p + 2, vx);
    pv_single(o, p, vm);
    l = (l + __shfl_xor_sync(0xffffffffu, l, 1)) + (__shfl_xor_sync(0xffffffffu, l, 2) + __shfl_xor_sync(0xffffffffu, l, 3));
    const uint4 u = make_uint4(pack_bf16(o[0][0], o[0][1]), pack_bf16(o[1][0], o[1][1]), pack_bf16(o[2][0], o[2][1]), pack_bf16(o[3][0], o[3][1]));
    st_async128(mapa(dst, 1), u.x, u.y, u.z, u.w, mapa(sb + RB_O, 1));
    st_async128(mapa(dst, 2), u.x, u.y, u.z, u.w, mapa(sb + RB_O, 2));
    const uint32_t dl = sb + RS_INV + (lane & 3) * 32 + (lane & 28);
    asm volatile("st.async.weak.shared::cluster.mbarrier::complete_tx::bytes.b32 [%0], %1, [%2];"
                 :: "r"(mapa(dl, 1 + (warp & 1))), "r"(__float_as_uint(l)), "r"(mapa(sb + RB_O, 1 + (warp & 1))) : "memory");
    sts128(dst, u);
    sts32(dl, __float_as_uint(l));
    __syncwarp();
    if (elect_one()) mbar_arrive(sb + RB_O);
    EV(warp == 0 && elect_one(), s, 15);
}

DEVI void ta_mask(float* c, int cw, int lane) {
    const int mt = cw >= 3, over = 8 * (cw - 3 * mt - 1) + 2 * (lane & 3) - 16 * mt - (lane >> 2);
    if (over > 0) c[0] = -INFINITY;
    if (over >= 0) c[1] = -INFINITY;
    if (over > 8) c[2] = -INFINITY;
    if (over >= 8) c[3] = -INFINITY;
}
DEVI void ta_scores(uint32_t sb, int seg, int warp, int lane) {
    const int tx = warp == 3 ? 0 : (warp == 2 ? 1 : 4 + 2 * warp), ty = warp == 3 ? 3 : tx + 1;
    const uint32_t qa = sb + RS_QX + ((warp < 2 ? 2 : 0) + ((lane >> 3) & 1)) * 2048 + ((lane >> 4) * 8 + (lane & 7)) * 16;
    const uint32_t ka = sb + RS_K + (warp < 2 ? tx - 3 : tx) * 2048 + lane * 16;
    float x[4] = {0.f, 0.f, 0.f, 0.f}, y[4] = {0.f, 0.f, 0.f, 0.f};
    mbar_wait(sb + RB_QX, seg & 1);
    if (warp < 3) {
#pragma unroll
        for (int j = 0; j < 4; j++) {
            uint32_t a0[4], a1[4], bx[4], by[4];
            ldsm4t(a0, qa + j * 512); ldsm4t(bx, ka + j * 512); ldsm4t(by, ka + 2048 + j * 512); ldsm4t(a1, qa + j * 512 + 256);
            mma16816(x, a0, bx[0], bx[1]); mma16816(y, a0, by[0], by[1]);
            mma16816(x, a1, bx[2], bx[3]); mma16816(y, a1, by[2], by[3]);
        }
        ta_mask(x, tx, lane); ta_mask(y, ty, lane);
    } else {
        mbar_wait(sb + RB_K, seg & 1);
#pragma unroll
        for (int j = 0; j < 4; j++) {
            uint32_t a0[4], a1[4], a2[4], a3[4], b[4];
            ldsm4t(a0, qa + j * 512); ldsm4t(b, ka + j * 512); ldsm4t(a2, qa + 4096 + j * 512);
            ldsm4t(a1, qa + j * 512 + 256); ldsm4t(a3, qa + 4096 + j * 512 + 256);
            mma16816(x, a0, b[0], b[1]); mma16816(y, a2, b[0], b[1]);
            mma16816(x, a1, b[2], b[3]); mma16816(y, a3, b[2], b[3]);
        }
    }
    nbar_sync(NB_WG + 1, 128);
    asm volatile("st.shared.v2.f32 [%0], {%1,%2};" :: "r"(sb + RS_QX + 4096 + tx * 256 + lane * 8), "f"(fmaxf(x[0], x[1])), "f"(fmaxf(x[2], x[3])) : "memory");
    asm volatile("st.shared.v2.f32 [%0], {%1,%2};" :: "r"(sb + RS_QX + 4096 + ty * 256 + lane * 8), "f"(fmaxf(y[0], y[1])), "f"(fmaxf(y[2], y[3])) : "memory");
    nbar_sync(NB_WG + 1, 128);
    float m[4] = {-INFINITY, -INFINITY, -INFINITY, -INFINITY};
#pragma unroll
    for (int n = 0; n < 8; n++) {
        if (n < 3 ? warp >= 2 : warp != 2) {
            const float2 v = lds64f(sb + RS_QX + 4096 + n * 256 + lane * 8);
            m[n < 3 ? 0 : 2] = fmaxf(m[n < 3 ? 0 : 2], v.x); m[n < 3 ? 1 : 3] = fmaxf(m[n < 3 ? 1 : 3], v.y);
        }
    }
#pragma unroll
    for (int o = 1; o < 4; o <<= 1) {
#pragma unroll
        for (int i = 0; i < 4; i++) m[i] = fmaxf(m[i], __shfl_xor_sync(0xffffffffu, m[i], o));
    }
    const float x0 = (warp < 2 ? m[2] : m[0]) * -SCALE_LOG2E, x1 = (warp < 2 ? m[3] : m[1]) * -SCALE_LOG2E;
    const float y0 = (warp == 2 ? m[0] : m[2]) * -SCALE_LOG2E, y1 = (warp == 2 ? m[1] : m[3]) * -SCALE_LOG2E;
    sts64(sb + RS_QX + tx * 256 + lane * 8, pack_bf16(ex2(fmaf(x[0], SCALE_LOG2E, x0)), ex2(fmaf(x[1], SCALE_LOG2E, x0))),
                                            pack_bf16(ex2(fmaf(x[2], SCALE_LOG2E, x1)), ex2(fmaf(x[3], SCALE_LOG2E, x1))));
    sts64(sb + RS_QX + ty * 256 + lane * 8, pack_bf16(ex2(fmaf(y[0], SCALE_LOG2E, y0)), ex2(fmaf(y[1], SCALE_LOG2E, y0))),
                                            pack_bf16(ex2(fmaf(y[2], SCALE_LOG2E, y1)), ex2(fmaf(y[3], SCALE_LOG2E, y1))));
}
template <int MT>
DEVI void ta_output(uint32_t sb, int seg, int head, int j, int lane) {
    const uint32_t pa = sb + RS_QX + MT * 768 + lane * 8, vb = sb + RS_V + j * 512;
    uint32_t p[6 + 4 * MT], v[12 + 8 * MT];
#pragma unroll
    for (int n = 0; n < 3 + 2 * MT; n++)
        asm volatile("ld.shared.v2.u32 {%0,%1}, [%2];" : "=r"(p[2 * n]), "=r"(p[2 * n + 1]) : "r"(pa + n * 256) : "memory");
#pragma unroll
    for (int q = 0; q < 2 + 2 * MT; q++) ldsm4(v + 4 * q, vb + (q >> 1) * 4096 + (q & 1) * 256 + v_frag_off(lane));
    ldsm4(v + 8 + 8 * MT, vb + 4096 + MT * 4096 + lane * 16);
    float o[4][4], l[4] = {0.f, 0.f, 0.f, 0.f};
#pragma unroll
    for (int n = 0; n < 4; n++) { o[n][0] = o[n][1] = o[n][2] = o[n][3] = 0.f; }
    mma16816(l, p, 0x3F803F80u, 0x3F803F80u);
    pv_pair(o, p, v);
    if (MT) { mma16816(l, p + 4, 0x3F803F80u, 0x3F803F80u); pv_pair(o, p + 4, v + 8); }
    mma1688(l, p[4 + 4 * MT], p[5 + 4 * MT], 0x3F803F80u);
    pv_single(o, p + 4 + 4 * MT, v + 8 + 8 * MT);
    const float i0 = rcp_fast(l[0]), i1 = rcp_fast(l[2]);
    bf16* dst = g_ox + (uint32_t)((seg * 32 + MT * 16 + (lane >> 2)) * HD + head * DH + j * 32 + (lane & 3) * 8);
    asm volatile("st.global.v4.u32 [%0], {%1,%2,%3,%4};" :: "l"(dst), "r"(pack_bf16(o[0][0] * i0, o[0][1] * i0)), "r"(pack_bf16(o[1][0] * i0, o[1][1] * i0)),
                 "r"(pack_bf16(o[2][0] * i0, o[2][1] * i0)), "r"(pack_bf16(o[3][0] * i0, o[3][1] * i0)) : "memory");
    asm volatile("st.global.v4.u32 [%0], {%1,%2,%3,%4};" :: "l"(dst + 8 * HD), "r"(pack_bf16(o[0][2] * i1, o[0][3] * i1)), "r"(pack_bf16(o[1][2] * i1, o[1][3] * i1)),
                 "r"(pack_bf16(o[2][2] * i1, o[2][3] * i1)), "r"(pack_bf16(o[3][2] * i1, o[3][3] * i1)) : "memory");
}

template <bool XP>
DEVI void big_main(const uint32_t* w, const uint32_t sb, const int g, const int warp, const uint32_t rank, const int head,
                   const CUtensorMap* tmX, const bf16* xg, const unsigned E) {
    float xa[32];
    uint32_t a[16];
    const uint32_t aB = __shfl_sync(0xffffffffu, sb + RS_MEM + (g * 32 + (tid_now() & 31)) * 16, tid_now() & 31);
#define lane0 ((int)(opaque(aB) >> 4) & 31)
    const uint32_t aA0 = sb + RS_WSS + g * (8192 + 4096) + a_frag_off(lane0, warp);
    const uint32_t aBf = sb + RS_MEM + g * 512 + b_frag_off(lane0);
    if constexpr (XP) {
        mbar_wait(sb + RB_XF + g * 8, 0);
        x_half<0>(xa, a, aA0, w, sb, 0, g, warp, tmX);
        mbar_wait(sb + RB_XF + g * 8, 1);
        x_half<1>(xa, a, aA0, w, sb, 0, g, warp, tmX);
        x_finish(xa, sb, 0, g, warp, lane0, tmX);
    }
    nbar_sync(NB_BIG, 256);
    for (int s = 0; s < NSEG; s++) {
        float c0[4], c1[4];
        mem_pass<XP>(c0, c1, a, w, sb, aA0, aBf, g, warp, s);
        EV(EV_BIG0 && c0[0] != 1.2345e30f, s, 3);
        const uint32_t xs = aB + (RS_O - RS_MEM) + (warp - g) * 512;
        sts128f(xs + g * 2048, c1);
        auto combine = [&]() {
            const uint32_t d = sb + (XP ? (rank == 1 ? RS_K : RS_V) : RS_Q) + (g * 4 + warp) * 256 + lane0 * 4;
            const uint32_t rbar = XP ? mapa(sb + (rank == 1 ? RB_K : RB_V), 0) : 0u;
            nbar_sync(NB_PAIR + warp, 64);
            const uint4 v = lds128(xs + (g ^ 1) * 2048);
            const uint32_t p0 = pack_bf16(c0[0] + __uint_as_float(v.x), c0[1] + __uint_as_float(v.y));
            const uint32_t p1 = pack_bf16(c0[2] + __uint_as_float(v.z), c0[3] + __uint_as_float(v.w));
            if constexpr (XP) { st_async32(mapa(d, 0), p0, rbar); st_async32(mapa(d + 128, 0), p1, rbar); }
            else { sts32(d, p0); sts32(d + 128, p1); }
            EV(EV_BIG0, s, 4);
        };
        combine();
        if constexpr (XP) {
            if (s == NSEG - 1) break;
            x_half<0>(xa, a, aA0, w, sb, s + 1, g, warp, tmX);
            EV(EV_BIG0, s, 5);
            EVCAL(s);
            mbar_wait(sb + RB_XF + g * 8, 1);
            nbar_sync(NB_WO, 384);
            EV(EV_BIG0 && lds32(sb + RS_O) != 0x12345678u, s, 6);
            x_half<1>(xa, a, aA0, w, sb, s + 1, g, warp, tmX);
            EV(EV_BIG0, s, 7);
            x_finish(xa, sb, s + 1, g, warp, lane0, tmX);
        } else {
            if (g == 0) {
                if (s < NSEG - 1) mem_attn(sb, s, warp, lane0);
            } else {
                if (s < NSEG - 1) mem_scores(sb, s, warp, lane0); else mbar_wait(sb + RB_KV, s & 1);
                if (s == 0 && warp == 0) {
                    wait_count_warp(&g_cnt[C_QH], 64 * E);
                    if (elect_one()) {
                        fence_proxy_global();
                        mbar_expect_tx(sb + RB_QX, 8192);
                        bulk_load(sb + RS_QX, g_qx + (uint32_t)(head * 4096), 8192, sb + RB_QX);
                    }
                    __syncwarp();
                }
                ta_scores(sb, s, warp, lane0);
            }
            EVCAL(s);
            mbar_wait(sb + RB_V, s & 1);
            if (s < NSEG - 1) nbar_sync(NB_WO, 384); else nbar_sync(NB_BIG, 256);
            EV(EV_BIG0 && lds32(sb + RS_O) != 0x12345678u, s, 6);
            if (g == 0) ta_output<0>(sb, s, head, warp, lane0); else ta_output<1>(sb, s, head, warp, lane0);
            nbar_sync(NB_BIG, 256);
            EV(EV_BIG0 && lds32(sb + RS_O) != 0x12345678u, s, 7);
            if (g == 0 && warp == 0 && s + 1 < NSEG) {
                if (elect_one()) {
                    mbar_arrive_remote(mapa(sb + RB_ATT, 1));
                    mbar_arrive_remote(mapa(sb + RB_ATT, 2));
                    mbar_expect_tx(sb + RB_KV, 8192);
                    mbar_expect_tx(sb + RB_K, 2048);
                    mbar_expect_tx(sb + RB_V, 2048 + 8192);
                    mbar_arrive(sb + RB_T);
                }
                __syncwarp();
            }
        }
    }
    if constexpr (!XP) { if (tid_now() == 0) signal_count(&g_prog[(NSEG - 1) >> 2]); }
#undef lane0
}

template <int T, int K0, int K1>
DEVI void wo_part(float* acc) {
    constexpr uint32_t dWo = cdesc(T < 5 ? RS_WO + T * 16384 : RS_WO5, 16), dO = cdesc(RS_O, 128);
#pragma unroll
    for (int kk = K0; kk < K1; kk++) {
        if (kk == 0) { if (T < 3) wgmma_n8_ss_first<0>(acc, dWo, dO); else wgmma_n8_ss<0, 0>(acc, dWo, dO); }
        else wgmma_n8_ss<0, 1>(acc, dWo + kk * 128, dO + kk * 16);
    }
    wg_commit();
}
DEVI void red3(uint8_t* p, uint32_t a, uint32_t b, uint32_t c, uint32_t one) {
    asm volatile("red.relaxed.gpu.global.add.noftz.v4.bf16x2 [%0], {%1,%2,%3,%4};" :: "l"(p), "r"(a), "r"(b), "r"(c), "r"(one) : "memory");
}
constexpr int ACC_CH = 3 * 16 * 1024;
template <bool Q>
DEVI void wo_phase(uint32_t sb, int s, int warp, uint8_t* p, uint32_t ainv, int gap) {
    float a0[4], a1[4], a2[4];
    fence_proxy_async();
    const float2 iv = lds64f(ainv);
    SCHED_FENCE();
    const float i0 = rcp_fast(iv.x), i1 = rcp_fast(iv.y);
#define WORD(a, h) pack_bf16(a[2 * h] * i0, a[2 * h + 1] * i1)
    wg_fence();
    wo_part<0, 0, 8>(a0); wo_part<1, 0, 8>(a1); wo_part<2, 0, 8>(a2);
    if (!Q && WO_REL == 4) nbar_arrive(NB_WO, 384);
    wg_wait<1>(); reg_fence<4>(a0); reg_fence<4>(a1);
    if (!Q && WO_REL == 3) nbar_arrive(NB_WO, 384);
    red3(p, WORD(a0, 0), WORD(a0, 1), WORD(a1, 0), 0x3F80u);
    SCHED_FENCE();
    EV(warp == 0 && elect_one(), s, 11);
    wg_wait<0>(); reg_fence<4>(a2);
    if (!Q && WO_REL == 2) nbar_arrive(NB_WO, 384);
    red3(p + ACC_CH, WORD(a2, 0), WORD(a2, 1), WORD(a1, 1), 0x3F80u);
    SCHED_FENCE();
    if (Q || WO_REL < 2) { const uint32_t t = clk32() + gap; while ((int)(clk32() - t) < 0) { } }
    wg_fence();
    wo_part<3, 0, 8>(a0); wo_part<4, 0, 8>(a1);
    if (Q) {
        wo_part<5, 0, 8>(a2);
        wg_wait<1>(); reg_fence<4>(a0); reg_fence<4>(a1);
        red3(p + 2 * ACC_CH, WORD(a0, 0), WORD(a0, 1), WORD(a1, 0), 0x3F80u);
        SCHED_FENCE();
        wg_wait<0>(); reg_fence<4>(a2);
        red3(p + 3 * ACC_CH, WORD(a2, 0), WORD(a2, 1), WORD(a1, 1), 0x3F80u);
        nbar_arrive(NB_WO, 384);
    } else {
        wg_wait<1>();
        nbar_arrive(NB_WO, 384);
        wg_wait<0>(); reg_fence<4>(a0); reg_fence<4>(a1);
        red3(p + 2 * ACC_CH, WORD(a0, 0), WORD(a0, 1), WORD(a1, 0), 0x3F80u);
        red3(p + 3 * ACC_CH, 0u, 0u, WORD(a1, 1), 0x3F80u);
    }
#undef WORD
}
DEVI void unit_pack(uint32_t* u, uint32_t x0, uint32_t x1, uint32_t x2, uint32_t x3) {
    u[0] = __byte_perm(x0, x1, 0x5410); u[1] = __byte_perm(x2, x3, 0x5410); u[2] = __byte_perm(x0, x1, 0x7632); u[3] = __byte_perm(x2, x3, 0x7632);
}
DEVI void unit_send(uint32_t d, const uint32_t* u, uint32_t bar, uint32_t r1, uint32_t r2) {
    st_async128(mapa(d, r1), u[0], u[1], u[2], u[3], mapa(bar, r1));
    st_async128(mapa(d, r2), u[0], u[1], u[2], u[3], mapa(bar, r2));
}
template <bool Q>
DEVI void stage_sums(uint32_t sb, int s, uint32_t rank, int warp, const uint8_t* src, uint32_t l, uint32_t gate) {
    uint4 v[4];
    while ((int)(clk32() - gate) < 0) { }
    EV(elect_one(), s, 16 + warp);
#pragma unroll
    for (int j = 0; j < 4; j++) v[j] = ld_rlx4(src + j * 1024);
    const uint32_t col = sb + RS_MEM + ((Q ? 0 : (rank == 1 ? 6 : 11)) + 3 * (warp >> 1)) * 1024 + ((l >> 2) & 0x300) + (l & 0x70);
    const uint32_t d0 = col + (warp & 1) * 2048, d1 = d0 ^ 160, d2 = (col ^ ((warp & 1) * 160)) + 1024;
    const uint32_t r1 = Q ? 1 : 0, r2 = Q ? 2 : 3 - rank, bar = sb + RB_G + 8 * (warp < 2 ? warp : 2);
    int n = 0;
    while (!__all_sync(0xffffffffu, v[0].w == 0x4200u && v[1].w == 0x4200u && v[2].w == 0x4200u && v[3].w == 0x4200u)) {
#pragma unroll
        for (int j = 0; j < 4; j++) v[j] = ld_rlx4(src + j * 1024);
        if (++n > SPIN_LIMIT) TRAP(0x20000000u | (s << 8) | warp);
    }
    EV(elect_one(), s, 24 + warp);
    uint32_t u[12];
    unit_pack(u + 8, v[0].z, v[1].z, v[2].z, v[3].z);
    unit_send(d2, u + 8, bar, r1, r2);
    if (Q || warp < 3) {
        unit_pack(u, v[0].x, v[1].x, v[2].x, v[3].x);
        unit_pack(u + 4, v[0].y, v[1].y, v[2].y, v[3].y);
        unit_send(d0, u, bar, r1, r2);
        unit_send(d1, u + 4, bar, r1, r2);
        sts128(d0, make_uint4(u[0], u[1], u[2], u[3]));
        sts128(d1, make_uint4(u[4], u[5], u[6], u[7]));
    }
    sts128(d2, make_uint4(u[8], u[9], u[10], u[11]));
    __syncwarp();
    if (elect_one()) mbar_expect_tx(bar, warp < 2 ? 3072u : (warp == 3 ? 0u : (Q ? 4096u : 5120u)));
    EV(elect_one(), s, 20 + warp);
}
DEVI void wo_permute(uint32_t a, int n) {
    const uint32_t flip = (a >> 3) & 16;
#pragma unroll 2
    for (int i = 0; i < n; i++, a += 4096) {
        const uint4 v = lds128(a ^ flip), u = lds128(a ^ flip ^ 16);
        sts128(a ^ flip, make_uint4(__byte_perm(v.x, v.y, 0x5410), __byte_perm(v.x, v.y, 0x7632), __byte_perm(u.x, u.y, 0x5410), __byte_perm(u.x, u.y, 0x7632)));
        sts128(a ^ flip ^ 16, make_uint4(__byte_perm(v.z, v.w, 0x5410), __byte_perm(v.z, v.w, 0x7632), __byte_perm(u.z, u.w, 0x5410), __byte_perm(u.z, u.w, 0x7632)));
    }
}
DEVI uint32_t acc_clear(int slot, int idx, uint32_t lo) {
    uint8_t* p = g_acc + (uint32_t)(slot * 128 + idx * 3072 + (lo < 3072 ? lo : lo - 1024));
    st_rlx4(p, 0u, 0u, 0u, 0u);
    uint32_t z; asm volatile("ld.relaxed.gpu.global.u32 %0, [%1];" : "=r"(z) : "l"(p) : "memory");
    return z;
}

template <bool Q>
DEVI void aux_main(uint32_t sb, int warp, uint32_t rank, int head, const CUtensorMap* tmX, const bf16* xg, unsigned E, const int delay, const int gap, const int vdelay) {
    const uint32_t lo = __shfl_sync(0xffffffffu, ((tid_now() >> 3) & 3) * 1024 + (tid_now() & 7) * 16, tid_now() & 31);
    for (int s = 0; s < NSEG - 1; s++) {
        if (!Q && warp == 0 && elect_one()) mbar_expect_tx(sb + RB_O, 2048 + 256);
        __syncwarp();
        const uint32_t slot = (s & 3) * 128;
        mbar_wait(sb + RB_O, s & 1);
        EV(warp == 0 && elect_one(), s, 10);
        wo_phase<Q>(sb, s, warp, g_acc + (uint32_t)(slot + (rank * 4 + warp) * 4096 + opaque(lo)), sb + RS_INV + ((opaque(lo) >> 1) & 24), gap);
        SCHED_FENCE();
        const uint32_t t_o = clk32();
        EV(warp == 0 && elect_one(), s, 12);
        {
            const uint32_t l = opaque(lo);
            stage_sums<Q>(sb, s, rank, warp, g_acc + (uint32_t)(slot + rank * 16384 + warp * ACC_CH + (l & 0xC00) * 4 + (l & 0x70)), l, t_o + delay);
        }
        EV(warp == 2 && elect_one(), s, 14);
        if (warp == 3) {
            if (Q) {
                mbar_wait(sb + RB_T, s & 1);
                if (s == 3) wait_count_warp(&g_cnt[C_Q], 64 * E);
                if (elect_one()) {
                    if (s == 3) fence_proxy_global();
                    fence_proxy_async();
                    mbar_expect_tx(sb + RB_QX, 8192);
                    bulk_load(sb + RS_QX, g_qx + (uint32_t)(((s + 1) * NH + head) * 4096), 8192, sb + RB_QX);
                    if (head == 0) { TLOG(1400 + s, 0, gtime()); TLOG(1400 + s, 1, clock64()); }
                }
                __syncwarp();
                const bool fresh = (s & 7) == 6 && s + 2 < NSEG;
                if (fresh) wait_count_warp(&g_cnt[C_Q + ((s + 2) >> 3)], 64 * E);
                if (elect_one()) {
                    if (fresh) fence_proxy_global();
                    if (s + 2 < NSEG && s != 2) l2_prefetch(g_qx + (uint32_t)(((s + 2) * NH + head) * 4096), 8192);
                    if (s + 4 < NSEG) l2_prefetch(xg + (uint32_t)(((s + 4) * 32 + head) * DM), 2048);
                    signal_count(&g_prog[s >> 2]);
                }
                __syncwarp();
            } else {
                const uint32_t zero = acc_clear((s + 2) & 3, 2 * head + (int)rank - 1, opaque(lo));
                mbar_wait(sb + RB_G + 16, s & 1);
                x_send(sb, s + 1, rank, vdelay);
                if (__any_sync(0xffffffffu, zero != 0u)) __trap();
            }
        }
    }
}

DEVI void load_weights(uint32_t sb, const CUtensorMap* tmW, const CUtensorMap* tmWo, int head, uint32_t rank) {
    const uint32_t bW = sb + RB_W, bSF = sb + RB_SF, bSE = sb + RB_SE;
    const int ntile = rank == 0 ? 6 : 5, tile0 = rank == 0 ? 0 : (rank == 1 ? 6 : 11);
    mbar_expect_tx(bW, R_NSS * 16384);
    mbar_expect_tx(sb + RB_WO, ntile * 16384);
    for (int pass = 0; pass < 2; pass++) {
        for (int pos = 0; pos < 16; pos++) {
            const int k = (int)((R_TORD_PACK >> (4 * pos)) & 15ull) * 64, rd = pos - pos / 3, slot = rd % 5;
            if (r_pos_ss(pos)) {
                if (pass) continue;
                const uint32_t dst = sb + RS_WSS + (pos / 3) * 16384;
                tma_load_2d(dst, tmW, head * DH, k, bW);
                tma_load_2d(dst + 8192, tmW, head * DH + 64, k, bW);
            } else if (pass == (rd >= 5)) {
                if (rd >= 5) mbar_wait(bSE + 8 * slot, ((rd / 5) - 1) & 1);
                mbar_expect_tx(bSF + 8 * slot, 16384);
                const uint32_t dst = sb + RS_WO + slot * 16384;
                tma_load_2d(dst, tmW, head * DH, k, bSF + 8 * slot);
                tma_load_2d(dst + 8192, tmW, head * DH + 64, k, bSF + 8 * slot);
            }
        }
    }
    if (rank == 0) tma_load_wo(sb + RS_WO5, tmWo, 5 * 64, head * 4, sb + RB_WO);
    for (int i = 1; i <= 5; i++) {
        const int slot = i % 5, last = slot + 10 < R_NRS ? slot + 10 : slot + 5;
        mbar_wait(bSE + 8 * slot, (last / 5) & 1);
        tma_load_wo(sb + RS_WO + slot * 16384, tmWo, (tile0 + slot) * 64, head * 4, sb + RB_WO);
    }
}
template <bool XP>
DEVI void big_prologue(uint32_t* w, uint32_t sb, int g, int warp, const bf16* __restrict__ mem0) {
    const int tid = tid_now(), lane = tid & 31;
    {
        const uint32_t* m = (const uint32_t*)(mem0 + (lane >> 2) * DM + (tid >> 5) * 16) + (lane & 3);
        uint32_t u[16];
#pragma unroll
        for (int j = 0; j < 8; j++) { u[2 * j] = m[j * 64]; u[2 * j + 1] = m[j * 64 + 4]; }
#pragma unroll
        for (int j = 0; j < 8; j++) sts64(sb + RS_MEM + ((tid >> 5) + j * 8) * 256 + b_frag_off(lane), u[2 * j], u[2 * j + 1]);
    }
    const uint32_t a0 = sb + RS_WO + g * (8192 + 4096) + a_frag_off(lane, warp), a1 = a0 + 8192 - g * 16384;
#pragma unroll
    for (int rd = 0; rd < R_NRS; rd++) {
        const int slot = rd % 5;
        mbar_wait(sb + RB_SF + 8 * slot, (rd / 5) & 1);
#pragma unroll
        for (int q = 0; q < 4; q++) {
            if (XP && rd == 0 && q == 3) {
                sts128(sb + RS_WX + g * 2048 + (tid & 127) * 16, lds128(sb + RS_WO + 8192 - g * 4096 + 2048 + (tid & 127) * 16));
                fence_proxy_async();
                nbar_sync(NB_WG + g, 128);
            } else ldsm4t(&w[rd * 16 + q * 4], ((q & 1) ? a1 : a0) + slot * 16384 + (q >> 1) * 2048);
        }
        mbar_arrive(sb + RB_SE + 8 * slot);
    }
    mbar_wait(sb + RB_W, 0);
}

#define REC_END() do { if (tid_now() == 0) TLOG(1024 + blockIdx.x, 1, gtime()); } while (0)
__global__ void __launch_bounds__(384, 1)
k_rec(const __grid_constant__ PMaps mp, const __grid_constant__ CUtensorMap tmWk, const __grid_constant__ CUtensorMap tmWv,
      const __grid_constant__ CUtensorMap tmWo, const __grid_constant__ CUtensorMap tmX, const bf16* __restrict__ mem0, const bf16* __restrict__ xg,
      int4 tq, int4 tk, int rec) {
    extern __shared__ __align__(1024) uint8_t smem_raw[];
    const uint32_t sb = smem_u32(smem_raw);
    if ((sb & 0x3FFFFu) != SB0) __trap();
    const int tid = threadIdx.x;
    const int wg = __shfl_sync(0xffffffffu, tid >> 7, 0), warp = __shfl_sync(0xffffffffu, (tid >> 5) & 3, 0);
    uint32_t rank; asm("mov.u32 %0, %%cluster_ctarank;" : "=r"(rank));
    int head; asm("mov.u32 %0, %%clusterid.x;" : "=r"(head));
    asm volatile("griddepcontrol.launch_dependents;");
    if (tid == 0 && rec) {
        mbar_init(sb + RB_G, 1);
        mbar_init(sb + RB_G + 8, 1);
        mbar_init(sb + RB_G + 16, 2);
        mbar_init(sb + RB_T, 1); mbar_init(sb + RB_WO, 1);
        mbar_init(sb + RB_K, 1); mbar_init(sb + RB_V, 1); mbar_init(sb + RB_KV, 1); mbar_init(sb + RB_QX, 1);
        mbar_init(sb + RB_O, rank == 0 ? 4 : 1); mbar_init(sb + RB_ATT, 1); mbar_init(sb + RB_W, 1);
        for (int i = 0; i < 5; i++) { mbar_init(sb + RB_SF + 8 * i, 1); mbar_init(sb + RB_SE + 8 * i, 256); }
        for (int i = 0; i < 2; i++) mbar_init(sb + RB_XF + 8 * i, X_SLOTS);
        fence_mbar_init();
        if (rank == 0) { mbar_expect_tx(sb + RB_KV, 8192); mbar_expect_tx(sb + RB_K, 2048); mbar_expect_tx(sb + RB_V, 2048 + 8192); }
    }
    __syncthreads();
    asm volatile("barrier.cluster.arrive.release.aligned;" ::: "memory");

    if (wg < 2) {
        reg_inc<REG_KB>();
        if (rank != 0) {
            uint32_t w[R_NRS * 16];
            if ((tid & 127) == 0) for (int j = 0; j < X_SLOTS; j++) x_load(sb, 0, j, wg, &tmX);
            __syncwarp();
            cluster_wait();
            big_prologue<true>(w, sb, wg, warp, mem0);
            big_main<true>(w, sb, wg, warp, rank, head, &tmX, xg, 0u);
            REC_END();
        } else if (rec) {
            uint32_t w[R_NRS * 16];
            cluster_wait();
            big_prologue<false>(w, sb, wg, warp, mem0);
            big_main<false>(w, sb, wg, warp, rank, head, &tmX, xg, *(volatile unsigned*)&g_epoch + 1);
            REC_END();
        } else cluster_wait();
        nbar_sync(0, 384);
        nbar_sync(0, 384);
        post_consumer(mp, sb, wg, warp);
    } else {
        reg_dec<504 - 2 * REG_KB>();
        if (rec) {
            if (tid == 256) {
                if (rank == 0) l2_prefetch(xg + (uint32_t)(head * 8 * DM), 16384);
                load_weights(sb, rank == 0 ? &mp.wq : (rank == 1 ? &tmWk : &tmWv), &tmWo, head, rank);
            }
            if (warp == 3 && rank != 0) {
                const uint32_t lo = ((tid >> 3) & 3) * 1024 + (tid & 7) * 16;
                acc_clear(0, 2 * head + (int)rank - 1, lo); acc_clear(1, 2 * head + (int)rank - 1, lo);
                __threadfence();
                __syncwarp();
                if (tid == 256 + 96) atomicAdd(&g_zero, 1u);
            }
            __syncwarp();
        }
        cluster_wait();
        const unsigned E = __shfl_sync(0xffffffffu, *(volatile unsigned*)&g_epoch + 1, 0);
        if (rec) {
            if (warp == 1) wait_count_warp(&g_zero, E * 64u);
            if (warp == 3 && rank != 0) x_send(sb, 0, rank, 0);
            mbar_wait(sb + RB_WO, 0);
            wo_permute(sb + RS_WO + (tid & 127) * 32, 20);
            if (rank == 0) wo_permute(sb + RS_WO5 + (tid & 127) * 32, 4);
            fence_proxy_async();
            nbar_sync(NB_AUX, 128);
            if (rank == 0) aux_main<true>(sb, warp, rank, head, &tmX, xg, E, warp == 0 ? tq.x : (warp == 1 ? tq.y : tq.z), tq.w, 0);
            else           aux_main<false>(sb, warp, rank, head, &tmX, xg, E, warp == 0 ? tk.x : (warp == 1 ? tk.y : tk.z), tq.w, tk.w);
        }
        const int t = tid_now();
        int id = 0;
        if (t >= 288 && t < 288 + 12) asm volatile("prefetch.tensormap [%0];" :: "l"(&mp.wq + (t - 288)) : "memory");
        if (warp == 0) id = post_claim(mp, E);
        __syncwarp();
        nbar_sync(0, 384);
        if (warp == 0) { if (elect_one()) post_init(sb); fence_proxy_async(); }
        __syncwarp();
        nbar_sync(0, 384);
        if (warp == 0) post_producer(mp, sb, E, id);
        else if (t == 288 || t == 320) post_helper(sb, warp - 1);
    }
    __syncthreads();
    asm volatile("griddepcontrol.wait;" ::: "memory");
}

typedef CUresult (*EncodeFn)(CUtensorMap*, CUtensorMapDataType, cuuint32_t, void*, const cuuint64_t*, const cuuint64_t*,
                             const cuuint32_t*, const cuuint32_t*, CUtensorMapInterleave, CUtensorMapSwizzle,
                             CUtensorMapL2promotion, CUtensorMapFloatOOBfill);

static CUtensorMap make_map(EncodeFn fn, const void* ptr, uint64_t inner, uint64_t outer, uint32_t box_inner, uint32_t box_outer) {
    CUtensorMap m;
    cuuint64_t dims[2] = {inner, outer};
    cuuint64_t strides[1] = {inner * 2};
    cuuint32_t box[2] = {box_inner, box_outer};
    cuuint32_t es[2] = {1, 1};
    fn(&m, CU_TENSOR_MAP_DATA_TYPE_BFLOAT16, 2, const_cast<void*>(ptr), dims, strides, box, es,
       CU_TENSOR_MAP_INTERLEAVE_NONE, CU_TENSOR_MAP_SWIZZLE_128B, CU_TENSOR_MAP_L2_PROMOTION_L2_256B, CU_TENSOR_MAP_FLOAT_OOB_FILL_NONE);
    return m;
}

static CUtensorMap make_wo_map(EncodeFn fn, const void* ptr, uint32_t ngrp) {
    CUtensorMap m;
    cuuint64_t dims[5] = {DM, 2, 4, 4, HD / 32};
    cuuint64_t strides[4] = {DM * 2, 8 * DM * 2, 2 * DM * 2, 32 * DM * 2};
    cuuint32_t box[5] = {64, 2, 4, 4, ngrp};
    cuuint32_t es[5] = {1, 1, 1, 1, 1};
    fn(&m, CU_TENSOR_MAP_DATA_TYPE_BFLOAT16, 5, const_cast<void*>(ptr), dims, strides, box, es,
       CU_TENSOR_MAP_INTERLEAVE_NONE, CU_TENSOR_MAP_SWIZZLE_128B, CU_TENSOR_MAP_L2_PROMOTION_L2_256B, CU_TENSOR_MAP_FLOAT_OOB_FILL_NONE);
    return m;
}

struct Maps {
    PMaps post;
    CUtensorMap wk16, wv16, wo128, x32;
};

extern "C" void kernel_launch(void* const* d_in, const int* in_sizes, int n_in, void* d_out, int out_size) {
    const bf16* A_x   = (const bf16*)d_in[0];
    const bf16* A_mem = (const bf16*)d_in[1];
    const bf16* A_Wq  = (const bf16*)d_in[2];
    const bf16* A_Wk  = (const bf16*)d_in[3];
    const bf16* A_Wv  = (const bf16*)d_in[4];
    const bf16* A_Wo  = (const bf16*)d_in[5];
    const bf16* B_x   = (const bf16*)d_in[7];
    const bf16* B_w   = (const bf16*)d_in[8];
    const bf16* B_wo  = (const bf16*)d_in[9];

    static EncodeFn fn = nullptr;
    static Maps mp;
    static const void* cached[10];
    const void* cur[10] = {A_x, A_mem, A_Wq, A_Wk, A_Wv, A_Wo, B_x, B_w, B_wo, d_out};
    bool same = fn != nullptr;
    for (int i = 0; i < 10 && same; i++) same = cached[i] == cur[i];
    if (!same) {
        if (!fn) {
            void* p = nullptr; cudaDriverEntryPointQueryResult qr;
            cudaGetDriverEntryPoint("cuTensorMapEncodeTiled", &p, cudaEnableDefault, &qr);
            fn = (EncodeFn)p;
            cudaFuncSetAttribute(k_rec, cudaFuncAttributeMaxDynamicSharedMemorySize, R_SMEM);
        }
        void *p_ox, *p_bqkv, *p_bo, *p_qx;
        cudaGetSymbolAddress(&p_qx, g_qx);
        cudaGetSymbolAddress(&p_ox, g_ox); cudaGetSymbolAddress(&p_bqkv, g_bqkv); cudaGetSymbolAddress(&p_bo, g_bo);
        mp.post.wq   = make_map(fn, A_Wq, HD, DM, 64, 64);
        mp.post.wo   = make_wo_map(fn, A_Wo, 2);
        mp.post.bw   = make_map(fn, B_w, 3 * DM, DM, 64, 64);
        mp.post.bwo  = make_map(fn, B_wo, DM, DM, 64, 64);
        mp.post.x    = make_map(fn, A_x, DM, S_TOK, 64, 128);
        mp.post.bx   = make_map(fn, B_x, DM, S_TOK, 64, 128);
        mp.post.bo   = make_map(fn, p_bo, DM, S_TOK, 64, 128);
        mp.post.ox   = make_map(fn, p_ox, HD, S_TOK, 64, 128);
        mp.post.cb   = make_map(fn, p_bqkv, 3 * DM, S_TOK, 64, 64);
        mp.post.cout = make_map(fn, d_out, 2 * DM, S_TOK, 64, 64);
        {
            cuuint64_t dims[4] = {256, 4, NH * 4, NSEG};
            cuuint64_t strides[3] = {512, 2048, NH * 8192};
            cuuint32_t box[4] = {256, 2, 4, 2};
            cuuint32_t es[4] = {1, 1, 1, 1};
            fn(&mp.post.cq, CU_TENSOR_MAP_DATA_TYPE_BFLOAT16, 4, p_qx, dims, strides, box, es,
               CU_TENSOR_MAP_INTERLEAVE_NONE, CU_TENSOR_MAP_SWIZZLE_NONE, CU_TENSOR_MAP_L2_PROMOTION_NONE, CU_TENSOR_MAP_FLOAT_OOB_FILL_NONE);
        }
        {
            int runs[48] = {K_QH, 0, 2, K_Q, 1, 7, K_B1, 0, 8, K_A4, 0, 4, K_B2, 0, 32, K_A4, 4, 2, K_B3, 0, 4, K_A3, 12, 2, K_B3, 4, 4, K_SK, 14, 2, -1};
            const int per[8] = {32, 24, 8, 8, 32, 8, 8 * P_SPLIT, 1};
            int n = 0, id = 0;
            for (; runs[3 * n] >= 0; n++) {
                mp.post.list.run[n] = make_int4(runs[3 * n], runs[3 * n + 1], id, id + runs[3 * n + 2] * per[runs[3 * n]]);
                id = mp.post.list.run[n].w;
            }
            mp.post.list.n = n;
            int dev = 0, nsm = 132;
            cudaGetDevice(&dev);
            cudaDeviceGetAttribute(&nsm, cudaDevAttrMultiProcessorCount, dev);
            mp.post.list.nworker = nsm > 96 ? nsm : 97;
        }
        {
            cuuint64_t dims[4] = {DM, 3, 2, S_TOK / 2};
            cuuint64_t strides[3] = {DM * 2, 3 * DM * 2, 3 * DM * 4};
            cuuint32_t box[4] = {64, 3, 1, 40};
            cuuint32_t es[4] = {1, 1, 1, 1};
            fn(&mp.post.b40, CU_TENSOR_MAP_DATA_TYPE_BFLOAT16, 4, p_bqkv, dims, strides, box, es,
               CU_TENSOR_MAP_INTERLEAVE_NONE, CU_TENSOR_MAP_SWIZZLE_128B, CU_TENSOR_MAP_L2_PROMOTION_L2_256B, CU_TENSOR_MAP_FLOAT_OOB_FILL_NONE);
        }
        mp.wk16 = make_map(fn, A_Wk, HD, DM, 64, 64);
        mp.wv16 = make_map(fn, A_Wv, HD, DM, 64, 64);
        mp.wo128 = make_wo_map(fn, A_Wo, 4);
        {
            cuuint64_t dims[3] = {64, S_TOK, DM / 64};
            cuuint64_t strides[2] = {DM * 2, 128};
            cuuint32_t box[3] = {32, 32, 2};
            cuuint32_t es[3] = {1, 1, 1};
            fn(&mp.x32, CU_TENSOR_MAP_DATA_TYPE_BFLOAT16, 3, const_cast<bf16*>(A_x), dims, strides, box, es,
               CU_TENSOR_MAP_INTERLEAVE_NONE, CU_TENSOR_MAP_SWIZZLE_64B, CU_TENSOR_MAP_L2_PROMOTION_L2_128B, CU_TENSOR_MAP_FLOAT_OOB_FILL_NONE);
        }
        for (int i = 0; i < 10; i++) cached[i] = cur[i];
    }

    cudaStream_t st = cudaStreamPerThread;
    int4 tq = make_int4(50, 150, 800, 80), tk = make_int4(100, 350, 850, 400);
    cudaLaunchConfig_t cfg = {};
    cfg.gridDim = dim3(96); cfg.blockDim = dim3(384); cfg.dynamicSmemBytes = R_SMEM; cfg.stream = st;
    cudaLaunchAttribute at[1];
    at[0].id = cudaLaunchAttributeClusterDimension;
    at[0].val.clusterDim.x = 3; at[0].val.clusterDim.y = 1; at[0].val.clusterDim.z = 1;
    cfg.attrs = at; cfg.numAttrs = 1;
    cudaLaunchKernelEx(&cfg, k_rec, mp.post, mp.wk16, mp.wv16, mp.wo128, mp.x32, A_mem, A_x, tq, tk, 1);
    cfg.gridDim = dim3(mp.post.list.nworker - 96);
    at[0].id = cudaLaunchAttributeProgrammaticStreamSerialization;
    at[0].val.programmaticStreamSerializationAllowed = 1;
    cudaLaunchKernelEx(&cfg, k_rec, mp.post, mp.wk16, mp.wv16, mp.wo128, mp.x32, A_mem, A_x, tq, tk, 0);
}
```

```cpp
#include <cuda_runtime.h>
#include <cuda_bf16.h>
#include <cuda.h>
#include <stdint.h>

typedef __nv_bfloat16 bf16;

constexpr int S_TOK = 2048;
constexpr int DM    = 1024;
constexpr int NH    = 32;
constexpr int DH    = 128;
constexpr int NSEG  = 64;
constexpr int HD    = NH * DH;

__device__ __align__(1024) bf16 g_qx[NSEG * NH * 4 * DH * 8];
__device__ __align__(1024) bf16 g_ox[S_TOK * HD];
__device__ __align__(1024) bf16 g_bqkv[S_TOK * 3 * DM];
__device__ __align__(1024) bf16 g_bo[S_TOK * DM];
__device__ __align__(1024) uint8_t g_acc[192 * 1024];

#define EV(cond, s, k) do {} while (0)
#define EVCAL(s) do {} while (0)

constexpr int P_NSK = 4;
__device__ unsigned g_epoch, g_qctr, g_done, g_zero;
enum { C_B1 = 0, C_B2 = 8, C_Q = 16, C_QH = 24, C_NONE = 31 };
__device__ unsigned g_cnt[32], g_prog[16], g_cnt_sk[P_NSK * 32];
constexpr int P_SPLIT = 4;
__device__ __align__(1024) uint4 g_skp[P_NSK * 8 * P_SPLIT * 2 * 8 * 128];
#define TLOG(i, k, v) do {} while (0)

#define DEVI __device__ __forceinline__

DEVI uint32_t opaque(uint32_t v) { uint32_t r; asm volatile("mov.u32 %0, %1;" : "=r"(r) : "r"(v)); return r; }
DEVI uint32_t smem_u32(const void* p) { return (uint32_t)__cvta_generic_to_shared(p); }

#define TRAP(code) __trap()
constexpr int SPIN_LIMIT = 1 << 22;
#define MBAR_HINT_NS 20000u
constexpr int SPIN_LIMIT_MBAR = 1 << 17;

DEVI void mbar_init(uint32_t bar, uint32_t cnt) { asm volatile("mbarrier.init.shared::cta.b64 [%0], %1;" :: "r"(bar), "r"(cnt)); }
DEVI void mbar_expect_tx(uint32_t bar, uint32_t bytes) {
    asm volatile("mbarrier.arrive.expect_tx.shared::cta.b64 _, [%0], %1;" :: "r"(bar), "r"(bytes) : "memory");
}
DEVI void mbar_arrive(uint32_t bar) { asm volatile("mbarrier.arrive.shared::cta.b64 _, [%0];" :: "r"(bar) : "memory"); }
DEVI bool mbar_try(uint32_t bar, uint32_t parity) {
    uint32_t ok;
    asm volatile("{.reg .pred p; mbarrier.try_wait.parity.shared::cta.b64 p, [%1], %2; selp.u32 %0, 1, 0, p;}"
                 : "=r"(ok) : "r"(bar), "r"(parity) : "memory");
    return ok;
}
DEVI bool mbar_try_cluster(uint32_t bar, uint32_t parity) {
    uint32_t ok;
    asm volatile("{.reg .pred p; mbarrier.try_wait.parity.acquire.cluster.shared::cta.b64 p, [%1], %2; selp.u32 %0, 1, 0, p;}"
                 : "=r"(ok) : "r"(bar), "r"(parity) : "memory");
    return ok;
}
DEVI bool mbar_try_hint(uint32_t bar, uint32_t parity) {
    uint32_t ok;
    asm volatile("{.reg .pred p; mbarrier.try_wait.parity.shared::cta.b64 p, [%1], %2, %3; selp.u32 %0, 1, 0, p;}"
                 : "=r"(ok) : "r"(bar), "r"(parity), "r"(MBAR_HINT_NS) : "memory");
    return ok;
}
DEVI void mbar_wait(uint32_t bar, uint32_t parity) {
    int n = 0;
    while (!mbar_try(bar, parity)) { if (++n > SPIN_LIMIT) TRAP(bar | (parity << 31)); }
}
DEVI void mbar_wait_sleepy(uint32_t bar, uint32_t parity) {
    int n = 0;
    while (!mbar_try_hint(bar, parity)) { if (++n > SPIN_LIMIT_MBAR) __trap(); }
}
DEVI void mbar_wait_cluster(uint32_t bar, uint32_t parity) {
    int n = 0;
    while (!mbar_try_cluster(bar, parity)) { if (++n > SPIN_LIMIT) __trap(); }
}
DEVI void mbar_spin(uint32_t bar, uint32_t parity) {
    uint32_t ok; int n = 0;
    do {
        asm volatile("{.reg .pred p; mbarrier.test_wait.parity.shared::cta.b64 p, [%1], %2; selp.u32 %0, 1, 0, p;}"
                     : "=r"(ok) : "r"(bar), "r"(parity) : "memory");
        if (++n > SPIN_LIMIT) __trap();
    } while (!ok);
}
DEVI void fence_mbar_init() { asm volatile("fence.mbarrier_init.release.cluster;" ::: "memory"); }
DEVI void fence_proxy_async() { asm volatile("fence.proxy.async.shared::cta;" ::: "memory"); }
DEVI void cluster_sync() {
    asm volatile("barrier.cluster.arrive.release.aligned;\n barrier.cluster.wait.acquire.aligned;" ::: "memory");
}
DEVI bool elect_one() {
    uint32_t e; asm volatile("{.reg .pred p; elect.sync _|p, 0xffffffff; selp.u32 %0, 1, 0, p;}" : "=r"(e)); return e;
}
DEVI void fence_proxy_global() { asm volatile("fence.proxy.async.global;" ::: "memory"); }
DEVI void cluster_wait() { asm volatile("barrier.cluster.wait.acquire.aligned;" ::: "memory"); }
DEVI void nbar_sync(int id, int n) { asm volatile("bar.sync %0, %1;" :: "r"(id), "r"(n) : "memory"); }
DEVI void nbar_arrive(int id, int n) { asm volatile("bar.arrive %0, %1;" :: "r"(id), "r"(n) : "memory"); }

DEVI void tma_load_2d(uint32_t dst, const CUtensorMap* map, int x, int y, uint32_t bar) {
    asm volatile("cp.async.bulk.tensor.2d.shared::cluster.global.mbarrier::complete_tx::bytes [%0], [%1, {%3, %4}], [%2];"
                 :: "r"(dst), "l"(map), "r"(bar), "r"(x), "r"(y) : "memory");
}
DEVI void tma_load_3d(uint32_t dst, const CUtensorMap* map, int x, int y, int z, uint32_t bar) {
    asm volatile("cp.async.bulk.tensor.3d.shared::cluster.global.mbarrier::complete_tx::bytes [%0], [%1, {%3, %4, %5}], [%2];"
                 :: "r"(dst), "l"(map), "r"(bar), "r"(x), "r"(y), "r"(z) : "memory");
}
DEVI void tma_load_wo(uint32_t dst, const CUtensorMap* map, int col, int k32, uint32_t bar) {
    asm volatile("cp.async.bulk.tensor.5d.shared::cluster.global.mbarrier::complete_tx::bytes [%0], [%1, {%3, %5, %5, %5, %4}], [%2];"
                 :: "r"(dst), "l"(map), "r"(bar), "r"(col), "r"(k32), "r"(0) : "memory");
}
DEVI void tma_store_2d(const CUtensorMap* map, uint32_t src, int x, int y) {
    asm volatile("cp.async.bulk.tensor.2d.global.shared::cta.bulk_group [%0, {%2, %3}], [%1];"
                 :: "l"(map), "r"(src), "r"(x), "r"(y) : "memory");
}
DEVI void bulk_load(uint32_t dst, const void* src, uint32_t bytes, uint32_t bar) {
    asm volatile("cp.async.bulk.shared::cluster.global.mbarrier::complete_tx::bytes [%0], [%1], %2, [%3];"
                 :: "r"(dst), "l"(src), "r"(bytes), "r"(bar) : "memory");
}
DEVI void tma_load_2d_mc(uint32_t dst, const CUtensorMap* map, int x, int y, uint32_t bar, uint16_t mask) {
    asm volatile("cp.async.bulk.tensor.2d.shared::cluster.global.mbarrier::complete_tx::bytes.multicast::cluster [%0], [%1, {%3, %4}], [%2], %5;"
                 :: "r"(dst), "l"(map), "r"(bar), "r"(x), "r"(y), "h"(mask) : "memory");
}
DEVI void bulk_copy_s2c(uint32_t dst_cluster, uint32_t src, uint32_t bytes, uint32_t bar_cluster) {
    asm volatile("cp.async.bulk.shared::cluster.shared::cta.mbarrier::complete_tx::bytes [%0], [%1], %2, [%3];"
                 :: "r"(dst_cluster), "r"(src), "r"(bytes), "r"(bar_cluster) : "memory");
}
DEVI void bulk_store(void* dst, uint32_t src, uint32_t bytes) {
    asm volatile("cp.async.bulk.global.shared::cta.bulk_group [%0], [%1], %2;" :: "l"(dst), "r"(src), "r"(bytes) : "memory");
}
DEVI void bulk_wait_read() { asm volatile("cp.async.bulk.wait_group.read 0;" ::: "memory"); }
DEVI void mbar_arrive_remote(uint32_t bar_cluster) {
    asm volatile("mbarrier.arrive.shared::cluster.b64 _, [%0];" :: "r"(bar_cluster) : "memory");
}
DEVI void mbar_expect_tx_remote(uint32_t bar_cluster, uint32_t bytes) {
    asm volatile("mbarrier.arrive.expect_tx.shared::cluster.b64 _, [%0], %1;" :: "r"(bar_cluster), "r"(bytes) : "memory");
}
DEVI void l2_prefetch(const void* p, uint32_t bytes) {
    asm volatile("cp.async.bulk.prefetch.L2.global [%0], %1;" :: "l"(p), "r"(bytes) : "memory");
}
DEVI void bulk_commit() { asm volatile("cp.async.bulk.commit_group;" ::: "memory"); }
DEVI void bulk_wait_all() { asm volatile("cp.async.bulk.wait_group 0;" ::: "memory"); }

DEVI void wg_fence() { asm volatile("wgmma.fence.sync.aligned;" ::: "memory"); }
DEVI void wg_commit() { asm volatile("wgmma.commit_group.sync.aligned;" ::: "memory"); }
template <int N> DEVI void wg_wait() { asm volatile("wgmma.wait_group.sync.aligned %0;" :: "n"(N) : "memory"); }

template <int R> DEVI void reg_dec() { asm volatile("setmaxnreg.dec.sync.aligned.u32 %0;" :: "n"(R)); }
template <int R> DEVI void reg_inc() { asm volatile("setmaxnreg.inc.sync.aligned.u32 %0;" :: "n"(R)); }

DEVI uint64_t mk_desc(uint32_t addr, uint32_t lbo, uint32_t sbo, uint32_t sw) {
    return (uint64_t)((addr & 0x3FFFF) >> 4) | ((uint64_t)(lbo >> 4) << 16) | ((uint64_t)(sbo >> 4) << 32) | ((uint64_t)sw << 62);
}

DEVI uint32_t desc_lo(uint32_t addr, uint32_t lbo) { return ((addr & 0x3FFFF) >> 4) | ((lbo >> 4) << 16); }
constexpr uint32_t DHI_SW128 = (1024u >> 4) | (1u << 30);
constexpr uint32_t DHI_SW64  = (512u >> 4) | (2u << 30);
constexpr uint32_t DHI_NONE  = (128u >> 4);

template <int TB, int SCALE_D>
DEVI void wgmma_n8_ss(float* d, uint32_t alo, uint32_t blo) {
    asm volatile("{.reg .b64 da, db; mov.b64 da, {%4, %6}; mov.b64 db, {%5, %7};\n"
                 "wgmma.mma_async.sync.aligned.m64n8k16.f32.bf16.bf16 {%0,%1,%2,%3}, da, db, %8, 1, 1, 1, %9;}"
                 : "+f"(d[0]), "+f"(d[1]), "+f"(d[2]), "+f"(d[3])
                 : "r"(alo), "r"(blo), "n"(DHI_SW128), "n"(DHI_NONE), "n"(SCALE_D), "n"(TB));
}

template <int TB>
DEVI void wgmma_n8_ss_first(float* d, uint32_t alo, uint32_t blo) {
    asm volatile("{.reg .b64 da, db; mov.b64 da, {%4, %6}; mov.b64 db, {%5, %7};\n"
                 "wgmma.mma_async.sync.aligned.m64n8k16.f32.bf16.bf16 {%0,%1,%2,%3}, da, db, 0, 1, 1, 1, %8;}"
                 : "=f"(d[0]), "=f"(d[1]), "=f"(d[2]), "=f"(d[3])
                 : "r"(alo), "r"(blo), "n"(DHI_SW128), "n"(DHI_NONE), "n"(TB));
}
DEVI void wgmma_n32_rs_first(float* d, const uint32_t* a, uint32_t blo) {
    asm volatile("{.reg .b64 db; mov.b64 db, {%20, %21};\n"
                 "wgmma.mma_async.sync.aligned.m64n32k16.f32.bf16.bf16 {%0,%1,%2,%3,%4,%5,%6,%7,%8,%9,%10,%11,%12,%13,%14,%15}, "
                 "{%16,%17,%18,%19}, db, 0, 1, 1, 0;}"
                 : "=f"(d[0]), "=f"(d[1]), "=f"(d[2]), "=f"(d[3]), "=f"(d[4]), "=f"(d[5]), "=f"(d[6]), "=f"(d[7]),
                   "=f"(d[8]), "=f"(d[9]), "=f"(d[10]), "=f"(d[11]), "=f"(d[12]), "=f"(d[13]), "=f"(d[14]), "=f"(d[15])
                 : "r"(a[0]), "r"(a[1]), "r"(a[2]), "r"(a[3]), "r"(blo), "n"(DHI_SW64));
}
template <int N> DEVI void reg_fence(float* d) {
#pragma unroll
    for (int i = 0; i < N; i++) asm volatile("" : "+f"(d[i]) :: "memory");
}
DEVI void wgmma_n32_rs(float* d, const uint32_t* a, uint32_t blo) {
    asm volatile("{.reg .b64 db; mov.b64 db, {%20, %21};\n"
                 "wgmma.mma_async.sync.aligned.m64n32k16.f32.bf16.bf16 {%0,%1,%2,%3,%4,%5,%6,%7,%8,%9,%10,%11,%12,%13,%14,%15}, "
                 "{%16,%17,%18,%19}, db, 1, 1, 1, 0;}"
                 : "+f"(d[0]), "+f"(d[1]), "+f"(d[2]), "+f"(d[3]), "+f"(d[4]), "+f"(d[5]), "+f"(d[6]), "+f"(d[7]),
                   "+f"(d[8]), "+f"(d[9]), "+f"(d[10]), "+f"(d[11]), "+f"(d[12]), "+f"(d[13]), "+f"(d[14]), "+f"(d[15])
                 : "r"(a[0]), "r"(a[1]), "r"(a[2]), "r"(a[3]), "r"(blo), "n"(DHI_SW64));
}
DEVI void wgmma_n32_ss(float* d, uint32_t alo, uint32_t blo) {
    asm volatile("{.reg .b64 da, db; mov.b64 da, {%16, %18}; mov.b64 db, {%17, %19};\n"
                 "wgmma.mma_async.sync.aligned.m64n32k16.f32.bf16.bf16 {%0,%1,%2,%3,%4,%5,%6,%7,%8,%9,%10,%11,%12,%13,%14,%15}, "
                 "da, db, 1, 1, 1, 1, 0;}"
                 : "+f"(d[0]), "+f"(d[1]), "+f"(d[2]), "+f"(d[3]), "+f"(d[4]), "+f"(d[5]), "+f"(d[6]), "+f"(d[7]),
                   "+f"(d[8]), "+f"(d[9]), "+f"(d[10]), "+f"(d[11]), "+f"(d[12]), "+f"(d[13]), "+f"(d[14]), "+f"(d[15])
                 : "r"(alo), "r"(blo), "n"(DHI_SW128), "n"(DHI_SW64));
}

template <bool FIRST>
DEVI void wgmma_n256_ss(float* d, uint64_t a, uint64_t b) {
    if (FIRST)
        asm volatile("wgmma.mma_async.sync.aligned.m64n256k16.f32.bf16.bf16 {%0,%1,%2,%3,%4,%5,%6,%7,%8,%9,%10,%11,%12,%13,%14,%15,%16,%17,%18,%19,%20,%21,%22,%23,%24,%25,%26,%27,%28,%29,%30,%31,%32,%33,%34,%35,%36,%37,%38,%39,%40,%41,%42,%43,%44,%45,%46,%47,%48,%49,%50,%51,%52,%53,%54,%55,%56,%57,%58,%59,%60,%61,%62,%63,%64,%65,%66,%67,%68,%69,%70,%71,%72,%73,%74,%75,%76,%77,%78,%79,%80,%81,%82,%83,%84,%85,%86,%87,%88,%89,%90,%91,%92,%93,%94,%95,%96,%97,%98,%99,%100,%101,%102,%103,%104,%105,%106,%107,%108,%109,%110,%111,%112,%113,%114,%115,%116,%117,%118,%119,%120,%121,%122,%123,%124,%125,%126,%127}, %128, %129, 0, 1, 1, 1, 0;"
            : "=f"(d[0]), "=f"(d[1]), "=f"(d[2]), "=f"(d[3]), "=f"(d[4]), "=f"(d[5]), "=f"(d[6]), "=f"(d[7]), "=f"(d[8]), "=f"(d[9]), "=f"(d[10]), "=f"(d[11]), "=f"(d[12]), "=f"(d[13]), "=f"(d[14]), "=f"(d[15]), "=f"(d[16]), "=f"(d[17]), "=f"(d[18]), "=f"(d[19]), "=f"(d[20]), "=f"(d[21]), "=f"(d[22]), "=f"(d[23]), "=f"(d[24]), "=f"(d[25]), "=f"(d[26]), "=f"(d[27]), "=f"(d[28]), "=f"(d[29]), "=f"(d[30]), "=f"(d[31]), "=f"(d[32]), "=f"(d[33]), "=f"(d[34]), "=f"(d[35]), "=f"(d[36]), "=f"(d[37]), "=f"(d[38]), "=f"(d[39]), "=f"(d[40]), "=f"(d[41]), "=f"(d[42]), "=f"(d[43]), "=f"(d[44]), "=f"(d[45]), "=f"(d[46]), "=f"(d[47]), "=f"(d[48]), "=f"(d[49]), "=f"(d[50]), "=f"(d[51]), "=f"(d[52]), "=f"(d[53]), "=f"(d[54]), "=f"(d[55]), "=f"(d[56]), "=f"(d[57]), "=f"(d[58]), "=f"(d[59]), "=f"(d[60]), "=f"(d[61]), "=f"(d[62]), "=f"(d[63]), "=f"(d[64]), "=f"(d[65]), "=f"(d[66]), "=f"(d[67]), "=f"(d[68]), "=f"(d[69]), "=f"(d[70]), "=f"(d[71]), "=f"(d[72]), "=f"(d[73]), "=f"(d[74]), "=f"(d[75]), "=f"(d[76]), "=f"(d[77]), "=f"(d[78]), "=f"(d[79]), "=f"(d[80]), "=f"(d[81]), "=f"(d[82]), "=f"(d[83]), "=f"(d[84]), "=f"(d[85]), "=f"(d[86]), "=f"(d[87]), "=f"(d[88]), "=f"(d[89]), "=f"(d[90]), "=f"(d[91]), "=f"(d[92]), "=f"(d[93]), "=f"(d[94]), "=f"(d[95]), "=f"(d[96]), "=f"(d[97]), "=f"(d[98]), "=f"(d[99]), "=f"(d[100]), "=f"(d[101]), "=f"(d[102]), "=f"(d[103]), "=f"(d[104]), "=f"(d[105]), "=f"(d[106]), "=f"(d[107]), "=f"(d[108]), "=f"(d[109]), "=f"(d[110]), "=f"(d[111]), "=f"(d[112]), "=f"(d[113]), "=f"(d[114]), "=f"(d[115]), "=f"(d[116]), "=f"(d[117]), "=f"(d[118]), "=f"(d[119]), "=f"(d[120]), "=f"(d[121]), "=f"(d[122]), "=f"(d[123]), "=f"(d[124]), "=f"(d[125]), "=f"(d[126]), "=f"(d[127]) : "l"(a), "l"(b));
    else
        asm volatile("wgmma.mma_async.sync.aligned.m64n256k16.f32.bf16.bf16 {%0,%1,%2,%3,%4,%5,%6,%7,%8,%9,%10,%11,%12,%13,%14,%15,%16,%17,%18,%19,%20,%21,%22,%23,%24,%25,%26,%27,%28,%29,%30,%31,%32,%33,%34,%35,%36,%37,%38,%39,%40,%41,%42,%43,%44,%45,%46,%47,%48,%49,%50,%51,%52,%53,%54,%55,%56,%57,%58,%59,%60,%61,%62,%63,%64,%65,%66,%67,%68,%69,%70,%71,%72,%73,%74,%75,%76,%77,%78,%79,%80,%81,%82,%83,%84,%85,%86,%87,%88,%89,%90,%91,%92,%93,%94,%95,%96,%97,%98,%99,%100,%101,%102,%103,%104,%105,%106,%107,%108,%109,%110,%111,%112,%113,%114,%115,%116,%117,%118,%119,%120,%121,%122,%123,%124,%125,%126,%127}, %128, %129, 1, 1, 1, 1, 0;"
            : "+f"(d[0]), "+f"(d[1]), "+f"(d[2]), "+f"(d[3]), "+f"(d[4]), "+f"(d[5]), "+f"(d[6]), "+f"(d[7]), "+f"(d[8]), "+f"(d[9]), "+f"(d[10]), "+f"(d[11]), "+f"(d[12]), "+f"(d[13]), "+f"(d[14]), "+f"(d[15]), "+f"(d[16]), "+f"(d[17]), "+f"(d[18]), "+f"(d[19]), "+f"(d[20]), "+f"(d[21]), "+f"(d[22]), "+f"(d[23]), "+f"(d[24]), "+f"(d[25]), "+f"(d[26]), "+f"(d[27]), "+f"(d[28]), "+f"(d[29]), "+f"(d[30]), "+f"(d[31]), "+f"(d[32]), "+f"(d[33]), "+f"(d[34]), "+f"(d[35]), "+f"(d[36]), "+f"(d[37]), "+f"(d[38]), "+f"(d[39]), "+f"(d[40]), "+f"(d[41]), "+f"(d[42]), "+f"(d[43]), "+f"(d[44]), "+f"(d[45]), "+f"(d[46]), "+f"(d[47]), "+f"(d[48]), "+f"(d[49]), "+f"(d[50]), "+f"(d[51]), "+f"(d[52]), "+f"(d[53]), "+f"(d[54]), "+f"(d[55]), "+f"(d[56]), "+f"(d[57]), "+f"(d[58]), "+f"(d[59]), "+f"(d[60]), "+f"(d[61]), "+f"(d[62]), "+f"(d[63]), "+f"(d[64]), "+f"(d[65]), "+f"(d[66]), "+f"(d[67]), "+f"(d[68]), "+f"(d[69]), "+f"(d[70]), "+f"(d[71]), "+f"(d[72]), "+f"(d[73]), "+f"(d[74]), "+f"(d[75]), "+f"(d[76]), "+f"(d[77]), "+f"(d[78]), "+f"(d[79]), "+f"(d[80]), "+f"(d[81]), "+f"(d[82]), "+f"(d[83]), "+f"(d[84]), "+f"(d[85]), "+f"(d[86]), "+f"(d[87]), "+f"(d[88]), "+f"(d[89]), "+f"(d[90]), "+f"(d[91]), "+f"(d[92]), "+f"(d[93]), "+f"(d[94]), "+f"(d[95]), "+f"(d[96]), "+f"(d[97]), "+f"(d[98]), "+f"(d[99]), "+f"(d[100]), "+f"(d[101]), "+f"(d[102]), "+f"(d[103]), "+f"(d[104]), "+f"(d[105]), "+f"(d[106]), "+f"(d[107]), "+f"(d[108]), "+f"(d[109]), "+f"(d[110]), "+f"(d[111]), "+f"(d[112]), "+f"(d[113]), "+f"(d[114]), "+f"(d[115]), "+f"(d[116]), "+f"(d[117]), "+f"(d[118]), "+f"(d[119]), "+f"(d[120]), "+f"(d[121]), "+f"(d[122]), "+f"(d[123]), "+f"(d[124]), "+f"(d[125]), "+f"(d[126]), "+f"(d[127]) : "l"(a), "l"(b));
}
template <bool FIRST>
DEVI void wgmma_n128_ss(float* d, uint64_t a, uint64_t b) {
    if (FIRST)
        asm volatile("wgmma.mma_async.sync.aligned.m64n128k16.f32.bf16.bf16 {%0,%1,%2,%3,%4,%5,%6,%7,%8,%9,%10,%11,%12,%13,%14,%15,%16,%17,%18,%19,%20,%21,%22,%23,%24,%25,%26,%27,%28,%29,%30,%31,%32,%33,%34,%35,%36,%37,%38,%39,%40,%41,%42,%43,%44,%45,%46,%47,%48,%49,%50,%51,%52,%53,%54,%55,%56,%57,%58,%59,%60,%61,%62,%63}, %64, %65, 0, 1, 1, 1, 0;"
            : "=f"(d[0]), "=f"(d[1]), "=f"(d[2]), "=f"(d[3]), "=f"(d[4]), "=f"(d[5]), "=f"(d[6]), "=f"(d[7]), "=f"(d[8]), "=f"(d[9]), "=f"(d[10]), "=f"(d[11]), "=f"(d[12]), "=f"(d[13]), "=f"(d[14]), "=f"(d[15]), "=f"(d[16]), "=f"(d[17]), "=f"(d[18]), "=f"(d[19]), "=f"(d[20]), "=f"(d[21]), "=f"(d[22]), "=f"(d[23]), "=f"(d[24]), "=f"(d[25]), "=f"(d[26]), "=f"(d[27]), "=f"(d[28]), "=f"(d[29]), "=f"(d[30]), "=f"(d[31]), "=f"(d[32]), "=f"(d[33]), "=f"(d[34]), "=f"(d[35]), "=f"(d[36]), "=f"(d[37]), "=f"(d[38]), "=f"(d[39]), "=f"(d[40]), "=f"(d[41]), "=f"(d[42]), "=f"(d[43]), "=f"(d[44]), "=f"(d[45]), "=f"(d[46]), "=f"(d[47]), "=f"(d[48]), "=f"(d[49]), "=f"(d[50]), "=f"(d[51]), "=f"(d[52]), "=f"(d[53]), "=f"(d[54]), "=f"(d[55]), "=f"(d[56]), "=f"(d[57]), "=f"(d[58]), "=f"(d[59]), "=f"(d[60]), "=f"(d[61]), "=f"(d[62]), "=f"(d[63]) : "l"(a), "l"(b));
    else
        asm volatile("wgmma.mma_async.sync.aligned.m64n128k16.f32.bf16.bf16 {%0,%1,%2,%3,%4,%5,%6,%7,%8,%9,%10,%11,%12,%13,%14,%15,%16,%17,%18,%19,%20,%21,%22,%23,%24,%25,%26,%27,%28,%29,%30,%31,%32,%33,%34,%35,%36,%37,%38,%39,%40,%41,%42,%43,%44,%45,%46,%47,%48,%49,%50,%51,%52,%53,%54,%55,%56,%57,%58,%59,%60,%61,%62,%63}, %64, %65, 1, 1, 1, 1, 0;"
            : "+f"(d[0]), "+f"(d[1]), "+f"(d[2]), "+f"(d[3]), "+f"(d[4]), "+f"(d[5]), "+f"(d[6]), "+f"(d[7]), "+f"(d[8]), "+f"(d[9]), "+f"(d[10]), "+f"(d[11]), "+f"(d[12]), "+f"(d[13]), "+f"(d[14]), "+f"(d[15]), "+f"(d[16]), "+f"(d[17]), "+f"(d[18]), "+f"(d[19]), "+f"(d[20]), "+f"(d[21]), "+f"(d[22]), "+f"(d[23]), "+f"(d[24]), "+f"(d[25]), "+f"(d[26]), "+f"(d[27]), "+f"(d[28]), "+f"(d[29]), "+f"(d[30]), "+f"(d[31]), "+f"(d[32]), "+f"(d[33]), "+f"(d[34]), "+f"(d[35]), "+f"(d[36]), "+f"(d[37]), "+f"(d[38]), "+f"(d[39]), "+f"(d[40]), "+f"(d[41]), "+f"(d[42]), "+f"(d[43]), "+f"(d[44]), "+f"(d[45]), "+f"(d[46]), "+f"(d[47]), "+f"(d[48]), "+f"(d[49]), "+f"(d[50]), "+f"(d[51]), "+f"(d[52]), "+f"(d[53]), "+f"(d[54]), "+f"(d[55]), "+f"(d[56]), "+f"(d[57]), "+f"(d[58]), "+f"(d[59]), "+f"(d[60]), "+f"(d[61]), "+f"(d[62]), "+f"(d[63]) : "l"(a), "l"(b));
}

template <bool FIRST>
DEVI void wgmma_n64_ss(float* d, uint64_t a, uint64_t b) {
    if (FIRST)
        asm volatile("wgmma.mma_async.sync.aligned.m64n64k16.f32.bf16.bf16 {%0,%1,%2,%3,%4,%5,%6,%7,%8,%9,%10,%11,%12,%13,%14,%15,%16,%17,%18,%19,%20,%21,%22,%23,%24,%25,%26,%27,%28,%29,%30,%31}, %32, %33, 0, 1, 1, 1, 0;"
            : "=f"(d[0]), "=f"(d[1]), "=f"(d[2]), "=f"(d[3]), "=f"(d[4]), "=f"(d[5]), "=f"(d[6]), "=f"(d[7]), "=f"(d[8]), "=f"(d[9]), "=f"(d[10]), "=f"(d[11]), "=f"(d[12]), "=f"(d[13]), "=f"(d[14]), "=f"(d[15]), "=f"(d[16]), "=f"(d[17]), "=f"(d[18]), "=f"(d[19]), "=f"(d[20]), "=f"(d[21]), "=f"(d[22]), "=f"(d[23]), "=f"(d[24]), "=f"(d[25]), "=f"(d[26]), "=f"(d[27]), "=f"(d[28]), "=f"(d[29]), "=f"(d[30]), "=f"(d[31]) : "l"(a), "l"(b));
    else
        asm volatile("wgmma.mma_async.sync.aligned.m64n64k16.f32.bf16.bf16 {%0,%1,%2,%3,%4,%5,%6,%7,%8,%9,%10,%11,%12,%13,%14,%15,%16,%17,%18,%19,%20,%21,%22,%23,%24,%25,%26,%27,%28,%29,%30,%31}, %32, %33, 1, 1, 1, 1, 0;"
            : "+f"(d[0]), "+f"(d[1]), "+f"(d[2]), "+f"(d[3]), "+f"(d[4]), "+f"(d[5]), "+f"(d[6]), "+f"(d[7]), "+f"(d[8]), "+f"(d[9]), "+f"(d[10]), "+f"(d[11]), "+f"(d[12]), "+f"(d[13]), "+f"(d[14]), "+f"(d[15]), "+f"(d[16]), "+f"(d[17]), "+f"(d[18]), "+f"(d[19]), "+f"(d[20]), "+f"(d[21]), "+f"(d[22]), "+f"(d[23]), "+f"(d[24]), "+f"(d[25]), "+f"(d[26]), "+f"(d[27]), "+f"(d[28]), "+f"(d[29]), "+f"(d[30]), "+f"(d[31]) : "l"(a), "l"(b));
}

DEVI void mma16816(float* d, const uint32_t* a, uint32_t b0, uint32_t b1) {
    asm volatile("mma.sync.aligned.m16n8k16.row.col.f32.bf16.bf16.f32 {%0,%1,%2,%3}, {%4,%5,%6,%7}, {%8,%9}, {%0,%1,%2,%3};"
                 : "+f"(d[0]), "+f"(d[1]), "+f"(d[2]), "+f"(d[3])
                 : "r"(a[0]), "r"(a[1]), "r"(a[2]), "r"(a[3]), "r"(b0), "r"(b1));
}
DEVI void mma1688(float* d, uint32_t a0, uint32_t a1, uint32_t b0) {
    asm volatile("mma.sync.aligned.m16n8k8.row.col.f32.bf16.bf16.f32 {%0,%1,%2,%3}, {%4,%5}, {%6}, {%0,%1,%2,%3};"
                 : "+f"(d[0]), "+f"(d[1]), "+f"(d[2]), "+f"(d[3]) : "r"(a0), "r"(a1), "r"(b0));
}
DEVI void ldsm4(uint32_t* r, uint32_t addr) {
    asm volatile("ldmatrix.sync.aligned.m8n8.x4.shared.b16 {%0,%1,%2,%3}, [%4];"
                 : "=r"(r[0]), "=r"(r[1]), "=r"(r[2]), "=r"(r[3]) : "r"(addr) : "memory");
}
DEVI void ldsm4t(uint32_t* r, uint32_t addr) {
    asm volatile("ldmatrix.sync.aligned.m8n8.x4.trans.shared.b16 {%0,%1,%2,%3}, [%4];"
                 : "=r"(r[0]), "=r"(r[1]), "=r"(r[2]), "=r"(r[3]) : "r"(addr) : "memory");
}
DEVI void ldsm2(uint32_t* r, uint32_t addr) {
    asm volatile("ldmatrix.sync.aligned.m8n8.x2.shared.b16 {%0,%1}, [%2];" : "=r"(r[0]), "=r"(r[1]) : "r"(addr) : "memory");
}
DEVI void ldsm1t(uint32_t& r, uint32_t addr) {
    asm volatile("ldmatrix.sync.aligned.m8n8.x1.trans.shared.b16 {%0}, [%1];" : "=r"(r) : "r"(addr) : "memory");
}
DEVI void stsm4(uint32_t addr, uint32_t r0, uint32_t r1, uint32_t r2, uint32_t r3) {
    asm volatile("stmatrix.sync.aligned.m8n8.x4.shared.b16 [%0], {%1,%2,%3,%4};" :: "r"(addr), "r"(r0), "r"(r1), "r"(r2), "r"(r3) : "memory");
}
DEVI void stsm4t(uint32_t addr, uint32_t r0, uint32_t r1, uint32_t r2, uint32_t r3) {
    asm volatile("stmatrix.sync.aligned.m8n8.x4.trans.shared.b16 [%0], {%1,%2,%3,%4};" :: "r"(addr), "r"(r0), "r"(r1), "r"(r2), "r"(r3) : "memory");
}
DEVI uint32_t movm_t(uint32_t a) {
    uint32_t d; asm volatile("movmatrix.sync.aligned.m8n8.trans.b16 %0, %1;" : "=r"(d) : "r"(a)); return d;
}
DEVI uint32_t pack_bf16(float lo, float hi) {
    uint32_t r; asm("cvt.rn.bf16x2.f32 %0, %1, %2;" : "=r"(r) : "f"(hi), "f"(lo)); return r;
}
DEVI float ex2(float x) { float y; asm("ex2.approx.ftz.f32 %0, %1;" : "=f"(y) : "f"(x)); return y; }

DEVI uint4 ld_rlx4(const void* p) {
    uint4 v;
    asm volatile("ld.relaxed.gpu.global.v4.u32 {%0,%1,%2,%3}, [%4];" : "=r"(v.x), "=r"(v.y), "=r"(v.z), "=r"(v.w) : "l"(p) : "memory");
    return v;
}
DEVI void ld_rlx4f(float* d, const void* p) {
    asm volatile("ld.relaxed.gpu.global.v4.f32 {%0,%1,%2,%3}, [%4];" : "=f"(d[0]), "=f"(d[1]), "=f"(d[2]), "=f"(d[3]) : "l"(p) : "memory");
}
DEVI bool all_nzf(const float* d) { return __float_as_uint(d[0]) && __float_as_uint(d[1]) && __float_as_uint(d[2]) && __float_as_uint(d[3]); }
DEVI void sts128f(uint32_t addr, const float* d) {
    asm volatile("st.shared.v4.f32 [%0], {%1,%2,%3,%4};" :: "r"(addr), "f"(d[0]), "f"(d[1]), "f"(d[2]), "f"(d[3]) : "memory");
}
DEVI void st_rlx4(void* p, uint32_t a, uint32_t b, uint32_t c, uint32_t d) {
    asm volatile("st.relaxed.gpu.global.v4.u32 [%0], {%1,%2,%3,%4};" :: "l"(p), "r"(a), "r"(b), "r"(c), "r"(d) : "memory");
}
DEVI void st_rlx(void* p, uint32_t v) { asm volatile("st.relaxed.gpu.global.u32 [%0], %1;" :: "l"(p), "r"(v) : "memory"); }
DEVI void sts128(uint32_t addr, uint4 v) {
    asm volatile("st.shared.v4.u32 [%0], {%1,%2,%3,%4};" :: "r"(addr), "r"(v.x), "r"(v.y), "r"(v.z), "r"(v.w) : "memory");
}
DEVI void sts64(uint32_t addr, uint32_t a, uint32_t b) { asm volatile("st.shared.v2.u32 [%0], {%1,%2};" :: "r"(addr), "r"(a), "r"(b) : "memory"); }
DEVI void sts32(uint32_t addr, uint32_t v) { asm volatile("st.shared.u32 [%0], %1;" :: "r"(addr), "r"(v) : "memory"); }
DEVI uint4 lds128(uint32_t addr) {
    uint4 v; asm volatile("ld.shared.v4.u32 {%0,%1,%2,%3}, [%4];" : "=r"(v.x), "=r"(v.y), "=r"(v.z), "=r"(v.w) : "r"(addr) : "memory"); return v;
}
DEVI float2 lds64f(uint32_t addr) {
    float2 v; asm volatile("ld.shared.v2.f32 {%0,%1}, [%2];" : "=f"(v.x), "=f"(v.y) : "r"(addr) : "memory"); return v;
}
DEVI void cp_async16(uint32_t dst, const void* src) {
    asm volatile("cp.async.cg.shared.global [%0], [%1], 16;" :: "r"(dst), "l"(src) : "memory");
}
DEVI void cp_async_commit() { asm volatile("cp.async.commit_group;" ::: "memory"); }
DEVI void cp_async_wait0() { asm volatile("cp.async.wait_group 0;" ::: "memory"); }
DEVI uint32_t lds32(uint32_t addr) { uint32_t v; asm volatile("ld.shared.u32 %0, [%1];" : "=r"(v) : "r"(addr) : "memory"); return v; }
DEVI float rcp_fast(float x) { float y; asm("rcp.approx.ftz.f32 %0, %1;" : "=f"(y) : "f"(x)); return y; }
DEVI bool all_nz(const uint4& v) { return v.x && v.y && v.z && v.w; }
DEVI uint32_t mapa(uint32_t addr, uint32_t rank) {
    uint32_t r; asm("mapa.shared::cluster.u32 %0, %1, %2;" : "=r"(r) : "r"(addr), "r"(rank)); return r;
}
DEVI void st_async32(uint32_t dst, uint32_t a, uint32_t bar) {
    asm volatile("st.async.weak.shared::cluster.mbarrier::complete_tx::bytes.b32 [%0], %1, [%2];" :: "r"(dst), "r"(a), "r"(bar) : "memory");
}
DEVI void st_async64(uint32_t dst, uint32_t a, uint32_t b, uint32_t bar) {
    asm volatile("st.async.weak.shared::cluster.mbarrier::complete_tx::bytes.v2.b32 [%0], {%1,%2}, [%3];"
                 :: "r"(dst), "r"(a), "r"(b), "r"(bar) : "memory");
}

DEVI void st_async128(uint32_t dst, uint32_t a, uint32_t b, uint32_t c, uint32_t d, uint32_t bar) {
    asm volatile("st.async.weak.shared::cluster.mbarrier::complete_tx::bytes.v4.b32 [%0], {%1,%2,%3,%4}, [%5];"
                 :: "r"(dst), "r"(a), "r"(b), "r"(c), "r"(d), "r"(bar) : "memory");
}

DEVI uint32_t b_addr(uint32_t sb, int row, int which, int chunk) { const int l = 3 * row + which; return sb + l * 128 + ((chunk ^ (l & 7)) * 16); }
DEVI void battn_warp(uint32_t st, uint32_t ebar, int i0, int par, int head, int hh, int mt, int lane) {
    const int gq = lane >> 2, t = lane & 3, r = 16 * mt + (lane & 7), b3 = (lane >> 3) & 1, b4 = lane >> 4;
    uint32_t a[8], k[8], k2[4], v[8], v2[4];
#pragma unroll
    for (int ks = 0; ks < 2; ks++) {
        ldsm4(a + 4 * ks, b_addr(st, 8 + r + b3 * 8, 0, hh * 4 + ks * 2 + b4));
        ldsm4(k + 4 * ks, b_addr(st, r + b4 * 8, 1, hh * 4 + ks * 2 + b3));
    }
    ldsm4(k2, b_addr(st, r + 16, 1, hh * 4 + (lane >> 3)));
#pragma unroll
    for (int n = 0; n < 2; n++) ldsm4t(v + 4 * n, b_addr(st, r + b3 * 8, 2, hh * 4 + 2 * n + b4));
    ldsm4t(v2, b_addr(st, r + 16, 2, hh * 4 + (lane >> 3)));
    float s[3][4];
#pragma unroll
    for (int n = 0; n < 3; n++) { s[n][0] = s[n][1] = s[n][2] = s[n][3] = 0.f; }
#pragma unroll
    for (int ks = 0; ks < 2; ks++) {
        mma16816(s[0], a + 4 * ks, k[4 * ks], k[4 * ks + 1]);
        mma16816(s[1], a + 4 * ks, k[4 * ks + 2], k[4 * ks + 3]);
        mma16816(s[2], a + 4 * ks, k2[2 * ks], k2[2 * ks + 1]);
    }
    const bool ex = i0 + 16 * mt > 0;
    float x[4], y[4];
#pragma unroll
    for (int c = 0; c < 2; c++) {
        const bool low = 2 * t + c <= gq;
        x[c] = !low && ex ? s[0][c] : -INFINITY; x[2 + c] = low ? s[1][c] : -INFINITY;
        y[c] = !low ? s[1][2 + c] : -INFINITY;   y[2 + c] = low ? s[2][2 + c] : -INFINITY;
    }
    float m0 = fmaxf(fmaxf(x[0], x[1]), fmaxf(x[2], x[3])), m1 = fmaxf(fmaxf(y[0], y[1]), fmaxf(y[2], y[3]));
    m0 = fmaxf(fmaxf(m0, __shfl_xor_sync(0xffffffffu, m0, 1)), fmaxf(__shfl_xor_sync(0xffffffffu, m0, 2), __shfl_xor_sync(0xffffffffu, m0, 3)));
    m1 = fmaxf(fmaxf(m1, __shfl_xor_sync(0xffffffffu, m1, 1)), fmaxf(__shfl_xor_sync(0xffffffffu, m1, 2), __shfl_xor_sync(0xffffffffu, m1, 3)));
    constexpr float C = 0.17677669529663687f * 1.4426950408889634f;
    m0 *= -C; m1 *= -C;
    const uint32_t p0[4] = {pack_bf16(ex2(fmaf(x[0], C, m0)), ex2(fmaf(x[1], C, m0))), 0u,
                            pack_bf16(ex2(fmaf(x[2], C, m0)), ex2(fmaf(x[3], C, m0))), pack_bf16(ex2(fmaf(y[0], C, m1)), ex2(fmaf(y[1], C, m1)))};
    const uint32_t p1 = pack_bf16(ex2(fmaf(y[2], C, m1)), ex2(fmaf(y[3], C, m1)));
    float o[4][4], l[4] = {0.f, 0.f, 0.f, 0.f};
#pragma unroll
    for (int n = 0; n < 4; n++) { o[n][0] = o[n][1] = o[n][2] = o[n][3] = 0.f; }
    mma16816(l, p0, 0x3F803F80u, 0x3F803F80u);
#pragma unroll
    for (int n = 0; n < 4; n++) mma16816(o[n], p0, v[2 * n], v[2 * n + 1]);
    mma1688(l, 0u, p1, 0x3F803F80u);
#pragma unroll
    for (int n = 0; n < 4; n++) mma1688(o[n], 0u, p1, v2[n]);
    if (lane == 0) mbar_arrive(ebar);
    const float i0f = rcp_fast(l[0]), i1f = rcp_fast(l[2]);
    uint4* dst = (uint4*)(g_bo + (uint32_t)((2 * (i0 + 16 * mt + gq) + par) * DM + head * 32 + t * 8));
    dst[0] = make_uint4(pack_bf16(o[0][0] * i0f, o[0][1] * i0f), pack_bf16(o[1][0] * i0f, o[1][1] * i0f),
                        pack_bf16(o[2][0] * i0f, o[2][1] * i0f), pack_bf16(o[3][0] * i0f, o[3][1] * i0f));
    dst[16 * DM / 8] = make_uint4(pack_bf16(o[0][2] * i1f, o[0][3] * i1f), pack_bf16(o[1][2] * i1f, o[1][3] * i1f),
                                  pack_bf16(o[2][2] * i1f, o[2][3] * i1f), pack_bf16(o[3][2] * i1f, o[3][3] * i1f));
}

constexpr float SCALE_LOG2E = 0.08838834764831845f * 1.4426950408889634f;

constexpr int P_UNITS = 12, P_STAGES = 6;
constexpr int PS_STG = P_UNITS * 16384;
constexpr int PS_BAR = PS_STG + 32768;
constexpr int P_SMEM = PS_BAR + 256;
static_assert(P_SMEM <= 232448, "smem");
enum { K_Q, K_B1, K_B3, K_A4, K_QH, K_A3, K_SK, K_B2, K_SN, K_END };
struct PList { int n, nworker; int4 run[16]; };
struct PTask { int kind, a, b, c; };
DEVI PTask p_decode(const PList& pl, int id) {
    for (int i = 0; i < pl.n; i++) {
        const int4 r = pl.run[i];
        if (id < r.w) {
            const int j = id - r.z;
            if (r.x == K_Q || r.x == K_QH) return {r.x, j & 31, r.y + (j >> 5), 0};
            if (r.x == K_B1) return {r.x, j % 24, r.y + j / 24, 0};
            if (r.x == K_B2) return {r.x, 0, r.y + j, 0};
            if (r.x == K_SK || r.x == K_SN) return {r.x, (j / P_SPLIT) & 7, r.y + j / (8 * P_SPLIT), j % P_SPLIT};
            return {r.x, j & 7, r.y + (j >> 3), 0};
        }
    }
    return {K_END, 0, 0, 0};
}
DEVI void wait_count(const unsigned* p, unsigned target) {
    int n = 0;
    while (true) {
        unsigned v; asm volatile("ld.acquire.gpu.global.u32 %0, [%1];" : "=r"(v) : "l"(p) : "memory");
        if ((int)(v - target) >= 0) break;
        __nanosleep(100);
        if (++n > SPIN_LIMIT) TRAP(0x10000000u | ((unsigned)(size_t)p & 0xFFFFu));
    }
}
DEVI void wait_count_warp(const unsigned* p, unsigned target) {
    int n = 0;
    while (true) {
        unsigned v; asm volatile("ld.acquire.gpu.global.u32 %0, [%1];" : "=r"(v) : "l"(p) : "memory");
        if (__all_sync(0xffffffffu, (int)(v - target) >= 0)) break;
        __nanosleep(100);
        if (++n > SPIN_LIMIT) TRAP(0x10000000u | ((unsigned)(size_t)p & 0xFFFFu));
    }
}
DEVI void signal_count(unsigned* p) { __threadfence(); atomicAdd(p, 1u); }

struct PMaps { CUtensorMap wq, bw, bwo, wo, x, bx, bo, ox, ox64, cb, cout, cq, b40; PList list; };
constexpr int PB_F = PS_BAR, PB_E = PB_F + 48, PB_TF = PB_F + 96, PB_TE = PB_F + 112, PB_S = PB_F + 128;
constexpr int PS_T = PB_F + 144, PS_SIG = PS_T + 32, PS_SK = PS_SIG + 16;

struct PRing {
    int st, ph, u;
    DEVI void next(int n) { u += n; if (u >= P_UNITS) u -= P_UNITS; if (++st == P_STAGES) { st = 0; ph ^= 1; } }
    DEVI uint32_t w(bool wide) const { return wide && u == P_UNITS - 2 ? 0u : u * 16384u; }
    DEVI uint32_t x(bool wide) const { return wide && u == P_UNITS - 2 ? u * 16384u : (u == P_UNITS - 1 ? 0u : (u + 1) * 16384u); }
};
struct POut { const CUtensorMap* map; int col, tok, cnt; bool blocked; };
DEVI void p_store(const uint32_t* pk, const POut& o, int c, uint32_t stg, int warp, int lane_, int barid, bool elected) {
    const int lane = (int)opaque((uint32_t)lane_);
    const int mi = lane >> 3, r = lane & 7;
    const uint32_t buf = stg + (c & 1) * 8192;
    if (elected) asm volatile("cp.async.bulk.wait_group.read 1;" ::: "memory");
    nbar_sync(barid, 128);
    if (o.blocked) {
#pragma unroll
        for (int j = 0; j < 8; j += 2)
            stsm4(buf + (j + (mi >> 1)) * 1024 + (warp * 16 + (mi & 1) * 8 + r) * 16, pk[2 * j], pk[2 * j + 1], pk[2 * j + 2], pk[2 * j + 3]);
    } else {
#pragma unroll
        for (int j = 0; j < 8; j += 2)
            stsm4t(buf + (8 * (j + (mi >> 1)) + r) * 128 + ((2 * warp + (mi & 1)) ^ r) * 16, pk[2 * j], pk[2 * j + 1], pk[2 * j + 2], pk[2 * j + 3]);
    }
    fence_proxy_async();
    nbar_sync(barid, 128);
    if (elected) {
        if (o.blocked)
            asm volatile("cp.async.bulk.tensor.4d.global.shared::cta.bulk_group [%0, {%2, %3, %4, %5}], [%1];"
                         :: "l"(o.map), "r"(buf), "r"(0), "r"((o.col >> 5) & 2), "r"((o.col >> 7) * 4), "r"((o.tok >> 5) + 2 * c) : "memory");
        else tma_store_2d(o.map, buf, o.col, o.tok + c * 64);
        bulk_commit();
    }
}
DEVI void p_signal(uint32_t sb, int g, int cnt, int& nsig) {
    sts32(sb + PS_SIG + g * 8 + (nsig & 1) * 4, (uint32_t)cnt);
    mbar_arrive(sb + PB_S + g * 8);
    nsig++;
}
DEVI void p_release(uint32_t sb, const PRing& r) {
    if (elect_one()) mbar_arrive(sb + PB_E + (r.st ? r.st - 1 : P_STAGES - 1) * 8);
}
template <int BN, bool FIRST>
DEVI void p_kblock(float* d, uint32_t sb, int g, PRing& r) {
    mbar_wait(sb + PB_F + r.st * 8, r.ph);
    const uint64_t da = mk_desc(sb + r.w(BN == 256) + g * 8192, 16, 1024, 1), db = mk_desc(sb + r.x(BN == 256), 16, 1024, 1);
    wg_fence();
#pragma unroll
    for (int kk = 0; kk < 4; kk++) {
        if (BN == 256) { if (FIRST && kk == 0) wgmma_n256_ss<true>(d, da, db); else wgmma_n256_ss<false>(d, da + (uint64_t)(kk * 128), db + (uint64_t)(kk * 2)); }
        if (BN == 128) { if (FIRST && kk == 0) wgmma_n128_ss<true>(d, da, db); else wgmma_n128_ss<false>(d, da + (uint64_t)(kk * 128), db + (uint64_t)(kk * 2)); }
        if (BN == 64)  { if (FIRST && kk == 0) wgmma_n64_ss<true>(d, da, db); else wgmma_n64_ss<false>(d, da + (uint64_t)(kk * 128), db + (uint64_t)(kk * 2)); }
    }
    wg_commit();
    if (!FIRST) {
        wg_wait<1>();
        p_release(sb, r);
    }
    r.next(BN == 256 ? 3 : 2);
}

DEVI int post_claim(const PMaps& mp, unsigned E) {
    unsigned v = 0;
    if ((threadIdx.x & 31) == 0) v = atomicAdd(&g_qctr, 1u);
    return (int)(__shfl_sync(0xffffffffu, v, 0) - (E - 1) * (unsigned)(mp.list.run[mp.list.n - 1].w + mp.list.nworker));
}
DEVI void post_producer(const PMaps& mp, uint32_t sb, unsigned E, int id) {
    PRing r = {0, 0, 0};
    int ts = 0, tp = 0, used = 0;
    uint32_t big = 0;
    auto reserve = [&](int n) {
        while (used + n > P_UNITS) {
            mbar_wait(sb + PB_E + ts * 8, tp);
            used -= 2 + ((big >> ts) & 1);
            if (++ts == P_STAGES) { ts = 0; tp ^= 1; }
        }
        used += n;
        big = (big & ~(1u << r.st)) | ((uint32_t)(n & 1) << r.st);
    };
    for (int i = 0;; i++) {
        mbar_wait(sb + PB_TE + (i & 1) * 8, ((i >> 1) & 1) ^ 1);
        if (i > 0) id = post_claim(mp, E);
        const PTask tk = p_decode(mp.list, id);
        const bool sn = tk.kind == K_SN, split = tk.kind == K_SK || sn, wide = tk.kind <= K_A4;
        const bool qk = tk.kind == K_Q || tk.kind == K_QH, ak = tk.kind == K_A4 || tk.kind == K_A3 || split;
        const int nk = split ? HD / 64 / P_SPLIT : (ak ? HD / 64 : DM / 64), kb0 = tk.c * (HD / 64 / P_SPLIT);
        const int tok0 = tk.b * (wide ? 256 : (sn ? 64 : 128)), grp = (tok0 >> 7) + (wide ? 1 : 0);
        const uint32_t bytes = wide ? 49152 : (sn ? 24576 : 32768);
        const CUtensorMap* tx = tk.kind == K_B1 ? &mp.bx : (qk ? &mp.x : (sn ? &mp.ox64 : (ak ? &mp.ox : &mp.bo)));
        const int npre = split && (i == 0 || __any_sync(0xffffffffu, (int)(*(volatile unsigned*)&g_prog[grp] - 128 * E) < 0)) ? P_STAGES : 0;
        PRing rp = r;
        for (int kb = kb0; kb < kb0 + npre; kb++) {
            reserve(2);
            const uint32_t bar = sb + PB_F + r.st * 8;
            if (elect_one()) {
                mbar_expect_tx(bar, bytes);
                tma_load_wo(sb + r.w(false), &mp.wo, tk.a * 128, kb * 2, bar);
                tma_load_wo(sb + r.w(false) + 8192, &mp.wo, tk.a * 128 + 64, kb * 2, bar);
            }
            r.next(2);
        }
        if (tk.kind == K_B2) {
            wait_count_warp(&g_cnt[C_B1 + (tk.b >> 2)], 48 * E);
            if ((tk.b & 3) == 0 && tk.b > 0) wait_count_warp(&g_cnt[C_B1 + (tk.b >> 2) - 1], 48 * E);
        } else if (tk.kind == K_B3) wait_count_warp(&g_cnt[C_B2 + tk.b], 8 * E);
        else if (ak) wait_count_warp(&g_prog[grp], 128 * E);
        fence_proxy_global();
        for (int kb = kb0; kb < kb0 + npre; kb++) {
            if (elect_one()) tma_load_2d(sb + rp.x(false), tx, kb * 64, tok0, sb + PB_F + rp.st * 8);
            rp.next(2);
        }
        if (elect_one()) {
            sts128(sb + PS_T + (i & 1) * 16, make_uint4((uint32_t)tk.kind | ((uint32_t)id << 8), (uint32_t)tk.a, (uint32_t)tk.b, (uint32_t)tk.c));
            mbar_arrive(sb + PB_TF + (i & 1) * 8);
        }
        if (tk.kind == K_END) break;
        if (tk.kind == K_B2) {
            for (int j = 0; j < 16; j++) {
                reserve(2);
                const uint32_t bar = sb + PB_F + r.st * 8;
                if (elect_one()) {
                    mbar_expect_tx(bar, 2 * 15360);
#pragma unroll
                    for (int u = 0; u < 2; u++) asm volatile("cp.async.bulk.tensor.4d.shared::cluster.global.mbarrier::complete_tx::bytes [%0], [%1, {%3, %4, %5, %6}], [%2];"
                                 :: "r"(sb + (u ? r.x(false) : r.w(false))), "l"(&mp.b40), "r"(bar), "r"(j * 64), "r"(0), "r"(u), "r"(tk.b * 32 - 8) : "memory");
                }
                r.next(2);
            }
            continue;
        }
        const CUtensorMap* tw = tk.kind == K_B1 ? &mp.bw : (qk ? &mp.wq : (ak ? &mp.wo : &mp.bwo));
        for (int kb = kb0 + npre; kb < kb0 + nk; kb++) {
            reserve(wide ? 3 : 2);
            const uint32_t aw = sb + r.w(wide), ax = sb + r.x(wide), bar = sb + PB_F + r.st * 8;
            if (elect_one()) {
                mbar_expect_tx(bar, bytes);
                if (ak || tk.kind == K_B3) {
                    tma_load_wo(aw, tw, tk.a * 128, kb * 2, bar);
                    tma_load_wo(aw + 8192, tw, tk.a * 128 + 64, kb * 2, bar);
                } else {
                    tma_load_2d(aw, tw, tk.a * 128, kb * 64, bar);
                    tma_load_2d(aw + 8192, tw, tk.a * 128 + 64, kb * 64, bar);
                }
                tma_load_2d(ax, tx, kb * 64, tok0, bar);
                if (wide) tma_load_2d(ax + 16384, tx, kb * 64, tok0 + 128, bar);
            }
            r.next(wide ? 3 : 2);
        }
    }
    if (elect_one()) {
        __threadfence();
        if (atomicAdd(&g_done, 1u) == E * mp.list.nworker - 1) { __threadfence(); *(volatile unsigned*)&g_epoch = E; }
    }
}
DEVI void post_helper(uint32_t sb, int g) {
    for (int n = 0;; n++) {
        mbar_wait_sleepy(sb + PB_S + g * 8, n & 1);
        const int cnt = (int)lds32(sb + PS_SIG + g * 8 + (n & 1) * 4);
        if (cnt < 0) break;
        signal_count(&g_cnt[cnt]);
    }
}
template <int BN>
DEVI void p_narrow(const PMaps& mp, const PTask& tk, uint32_t sb, int g, int warp, PRing& r, int& nsig) {
    const int barid = 1 + g, tid = threadIdx.x;
    const bool elected = (tid & 127) == 0, split = BN == 64 || tk.kind == K_SK;
    constexpr int NV = BN / 16;
    float d[BN / 2];
    const int nk = split ? HD / 64 / P_SPLIT : (tk.kind == K_A3 ? HD / 64 : DM / 64);
    p_kblock<BN, true>(d, sb, g, r);
#pragma unroll 1
    for (int kb = 1; kb < nk; kb++) p_kblock<BN, false>(d, sb, g, r);
    wg_wait<0>();
    reg_fence<BN / 2>(d);
    p_release(sb, r);
    if (split) {
        const int tile = (tk.b * (BN / 64) - 2 * (16 - P_NSK)) * 8 + tk.a * (BN / 64);
        uint4* const base = g_skp + (uint32_t)(tile * P_SPLIT * 1024 + g * NV * 128 + (tid & 127));
#pragma unroll
        for (int j = 0; j < NV; j++)
            base[tk.c * NV * 256 + j * 128] = make_uint4(pack_bf16(d[8 * j], d[8 * j + 1]), pack_bf16(d[8 * j + 2], d[8 * j + 3]),
                                                         pack_bf16(d[8 * j + 4], d[8 * j + 5]), pack_bf16(d[8 * j + 6], d[8 * j + 7]));
        nbar_sync(barid, 128);
        if (elected) {
            unsigned old;
            asm volatile("atom.acq_rel.gpu.global.add.u32 %0, [%1], 1;" : "=r"(old) : "l"(&g_cnt_sk[tile * 2 + g]) : "memory");
            sts32(sb + PS_SK + g * 4, old % P_SPLIT);
        }
        nbar_sync(barid, 128);
        const bool last = lds32(sb + PS_SK + g * 4) == P_SPLIT - 1;
        nbar_sync(barid, 128);
        if (!last) return;
        uint4 v[(P_SPLIT - 1) * NV];
#pragma unroll
        for (int j = 0; j < (P_SPLIT - 1) * NV; j++) v[j] = __ldcg(base + ((tk.c + 1 + j / NV) % P_SPLIT) * NV * 256 + (j % NV) * 128);
#pragma unroll
        for (int j = 0; j < (P_SPLIT - 1) * NV; j++) {
            float* e = d + 8 * (j % NV);
            e[0] += __uint_as_float(v[j].x << 16); e[1] += __uint_as_float(v[j].x & 0xFFFF0000u);
            e[2] += __uint_as_float(v[j].y << 16); e[3] += __uint_as_float(v[j].y & 0xFFFF0000u);
            e[4] += __uint_as_float(v[j].z << 16); e[5] += __uint_as_float(v[j].z & 0xFFFF0000u);
            e[6] += __uint_as_float(v[j].w << 16); e[7] += __uint_as_float(v[j].w & 0xFFFF0000u);
        }
    }
    const bool qh = BN == 128 && tk.kind == K_QH;
    const POut o = {qh ? &mp.cq : &mp.cout, tk.a * 128 + g * 64, tk.b * BN, 0, qh};
    uint32_t q[BN / 4];
#pragma unroll
    for (int j = 0; j < BN / 4; j++) q[j] = pack_bf16(d[2 * j], d[2 * j + 1]);
    if (BN == 64 && elected) bulk_wait_read();
#pragma unroll
    for (int c = 0; c < BN / 64; c++) p_store(q + 16 * c, o, c, sb + PS_STG + g * 16384, warp, tid & 31, barid, elected);
    if (BN == 64 && elected) bulk_wait_read();
    if (elected && qh) { bulk_wait_all(); p_signal(sb, g, tk.b == 0 ? C_QH : C_Q, nsig); }
}
DEVI void post_consumer(const PMaps& mp, uint32_t sb, int g, int warp) {
    const int barid = 1 + g, tid = threadIdx.x, lane = tid & 31;
    const bool elected = (tid & 127) == 0;
    const uint32_t stg = sb + PS_STG + g * 16384;
    int nsig = 0;
    PRing r = {0, 0, 0};
    uint32_t pk[64];
    POut out;
    bool pend = false;
#pragma unroll
    for (int i = 0; i < 64; i++) pk[i] = 0u;
    for (int i = 0;; i++) {
        const uint32_t bTF = sb + PB_TF + (i & 1) * 8;
        if (pend) {
            uint32_t now;
            asm volatile("{.reg .pred p, q; mbarrier.test_wait.parity.shared::cta.b64 p, [%1], %2; bar.red.and.pred q, %3, 128, p; selp.u32 %0, 1, 0, q;}"
                         : "=r"(now) : "r"(bTF), "r"((i >> 1) & 1), "r"(barid) : "memory");
            if (!now || (lds32(sb + PS_T + (i & 1) * 16) & 255u) > K_A4) {
#pragma unroll
                for (int c = 0; c < 4; c++) p_store(pk + 16 * c, out, c, stg, warp, lane, barid, elected);
                if (elected && out.cnt != C_NONE) { bulk_wait_all(); p_signal(sb, g, out.cnt, nsig); }
                pend = false;
            }
        }
        mbar_wait(bTF, (i >> 1) & 1);
        const uint4 tw = lds128(sb + PS_T + (i & 1) * 16);
        mbar_arrive(sb + PB_TE + (i & 1) * 8);
        const PTask tk = {(int)(tw.x & 255u), (int)tw.y, (int)tw.z, (int)tw.w};
        if (tk.kind == K_END) break;
        if (tk.kind <= K_A4) {
            float d[128];
            const int nk = tk.kind == K_A4 ? HD / 64 : DM / 64;
            p_kblock<256, true>(d, sb, g, r);
            if (pend) p_store(pk, out, 0, stg, warp, lane, barid, elected);
#pragma unroll
            for (int c = 1; c < 4; c++) {
                p_kblock<256, false>(d, sb, g, r);
                if (pend) p_store(pk + 16 * c, out, c, stg, warp, lane, barid, elected);
            }
#pragma unroll 1
            for (int kb = 4; kb < nk; kb++) {
                p_kblock<256, false>(d, sb, g, r);
                if (kb == 6 && pend && elected && out.cnt != C_NONE) { bulk_wait_all(); p_signal(sb, g, out.cnt, nsig); }
            }
            wg_wait<0>();
            reg_fence<128>(d);
            p_release(sb, r);
#pragma unroll
            for (int j = 0; j < 64; j++) pk[j] = pack_bf16(d[2 * j], d[2 * j + 1]);
            out.map = tk.kind == K_Q ? &mp.cq : (tk.kind == K_B1 ? &mp.cb : &mp.cout);
            out.col = tk.a * 128 + g * 64 + (tk.kind == K_B3 ? DM : 0);
            out.tok = tk.b * 256;
            out.cnt = tk.kind == K_Q ? C_Q + tk.b : (tk.kind == K_B1 ? C_B1 + tk.b : C_NONE);
            out.blocked = tk.kind == K_Q;
            pend = true;
        } else if (tk.kind == K_B2) {
#pragma unroll 2
            for (int j = 0; j < 16; j++) {
                mbar_wait(sb + PB_F + r.st * 8, r.ph);
                const uint32_t a = sb + (g ? r.x(false) : r.w(false));
                battn_warp(a, sb + PB_E + r.st * 8, tk.b * 32, g, j * 2 + (warp >> 1), warp >> 1, warp & 1, lane);
                r.next(2);
            }
            nbar_sync(barid, 128);
            if (elected) p_signal(sb, g, C_B2 + (tk.b >> 2), nsig);
#pragma unroll
            for (int j = 0; j < 64; j++) pk[j] = 0u;
        } else {
            if (tk.kind == K_SN) p_narrow<64>(mp, tk, sb, g, warp, r, nsig); else p_narrow<128>(mp, tk, sb, g, warp, r, nsig);
#pragma unroll
            for (int j = 0; j < 64; j++) pk[j] = 0u;
        }
    }
    if (elected) { bulk_wait_all(); p_signal(sb, g, -1, nsig); }
}
DEVI void post_init(uint32_t sb) {
    for (int i = 0; i < P_STAGES; i++) { mbar_init(sb + PB_F + i * 8, 1); mbar_init(sb + PB_E + i * 8, 8); }
    for (int i = 0; i < 2; i++) { mbar_init(sb + PB_TF + i * 8, 1); mbar_init(sb + PB_TE + i * 8, 256); mbar_init(sb + PB_S + i * 8, 1); }
    fence_mbar_init();
}

constexpr unsigned long long R_TORD_PACK = 0xf5ea4937dc1826b0ull;
__host__ __device__ constexpr int r_tord(int pos) { return (int)((R_TORD_PACK >> (4 * pos)) & 15ull); }
__host__ __device__ constexpr int r_tinv(int T) { for (int p = 0; p < 16; p++) if (r_tord(p) == T) return p; return 0; }
__host__ __device__ constexpr bool r_pos_ss(int pos) { return pos % 3 == 2; }
__host__ __device__ constexpr int r_ss(int pos) { return pos / 3; }
__host__ __device__ constexpr int r_rs(int pos) { return pos - pos / 3; }
constexpr int R_NRS = 11, R_NSS = 5;
constexpr int R_G1 = 3, R_G2 = 9;
#define REG_KB 232
#define A_AT 2
#define A_PRE 4
#define WO_REL 0
constexpr int X_SLOTS = 4;
constexpr int X_NST = 8;

constexpr int RS_WSS  = 0;
constexpr int RS_WO   = RS_WSS + R_NSS * 16384;
constexpr int RS_MEM  = RS_WO + 5 * 16384;
constexpr int RS_O    = RS_MEM + 16384;
constexpr int RS_SX   = RS_O + 2048;
constexpr int RS_BAR  = RS_SX + 2048;
constexpr int RS_TAIL = RS_BAR + 1024;
constexpr int RS_WO5  = RS_TAIL;
constexpr int RS_K    = RS_WO5 + 16384;
constexpr int RS_V    = RS_K + 10240;
constexpr int RS_Q    = RS_V + 10240;
constexpr int RS_QX   = RS_Q + 2048;
constexpr int RS_QEND = RS_QX + 8192;
constexpr int RS_X    = RS_TAIL;
constexpr int X_PITCH = X_SLOTS * 4096;
constexpr int RS_XD   = RS_X + 2 * X_PITCH;
constexpr int RS_WX   = RS_XD + 8192;
constexpr int RS_KEND = RS_WX + 4096;
constexpr int RS_EV   = RS_BAR + 256;
constexpr int R_SMEM  = RS_KEND > RS_QEND ? RS_KEND : RS_QEND;
static_assert(R_SMEM <= 232448 && P_SMEM <= R_SMEM, "smem");
static_assert(RS_TAIL % 1024 == 0 && RS_MEM % 1024 == 0, "alignment");

constexpr int RB_G = RS_BAR, RB_K = RS_BAR + 24, RB_V = RS_BAR + 32, RB_KV = RS_BAR + 40, RB_QX = RS_BAR + 48, RB_O = RS_BAR + 56;
constexpr int RB_ATT = RS_BAR + 64, RB_W = RS_BAR + 72, RB_SF = RS_BAR + 80, RB_SE = RB_SF + 40, RB_XF = RB_SE + 40;
constexpr int RB_WO = RB_XF + 56, RB_T = RB_XF + 64, RS_INV = RS_SX + 1024;
static_assert(RB_T + 8 <= RS_EV, "barriers");
constexpr uint32_t SB0 = 1024;
__host__ __device__ constexpr uint32_t cdesc(uint32_t off, uint32_t lbo) { return ((SB0 + off) >> 4) | ((lbo >> 4) << 16); }
#define SCHED_FENCE() __syncwarp()
constexpr int NB_BIG = 1, NB_Q = 2, NB_AUX = 3, NB_WO = 4, NB_XS = 5, NB_WG = 6, NB_PAIR = 8;

DEVI int tid_now() { int t; asm volatile("mov.u32 %0, %%tid.x;" : "=r"(t)); return t; }
DEVI uint32_t a_frag_off(int lane, int warp) { return (uint32_t)((((lane >> 4) * 8 + (lane & 7)) * 128) + (((2 * warp + ((lane >> 3) & 1)) ^ (lane & 7)) * 16)); }
DEVI uint32_t b_frag_off(int lane) { return (uint32_t)((lane & 3) * 64 + (((lane >> 2) * 8) ^ ((lane & 2) * 16))); }
DEVI void lds_b(uint32_t* b, uint32_t a) {
    asm volatile("ld.shared.v2.u32 {%0,%1}, [%2];" : "=r"(b[0]), "=r"(b[1]) : "r"(a) : "memory");
    asm volatile("ld.shared.v2.u32 {%0,%1}, [%2];" : "=r"(b[2]), "=r"(b[3]) : "r"(a + 256) : "memory");
}
DEVI uint32_t clk32() { unsigned long long c; asm volatile("mov.u64 %0, %%clock64;" : "=l"(c)); return (uint32_t)c; }

__host__ __device__ constexpr int x_pair(int j) { return j == 0 || j > 3 ? j : (j == 3 ? 1 : j + 1); }
DEVI void x_load(uint32_t sb, int seg, int j, int g, const CUtensorMap* tmX) {
    const uint32_t bar = sb + RB_XF + g * 8;
    mbar_expect_tx(bar, 4096);
    tma_load_3d(sb + RS_X + g * X_PITCH + (j % X_SLOTS) * 4096, tmX, g * 32, seg * 32, x_pair(j) * 2, bar);
}
DEVI void x_refill(uint32_t sb, int seg, int j, int g, int warp, const CUtensorMap* tmX) {
    const int sn = j + X_SLOTS < X_NST ? seg : seg + 1;
    if (warp == (j & 3) && sn < NSEG) {
        if (elect_one()) x_load(sb, sn, (j + X_SLOTS) % X_NST, g, tmX);
    }
}
template <int H>
DEVI void x_half(float* xa, uint32_t* a, uint32_t aA0, const uint32_t* w, uint32_t sb, int seg, int g0, int warp, const CUtensorMap* tmX) {
    wg_fence();
#pragma unroll
    for (int grp = 0; grp < 4; grp++) {
        const int g = (int)opaque((uint32_t)g0);
        const uint32_t dW0 = cdesc(RS_WSS, 16) + g * 768, dW1 = cdesc(RS_WSS + 8192, 16) - g * 256;
#pragma unroll
        for (int i = 0; i < 8; i++) {
            const bool last = H == 1 && grp >= 2;
            const int j = last ? 6 + (i >> 2) : 4 * H + grp, q = last ? 2 * (i & 3) + (grp == 2) : i;
            const int pos = r_tinv(2 * x_pair(j) + (q >> 2)), kk = (q >> 1) & 1, mt = q & 1;
            const uint32_t db = cdesc(RS_X + (j % X_SLOTS) * 4096, 16) + g * (X_PITCH >> 4) + (q >> 2) * 128 + kk * 2;
            if (j == 0 && q < 2)   wgmma_n32_rs_first(xa + 16 * mt, &w[((r_rs(pos) * 2 + kk) * 2 + mt) * 4], db);
            else if (j == 0 && q == 3) wgmma_n32_ss(xa + 16, cdesc(RS_WX, 16) + g * 128, db);
            else if (r_pos_ss(pos)) wgmma_n32_ss(xa + 16 * mt, (mt ? dW1 : dW0) + r_ss(pos) * 1024 + kk * 128, db);
            else                   wgmma_n32_rs(xa + 16 * mt, &w[((r_rs(pos) * 2 + kk) * 2 + mt) * 4], db);
        }
        wg_commit();
    }
    const int g = (int)opaque((uint32_t)g0);
    auto prefetch = [&]() {
        SCHED_FENCE();
#pragma unroll
        for (int q = 0; q < A_PRE; q++) ldsm4t(a + 4 * q, aA0 + (q & 1) * (8192 - g * 16384) + (q >> 1) * 2048);
        SCHED_FENCE();
    };
    if (H == 1 && A_AT == 1) prefetch();
    wg_wait<3>(); x_refill(sb, seg, 4 * H, g, warp, tmX);
    if (H == 1 && A_AT == 2) prefetch();
    wg_wait<2>(); x_refill(sb, seg, 4 * H + 1, g, warp, tmX);
    if (H == 1 && A_AT == 3) prefetch();
    if (H == 0 && A_AT == 5) prefetch();
    wg_wait<1>();
    if (H == 0) {
        if (A_AT == 4) prefetch();
        x_refill(sb, seg, 2, g, warp, tmX);
        wg_wait<0>(); reg_fence<32>(xa); x_refill(sb, seg, 3, g, warp, tmX);
    } else reg_fence<16>(xa + 16);
}
DEVI void x_finish(float* xa, uint32_t sb, int seg, int g, int warp, int lane, const CUtensorMap* tmX) {
    const uint32_t d = sb + RS_XD + (lane >> 4) * 2048 + warp * 256 + (lane & 15) * 16;
#pragma unroll
    for (int i = 0; i < 2; i++) {
        const float* x = xa + 16 + 8 * i;
        sts128(d + (g ^ 1) * 1024 + i * 4096, make_uint4(pack_bf16(x[0], x[1]), pack_bf16(x[2], x[3]), pack_bf16(x[4], x[5]), pack_bf16(x[6], x[7])));
    }
    nbar_sync(NB_PAIR + warp, 64);
    float y[16];
#pragma unroll
    for (int i = 0; i < 2; i++) {
        const uint4 v = lds128(d + g * 1024 + i * 4096);
        const uint32_t u[4] = {v.x, v.y, v.z, v.w};
#pragma unroll
        for (int j = 0; j < 4; j++) { y[8 * i + 2 * j] = __uint_as_float(u[j] << 16); y[8 * i + 2 * j + 1] = __uint_as_float(u[j] & 0xFFFF0000u); }
    }
    reg_fence<16>(y);
    wg_wait<0>();
    reg_fence<16>(xa);
    uint32_t p[8];
#pragma unroll
    for (int j = 0; j < 8; j++) p[j] = pack_bf16(xa[2 * j] + y[2 * j], xa[2 * j + 1] + y[2 * j + 1]);
    __syncwarp();
    stsm4(d + g * 1024, p[0], p[1], p[2], p[3]);
    stsm4(d + g * 1024 + 4096, p[4], p[5], p[6], p[7]);
    nbar_arrive(NB_XS, 256 + 32);
    x_refill(sb, seg, X_NST - 2, g, warp, tmX);
    x_refill(sb, seg, X_NST - 1, g, warp, tmX);
}
DEVI void x_send(uint32_t sb, int seg, uint32_t rank, int vdelay) {
    mbar_wait(sb + RB_ATT, (seg - 1) & 1);
    nbar_sync(NB_XS, 256 + 32);
    if (rank == 2) { const uint32_t t = clk32() + vdelay; while ((int)(clk32() - t) < 0) { } }
    if (elect_one()) {
        fence_proxy_async();
        bulk_copy_s2c(mapa(sb + (rank == 1 ? RS_K : RS_V) + 2048, 0), sb + RS_XD, 8192, mapa(sb + (rank == 1 ? RB_KV : RB_V), 0));
    }
    __syncwarp();
}

template <bool XP>
DEVI void mem_pass(float* c0, float* c1, uint32_t* a, const uint32_t* w, uint32_t sb, uint32_t aA0, uint32_t aB, int g, int warp, int s) {
    const uint32_t aA1 = aA0 + 8192 - g * 16384, par = (s - 1) & 1;
    uint32_t b[2][4], e[4];
    float d0[4], d1[4];
    if (XP) ldsm4t(e, aA0 + opaque((RS_WX - RS_WSS) - g * (8192 + 2048)));
#pragma unroll
    for (int q = XP ? A_PRE : 0; q < 4; q++) ldsm4t(a + 4 * q, ((q & 1) ? aA1 : aA0) + (q >> 1) * 2048);
#pragma unroll
    for (int i = 0; i < 4; i++) { c0[i] = 0.f; c1[i] = 0.f; d0[i] = 0.f; d1[i] = 0.f; }
    EV(EV_BIG0, s, 0);
    mbar_wait(sb + RB_G, par);
    EV(EV_BIG0, s, 1);
    lds_b(b[0], aB + r_tord(0) * 1024);
    bool in = false;
#pragma unroll
    for (int pos = 0; pos < 16; pos++) {
        if (pos + 1 < 16) {
            if (pos + 1 == R_G1 && !in) mbar_wait(sb + RB_G + 8, par);
            if (pos + 1 == R_G2) { if (!in) mbar_wait(sb + RB_G + 16, par); EV(EV_BIG0, s, 2); }
            lds_b(b[(pos + 1) & 1], aB + r_tord(pos + 1) * 1024);
        }
        if (pos + 2 == R_G1) in = mbar_try(sb + RB_G + 8, par);
        if (pos + 2 == R_G2) in = mbar_try(sb + RB_G + 16, par);
        if (XP && pos == 12) in = s == NSEG - 1 || mbar_try(sb + RB_XF + g * 8, 0);
        if (XP && pos == 14) { if (!in) mbar_wait(sb + RB_XF + g * 8, 0); in = mbar_try(sb + RB_ATT, par); }
        const uint32_t* bb = b[pos & 1];
        const uint32_t* aa = r_pos_ss(pos) ? a : &w[r_rs(pos) * 16];
        mma16816(c1, aa + 4, bb[0], bb[1]);
        mma16816(d1, XP && pos == 0 ? e : aa + 12, bb[2], bb[3]);
        mma16816(c0, aa, bb[0], bb[1]);
        mma16816(d0, aa + 8, bb[2], bb[3]);
        if (r_pos_ss(pos) && pos + 3 < 16) {
#pragma unroll
            for (int q = 0; q < 4; q++) ldsm4t(a + 4 * q, ((q & 1) ? aA1 : aA0) + (r_ss(pos) + 1) * 16384 + (q >> 1) * 2048);
        }
        SCHED_FENCE();
    }
    if (XP && !in) mbar_wait(sb + RB_ATT, par);
#pragma unroll
    for (int i = 0; i < 4; i++) { c1[i] += d1[i]; c0[i] += d0[i]; }
}

DEVI uint32_t k_frag_off(int lane) { return (uint32_t)((((lane >> 3) & 1) * 16 + (lane >> 4) * 8 + (lane & 7)) * 16); }
DEVI uint32_t v_frag_off(int lane) { return (uint32_t)(((lane >> 3) & 1) * 2048 + ((lane >> 4) * 8 + (lane & 7)) * 16); }
DEVI void pv_pair(float (*o)[4], const uint32_t* p, const uint32_t* v) {
#pragma unroll
    for (int n = 0; n < 4; n++) mma16816(o[n], p, v[2 * n], v[2 * n + 1]);
}
DEVI void pv_single(float (*o)[4], const uint32_t* p, const uint32_t* v) {
#pragma unroll
    for (int n = 0; n < 4; n++) mma1688(o[n], p[0], p[1], v[n]);
}
DEVI void s_tile(const uint32_t* qa, const uint32_t* k, float& s0, float& s1) {
    float c[4][4];
#pragma unroll
    for (int q = 0; q < 4; q++) { c[q][0] = c[q][1] = c[q][2] = c[q][3] = 0.f; }
#pragma unroll
    for (int q = 0; q < 4; q++) {
        mma16816(c[2 * (q & 1)], qa + 4 * q, k[4 * q], k[4 * q + 1]);
        mma16816(c[2 * (q & 1) + 1], qa + 4 * q, k[4 * q + 2], k[4 * q + 3]);
    }
    s0 = (c[0][0] + c[1][2]) + (c[2][0] + c[3][2]);
    s1 = (c[0][1] + c[1][3]) + (c[2][1] + c[3][3]);
}
DEVI void mem_scores(uint32_t sb, int s, int warp, int lane) {
    const uint32_t ka = sb + RS_K + k_frag_off(lane) + (1 + warp) * 2048;
    uint32_t qa[16], kx[16];
    const bool in = mbar_try(sb + RB_KV, s & 1);
    nbar_sync(NB_Q, 256);
#pragma unroll
    for (int q = 0; q < 4; q++) ldsm4t(qa + 4 * q, sb + RS_Q + q * 512 + lane * 16);
    if (!in) mbar_wait(sb + RB_KV, s & 1);
#pragma unroll
    for (int q = 0; q < 4; q++) ldsm4t(kx + 4 * q, ka + q * 512);
    SCHED_FENCE();
    float s0, s1;
    s_tile(qa, kx, s0, s1);
    asm volatile("st.shared.v2.f32 [%0], {%1,%2};" :: "r"(sb + RS_SX + warp * 256 + lane * 8), "f"(s0), "f"(s1) : "memory");
    nbar_arrive(NB_XS, 256);
}
DEVI void mem_attn(uint32_t sb, int s, int warp, int lane) {
    const uint32_t ka = sb + RS_K + k_frag_off(lane), va = sb + RS_V + warp * 512;
    const uint32_t dst = sb + RS_O + warp * 512 + (lane & 3) * 128 + (lane >> 2) * 16;
    [[maybe_unused]] constexpr int g = 0;
    uint32_t qa[16], vx[16];
    float sc[10];
    nbar_sync(NB_Q, 256);
    EV(EV_BIG0 && lds32(sb + RS_Q) != 0x12345678u, s, 8);
#pragma unroll
    for (int q = 0; q < 4; q++) ldsm4t(qa + 4 * q, sb + RS_Q + q * 512 + lane * 16);
    mbar_wait(sb + RB_K, s & 1);
    EV(EV_BIG0, s, 9);
    {
        uint32_t km[16];
#pragma unroll
        for (int q = 0; q < 4; q++) ldsm4t(km + 4 * q, ka + q * 512);
        nbar_sync(NB_XS, 256);
        s_tile(qa, km, sc[0], sc[1]);
    }
#pragma unroll
    for (int n = 0; n < 4; n++) { const float2 v = lds64f(sb + RS_SX + n * 256 + lane * 8); sc[2 + 2 * n] = v.x; sc[3 + 2 * n] = v.y; }
    const bool v_in = mbar_try(sb + RB_V, s & 1);
    float m = fmaxf(fmaxf(fmaxf(sc[2], sc[3]), fmaxf(sc[4], sc[5])), fmaxf(fmaxf(sc[6], sc[7]), fmaxf(sc[8], sc[9])));
    m = fmaxf(m, fmaxf(sc[0], sc[1]));
    m = fmaxf(fmaxf(m, __shfl_xor_sync(0xffffffffu, m, 1)), fmaxf(__shfl_xor_sync(0xffffffffu, m, 2), __shfl_xor_sync(0xffffffffu, m, 3)));
    EV(warp == 0 && m != 1.2345e30f && elect_one(), s, 5);
    if (!v_in) mbar_wait(sb + RB_V, s & 1);
    EV(warp == 0 && elect_one(), s, 13);
    uint32_t vm[4], p[10];
#pragma unroll
    for (int q = 3; q >= 0; q--) ldsm4(vx + 4 * q, va + 2048 + (q >> 1) * 4096 + (q & 1) * 256 + v_frag_off(lane));
    ldsm4(vm, va + lane * 16);
    SCHED_FENCE();
    const float nm = -m * SCALE_LOG2E;
    float l = 0.f;
#pragma unroll
    for (int n = 4; n >= 0; n--) {
        const float e0 = ex2(fmaf(sc[2 * n], SCALE_LOG2E, nm)), e1 = ex2(fmaf(sc[2 * n + 1], SCALE_LOG2E, nm));
        l += e0 + e1;
        p[2 * n] = pack_bf16(e0, e1); p[2 * n + 1] = __float_as_uint(e0);
    }
    float o[4][4];
#pragma unroll
    for (int n = 0; n < 4; n++) { o[n][0] = o[n][1] = o[n][2] = o[n][3] = 0.f; }
    pv_pair(o, p + 6, vx + 8);
    pv_pair(o, p + 2, vx);
    pv_single(o, p, vm);
    l = (l + __shfl_xor_sync(0xffffffffu, l, 1)) + (__shfl_xor_sync(0xffffffffu, l, 2) + __shfl_xor_sync(0xffffffffu, l, 3));
    const uint4 u = make_uint4(pack_bf16(o[0][0], o[0][1]), pack_bf16(o[1][0], o[1][1]), pack_bf16(o[2][0], o[2][1]), pack_bf16(o[3][0], o[3][1]));
    st_async128(mapa(dst, 1), u.x, u.y, u.z, u.w, mapa(sb + RB_O, 1));
    st_async128(mapa(dst, 2), u.x, u.y, u.z, u.w, mapa(sb + RB_O, 2));
    const uint32_t dl = sb + RS_INV + (lane & 3) * 32 + (lane & 28);
    asm volatile("st.async.weak.shared::cluster.mbarrier::complete_tx::bytes.b32 [%0], %1, [%2];"
                 :: "r"(mapa(dl, 1 + (warp & 1))), "r"(__float_as_uint(l)), "r"(mapa(sb + RB_O, 1 + (warp & 1))) : "memory");
    sts128(dst, u);
    sts32(dl, __float_as_uint(l));
    __syncwarp();
    if (elect_one()) mbar_arrive(sb + RB_O);
    EV(warp == 0 && elect_one(), s, 15);
}

DEVI void ta_mask(float* c, int cw, int lane) {
    const int mt = cw >= 3, over = 8 * (cw - 3 * mt - 1) + 2 * (lane & 3) - 16 * mt - (lane >> 2);
    if (over > 0) c[0] = -INFINITY;
    if (over >= 0) c[1] = -INFINITY;
    if (over > 8) c[2] = -INFINITY;
    if (over >= 8) c[3] = -INFINITY;
}
DEVI void ta_scores(uint32_t sb, int seg, int warp, int lane) {
    const int tx = warp == 3 ? 0 : (warp == 2 ? 1 : 4 + 2 * warp), ty = warp == 3 ? 3 : tx + 1;
    const uint32_t qa = sb + RS_QX + ((warp < 2 ? 2 : 0) + ((lane >> 3) & 1)) * 2048 + ((lane >> 4) * 8 + (lane & 7)) * 16;
    const uint32_t ka = sb + RS_K + (warp < 2 ? tx - 3 : tx) * 2048 + lane * 16;
    float x[4] = {0.f, 0.f, 0.f, 0.f}, y[4] = {0.f, 0.f, 0.f, 0.f};
    mbar_wait(sb + RB_QX, seg & 1);
    if (warp < 3) {
#pragma unroll
        for (int j = 0; j < 4; j++) {
            uint32_t a0[4], a1[4], bx[4], by[4];
            ldsm4t(a0, qa + j * 512); ldsm4t(bx, ka + j * 512); ldsm4t(by, ka + 2048 + j * 512); ldsm4t(a1, qa + j * 512 + 256);
            mma16816(x, a0, bx[0], bx[1]); mma16816(y, a0, by[0], by[1]);
            mma16816(x, a1, bx[2], bx[3]); mma16816(y, a1, by[2], by[3]);
        }
        ta_mask(x, tx, lane); ta_mask(y, ty, lane);
    } else {
        mbar_wait(sb + RB_K, seg & 1);
#pragma unroll
        for (int j = 0; j < 4; j++) {
            uint32_t a0[4], a1[4], a2[4], a3[4], b[4];
            ldsm4t(a0, qa + j * 512); ldsm4t(b, ka + j * 512); ldsm4t(a2, qa + 4096 + j * 512);
            ldsm4t(a1, qa + j * 512 + 256); ldsm4t(a3, qa + 4096 + j * 512 + 256);
            mma16816(x, a0, b[0], b[1]); mma16816(y, a2, b[0], b[1]);
            mma16816(x, a1, b[2], b[3]); mma16816(y, a3, b[2], b[3]);
        }
    }
    nbar_sync(NB_WG + 1, 128);
    asm volatile("st.shared.v2.f32 [%0], {%1,%2};" :: "r"(sb + RS_QX + 4096 + tx * 256 + lane * 8), "f"(fmaxf(x[0], x[1])), "f"(fmaxf(x[2], x[3])) : "memory");
    asm volatile("st.shared.v2.f32 [%0], {%1,%2};" :: "r"(sb + RS_QX + 4096 + ty * 256 + lane * 8), "f"(fmaxf(y[0], y[1])), "f"(fmaxf(y[2], y[3])) : "memory");
    nbar_sync(NB_WG + 1, 128);
    float m[4] = {-INFINITY, -INFINITY, -INFINITY, -INFINITY};
#pragma unroll
    for (int n = 0; n < 8; n++) {
        if (n < 3 ? warp >= 2 : warp != 2) {
            const float2 v = lds64f(sb + RS_QX + 4096 + n * 256 + lane * 8);
            m[n < 3 ? 0 : 2] = fmaxf(m[n < 3 ? 0 : 2], v.x); m[n < 3 ? 1 : 3] = fmaxf(m[n < 3 ? 1 : 3], v.y);
        }
    }
#pragma unroll
    for (int o = 1; o < 4; o <<= 1) {
#pragma unroll
        for (int i = 0; i < 4; i++) m[i] = fmaxf(m[i], __shfl_xor_sync(0xffffffffu, m[i], o));
    }
    const float x0 = (warp < 2 ? m[2] : m[0]) * -SCALE_LOG2E, x1 = (warp < 2 ? m[3] : m[1]) * -SCALE_LOG2E;
    const float y0 = (warp == 2 ? m[0] : m[2]) * -SCALE_LOG2E, y1 = (warp == 2 ? m[1] : m[3]) * -SCALE_LOG2E;
    sts64(sb + RS_QX + tx * 256 + lane * 8, pack_bf16(ex2(fmaf(x[0], SCALE_LOG2E, x0)), ex2(fmaf(x[1], SCALE_LOG2E, x0))),
                                            pack_bf16(ex2(fmaf(x[2], SCALE_LOG2E, x1)), ex2(fmaf(x[3], SCALE_LOG2E, x1))));
    sts64(sb + RS_QX + ty * 256 + lane * 8, pack_bf16(ex2(fmaf(y[0], SCALE_LOG2E, y0)), ex2(fmaf(y[1], SCALE_LOG2E, y0))),
                                            pack_bf16(ex2(fmaf(y[2], SCALE_LOG2E, y1)), ex2(fmaf(y[3], SCALE_LOG2E, y1))));
}
template <int MT>
DEVI void ta_output(uint32_t sb, int seg, int head, int j, int lane) {
    const uint32_t pa = sb + RS_QX + MT * 768 + lane * 8, vb = sb + RS_V + j * 512;
    uint32_t p[6 + 4 * MT], v[12 + 8 * MT];
#pragma unroll
    for (int n = 0; n < 3 + 2 * MT; n++)
        asm volatile("ld.shared.v2.u32 {%0,%1}, [%2];" : "=r"(p[2 * n]), "=r"(p[2 * n + 1]) : "r"(pa + n * 256) : "memory");
#pragma unroll
    for (int q = 0; q < 2 + 2 * MT; q++) ldsm4(v + 4 * q, vb + (q >> 1) * 4096 + (q & 1) * 256 + v_frag_off(lane));
    ldsm4(v + 8 + 8 * MT, vb + 4096 + MT * 4096 + lane * 16);
    float o[4][4], l[4] = {0.f, 0.f, 0.f, 0.f};
#pragma unroll
    for (int n = 0; n < 4; n++) { o[n][0] = o[n][1] = o[n][2] = o[n][3] = 0.f; }
    mma16816(l, p, 0x3F803F80u, 0x3F803F80u);
    pv_pair(o, p, v);
    if (MT) { mma16816(l, p + 4, 0x3F803F80u, 0x3F803F80u); pv_pair(o, p + 4, v + 8); }
    mma1688(l, p[4 + 4 * MT], p[5 + 4 * MT], 0x3F803F80u);
    pv_single(o, p + 4 + 4 * MT, v + 8 + 8 * MT);
    const float i0 = rcp_fast(l[0]), i1 = rcp_fast(l[2]);
    bf16* dst = g_ox + (uint32_t)((seg * 32 + MT * 16 + (lane >> 2)) * HD + head * DH + j * 32 + (lane & 3) * 8);
    asm volatile("st.global.v4.u32 [%0], {%1,%2,%3,%4};" :: "l"(dst), "r"(pack_bf16(o[0][0] * i0, o[0][1] * i0)), "r"(pack_bf16(o[1][0] * i0, o[1][1] * i0)),
                 "r"(pack_bf16(o[2][0] * i0, o[2][1] * i0)), "r"(pack_bf16(o[3][0] * i0, o[3][1] * i0)) : "memory");
    asm volatile("st.global.v4.u32 [%0], {%1,%2,%3,%4};" :: "l"(dst + 8 * HD), "r"(pack_bf16(o[0][2] * i1, o[0][3] * i1)), "r"(pack_bf16(o[1][2] * i1, o[1][3] * i1)),
                 "r"(pack_bf16(o[2][2] * i1, o[2][3] * i1)), "r"(pack_bf16(o[3][2] * i1, o[3][3] * i1)) : "memory");
}

template <bool XP>
DEVI void big_main(const uint32_t* w, const uint32_t sb, const int g, const int warp, const uint32_t rank, const int head,
                   const CUtensorMap* tmX, const bf16* xg, const unsigned E) {
    float xa[32];
    uint32_t a[16];
    const uint32_t aB = __shfl_sync(0xffffffffu, sb + RS_MEM + (g * 32 + (tid_now() & 31)) * 16, tid_now() & 31);
#define lane0 ((int)(opaque(aB) >> 4) & 31)
    const uint32_t aA0 = sb + RS_WSS + g * (8192 + 4096) + a_frag_off(lane0, warp);
    const uint32_t aBf = sb + RS_MEM + g * 512 + b_frag_off(lane0);
    if constexpr (XP) {
        mbar_wait(sb + RB_XF + g * 8, 0);
        x_half<0>(xa, a, aA0, w, sb, 0, g, warp, tmX);
        mbar_wait(sb + RB_XF + g * 8, 1);
        x_half<1>(xa, a, aA0, w, sb, 0, g, warp, tmX);
        x_finish(xa, sb, 0, g, warp, lane0, tmX);
    }
    nbar_sync(NB_BIG, 256);
    for (int s = 0; s < NSEG; s++) {
        float c0[4], c1[4];
        mem_pass<XP>(c0, c1, a, w, sb, aA0, aBf, g, warp, s);
        EV(EV_BIG0 && c0[0] != 1.2345e30f, s, 3);
        const uint32_t xs = aB + (RS_O - RS_MEM) + (warp - g) * 512;
        sts128f(xs + g * 2048, c1);
        auto combine = [&]() {
            const uint32_t d = sb + (XP ? (rank == 1 ? RS_K : RS_V) : RS_Q) + (g * 4 + warp) * 256 + lane0 * 4;
            const uint32_t rbar = XP ? mapa(sb + (rank == 1 ? RB_K : RB_V), 0) : 0u;
            nbar_sync(NB_PAIR + warp, 64);
            const uint4 v = lds128(xs + (g ^ 1) * 2048);
            const uint32_t p0 = pack_bf16(c0[0] + __uint_as_float(v.x), c0[1] + __uint_as_float(v.y));
            const uint32_t p1 = pack_bf16(c0[2] + __uint_as_float(v.z), c0[3] + __uint_as_float(v.w));
            if constexpr (XP) { st_async32(mapa(d, 0), p0, rbar); st_async32(mapa(d + 128, 0), p1, rbar); }
            else { sts32(d, p0); sts32(d + 128, p1); }
            EV(EV_BIG0, s, 4);
        };
        combine();
        if constexpr (XP) {
            if (s == NSEG - 1) break;
            x_half<0>(xa, a, aA0, w, sb, s + 1, g, warp, tmX);
            EV(EV_BIG0, s, 5);
            EVCAL(s);
            mbar_wait(sb + RB_XF + g * 8, 1);
            nbar_sync(NB_WO, 384);
            EV(EV_BIG0 && lds32(sb + RS_O) != 0x12345678u, s, 6);
            x_half<1>(xa, a, aA0, w, sb, s + 1, g, warp, tmX);
            EV(EV_BIG0, s, 7);
            x_finish(xa, sb, s + 1, g, warp, lane0, tmX);
        } else {
            if (g == 0) {
                if (s < NSEG - 1) mem_attn(sb, s, warp, lane0);
            } else {
                if (s < NSEG - 1) mem_scores(sb, s, warp, lane0); else mbar_wait(sb + RB_KV, s & 1);
                if (s == 0 && warp == 0) {
                    wait_count_warp(&g_cnt[C_QH], 64 * E);
                    if (elect_one()) {
                        fence_proxy_global();
                        mbar_expect_tx(sb + RB_QX, 8192);
                        bulk_load(sb + RS_QX, g_qx + (uint32_t)(head * 4096), 8192, sb + RB_QX);
                    }
                    __syncwarp();
                }
                ta_scores(sb, s, warp, lane0);
            }
            EVCAL(s);
            mbar_wait(sb + RB_V, s & 1);
            if (s < NSEG - 1) nbar_sync(NB_WO, 384); else nbar_sync(NB_BIG, 256);
            EV(EV_BIG0 && lds32(sb + RS_O) != 0x12345678u, s, 6);
            if (g == 0) ta_output<0>(sb, s, head, warp, lane0); else ta_output<1>(sb, s, head, warp, lane0);
            nbar_sync(NB_BIG, 256);
            EV(EV_BIG0 && lds32(sb + RS_O) != 0x12345678u, s, 7);
            if (g == 0 && warp == 0 && s + 1 < NSEG) {
                if (elect_one()) {
                    mbar_arrive_remote(mapa(sb + RB_ATT, 1));
                    mbar_arrive_remote(mapa(sb + RB_ATT, 2));
                    mbar_expect_tx(sb + RB_KV, 8192);
                    mbar_expect_tx(sb + RB_K, 2048);
                    mbar_expect_tx(sb + RB_V, 2048 + 8192);
                    mbar_arrive(sb + RB_T);
                }
                __syncwarp();
            }
        }
    }
    if constexpr (!XP) { if (tid_now() == 0) signal_count(&g_prog[(NSEG - 1) >> 2]); }
#undef lane0
}

template <int T, int K0, int K1>
DEVI void wo_part(float* acc) {
    constexpr uint32_t dWo = cdesc(T < 5 ? RS_WO + T * 16384 : RS_WO5, 16), dO = cdesc(RS_O, 128);
#pragma unroll
    for (int kk = K0; kk < K1; kk++) {
        if (kk == 0) { if (T < 3) wgmma_n8_ss_first<0>(acc, dWo, dO); else wgmma_n8_ss<0, 0>(acc, dWo, dO); }
        else wgmma_n8_ss<0, 1>(acc, dWo + kk * 128, dO + kk * 16);
    }
    wg_commit();
}
DEVI void red3(uint8_t* p, uint32_t a, uint32_t b, uint32_t c, uint32_t one) {
    asm volatile("red.relaxed.gpu.global.add.noftz.v4.bf16x2 [%0], {%1,%2,%3,%4};" :: "l"(p), "r"(a), "r"(b), "r"(c), "r"(one) : "memory");
}
constexpr int ACC_CH = 3 * 16 * 1024;
template <bool Q>
DEVI void wo_phase(uint32_t sb, int s, int warp, uint8_t* p, uint32_t ainv, int gap) {
    float a0[4], a1[4], a2[4];
    fence_proxy_async();
    const float2 iv = lds64f(ainv);
    SCHED_FENCE();
    const float i0 = rcp_fast(iv.x), i1 = rcp_fast(iv.y);
#define WORD(a, h) pack_bf16(a[2 * h] * i0, a[2 * h + 1] * i1)
    wg_fence();
    wo_part<0, 0, 8>(a0); wo_part<1, 0, 8>(a1); wo_part<2, 0, 8>(a2);
    if (!Q && WO_REL == 4) nbar_arrive(NB_WO, 384);
    wg_wait<1>(); reg_fence<4>(a0); reg_fence<4>(a1);
    if (!Q && WO_REL == 3) nbar_arrive(NB_WO, 384);
    red3(p, WORD(a0, 0), WORD(a0, 1), WORD(a1, 0), 0x3F80u);
    SCHED_FENCE();
    EV(warp == 0 && elect_one(), s, 11);
    wg_wait<0>(); reg_fence<4>(a2);
    if (!Q && WO_REL == 2) nbar_arrive(NB_WO, 384);
    red3(p + ACC_CH, WORD(a2, 0), WORD(a2, 1), WORD(a1, 1), 0x3F80u);
    SCHED_FENCE();
    if (Q || WO_REL < 2) { const uint32_t t = clk32() + gap; while ((int)(clk32() - t) < 0) { } }
    wg_fence();
    wo_part<3, 0, 8>(a0); wo_part<4, 0, 8>(a1);
    if (Q) {
        wo_part<5, 0, 8>(a2);
        wg_wait<1>(); reg_fence<4>(a0); reg_fence<4>(a1);
        red3(p + 2 * ACC_CH, WORD(a0, 0), WORD(a0, 1), WORD(a1, 0), 0x3F80u);
        SCHED_FENCE();
        wg_wait<0>(); reg_fence<4>(a2);
        red3(p + 3 * ACC_CH, WORD(a2, 0), WORD(a2, 1), WORD(a1, 1), 0x3F80u);
        nbar_arrive(NB_WO, 384);
    } else {
        wg_wait<1>();
        nbar_arrive(NB_WO, 384);
        wg_wait<0>(); reg_fence<4>(a0); reg_fence<4>(a1);
        red3(p + 2 * ACC_CH, WORD(a0, 0), WORD(a0, 1), WORD(a1, 0), 0x3F80u);
        red3(p + 3 * ACC_CH, 0u, 0u, WORD(a1, 1), 0x3F80u);
    }
#undef WORD
}
DEVI void unit_pack(uint32_t* u, uint32_t x0, uint32_t x1, uint32_t x2, uint32_t x3) {
    u[0] = __byte_perm(x0, x1, 0x5410); u[1] = __byte_perm(x2, x3, 0x5410); u[2] = __byte_perm(x0, x1, 0x7632); u[3] = __byte_perm(x2, x3, 0x7632);
}
DEVI void unit_send(uint32_t d, const uint32_t* u, uint32_t bar, uint32_t r1, uint32_t r2) {
    st_async128(mapa(d, r1), u[0], u[1], u[2], u[3], mapa(bar, r1));
    st_async128(mapa(d, r2), u[0], u[1], u[2], u[3], mapa(bar, r2));
}
template <bool Q>
DEVI void stage_sums(uint32_t sb, int s, uint32_t rank, int warp, const uint8_t* src, uint32_t l, uint32_t gate) {
    uint4 v[4];
    while ((int)(clk32() - gate) < 0) { }
    EV(elect_one(), s, 16 + warp);
#pragma unroll
    for (int j = 0; j < 4; j++) v[j] = ld_rlx4(src + j * 1024);
    const uint32_t col = sb + RS_MEM + ((Q ? 0 : (rank == 1 ? 6 : 11)) + 3 * (warp >> 1)) * 1024 + ((l >> 2) & 0x300) + (l & 0x70);
    const uint32_t d0 = col + (warp & 1) * 2048, d1 = d0 ^ 160, d2 = (col ^ ((warp & 1) * 160)) + 1024;
    const uint32_t r1 = Q ? 1 : 0, r2 = Q ? 2 : 3 - rank, bar = sb + RB_G + 8 * (warp < 2 ? warp : 2);
    int n = 0;
    while (!__all_sync(0xffffffffu, v[0].w == 0x4200u && v[1].w == 0x4200u && v[2].w == 0x4200u && v[3].w == 0x4200u)) {
#pragma unroll
        for (int j = 0; j < 4; j++) v[j] = ld_rlx4(src + j * 1024);
        if (++n > SPIN_LIMIT) TRAP(0x20000000u | (s << 8) | warp);
    }
    EV(elect_one(), s, 24 + warp);
    uint32_t u[12];
    unit_pack(u + 8, v[0].z, v[1].z, v[2].z, v[3].z);
    unit_send(d2, u + 8, bar, r1, r2);
    if (Q || warp < 3) {
        unit_pack(u, v[0].x, v[1].x, v[2].x, v[3].x);
        unit_pack(u + 4, v[0].y, v[1].y, v[2].y, v[3].y);
        unit_send(d0, u, bar, r1, r2);
        unit_send(d1, u + 4, bar, r1, r2);
        sts128(d0, make_uint4(u[0], u[1], u[2], u[3]));
        sts128(d1, make_uint4(u[4], u[5], u[6], u[7]));
    }
    sts128(d2, make_uint4(u[8], u[9], u[10], u[11]));
    __syncwarp();
    if (elect_one()) mbar_expect_tx(bar, warp < 2 ? 3072u : (warp == 3 ? 0u : (Q ? 4096u : 5120u)));
    EV(elect_one(), s, 20 + warp);
}
DEVI void wo_permute(uint32_t a, int n) {
    const uint32_t flip = (a >> 3) & 16;
#pragma unroll 2
    for (int i = 0; i < n; i++, a += 4096) {
        const uint4 v = lds128(a ^ flip), u = lds128(a ^ flip ^ 16);
        sts128(a ^ flip, make_uint4(__byte_perm(v.x, v.y, 0x5410), __byte_perm(v.x, v.y, 0x7632), __byte_perm(u.x, u.y, 0x5410), __byte_perm(u.x, u.y, 0x7632)));
        sts128(a ^ flip ^ 16, make_uint4(__byte_perm(v.z, v.w, 0x5410), __byte_perm(v.z, v.w, 0x7632), __byte_perm(u.z, u.w, 0x5410), __byte_perm(u.z, u.w, 0x7632)));
    }
}
DEVI uint32_t acc_clear(int slot, int idx, uint32_t lo) {
    uint8_t* p = g_acc + (uint32_t)(slot * 128 + idx * 3072 + (lo < 3072 ? lo : lo - 1024));
    st_rlx4(p, 0u, 0u, 0u, 0u);
    uint32_t z; asm volatile("ld.relaxed.gpu.global.u32 %0, [%1];" : "=r"(z) : "l"(p) : "memory");
    return z;
}

template <bool Q>
DEVI void aux_main(uint32_t sb, int warp, uint32_t rank, int head, const CUtensorMap* tmX, const bf16* xg, unsigned E, const int delay, const int gap, const int vdelay) {
    const uint32_t lo = __shfl_sync(0xffffffffu, ((tid_now() >> 3) & 3) * 1024 + (tid_now() & 7) * 16, tid_now() & 31);
    for (int s = 0; s < NSEG - 1; s++) {
        if (!Q && warp == 0 && elect_one()) mbar_expect_tx(sb + RB_O, 2048 + 256);
        __syncwarp();
        const uint32_t slot = (s & 3) * 128;
        mbar_wait(sb + RB_O, s & 1);
        EV(warp == 0 && elect_one(), s, 10);
        wo_phase<Q>(sb, s, warp, g_acc + (uint32_t)(slot + (rank * 4 + warp) * 4096 + opaque(lo)), sb + RS_INV + ((opaque(lo) >> 1) & 24), gap);
        SCHED_FENCE();
        const uint32_t t_o = clk32();
        EV(warp == 0 && elect_one(), s, 12);
        {
            const uint32_t l = opaque(lo);
            stage_sums<Q>(sb, s, rank, warp, g_acc + (uint32_t)(slot + rank * 16384 + warp * ACC_CH + (l & 0xC00) * 4 + (l & 0x70)), l, t_o + delay);
        }
        EV(warp == 2 && elect_one(), s, 14);
        if (warp == 3) {
            if (Q) {
                mbar_wait(sb + RB_T, s & 1);
                if (s == 3) wait_count_warp(&g_cnt[C_Q], 64 * E);
                if (elect_one()) {
                    if (s == 3) fence_proxy_global();
                    fence_proxy_async();
                    mbar_expect_tx(sb + RB_QX, 8192);
                    bulk_load(sb + RS_QX, g_qx + (uint32_t)(((s + 1) * NH + head) * 4096), 8192, sb + RB_QX);
                    if (head == 0) { TLOG(1400 + s, 0, gtime()); TLOG(1400 + s, 1, clock64()); }
                }
                __syncwarp();
                const bool fresh = (s & 7) == 6 && s + 2 < NSEG;
                if (fresh) wait_count_warp(&g_cnt[C_Q + ((s + 2) >> 3)], 64 * E);
                if (elect_one()) {
                    if (fresh) fence_proxy_global();
                    if (s + 2 < NSEG && s != 2) l2_prefetch(g_qx + (uint32_t)(((s + 2) * NH + head) * 4096), 8192);
                    if (s + 4 < NSEG) l2_prefetch(xg + (uint32_t)(((s + 4) * 32 + head) * DM), 2048);
                    signal_count(&g_prog[s >> 2]);
                }
                __syncwarp();
            } else {
                const uint32_t zero = acc_clear((s + 2) & 3, 2 * head + (int)rank - 1, opaque(lo));
                mbar_wait(sb + RB_G + 16, s & 1);
                x_send(sb, s + 1, rank, vdelay);
                if (__any_sync(0xffffffffu, zero != 0u)) __trap();
            }
        }
    }
}

DEVI void load_weights(uint32_t sb, const CUtensorMap* tmW, const CUtensorMap* tmWo, int head, uint32_t rank) {
    const uint32_t bW = sb + RB_W, bSF = sb + RB_SF, bSE = sb + RB_SE;
    const int ntile = rank == 0 ? 6 : 5, tile0 = rank == 0 ? 0 : (rank == 1 ? 6 : 11);
    mbar_expect_tx(bW, R_NSS * 16384);
    mbar_expect_tx(sb + RB_WO, ntile * 16384);
    for (int pass = 0; pass < 2; pass++) {
        for (int pos = 0; pos < 16; pos++) {
            const int k = (int)((R_TORD_PACK >> (4 * pos)) & 15ull) * 64, rd = pos - pos / 3, slot = rd % 5;
            if (r_pos_ss(pos)) {
                if (pass) continue;
                const uint32_t dst = sb + RS_WSS + (pos / 3) * 16384;
                tma_load_2d(dst, tmW, head * DH, k, bW);
                tma_load_2d(dst + 8192, tmW, head * DH + 64, k, bW);
            } else if (pass == (rd >= 5)) {
                if (rd >= 5) mbar_wait(bSE + 8 * slot, ((rd / 5) - 1) & 1);
                mbar_expect_tx(bSF + 8 * slot, 16384);
                const uint32_t dst = sb + RS_WO + slot * 16384;
                tma_load_2d(dst, tmW, head * DH, k, bSF + 8 * slot);
                tma_load_2d(dst + 8192, tmW, head * DH + 64, k, bSF + 8 * slot);
            }
        }
    }
    if (rank == 0) tma_load_wo(sb + RS_WO5, tmWo, 5 * 64, head * 4, sb + RB_WO);
    for (int i = 1; i <= 5; i++) {
        const int slot = i % 5, last = slot + 10 < R_NRS ? slot + 10 : slot + 5;
        mbar_wait(bSE + 8 * slot, (last / 5) & 1);
        tma_load_wo(sb + RS_WO + slot * 16384, tmWo, (tile0 + slot) * 64, head * 4, sb + RB_WO);
    }
}
template <bool XP>
DEVI void big_prologue(uint32_t* w, uint32_t sb, int g, int warp, const bf16* __restrict__ mem0) {
    const int tid = tid_now(), lane = tid & 31;
    {
        const uint32_t* m = (const uint32_t*)(mem0 + (lane >> 2) * DM + (tid >> 5) * 16) + (lane & 3);
        uint32_t u[16];
#pragma unroll
        for (int j = 0; j < 8; j++) { u[2 * j] = m[j * 64]; u[2 * j + 1] = m[j * 64 + 4]; }
#pragma unroll
        for (int j = 0; j < 8; j++) sts64(sb + RS_MEM + ((tid >> 5) + j * 8) * 256 + b_frag_off(lane), u[2 * j], u[2 * j + 1]);
    }
    const uint32_t a0 = sb + RS_WO + g * (8192 + 4096) + a_frag_off(lane, warp), a1 = a0 + 8192 - g * 16384;
#pragma unroll
    for (int rd = 0; rd < R_NRS; rd++) {
        const int slot = rd % 5;
        mbar_wait(sb + RB_SF + 8 * slot, (rd / 5) & 1);
#pragma unroll
        for (int q = 0; q < 4; q++) {
            if (XP && rd == 0 && q == 3) {
                sts128(sb + RS_WX + g * 2048 + (tid & 127) * 16, lds128(sb + RS_WO + 8192 - g * 4096 + 2048 + (tid & 127) * 16));
                fence_proxy_async();
                nbar_sync(NB_WG + g, 128);
            } else ldsm4t(&w[rd * 16 + q * 4], ((q & 1) ? a1 : a0) + slot * 16384 + (q >> 1) * 2048);
        }
        mbar_arrive(sb + RB_SE + 8 * slot);
    }
    mbar_wait(sb + RB_W, 0);
}

#define REC_END() do { if (tid_now() == 0) TLOG(1024 + blockIdx.x, 1, gtime()); } while (0)
__global__ void __launch_bounds__(384, 1)
k_rec(const __grid_constant__ PMaps mp, const __grid_constant__ CUtensorMap tmWk, const __grid_constant__ CUtensorMap tmWv,
      const __grid_constant__ CUtensorMap tmWo, const __grid_constant__ CUtensorMap tmX, const bf16* __restrict__ mem0, const bf16* __restrict__ xg,
      int4 tq, int4 tk, int rec) {
    extern __shared__ __align__(1024) uint8_t smem_raw[];
    const uint32_t sb = smem_u32(smem_raw);
    if ((sb & 0x3FFFFu) != SB0) __trap();
    const int tid = threadIdx.x;
    const int wg = __shfl_sync(0xffffffffu, tid >> 7, 0), warp = __shfl_sync(0xffffffffu, (tid >> 5) & 3, 0);
    uint32_t rank; asm("mov.u32 %0, %%cluster_ctarank;" : "=r"(rank));
    int head; asm("mov.u32 %0, %%clusterid.x;" : "=r"(head));
    asm volatile("griddepcontrol.launch_dependents;");
    if (tid == 0 && rec) {
        mbar_init(sb + RB_G, 1);
        mbar_init(sb + RB_G + 8, 1);
        mbar_init(sb + RB_G + 16, 2);
        mbar_init(sb + RB_T, 1); mbar_init(sb + RB_WO, 1);
        mbar_init(sb + RB_K, 1); mbar_init(sb + RB_V, 1); mbar_init(sb + RB_KV, 1); mbar_init(sb + RB_QX, 1);
        mbar_init(sb + RB_O, rank == 0 ? 4 : 1); mbar_init(sb + RB_ATT, 1); mbar_init(sb + RB_W, 1);
        for (int i = 0; i < 5; i++) { mbar_init(sb + RB_SF + 8 * i, 1); mbar_init(sb + RB_SE + 8 * i, 256); }
        for (int i = 0; i < 2; i++) mbar_init(sb + RB_XF + 8 * i, X_SLOTS);
        fence_mbar_init();
        if (rank == 0) { mbar_expect_tx(sb + RB_KV, 8192); mbar_expect_tx(sb + RB_K, 2048); mbar_expect_tx(sb + RB_V, 2048 + 8192); }
    }
    __syncthreads();
    asm volatile("barrier.cluster.arrive.release.aligned;" ::: "memory");

    if (wg < 2) {
        reg_inc<REG_KB>();
        if (rank != 0) {
            uint32_t w[R_NRS * 16];
            if ((tid & 127) == 0) for (int j = 0; j < X_SLOTS; j++) x_load(sb, 0, j, wg, &tmX);
            __syncwarp();
            cluster_wait();
            big_prologue<true>(w, sb, wg, warp, mem0);
            big_main<true>(w, sb, wg, warp, rank, head, &tmX, xg, 0u);
            REC_END();
        } else if (rec) {
            uint32_t w[R_NRS * 16];
            cluster_wait();
            big_prologue<false>(w, sb, wg, warp, mem0);
            big_main<false>(w, sb, wg, warp, rank, head, &tmX, xg, *(volatile unsigned*)&g_epoch + 1);
            REC_END();
        } else cluster_wait();
        nbar_sync(0, 384);
        nbar_sync(0, 384);
        post_consumer(mp, sb, wg, warp);
    } else {
        reg_dec<504 - 2 * REG_KB>();
        if (rec) {
            if (tid == 256) {
                if (rank == 0) l2_prefetch(xg + (uint32_t)(head * 8 * DM), 16384);
                load_weights(sb, rank == 0 ? &mp.wq : (rank == 1 ? &tmWk : &tmWv), &tmWo, head, rank);
            }
            if (warp == 3 && rank != 0) {
                const uint32_t lo = ((tid >> 3) & 3) * 1024 + (tid & 7) * 16;
                acc_clear(0, 2 * head + (int)rank - 1, lo); acc_clear(1, 2 * head + (int)rank - 1, lo);
                __threadfence();
                __syncwarp();
                if (tid == 256 + 96) atomicAdd(&g_zero, 1u);
            }
            __syncwarp();
        }
        cluster_wait();
        const unsigned E = __shfl_sync(0xffffffffu, *(volatile unsigned*)&g_epoch + 1, 0);
        if (rec) {
            if (warp == 1) wait_count_warp(&g_zero, E * 64u);
            if (warp == 3 && rank != 0) x_send(sb, 0, rank, 0);
            mbar_wait(sb + RB_WO, 0);
            wo_permute(sb + RS_WO + (tid & 127) * 32, 20);
            if (rank == 0) wo_permute(sb + RS_WO5 + (tid & 127) * 32, 4);
            fence_proxy_async();
            nbar_sync(NB_AUX, 128);
            if (rank == 0) aux_main<true>(sb, warp, rank, head, &tmX, xg, E, warp == 0 ? tq.x : (warp == 1 ? tq.y : tq.z), tq.w, 0);
            else           aux_main<false>(sb, warp, rank, head, &tmX, xg, E, warp == 0 ? tk.x : (warp == 1 ? tk.y : tk.z), tq.w, tk.w);
        }
        const int t = tid_now();
        int id = 0;
        if (t >= 288 && t < 288 + 13) asm volatile("prefetch.tensormap [%0];" :: "l"(&mp.wq + (t - 288)) : "memory");
        if (warp == 0 && rank != 0) id = post_claim(mp, E);
        nbar_sync(0, 384);
        if (warp == 0) { if (elect_one()) post_init(sb); fence_proxy_async(); }
        __syncwarp();
        nbar_sync(0, 384);
        if (warp == 0) post_producer(mp, sb, E, rank != 0 ? id : post_claim(mp, E));
        else if (t == 288 || t == 320) post_helper(sb, warp - 1);
    }
    __syncthreads();
    asm volatile("griddepcontrol.wait;" ::: "memory");
}

typedef CUresult (*EncodeFn)(CUtensorMap*, CUtensorMapDataType, cuuint32_t, void*, const cuuint64_t*, const cuuint64_t*,
                             const cuuint32_t*, const cuuint32_t*, CUtensorMapInterleave, CUtensorMapSwizzle,
                             CUtensorMapL2promotion, CUtensorMapFloatOOBfill);

static CUtensorMap make_map(EncodeFn fn, const void* ptr, uint64_t inner, uint64_t outer, uint32_t box_inner, uint32_t box_outer) {
    CUtensorMap m;
    cuuint64_t dims[2] = {inner, outer};
    cuuint64_t strides[1] = {inner * 2};
    cuuint32_t box[2] = {box_inner, box_outer};
    cuuint32_t es[2] = {1, 1};
    fn(&m, CU_TENSOR_MAP_DATA_TYPE_BFLOAT16, 2, const_cast<void*>(ptr), dims, strides, box, es,
       CU_TENSOR_MAP_INTERLEAVE_NONE, CU_TENSOR_MAP_SWIZZLE_128B, CU_TENSOR_MAP_L2_PROMOTION_L2_256B, CU_TENSOR_MAP_FLOAT_OOB_FILL_NONE);
    return m;
}

static CUtensorMap make_wo_map(EncodeFn fn, const void* ptr, uint64_t rows, uint32_t ngrp) {
    CUtensorMap m;
    cuuint64_t dims[5] = {DM, 2, 4, 4, rows / 32};
    cuuint64_t strides[4] = {DM * 2, 8 * DM * 2, 2 * DM * 2, 32 * DM * 2};
    cuuint32_t box[5] = {64, 2, 4, 4, ngrp};
    cuuint32_t es[5] = {1, 1, 1, 1, 1};
    fn(&m, CU_TENSOR_MAP_DATA_TYPE_BFLOAT16, 5, const_cast<void*>(ptr), dims, strides, box, es,
       CU_TENSOR_MAP_INTERLEAVE_NONE, CU_TENSOR_MAP_SWIZZLE_128B, CU_TENSOR_MAP_L2_PROMOTION_L2_256B, CU_TENSOR_MAP_FLOAT_OOB_FILL_NONE);
    return m;
}

struct Maps {
    PMaps post;
    CUtensorMap wk16, wv16, wo128, x32;
};

extern "C" void kernel_launch(void* const* d_in, const int* in_sizes, int n_in, void* d_out, int out_size) {
    const bf16* A_x   = (const bf16*)d_in[0];
    const bf16* A_mem = (const bf16*)d_in[1];
    const bf16* A_Wq  = (const bf16*)d_in[2];
    const bf16* A_Wk  = (const bf16*)d_in[3];
    const bf16* A_Wv  = (const bf16*)d_in[4];
    const bf16* A_Wo  = (const bf16*)d_in[5];
    const bf16* B_x   = (const bf16*)d_in[7];
    const bf16* B_w   = (const bf16*)d_in[8];
    const bf16* B_wo  = (const bf16*)d_in[9];

    static EncodeFn fn = nullptr;
    static Maps mp;
    static const void* cached[10];
    const void* cur[10] = {A_x, A_mem, A_Wq, A_Wk, A_Wv, A_Wo, B_x, B_w, B_wo, d_out};
    bool same = fn != nullptr;
    for (int i = 0; i < 10 && same; i++) same = cached[i] == cur[i];
    if (!same) {
        if (!fn) {
            void* p = nullptr; cudaDriverEntryPointQueryResult qr;
            cudaGetDriverEntryPoint("cuTensorMapEncodeTiled", &p, cudaEnableDefault, &qr);
            fn = (EncodeFn)p;
            cudaFuncSetAttribute(k_rec, cudaFuncAttributeMaxDynamicSharedMemorySize, R_SMEM);
        }
        void *p_ox, *p_bqkv, *p_bo, *p_qx;
        cudaGetSymbolAddress(&p_qx, g_qx);
        cudaGetSymbolAddress(&p_ox, g_ox); cudaGetSymbolAddress(&p_bqkv, g_bqkv); cudaGetSymbolAddress(&p_bo, g_bo);
        mp.post.wq   = make_map(fn, A_Wq, HD, DM, 64, 64);
        mp.post.wo   = make_wo_map(fn, A_Wo, HD, 2);
        mp.post.bw   = make_map(fn, B_w, 3 * DM, DM, 64, 64);
        mp.post.bwo  = make_wo_map(fn, B_wo, DM, 2);
        mp.post.x    = make_map(fn, A_x, DM, S_TOK, 64, 128);
        mp.post.bx   = make_map(fn, B_x, DM, S_TOK, 64, 128);
        mp.post.bo   = make_map(fn, p_bo, DM, S_TOK, 64, 128);
        mp.post.ox   = make_map(fn, p_ox, HD, S_TOK, 64, 128);
        mp.post.ox64 = make_map(fn, p_ox, HD, S_TOK, 64, 64);
        mp.post.cb   = make_map(fn, p_bqkv, 3 * DM, S_TOK, 64, 64);
        mp.post.cout = make_map(fn, d_out, 2 * DM, S_TOK, 64, 64);
        {
            cuuint64_t dims[4] = {256, 4, NH * 4, NSEG};
            cuuint64_t strides[3] = {512, 2048, NH * 8192};
            cuuint32_t box[4] = {256, 2, 4, 2};
            cuuint32_t es[4] = {1, 1, 1, 1};
            fn(&mp.post.cq, CU_TENSOR_MAP_DATA_TYPE_BFLOAT16, 4, p_qx, dims, strides, box, es,
               CU_TENSOR_MAP_INTERLEAVE_NONE, CU_TENSOR_MAP_SWIZZLE_NONE, CU_TENSOR_MAP_L2_PROMOTION_NONE, CU_TENSOR_MAP_FLOAT_OOB_FILL_NONE);
        }
        {
            int runs[48] = {K_QH, 0, 2, K_Q, 1, 7, K_B1, 0, 8, K_A4, 0, 4, K_B2, 0, 32, K_A4, 4, 2, K_B3, 0, 4, K_A3, 12, 1, K_B3, 4, 1, K_A3, 13, 1,
                            K_B3, 5, 3, K_SN, 28, 4, -1};
            const int per[9] = {32, 24, 8, 8, 32, 8, 8 * P_SPLIT, 1, 8 * P_SPLIT};
            int n = 0, id = 0;
            for (; runs[3 * n] >= 0; n++) {
                mp.post.list.run[n] = make_int4(runs[3 * n], runs[3 * n + 1], id, id + runs[3 * n + 2] * per[runs[3 * n]]);
                id = mp.post.list.run[n].w;
            }
            mp.post.list.n = n;
            int dev = 0, nsm = 132;
            cudaGetDevice(&dev);
            cudaDeviceGetAttribute(&nsm, cudaDevAttrMultiProcessorCount, dev);
            mp.post.list.nworker = nsm > 96 ? nsm : 97;
        }
        {
            cuuint64_t dims[4] = {DM, 3, 2, S_TOK / 2};
            cuuint64_t strides[3] = {DM * 2, 3 * DM * 2, 3 * DM * 4};
            cuuint32_t box[4] = {64, 3, 1, 40};
            cuuint32_t es[4] = {1, 1, 1, 1};
            fn(&mp.post.b40, CU_TENSOR_MAP_DATA_TYPE_BFLOAT16, 4, p_bqkv, dims, strides, box, es,
               CU_TENSOR_MAP_INTERLEAVE_NONE, CU_TENSOR_MAP_SWIZZLE_128B, CU_TENSOR_MAP_L2_PROMOTION_L2_256B, CU_TENSOR_MAP_FLOAT_OOB_FILL_NONE);
        }
        mp.wk16 = make_map(fn, A_Wk, HD, DM, 64, 64);
        mp.wv16 = make_map(fn, A_Wv, HD, DM, 64, 64);
        mp.wo128 = make_wo_map(fn, A_Wo, HD, 4);
        {
            cuuint64_t dims[3] = {64, S_TOK, DM / 64};
            cuuint64_t strides[2] = {DM * 2, 128};
            cuuint32_t box[3] = {32, 32, 2};
            cuuint32_t es[3] = {1, 1, 1};
            fn(&mp.x32, CU_TENSOR_MAP_DATA_TYPE_BFLOAT16, 3, const_cast<bf16*>(A_x), dims, strides, box, es,
               CU_TENSOR_MAP_INTERLEAVE_NONE, CU_TENSOR_MAP_SWIZZLE_64B, CU_TENSOR_MAP_L2_PROMOTION_L2_128B, CU_TENSOR_MAP_FLOAT_OOB_FILL_NONE);
        }
        for (int i = 0; i < 10; i++) cached[i] = cur[i];
    }

    cudaStream_t st = cudaStreamPerThread;
    int4 tq = make_int4(50, 150, 800, 80), tk = make_int4(100, 350, 850, 400);
    cudaLaunchConfig_t cfg = {};
    cfg.gridDim = dim3(96); cfg.blockDim = dim3(384); cfg.dynamicSmemBytes = R_SMEM; cfg.stream = st;
    cudaLaunchAttribute at[1];
    at[0].id = cudaLaunchAttributeClusterDimension;
    at[0].val.clusterDim.x = 3; at[0].val.clusterDim.y = 1; at[0].val.clusterDim.z = 1;
    cfg.attrs = at; cfg.numAttrs = 1;
    cudaLaunchKernelEx(&cfg, k_rec, mp.post, mp.wk16, mp.wv16, mp.wo128, mp.x32, A_mem, A_x, tq, tk, 1);
    cfg.gridDim = dim3(mp.post.list.nworker - 96);
    at[0].id = cudaLaunchAttributeProgrammaticStreamSerialization;
    at[0].val.programmaticStreamSerializationAllowed = 1;
    cudaLaunchKernelEx(&cfg, k_rec, mp.post, mp.wk16, mp.wv16, mp.wo128, mp.x32, A_mem, A_x, tq, tk, 0);
}
```

```cpp
#include <cuda_runtime.h>
#include <cuda_bf16.h>
#include <cuda.h>
#include <stdint.h>

typedef __nv_bfloat16 bf16;

constexpr int S_TOK = 2048;
constexpr int DM    = 1024;
constexpr int NH    = 32;
constexpr int DH    = 128;
constexpr int NSEG  = 64;
constexpr int HD    = NH * DH;

__device__ __align__(1024) bf16 g_qx[NSEG * NH * 4 * DH * 8];
__device__ __align__(1024) bf16 g_ox[S_TOK * HD];
__device__ __align__(1024) bf16 g_bqkv[S_TOK * 3 * DM];
__device__ __align__(1024) bf16 g_bo[S_TOK * DM];
__device__ __align__(1024) uint8_t g_acc[192 * 1024];

#define EV(cond, s, k) do {} while (0)
#define EVCAL(s) do {} while (0)

constexpr int P_NSK = 4;
__device__ unsigned g_epoch, g_qctr, g_done, g_zero;
enum { C_B1 = 0, C_B2 = 8, C_Q = 16, C_QH = 24, C_NONE = 31 };
__device__ unsigned g_cnt[32], g_prog[16], g_cnt_sk[P_NSK * 32];
constexpr int P_SPLIT = 4;
__device__ __align__(1024) uint4 g_skp[P_NSK * 8 * P_SPLIT * 2 * 8 * 128];
#define TLOG(i, k, v) do {} while (0)

#define DEVI __device__ __forceinline__

DEVI uint32_t opaque(uint32_t v) { uint32_t r; asm volatile("mov.u32 %0, %1;" : "=r"(r) : "r"(v)); return r; }
DEVI uint32_t smem_u32(const void* p) { return (uint32_t)__cvta_generic_to_shared(p); }

#define TRAP(code) __trap()
constexpr int SPIN_LIMIT = 1 << 22;
#define MBAR_HINT_NS 20000u
constexpr int SPIN_LIMIT_MBAR = 1 << 17;

DEVI void mbar_init(uint32_t bar, uint32_t cnt) { asm volatile("mbarrier.init.shared::cta.b64 [%0], %1;" :: "r"(bar), "r"(cnt)); }
DEVI void mbar_expect_tx(uint32_t bar, uint32_t bytes) {
    asm volatile("mbarrier.arrive.expect_tx.shared::cta.b64 _, [%0], %1;" :: "r"(bar), "r"(bytes) : "memory");
}
DEVI void mbar_arrive(uint32_t bar) { asm volatile("mbarrier.arrive.shared::cta.b64 _, [%0];" :: "r"(bar) : "memory"); }
DEVI bool mbar_try(uint32_t bar, uint32_t parity) {
    uint32_t ok;
    asm volatile("{.reg .pred p; mbarrier.try_wait.parity.shared::cta.b64 p, [%1], %2; selp.u32 %0, 1, 0, p;}"
                 : "=r"(ok) : "r"(bar), "r"(parity) : "memory");
    return ok;
}
DEVI bool mbar_try_cluster(uint32_t bar, uint32_t parity) {
    uint32_t ok;
    asm volatile("{.reg .pred p; mbarrier.try_wait.parity.acquire.cluster.shared::cta.b64 p, [%1], %2; selp.u32 %0, 1, 0, p;}"
                 : "=r"(ok) : "r"(bar), "r"(parity) : "memory");
    return ok;
}
DEVI bool mbar_try_hint(uint32_t bar, uint32_t parity) {
    uint32_t ok;
    asm volatile("{.reg .pred p; mbarrier.try_wait.parity.shared::cta.b64 p, [%1], %2, %3; selp.u32 %0, 1, 0, p;}"
                 : "=r"(ok) : "r"(bar), "r"(parity), "r"(MBAR_HINT_NS) : "memory");
    return ok;
}
DEVI void mbar_wait(uint32_t bar, uint32_t parity) {
    int n = 0;
    while (!mbar_try(bar, parity)) { if (++n > SPIN_LIMIT) TRAP(bar | (parity << 31)); }
}
DEVI void mbar_wait_sleepy(uint32_t bar, uint32_t parity) {
    int n = 0;
    while (!mbar_try_hint(bar, parity)) { if (++n > SPIN_LIMIT_MBAR) __trap(); }
}
DEVI void mbar_wait_cluster(uint32_t bar, uint32_t parity) {
    int n = 0;
    while (!mbar_try_cluster(bar, parity)) { if (++n > SPIN_LIMIT) __trap(); }
}
DEVI void mbar_spin(uint32_t bar, uint32_t parity) {
    uint32_t ok; int n = 0;
    do {
        asm volatile("{.reg .pred p; mbarrier.test_wait.parity.shared::cta.b64 p, [%1], %2; selp.u32 %0, 1, 0, p;}"
                     : "=r"(ok) : "r"(bar), "r"(parity) : "memory");
        if (++n > SPIN_LIMIT) __trap();
    } while (!ok);
}
DEVI void fence_mbar_init() { asm volatile("fence.mbarrier_init.release.cluster;" ::: "memory"); }
DEVI void fence_proxy_async() { asm volatile("fence.proxy.async.shared::cta;" ::: "memory"); }
DEVI void cluster_sync() {
    asm volatile("barrier.cluster.arrive.release.aligned;\n barrier.cluster.wait.acquire.aligned;" ::: "memory");
}
DEVI bool elect_one() {
    uint32_t e; asm volatile("{.reg .pred p; elect.sync _|p, 0xffffffff; selp.u32 %0, 1, 0, p;}" : "=r"(e)); return e;
}
DEVI void fence_proxy_global() { asm volatile("fence.proxy.async.global;" ::: "memory"); }
DEVI void cluster_wait() { asm volatile("barrier.cluster.wait.acquire.aligned;" ::: "memory"); }
DEVI void nbar_sync(int id, int n) { asm volatile("bar.sync %0, %1;" :: "r"(id), "r"(n) : "memory"); }
DEVI void nbar_arrive(int id, int n) { asm volatile("bar.arrive %0, %1;" :: "r"(id), "r"(n) : "memory"); }

DEVI void tma_load_2d(uint32_t dst, const CUtensorMap* map, int x, int y, uint32_t bar) {
    asm volatile("cp.async.bulk.tensor.2d.shared::cluster.global.mbarrier::complete_tx::bytes [%0], [%1, {%3, %4}], [%2];"
                 :: "r"(dst), "l"(map), "r"(bar), "r"(x), "r"(y) : "memory");
}
DEVI void tma_load_3d(uint32_t dst, const CUtensorMap* map, int x, int y, int z, uint32_t bar) {
    asm volatile("cp.async.bulk.tensor.3d.shared::cluster.global.mbarrier::complete_tx::bytes [%0], [%1, {%3, %4, %5}], [%2];"
                 :: "r"(dst), "l"(map), "r"(bar), "r"(x), "r"(y), "r"(z) : "memory");
}
DEVI void tma_load_wo(uint32_t dst, const CUtensorMap* map, int col, int k32, uint32_t bar) {
    asm volatile("cp.async.bulk.tensor.5d.shared::cluster.global.mbarrier::complete_tx::bytes [%0], [%1, {%3, %5, %5, %5, %4}], [%2];"
                 :: "r"(dst), "l"(map), "r"(bar), "r"(col), "r"(k32), "r"(0) : "memory");
}
DEVI void tma_store_2d(const CUtensorMap* map, uint32_t src, int x, int y) {
    asm volatile("cp.async.bulk.tensor.2d.global.shared::cta.bulk_group [%0, {%2, %3}], [%1];"
                 :: "l"(map), "r"(src), "r"(x), "r"(y) : "memory");
}
DEVI void bulk_load(uint32_t dst, const void* src, uint32_t bytes, uint32_t bar) {
    asm volatile("cp.async.bulk.shared::cluster.global.mbarrier::complete_tx::bytes [%0], [%1], %2, [%3];"
                 :: "r"(dst), "l"(src), "r"(bytes), "r"(bar) : "memory");
}
DEVI void tma_load_2d_mc(uint32_t dst, const CUtensorMap* map, int x, int y, uint32_t bar, uint16_t mask) {
    asm volatile("cp.async.bulk.tensor.2d.shared::cluster.global.mbarrier::complete_tx::bytes.multicast::cluster [%0], [%1, {%3, %4}], [%2], %5;"
                 :: "r"(dst), "l"(map), "r"(bar), "r"(x), "r"(y), "h"(mask) : "memory");
}
DEVI void bulk_copy_s2c(uint32_t dst_cluster, uint32_t src, uint32_t bytes, uint32_t bar_cluster) {
    asm volatile("cp.async.bulk.shared::cluster.shared::cta.mbarrier::complete_tx::bytes [%0], [%1], %2, [%3];"
                 :: "r"(dst_cluster), "r"(src), "r"(bytes), "r"(bar_cluster) : "memory");
}
DEVI void bulk_store(void* dst, uint32_t src, uint32_t bytes) {
    asm volatile("cp.async.bulk.global.shared::cta.bulk_group [%0], [%1], %2;" :: "l"(dst), "r"(src), "r"(bytes) : "memory");
}
DEVI void bulk_wait_read() { asm volatile("cp.async.bulk.wait_group.read 0;" ::: "memory"); }
DEVI void mbar_arrive_remote(uint32_t bar_cluster) {
    asm volatile("mbarrier.arrive.shared::cluster.b64 _, [%0];" :: "r"(bar_cluster) : "memory");
}
DEVI void mbar_expect_tx_remote(uint32_t bar_cluster, uint32_t bytes) {
    asm volatile("mbarrier.arrive.expect_tx.shared::cluster.b64 _, [%0], %1;" :: "r"(bar_cluster), "r"(bytes) : "memory");
}
DEVI void l2_prefetch(const void* p, uint32_t bytes) {
    asm volatile("cp.async.bulk.prefetch.L2.global [%0], %1;" :: "l"(p), "r"(bytes) : "memory");
}
DEVI void bulk_commit() { asm volatile("cp.async.bulk.commit_group;" ::: "memory"); }
DEVI void bulk_wait_all() { asm volatile("cp.async.bulk.wait_group 0;" ::: "memory"); }

DEVI void wg_fence() { asm volatile("wgmma.fence.sync.aligned;" ::: "memory"); }
DEVI void wg_commit() { asm volatile("wgmma.commit_group.sync.aligned;" ::: "memory"); }
template <int N> DEVI void wg_wait() { asm volatile("wgmma.wait_group.sync.aligned %0;" :: "n"(N) : "memory"); }

template <int R> DEVI void reg_dec() { asm volatile("setmaxnreg.dec.sync.aligned.u32 %0;" :: "n"(R)); }
template <int R> DEVI void reg_inc() { asm volatile("setmaxnreg.inc.sync.aligned.u32 %0;" :: "n"(R)); }

DEVI uint64_t mk_desc(uint32_t addr, uint32_t lbo, uint32_t sbo, uint32_t sw) {
    return (uint64_t)((addr & 0x3FFFF) >> 4) | ((uint64_t)(lbo >> 4) << 16) | ((uint64_t)(sbo >> 4) << 32) | ((uint64_t)sw << 62);
}

DEVI uint32_t desc_lo(uint32_t addr, uint32_t lbo) { return ((addr & 0x3FFFF) >> 4) | ((lbo >> 4) << 16); }
constexpr uint32_t DHI_SW128 = (1024u >> 4) | (1u << 30);
constexpr uint32_t DHI_SW64  = (512u >> 4) | (2u << 30);
constexpr uint32_t DHI_NONE  = (128u >> 4);

template <int TB, int SCALE_D>
DEVI void wgmma_n8_ss(float* d, uint32_t alo, uint32_t blo) {
    asm volatile("{.reg .b64 da, db; mov.b64 da, {%4, %6}; mov.b64 db, {%5, %7};\n"
                 "wgmma.mma_async.sync.aligned.m64n8k16.f32.bf16.bf16 {%0,%1,%2,%3}, da, db, %8, 1, 1, 1, %9;}"
                 : "+f"(d[0]), "+f"(d[1]), "+f"(d[2]), "+f"(d[3])
                 : "r"(alo), "r"(blo), "n"(DHI_SW128), "n"(DHI_NONE), "n"(SCALE_D), "n"(TB));
}

template <int TB>
DEVI void wgmma_n8_ss_first(float* d, uint32_t alo, uint32_t blo) {
    asm volatile("{.reg .b64 da, db; mov.b64 da, {%4, %6}; mov.b64 db, {%5, %7};\n"
                 "wgmma.mma_async.sync.aligned.m64n8k16.f32.bf16.bf16 {%0,%1,%2,%3}, da, db, 0, 1, 1, 1, %8;}"
                 : "=f"(d[0]), "=f"(d[1]), "=f"(d[2]), "=f"(d[3])
                 : "r"(alo), "r"(blo), "n"(DHI_SW128), "n"(DHI_NONE), "n"(TB));
}
DEVI void wgmma_n32_rs_first(float* d, const uint32_t* a, uint32_t blo) {
    asm volatile("{.reg .b64 db; mov.b64 db, {%20, %21};\n"
                 "wgmma.mma_async.sync.aligned.m64n32k16.f32.bf16.bf16 {%0,%1,%2,%3,%4,%5,%6,%7,%8,%9,%10,%11,%12,%13,%14,%15}, "
                 "{%16,%17,%18,%19}, db, 0, 1, 1, 0;}"
                 : "=f"(d[0]), "=f"(d[1]), "=f"(d[2]), "=f"(d[3]), "=f"(d[4]), "=f"(d[5]), "=f"(d[6]), "=f"(d[7]),
                   "=f"(d[8]), "=f"(d[9]), "=f"(d[10]), "=f"(d[11]), "=f"(d[12]), "=f"(d[13]), "=f"(d[14]), "=f"(d[15])
                 : "r"(a[0]), "r"(a[1]), "r"(a[2]), "r"(a[3]), "r"(blo), "n"(DHI_SW64));
}
template <int N> DEVI void reg_fence(float* d) {
#pragma unroll
    for (int i = 0; i < N; i++) asm volatile("" : "+f"(d[i]) :: "memory");
}
DEVI void wgmma_n32_rs(float* d, const uint32_t* a, uint32_t blo) {
    asm volatile("{.reg .b64 db; mov.b64 db, {%20, %21};\n"
                 "wgmma.mma_async.sync.aligned.m64n32k16.f32.bf16.bf16 {%0,%1,%2,%3,%4,%5,%6,%7,%8,%9,%10,%11,%12,%13,%14,%15}, "
                 "{%16,%17,%18,%19}, db, 1, 1, 1, 0;}"
                 : "+f"(d[0]), "+f"(d[1]), "+f"(d[2]), "+f"(d[3]), "+f"(d[4]), "+f"(d[5]), "+f"(d[6]), "+f"(d[7]),
                   "+f"(d[8]), "+f"(d[9]), "+f"(d[10]), "+f"(d[11]), "+f"(d[12]), "+f"(d[13]), "+f"(d[14]), "+f"(d[15])
                 : "r"(a[0]), "r"(a[1]), "r"(a[2]), "r"(a[3]), "r"(blo), "n"(DHI_SW64));
}
DEVI void wgmma_n32_ss(float* d, uint32_t alo, uint32_t blo) {
    asm volatile("{.reg .b64 da, db; mov.b64 da, {%16, %18}; mov.b64 db, {%17, %19};\n"
                 "wgmma.mma_async.sync.aligned.m64n32k16.f32.bf16.bf16 {%0,%1,%2,%3,%4,%5,%6,%7,%8,%9,%10,%11,%12,%13,%14,%15}, "
                 "da, db, 1, 1, 1, 1, 0;}"
                 : "+f"(d[0]), "+f"(d[1]), "+f"(d[2]), "+f"(d[3]), "+f"(d[4]), "+f"(d[5]), "+f"(d[6]), "+f"(d[7]),
                   "+f"(d[8]), "+f"(d[9]), "+f"(d[10]), "+f"(d[11]), "+f"(d[12]), "+f"(d[13]), "+f"(d[14]), "+f"(d[15])
                 : "r"(alo), "r"(blo), "n"(DHI_SW128), "n"(DHI_SW64));
}

template <bool FIRST>
DEVI void wgmma_n256_ss(float* d, uint64_t a, uint64_t b) {
    if (FIRST)
        asm volatile("wgmma.mma_async.sync.aligned.m64n256k16.f32.bf16.bf16 {%0,%1,%2,%3,%4,%5,%6,%7,%8,%9,%10,%11,%12,%13,%14,%15,%16,%17,%18,%19,%20,%21,%22,%23,%24,%25,%26,%27,%28,%29,%30,%31,%32,%33,%34,%35,%36,%37,%38,%39,%40,%41,%42,%43,%44,%45,%46,%47,%48,%49,%50,%51,%52,%53,%54,%55,%56,%57,%58,%59,%60,%61,%62,%63,%64,%65,%66,%67,%68,%69,%70,%71,%72,%73,%74,%75,%76,%77,%78,%79,%80,%81,%82,%83,%84,%85,%86,%87,%88,%89,%90,%91,%92,%93,%94,%95,%96,%97,%98,%99,%100,%101,%102,%103,%104,%105,%106,%107,%108,%109,%110,%111,%112,%113,%114,%115,%116,%117,%118,%119,%120,%121,%122,%123,%124,%125,%126,%127}, %128, %129, 0, 1, 1, 1, 0;"
            : "=f"(d[0]), "=f"(d[1]), "=f"(d[2]), "=f"(d[3]), "=f"(d[4]), "=f"(d[5]), "=f"(d[6]), "=f"(d[7]), "=f"(d[8]), "=f"(d[9]), "=f"(d[10]), "=f"(d[11]), "=f"(d[12]), "=f"(d[13]), "=f"(d[14]), "=f"(d[15]), "=f"(d[16]), "=f"(d[17]), "=f"(d[18]), "=f"(d[19]), "=f"(d[20]), "=f"(d[21]), "=f"(d[22]), "=f"(d[23]), "=f"(d[24]), "=f"(d[25]), "=f"(d[26]), "=f"(d[27]), "=f"(d[28]), "=f"(d[29]), "=f"(d[30]), "=f"(d[31]), "=f"(d[32]), "=f"(d[33]), "=f"(d[34]), "=f"(d[35]), "=f"(d[36]), "=f"(d[37]), "=f"(d[38]), "=f"(d[39]), "=f"(d[40]), "=f"(d[41]), "=f"(d[42]), "=f"(d[43]), "=f"(d[44]), "=f"(d[45]), "=f"(d[46]), "=f"(d[47]), "=f"(d[48]), "=f"(d[49]), "=f"(d[50]), "=f"(d[51]), "=f"(d[52]), "=f"(d[53]), "=f"(d[54]), "=f"(d[55]), "=f"(d[56]), "=f"(d[57]), "=f"(d[58]), "=f"(d[59]), "=f"(d[60]), "=f"(d[61]), "=f"(d[62]), "=f"(d[63]), "=f"(d[64]), "=f"(d[65]), "=f"(d[66]), "=f"(d[67]), "=f"(d[68]), "=f"(d[69]), "=f"(d[70]), "=f"(d[71]), "=f"(d[72]), "=f"(d[73]), "=f"(d[74]), "=f"(d[75]), "=f"(d[76]), "=f"(d[77]), "=f"(d[78]), "=f"(d[79]), "=f"(d[80]), "=f"(d[81]), "=f"(d[82]), "=f"(d[83]), "=f"(d[84]), "=f"(d[85]), "=f"(d[86]), "=f"(d[87]), "=f"(d[88]), "=f"(d[89]), "=f"(d[90]), "=f"(d[91]), "=f"(d[92]), "=f"(d[93]), "=f"(d[94]), "=f"(d[95]), "=f"(d[96]), "=f"(d[97]), "=f"(d[98]), "=f"(d[99]), "=f"(d[100]), "=f"(d[101]), "=f"(d[102]), "=f"(d[103]), "=f"(d[104]), "=f"(d[105]), "=f"(d[106]), "=f"(d[107]), "=f"(d[108]), "=f"(d[109]), "=f"(d[110]), "=f"(d[111]), "=f"(d[112]), "=f"(d[113]), "=f"(d[114]), "=f"(d[115]), "=f"(d[116]), "=f"(d[117]), "=f"(d[118]), "=f"(d[119]), "=f"(d[120]), "=f"(d[121]), "=f"(d[122]), "=f"(d[123]), "=f"(d[124]), "=f"(d[125]), "=f"(d[126]), "=f"(d[127]) : "l"(a), "l"(b));
    else
        asm volatile("wgmma.mma_async.sync.aligned.m64n256k16.f32.bf16.bf16 {%0,%1,%2,%3,%4,%5,%6,%7,%8,%9,%10,%11,%12,%13,%14,%15,%16,%17,%18,%19,%20,%21,%22,%23,%24,%25,%26,%27,%28,%29,%30,%31,%32,%33,%34,%35,%36,%37,%38,%39,%40,%41,%42,%43,%44,%45,%46,%47,%48,%49,%50,%51,%52,%53,%54,%55,%56,%57,%58,%59,%60,%61,%62,%63,%64,%65,%66,%67,%68,%69,%70,%71,%72,%73,%74,%75,%76,%77,%78,%79,%80,%81,%82,%83,%84,%85,%86,%87,%88,%89,%90,%91,%92,%93,%94,%95,%96,%97,%98,%99,%100,%101,%102,%103,%104,%105,%106,%107,%108,%109,%110,%111,%112,%113,%114,%115,%116,%117,%118,%119,%120,%121,%122,%123,%124,%125,%126,%127}, %128, %129, 1, 1, 1, 1, 0;"
            : "+f"(d[0]), "+f"(d[1]), "+f"(d[2]), "+f"(d[3]), "+f"(d[4]), "+f"(d[5]), "+f"(d[6]), "+f"(d[7]), "+f"(d[8]), "+f"(d[9]), "+f"(d[10]), "+f"(d[11]), "+f"(d[12]), "+f"(d[13]), "+f"(d[14]), "+f"(d[15]), "+f"(d[16]), "+f"(d[17]), "+f"(d[18]), "+f"(d[19]), "+f"(d[20]), "+f"(d[21]), "+f"(d[22]), "+f"(d[23]), "+f"(d[24]), "+f"(d[25]), "+f"(d[26]), "+f"(d[27]), "+f"(d[28]), "+f"(d[29]), "+f"(d[30]), "+f"(d[31]), "+f"(d[32]), "+f"(d[33]), "+f"(d[34]), "+f"(d[35]), "+f"(d[36]), "+f"(d[37]), "+f"(d[38]), "+f"(d[39]), "+f"(d[40]), "+f"(d[41]), "+f"(d[42]), "+f"(d[43]), "+f"(d[44]), "+f"(d[45]), "+f"(d[46]), "+f"(d[47]), "+f"(d[48]), "+f"(d[49]), "+f"(d[50]), "+f"(d[51]), "+f"(d[52]), "+f"(d[53]), "+f"(d[54]), "+f"(d[55]), "+f"(d[56]), "+f"(d[57]), "+f"(d[58]), "+f"(d[59]), "+f"(d[60]), "+f"(d[61]), "+f"(d[62]), "+f"(d[63]), "+f"(d[64]), "+f"(d[65]), "+f"(d[66]), "+f"(d[67]), "+f"(d[68]), "+f"(d[69]), "+f"(d[70]), "+f"(d[71]), "+f"(d[72]), "+f"(d[73]), "+f"(d[74]), "+f"(d[75]), "+f"(d[76]), "+f"(d[77]), "+f"(d[78]), "+f"(d[79]), "+f"(d[80]), "+f"(d[81]), "+f"(d[82]), "+f"(d[83]), "+f"(d[84]), "+f"(d[85]), "+f"(d[86]), "+f"(d[87]), "+f"(d[88]), "+f"(d[89]), "+f"(d[90]), "+f"(d[91]), "+f"(d[92]), "+f"(d[93]), "+f"(d[94]), "+f"(d[95]), "+f"(d[96]), "+f"(d[97]), "+f"(d[98]), "+f"(d[99]), "+f"(d[100]), "+f"(d[101]), "+f"(d[102]), "+f"(d[103]), "+f"(d[104]), "+f"(d[105]), "+f"(d[106]), "+f"(d[107]), "+f"(d[108]), "+f"(d[109]), "+f"(d[110]), "+f"(d[111]), "+f"(d[112]), "+f"(d[113]), "+f"(d[114]), "+f"(d[115]), "+f"(d[116]), "+f"(d[117]), "+f"(d[118]), "+f"(d[119]), "+f"(d[120]), "+f"(d[121]), "+f"(d[122]), "+f"(d[123]), "+f"(d[124]), "+f"(d[125]), "+f"(d[126]), "+f"(d[127]) : "l"(a), "l"(b));
}
template <bool FIRST>
DEVI void wgmma_n128_ss(float* d, uint64_t a, uint64_t b) {
    if (FIRST)
        asm volatile("wgmma.mma_async.sync.aligned.m64n128k16.f32.bf16.bf16 {%0,%1,%2,%3,%4,%5,%6,%7,%8,%9,%10,%11,%12,%13,%14,%15,%16,%17,%18,%19,%20,%21,%22,%23,%24,%25,%26,%27,%28,%29,%30,%31,%32,%33,%34,%35,%36,%37,%38,%39,%40,%41,%42,%43,%44,%45,%46,%47,%48,%49,%50,%51,%52,%53,%54,%55,%56,%57,%58,%59,%60,%61,%62,%63}, %64, %65, 0, 1, 1, 1, 0;"
            : "=f"(d[0]), "=f"(d[1]), "=f"(d[2]), "=f"(d[3]), "=f"(d[4]), "=f"(d[5]), "=f"(d[6]), "=f"(d[7]), "=f"(d[8]), "=f"(d[9]), "=f"(d[10]), "=f"(d[11]), "=f"(d[12]), "=f"(d[13]), "=f"(d[14]), "=f"(d[15]), "=f"(d[16]), "=f"(d[17]), "=f"(d[18]), "=f"(d[19]), "=f"(d[20]), "=f"(d[21]), "=f"(d[22]), "=f"(d[23]), "=f"(d[24]), "=f"(d[25]), "=f"(d[26]), "=f"(d[27]), "=f"(d[28]), "=f"(d[29]), "=f"(d[30]), "=f"(d[31]), "=f"(d[32]), "=f"(d[33]), "=f"(d[34]), "=f"(d[35]), "=f"(d[36]), "=f"(d[37]), "=f"(d[38]), "=f"(d[39]), "=f"(d[40]), "=f"(d[41]), "=f"(d[42]), "=f"(d[43]), "=f"(d[44]), "=f"(d[45]), "=f"(d[46]), "=f"(d[47]), "=f"(d[48]), "=f"(d[49]), "=f"(d[50]), "=f"(d[51]), "=f"(d[52]), "=f"(d[53]), "=f"(d[54]), "=f"(d[55]), "=f"(d[56]), "=f"(d[57]), "=f"(d[58]), "=f"(d[59]), "=f"(d[60]), "=f"(d[61]), "=f"(d[62]), "=f"(d[63]) : "l"(a), "l"(b));
    else
        asm volatile("wgmma.mma_async.sync.aligned.m64n128k16.f32.bf16.bf16 {%0,%1,%2,%3,%4,%5,%6,%7,%8,%9,%10,%11,%12,%13,%14,%15,%16,%17,%18,%19,%20,%21,%22,%23,%24,%25,%26,%27,%28,%29,%30,%31,%32,%33,%34,%35,%36,%37,%38,%39,%40,%41,%42,%43,%44,%45,%46,%47,%48,%49,%50,%51,%52,%53,%54,%55,%56,%57,%58,%59,%60,%61,%62,%63}, %64, %65, 1, 1, 1, 1, 0;"
            : "+f"(d[0]), "+f"(d[1]), "+f"(d[2]), "+f"(d[3]), "+f"(d[4]), "+f"(d[5]), "+f"(d[6]), "+f"(d[7]), "+f"(d[8]), "+f"(d[9]), "+f"(d[10]), "+f"(d[11]), "+f"(d[12]), "+f"(d[13]), "+f"(d[14]), "+f"(d[15]), "+f"(d[16]), "+f"(d[17]), "+f"(d[18]), "+f"(d[19]), "+f"(d[20]), "+f"(d[21]), "+f"(d[22]), "+f"(d[23]), "+f"(d[24]), "+f"(d[25]), "+f"(d[26]), "+f"(d[27]), "+f"(d[28]), "+f"(d[29]), "+f"(d[30]), "+f"(d[31]), "+f"(d[32]), "+f"(d[33]), "+f"(d[34]), "+f"(d[35]), "+f"(d[36]), "+f"(d[37]), "+f"(d[38]), "+f"(d[39]), "+f"(d[40]), "+f"(d[41]), "+f"(d[42]), "+f"(d[43]), "+f"(d[44]), "+f"(d[45]), "+f"(d[46]), "+f"(d[47]), "+f"(d[48]), "+f"(d[49]), "+f"(d[50]), "+f"(d[51]), "+f"(d[52]), "+f"(d[53]), "+f"(d[54]), "+f"(d[55]), "+f"(d[56]), "+f"(d[57]), "+f"(d[58]), "+f"(d[59]), "+f"(d[60]), "+f"(d[61]), "+f"(d[62]), "+f"(d[63]) : "l"(a), "l"(b));
}

template <bool FIRST>
DEVI void wgmma_n64_ss(float* d, uint64_t a, uint64_t b) {
    if (FIRST)
        asm volatile("wgmma.mma_async.sync.aligned.m64n64k16.f32.bf16.bf16 {%0,%1,%2,%3,%4,%5,%6,%7,%8,%9,%10,%11,%12,%13,%14,%15,%16,%17,%18,%19,%20,%21,%22,%23,%24,%25,%26,%27,%28,%29,%30,%31}, %32, %33, 0, 1, 1, 1, 0;"
            : "=f"(d[0]), "=f"(d[1]), "=f"(d[2]), "=f"(d[3]), "=f"(d[4]), "=f"(d[5]), "=f"(d[6]), "=f"(d[7]), "=f"(d[8]), "=f"(d[9]), "=f"(d[10]), "=f"(d[11]), "=f"(d[12]), "=f"(d[13]), "=f"(d[14]), "=f"(d[15]), "=f"(d[16]), "=f"(d[17]), "=f"(d[18]), "=f"(d[19]), "=f"(d[20]), "=f"(d[21]), "=f"(d[22]), "=f"(d[23]), "=f"(d[24]), "=f"(d[25]), "=f"(d[26]), "=f"(d[27]), "=f"(d[28]), "=f"(d[29]), "=f"(d[30]), "=f"(d[31]) : "l"(a), "l"(b));
    else
        asm volatile("wgmma.mma_async.sync.aligned.m64n64k16.f32.bf16.bf16 {%0,%1,%2,%3,%4,%5,%6,%7,%8,%9,%10,%11,%12,%13,%14,%15,%16,%17,%18,%19,%20,%21,%22,%23,%24,%25,%26,%27,%28,%29,%30,%31}, %32, %33, 1, 1, 1, 1, 0;"
            : "+f"(d[0]), "+f"(d[1]), "+f"(d[2]), "+f"(d[3]), "+f"(d[4]), "+f"(d[5]), "+f"(d[6]), "+f"(d[7]), "+f"(d[8]), "+f"(d[9]), "+f"(d[10]), "+f"(d[11]), "+f"(d[12]), "+f"(d[13]), "+f"(d[14]), "+f"(d[15]), "+f"(d[16]), "+f"(d[17]), "+f"(d[18]), "+f"(d[19]), "+f"(d[20]), "+f"(d[21]), "+f"(d[22]), "+f"(d[23]), "+f"(d[24]), "+f"(d[25]), "+f"(d[26]), "+f"(d[27]), "+f"(d[28]), "+f"(d[29]), "+f"(d[30]), "+f"(d[31]) : "l"(a), "l"(b));
}

DEVI void mma16816(float* d, const uint32_t* a, uint32_t b0, uint32_t b1) {
    asm volatile("mma.sync.aligned.m16n8k16.row.col.f32.bf16.bf16.f32 {%0,%1,%2,%3}, {%4,%5,%6,%7}, {%8,%9}, {%0,%1,%2,%3};"
                 : "+f"(d[0]), "+f"(d[1]), "+f"(d[2]), "+f"(d[3])
                 : "r"(a[0]), "r"(a[1]), "r"(a[2]), "r"(a[3]), "r"(b0), "r"(b1));
}
DEVI void mma1688(float* d, uint32_t a0, uint32_t a1, uint32_t b0) {
    asm volatile("mma.sync.aligned.m16n8k8.row.col.f32.bf16.bf16.f32 {%0,%1,%2,%3}, {%4,%5}, {%6}, {%0,%1,%2,%3};"
                 : "+f"(d[0]), "+f"(d[1]), "+f"(d[2]), "+f"(d[3]) : "r"(a0), "r"(a1), "r"(b0));
}
DEVI void ldsm4(uint32_t* r, uint32_t addr) {
    asm volatile("ldmatrix.sync.aligned.m8n8.x4.shared.b16 {%0,%1,%2,%3}, [%4];"
                 : "=r"(r[0]), "=r"(r[1]), "=r"(r[2]), "=r"(r[3]) : "r"(addr) : "memory");
}
DEVI void ldsm4t(uint32_t* r, uint32_t addr) {
    asm volatile("ldmatrix.sync.aligned.m8n8.x4.trans.shared.b16 {%0,%1,%2,%3}, [%4];"
                 : "=r"(r[0]), "=r"(r[1]), "=r"(r[2]), "=r"(r[3]) : "r"(addr) : "memory");
}
DEVI void ldsm2(uint32_t* r, uint32_t addr) {
    asm volatile("ldmatrix.sync.aligned.m8n8.x2.shared.b16 {%0,%1}, [%2];" : "=r"(r[0]), "=r"(r[1]) : "r"(addr) : "memory");
}
DEVI void ldsm1t(uint32_t& r, uint32_t addr) {
    asm volatile("ldmatrix.sync.aligned.m8n8.x1.trans.shared.b16 {%0}, [%1];" : "=r"(r) : "r"(addr) : "memory");
}
DEVI void stsm4(uint32_t addr, uint32_t r0, uint32_t r1, uint32_t r2, uint32_t r3) {
    asm volatile("stmatrix.sync.aligned.m8n8.x4.shared.b16 [%0], {%1,%2,%3,%4};" :: "r"(addr), "r"(r0), "r"(r1), "r"(r2), "r"(r3) : "memory");
}
DEVI void stsm4t(uint32_t addr, uint32_t r0, uint32_t r1, uint32_t r2, uint32_t r3) {
    asm volatile("stmatrix.sync.aligned.m8n8.x4.trans.shared.b16 [%0], {%1,%2,%3,%4};" :: "r"(addr), "r"(r0), "r"(r1), "r"(r2), "r"(r3) : "memory");
}
DEVI uint32_t movm_t(uint32_t a) {
    uint32_t d; asm volatile("movmatrix.sync.aligned.m8n8.trans.b16 %0, %1;" : "=r"(d) : "r"(a)); return d;
}
DEVI uint32_t pack_bf16(float lo, float hi) {
    uint32_t r; asm("cvt.rn.bf16x2.f32 %0, %1, %2;" : "=r"(r) : "f"(hi), "f"(lo)); return r;
}
DEVI float ex2(float x) { float y; asm("ex2.approx.ftz.f32 %0, %1;" : "=f"(y) : "f"(x)); return y; }

DEVI uint4 ld_rlx4(const void* p) {
    uint4 v;
    asm volatile("ld.relaxed.gpu.global.v4.u32 {%0,%1,%2,%3}, [%4];" : "=r"(v.x), "=r"(v.y), "=r"(v.z), "=r"(v.w) : "l"(p) : "memory");
    return v;
}
DEVI void ld_rlx4f(float* d, const void* p) {
    asm volatile("ld.relaxed.gpu.global.v4.f32 {%0,%1,%2,%3}, [%4];" : "=f"(d[0]), "=f"(d[1]), "=f"(d[2]), "=f"(d[3]) : "l"(p) : "memory");
}
DEVI bool all_nzf(const float* d) { return __float_as_uint(d[0]) && __float_as_uint(d[1]) && __float_as_uint(d[2]) && __float_as_uint(d[3]); }
DEVI void sts128f(uint32_t addr, const float* d) {
    asm volatile("st.shared.v4.f32 [%0], {%1,%2,%3,%4};" :: "r"(addr), "f"(d[0]), "f"(d[1]), "f"(d[2]), "f"(d[3]) : "memory");
}
DEVI void st_rlx4(void* p, uint32_t a, uint32_t b, uint32_t c, uint32_t d) {
    asm volatile("st.relaxed.gpu.global.v4.u32 [%0], {%1,%2,%3,%4};" :: "l"(p), "r"(a), "r"(b), "r"(c), "r"(d) : "memory");
}
DEVI void st_rlx(void* p, uint32_t v) { asm volatile("st.relaxed.gpu.global.u32 [%0], %1;" :: "l"(p), "r"(v) : "memory"); }
DEVI void sts128(uint32_t addr, uint4 v) {
    asm volatile("st.shared.v4.u32 [%0], {%1,%2,%3,%4};" :: "r"(addr), "r"(v.x), "r"(v.y), "r"(v.z), "r"(v.w) : "memory");
}
DEVI void sts64(uint32_t addr, uint32_t a, uint32_t b) { asm volatile("st.shared.v2.u32 [%0], {%1,%2};" :: "r"(addr), "r"(a), "r"(b) : "memory"); }
DEVI void sts32(uint32_t addr, uint32_t v) { asm volatile("st.shared.u32 [%0], %1;" :: "r"(addr), "r"(v) : "memory"); }
DEVI uint4 lds128(uint32_t addr) {
    uint4 v; asm volatile("ld.shared.v4.u32 {%0,%1,%2,%3}, [%4];" : "=r"(v.x), "=r"(v.y), "=r"(v.z), "=r"(v.w) : "r"(addr) : "memory"); return v;
}
DEVI float2 lds64f(uint32_t addr) {
    float2 v; asm volatile("ld.shared.v2.f32 {%0,%1}, [%2];" : "=f"(v.x), "=f"(v.y) : "r"(addr) : "memory"); return v;
}
DEVI void cp_async16(uint32_t dst, const void* src) {
    asm volatile("cp.async.cg.shared.global [%0], [%1], 16;" :: "r"(dst), "l"(src) : "memory");
}
DEVI void cp_async_commit() { asm volatile("cp.async.commit_group;" ::: "memory"); }
DEVI void cp_async_wait0() { asm volatile("cp.async.wait_group 0;" ::: "memory"); }
DEVI uint32_t lds32(uint32_t addr) { uint32_t v; asm volatile("ld.shared.u32 %0, [%1];" : "=r"(v) : "r"(addr) : "memory"); return v; }
DEVI float rcp_fast(float x) { float y; asm("rcp.approx.ftz.f32 %0, %1;" : "=f"(y) : "f"(x)); return y; }
DEVI bool all_nz(const uint4& v) { return v.x && v.y && v.z && v.w; }
DEVI uint32_t mapa(uint32_t addr, uint32_t rank) {
    uint32_t r; asm("mapa.shared::cluster.u32 %0, %1, %2;" : "=r"(r) : "r"(addr), "r"(rank)); return r;
}
DEVI void st_async32(uint32_t dst, uint32_t a, uint32_t bar) {
    asm volatile("st.async.weak.shared::cluster.mbarrier::complete_tx::bytes.b32 [%0], %1, [%2];" :: "r"(dst), "r"(a), "r"(bar) : "memory");
}
DEVI void st_async64(uint32_t dst, uint32_t a, uint32_t b, uint32_t bar) {
    asm volatile("st.async.weak.shared::cluster.mbarrier::complete_tx::bytes.v2.b32 [%0], {%1,%2}, [%3];"
                 :: "r"(dst), "r"(a), "r"(b), "r"(bar) : "memory");
}

DEVI void st_async128(uint32_t dst, uint32_t a, uint32_t b, uint32_t c, uint32_t d, uint32_t bar) {
    asm volatile("st.async.weak.shared::cluster.mbarrier::complete_tx::bytes.v4.b32 [%0], {%1,%2,%3,%4}, [%5];"
                 :: "r"(dst), "r"(a), "r"(b), "r"(c), "r"(d), "r"(bar) : "memory");
}

DEVI uint32_t b_addr(uint32_t sb, int row, int which, int chunk) { const int l = 3 * row + which; return sb + l * 128 + ((chunk ^ (l & 7)) * 16); }
DEVI void battn_warp(uint32_t st, uint32_t ebar, int i0, int par, int head, int hh, int mt, int lane) {
    const int gq = lane >> 2, t = lane & 3, r = 16 * mt + (lane & 7), b3 = (lane >> 3) & 1, b4 = lane >> 4;
    uint32_t a[8], k[8], k2[4], v[8], v2[4];
#pragma unroll
    for (int ks = 0; ks < 2; ks++) {
        ldsm4(a + 4 * ks, b_addr(st, 8 + r + b3 * 8, 0, hh * 4 + ks * 2 + b4));
        ldsm4(k + 4 * ks, b_addr(st, r + b4 * 8, 1, hh * 4 + ks * 2 + b3));
    }
    ldsm4(k2, b_addr(st, r + 16, 1, hh * 4 + (lane >> 3)));
#pragma unroll
    for (int n = 0; n < 2; n++) ldsm4t(v + 4 * n, b_addr(st, r + b3 * 8, 2, hh * 4 + 2 * n + b4));
    ldsm4t(v2, b_addr(st, r + 16, 2, hh * 4 + (lane >> 3)));
    float s[3][4];
#pragma unroll
    for (int n = 0; n < 3; n++) { s[n][0] = s[n][1] = s[n][2] = s[n][3] = 0.f; }
#pragma unroll
    for (int ks = 0; ks < 2; ks++) {
        mma16816(s[0], a + 4 * ks, k[4 * ks], k[4 * ks + 1]);
        mma16816(s[1], a + 4 * ks, k[4 * ks + 2], k[4 * ks + 3]);
        mma16816(s[2], a + 4 * ks, k2[2 * ks], k2[2 * ks + 1]);
    }
    const bool ex = i0 + 16 * mt > 0;
    float x[4], y[4];
#pragma unroll
    for (int c = 0; c < 2; c++) {
        const bool low = 2 * t + c <= gq;
        x[c] = !low && ex ? s[0][c] : -INFINITY; x[2 + c] = low ? s[1][c] : -INFINITY;
        y[c] = !low ? s[1][2 + c] : -INFINITY;   y[2 + c] = low ? s[2][2 + c] : -INFINITY;
    }
    float m0 = fmaxf(fmaxf(x[0], x[1]), fmaxf(x[2], x[3])), m1 = fmaxf(fmaxf(y[0], y[1]), fmaxf(y[2], y[3]));
    m0 = fmaxf(fmaxf(m0, __shfl_xor_sync(0xffffffffu, m0, 1)), fmaxf(__shfl_xor_sync(0xffffffffu, m0, 2), __shfl_xor_sync(0xffffffffu, m0, 3)));
    m1 = fmaxf(fmaxf(m1, __shfl_xor_sync(0xffffffffu, m1, 1)), fmaxf(__shfl_xor_sync(0xffffffffu, m1, 2), __shfl_xor_sync(0xffffffffu, m1, 3)));
    constexpr float C = 0.17677669529663687f * 1.4426950408889634f;
    m0 *= -C; m1 *= -C;
    const uint32_t p0[4] = {pack_bf16(ex2(fmaf(x[0], C, m0)), ex2(fmaf(x[1], C, m0))), 0u,
                            pack_bf16(ex2(fmaf(x[2], C, m0)), ex2(fmaf(x[3], C, m0))), pack_bf16(ex2(fmaf(y[0], C, m1)), ex2(fmaf(y[1], C, m1)))};
    const uint32_t p1 = pack_bf16(ex2(fmaf(y[2], C, m1)), ex2(fmaf(y[3], C, m1)));
    float o[4][4], l[4] = {0.f, 0.f, 0.f, 0.f};
#pragma unroll
    for (int n = 0; n < 4; n++) { o[n][0] = o[n][1] = o[n][2] = o[n][3] = 0.f; }
    mma16816(l, p0, 0x3F803F80u, 0x3F803F80u);
#pragma unroll
    for (int n = 0; n < 4; n++) mma16816(o[n], p0, v[2 * n], v[2 * n + 1]);
    mma1688(l, 0u, p1, 0x3F803F80u);
#pragma unroll
    for (int n = 0; n < 4; n++) mma1688(o[n], 0u, p1, v2[n]);
    if (lane == 0) mbar_arrive(ebar);
    const float i0f = rcp_fast(l[0]), i1f = rcp_fast(l[2]);
    uint4* dst = (uint4*)(g_bo + (uint32_t)((2 * (i0 + 16 * mt + gq) + par) * DM + head * 32 + t * 8));
    dst[0] = make_uint4(pack_bf16(o[0][0] * i0f, o[0][1] * i0f), pack_bf16(o[1][0] * i0f, o[1][1] * i0f),
                        pack_bf16(o[2][0] * i0f, o[2][1] * i0f), pack_bf16(o[3][0] * i0f, o[3][1] * i0f));
    dst[16 * DM / 8] = make_uint4(pack_bf16(o[0][2] * i1f, o[0][3] * i1f), pack_bf16(o[1][2] * i1f, o[1][3] * i1f),
                                  pack_bf16(o[2][2] * i1f, o[2][3] * i1f), pack_bf16(o[3][2] * i1f, o[3][3] * i1f));
}

constexpr float SCALE_LOG2E = 0.08838834764831845f * 1.4426950408889634f;

constexpr int P_UNITS = 12, P_STAGES = 6;
constexpr int PS_STG = P_UNITS * 16384;
constexpr int PS_BAR = PS_STG + 32768;
constexpr int P_SMEM = PS_BAR + 256;
static_assert(P_SMEM <= 232448, "smem");
enum { K_Q, K_B1, K_B3, K_A4, K_QH, K_A3, K_SK, K_B2, K_SN, K_END };
struct PList { int n, nworker; int4 run[16]; };
struct PTask { int kind, a, b, c; };
DEVI PTask p_decode(const PList& pl, int id) {
    for (int i = 0; i < pl.n; i++) {
        const int4 r = pl.run[i];
        if (id < r.w) {
            const int j = id - r.z;
            if (r.x == K_Q || r.x == K_QH) return {r.x, j & 31, r.y + (j >> 5), 0};
            if (r.x == K_B1) return {r.x, j % 24, r.y + j / 24, 0};
            if (r.x == K_B2) return {r.x, 0, r.y + j, 0};
            if (r.x == K_SK || r.x == K_SN) return {r.x, (j / P_SPLIT) & 7, r.y + j / (8 * P_SPLIT), j % P_SPLIT};
            return {r.x, j & 7, r.y + (j >> 3), 0};
        }
    }
    return {K_END, 0, 0, 0};
}
DEVI void wait_count(const unsigned* p, unsigned target) {
    int n = 0;
    while (true) {
        unsigned v; asm volatile("ld.acquire.gpu.global.u32 %0, [%1];" : "=r"(v) : "l"(p) : "memory");
        if ((int)(v - target) >= 0) break;
        __nanosleep(100);
        if (++n > SPIN_LIMIT) TRAP(0x10000000u | ((unsigned)(size_t)p & 0xFFFFu));
    }
}
DEVI void wait_count_warp(const unsigned* p, unsigned target) {
    int n = 0;
    while (true) {
        unsigned v; asm volatile("ld.acquire.gpu.global.u32 %0, [%1];" : "=r"(v) : "l"(p) : "memory");
        if (__all_sync(0xffffffffu, (int)(v - target) >= 0)) break;
        __nanosleep(100);
        if (++n > SPIN_LIMIT) TRAP(0x10000000u | ((unsigned)(size_t)p & 0xFFFFu));
    }
}
DEVI void signal_count(unsigned* p) { __threadfence(); atomicAdd(p, 1u); }

struct PMaps { CUtensorMap wq, bw, bwo, wo, x, bx, bo, ox, ox64, cb, cout, cq, b40; PList list; };
constexpr int PB_F = PS_BAR, PB_E = PB_F + 48, PB_TF = PB_F + 96, PB_TE = PB_F + 112, PB_S = PB_F + 128;
constexpr int PS_T = PB_F + 144, PS_SIG = PS_T + 32, PS_SK = PS_SIG + 16;

struct PRing {
    int st, ph, u;
    DEVI void next(int n) { u += n; if (u >= P_UNITS) u -= P_UNITS; if (++st == P_STAGES) { st = 0; ph ^= 1; } }
    DEVI uint32_t w(bool wide) const { return wide && u == P_UNITS - 2 ? 0u : u * 16384u; }
    DEVI uint32_t x(bool wide) const { return wide && u == P_UNITS - 2 ? u * 16384u : (u == P_UNITS - 1 ? 0u : (u + 1) * 16384u); }
};
struct POut { const CUtensorMap* map; int col, tok, cnt; bool blocked; };
DEVI void p_store(const uint32_t* pk, const POut& o, int c, uint32_t stg, int warp, int lane_, int barid, bool elected) {
    const int lane = (int)opaque((uint32_t)lane_);
    const int mi = lane >> 3, r = lane & 7;
    const uint32_t buf = stg + (c & 1) * 8192;
    if (elected) asm volatile("cp.async.bulk.wait_group.read 1;" ::: "memory");
    nbar_sync(barid, 128);
    if (o.blocked) {
#pragma unroll
        for (int j = 0; j < 8; j += 2)
            stsm4(buf + (j + (mi >> 1)) * 1024 + (warp * 16 + (mi & 1) * 8 + r) * 16, pk[2 * j], pk[2 * j + 1], pk[2 * j + 2], pk[2 * j + 3]);
    } else {
#pragma unroll
        for (int j = 0; j < 8; j += 2)
            stsm4t(buf + (8 * (j + (mi >> 1)) + r) * 128 + ((2 * warp + (mi & 1)) ^ r) * 16, pk[2 * j], pk[2 * j + 1], pk[2 * j + 2], pk[2 * j + 3]);
    }
    fence_proxy_async();
    nbar_sync(barid, 128);
    if (elected) {
        if (o.blocked)
            asm volatile("cp.async.bulk.tensor.4d.global.shared::cta.bulk_group [%0, {%2, %3, %4, %5}], [%1];"
                         :: "l"(o.map), "r"(buf), "r"(0), "r"((o.col >> 5) & 2), "r"((o.col >> 7) * 4), "r"((o.tok >> 5) + 2 * c) : "memory");
        else tma_store_2d(o.map, buf, o.col, o.tok + c * 64);
        bulk_commit();
    }
}
DEVI void p_signal(uint32_t sb, int g, int cnt, int& nsig) {
    sts32(sb + PS_SIG + g * 8 + (nsig & 1) * 4, (uint32_t)cnt);
    mbar_arrive(sb + PB_S + g * 8);
    nsig++;
}
DEVI void p_release(uint32_t sb, const PRing& r) {
    if (elect_one()) mbar_arrive(sb + PB_E + (r.st ? r.st - 1 : P_STAGES - 1) * 8);
}
template <int BN, bool FIRST>
DEVI void p_kblock(float* d, uint32_t sb, int g, PRing& r) {
    mbar_wait(sb + PB_F + r.st * 8, r.ph);
    const uint64_t da = mk_desc(sb + r.w(BN == 256) + g * 8192, 16, 1024, 1), db = mk_desc(sb + r.x(BN == 256), 16, 1024, 1);
    wg_fence();
#pragma unroll
    for (int kk = 0; kk < 4; kk++) {
        if (BN == 256) { if (FIRST && kk == 0) wgmma_n256_ss<true>(d, da, db); else wgmma_n256_ss<false>(d, da + (uint64_t)(kk * 128), db + (uint64_t)(kk * 2)); }
        if (BN == 128) { if (FIRST && kk == 0) wgmma_n128_ss<true>(d, da, db); else wgmma_n128_ss<false>(d, da + (uint64_t)(kk * 128), db + (uint64_t)(kk * 2)); }
        if (BN == 64)  { if (FIRST && kk == 0) wgmma_n64_ss<true>(d, da, db); else wgmma_n64_ss<false>(d, da + (uint64_t)(kk * 128), db + (uint64_t)(kk * 2)); }
    }
    wg_commit();
    if (!FIRST) {
        wg_wait<1>();
        p_release(sb, r);
    }
    r.next(BN == 256 ? 3 : 2);
}

DEVI int post_claim(const PMaps& mp, unsigned E) {
    unsigned v = 0;
    if ((threadIdx.x & 31) == 0) v = atomicAdd(&g_qctr, 1u);
    return (int)(__shfl_sync(0xffffffffu, v, 0) - (E - 1) * (unsigned)(mp.list.run[mp.list.n - 1].w + mp.list.nworker));
}
DEVI void post_producer(const PMaps& mp, uint32_t sb, unsigned E, int id) {
    PRing r = {0, 0, 0};
    int ts = 0, tp = 0, used = 0;
    uint32_t big = 0;
    auto reserve = [&](int n) {
        while (used + n > P_UNITS) {
            mbar_wait(sb + PB_E + ts * 8, tp);
            used -= 2 + ((big >> ts) & 1);
            if (++ts == P_STAGES) { ts = 0; tp ^= 1; }
        }
        used += n;
        big = (big & ~(1u << r.st)) | ((uint32_t)(n & 1) << r.st);
    };
    for (int i = 0;; i++) {
        mbar_wait(sb + PB_TE + (i & 1) * 8, ((i >> 1) & 1) ^ 1);
        if (i > 0) id = post_claim(mp, E);
        const PTask tk = p_decode(mp.list, id);
        const bool sn = tk.kind == K_SN, split = tk.kind == K_SK || sn, wide = tk.kind <= K_A4;
        const bool qk = tk.kind == K_Q || tk.kind == K_QH, ak = tk.kind == K_A4 || tk.kind == K_A3 || split;
        const int nk = split ? HD / 64 / P_SPLIT : (ak ? HD / 64 : DM / 64), kb0 = tk.c * (HD / 64 / P_SPLIT);
        const int tok0 = tk.b * (wide ? 256 : (sn ? 64 : 128)), grp = (tok0 >> 7) + (wide ? 1 : 0);
        const uint32_t bytes = wide ? 49152 : (sn ? 24576 : 32768);
        const CUtensorMap* tx = tk.kind == K_B1 ? &mp.bx : (qk ? &mp.x : (sn ? &mp.ox64 : (ak ? &mp.ox : &mp.bo)));
        const int npre = split && (i == 0 || __any_sync(0xffffffffu, (int)(*(volatile unsigned*)&g_prog[grp] - 128 * E) < 0)) ? P_STAGES : 0;
        PRing rp = r;
        for (int kb = kb0; kb < kb0 + npre; kb++) {
            reserve(2);
            const uint32_t bar = sb + PB_F + r.st * 8;
            if (elect_one()) {
                mbar_expect_tx(bar, bytes);
                tma_load_wo(sb + r.w(false), &mp.wo, tk.a * 128, kb * 2, bar);
                tma_load_wo(sb + r.w(false) + 8192, &mp.wo, tk.a * 128 + 64, kb * 2, bar);
            }
            r.next(2);
        }
        if (tk.kind == K_B2) {
            wait_count_warp(&g_cnt[C_B1 + (tk.b >> 2)], 48 * E);
            if ((tk.b & 3) == 0 && tk.b > 0) wait_count_warp(&g_cnt[C_B1 + (tk.b >> 2) - 1], 48 * E);
        } else if (tk.kind == K_B3) wait_count_warp(&g_cnt[C_B2 + tk.b], 8 * E);
        else if (ak) wait_count_warp(&g_prog[grp], 128 * E);
        fence_proxy_global();
        for (int kb = kb0; kb < kb0 + npre; kb++) {
            if (elect_one()) tma_load_2d(sb + rp.x(false), tx, kb * 64, tok0, sb + PB_F + rp.st * 8);
            rp.next(2);
        }
        if (elect_one()) {
            sts128(sb + PS_T + (i & 1) * 16, make_uint4((uint32_t)tk.kind | ((uint32_t)id << 8), (uint32_t)tk.a, (uint32_t)tk.b, (uint32_t)tk.c));
            mbar_arrive(sb + PB_TF + (i & 1) * 8);
        }
        if (tk.kind == K_END) break;
        if (tk.kind == K_B2) {
            for (int j = 0; j < 16; j++) {
                reserve(2);
                const uint32_t bar = sb + PB_F + r.st * 8;
                if (elect_one()) {
                    mbar_expect_tx(bar, 2 * 15360);
#pragma unroll
                    for (int u = 0; u < 2; u++) asm volatile("cp.async.bulk.tensor.4d.shared::cluster.global.mbarrier::complete_tx::bytes [%0], [%1, {%3, %4, %5, %6}], [%2];"
                                 :: "r"(sb + (u ? r.x(false) : r.w(false))), "l"(&mp.b40), "r"(bar), "r"(j * 64), "r"(0), "r"(u), "r"(tk.b * 32 - 8) : "memory");
                }
                r.next(2);
            }
            continue;
        }
        const CUtensorMap* tw = tk.kind == K_B1 ? &mp.bw : (qk ? &mp.wq : (ak ? &mp.wo : &mp.bwo));
        for (int kb = kb0 + npre; kb < kb0 + nk; kb++) {
            reserve(wide ? 3 : 2);
            const uint32_t aw = sb + r.w(wide), ax = sb + r.x(wide), bar = sb + PB_F + r.st * 8;
            if (elect_one()) {
                mbar_expect_tx(bar, bytes);
                if (ak || tk.kind == K_B3) {
                    tma_load_wo(aw, tw, tk.a * 128, kb * 2, bar);
                    tma_load_wo(aw + 8192, tw, tk.a * 128 + 64, kb * 2, bar);
                } else {
                    tma_load_2d(aw, tw, tk.a * 128, kb * 64, bar);
                    tma_load_2d(aw + 8192, tw, tk.a * 128 + 64, kb * 64, bar);
                }
                tma_load_2d(ax, tx, kb * 64, tok0, bar);
                if (wide) tma_load_2d(ax + 16384, tx, kb * 64, tok0 + 128, bar);
            }
            r.next(wide ? 3 : 2);
        }
    }
    if (elect_one()) {
        __threadfence();
        if (atomicAdd(&g_done, 1u) == E * mp.list.nworker - 1) { __threadfence(); *(volatile unsigned*)&g_epoch = E; }
    }
}
DEVI void post_helper(uint32_t sb, int g) {
    for (int n = 0;; n++) {
        mbar_wait_sleepy(sb + PB_S + g * 8, n & 1);
        const int cnt = (int)lds32(sb + PS_SIG + g * 8 + (n & 1) * 4);
        if (cnt < 0) break;
        signal_count(&g_cnt[cnt]);
    }
}
template <int BN>
DEVI void p_narrow(const PMaps& mp, const PTask& tk, uint32_t sb, int g, int warp, PRing& r, int& nsig) {
    const int barid = 1 + g, tid = threadIdx.x;
    const bool elected = (tid & 127) == 0, split = BN == 64 || tk.kind == K_SK;
    constexpr int NV = BN / 16;
    float d[BN / 2];
    const int nk = split ? HD / 64 / P_SPLIT : (tk.kind == K_A3 ? HD / 64 : DM / 64);
    p_kblock<BN, true>(d, sb, g, r);
#pragma unroll 1
    for (int kb = 1; kb < nk; kb++) p_kblock<BN, false>(d, sb, g, r);
    wg_wait<0>();
    reg_fence<BN / 2>(d);
    p_release(sb, r);
    if (split) {
        const int tile = (tk.b * (BN / 64) - 2 * (16 - P_NSK)) * 8 + tk.a * (BN / 64);
        uint4* const base = g_skp + (uint32_t)(tile * P_SPLIT * 1024 + g * NV * 128 + (tid & 127));
#pragma unroll
        for (int j = 0; j < NV; j++)
            base[tk.c * NV * 256 + j * 128] = make_uint4(pack_bf16(d[8 * j], d[8 * j + 1]), pack_bf16(d[8 * j + 2], d[8 * j + 3]),
                                                         pack_bf16(d[8 * j + 4], d[8 * j + 5]), pack_bf16(d[8 * j + 6], d[8 * j + 7]));
        nbar_sync(barid, 128);
        if (elected) {
            unsigned old;
            asm volatile("atom.acq_rel.gpu.global.add.u32 %0, [%1], 1;" : "=r"(old) : "l"(&g_cnt_sk[tile * 2 + g]) : "memory");
            sts32(sb + PS_SK + g * 4, old % P_SPLIT);
        }
        nbar_sync(barid, 128);
        const bool last = lds32(sb + PS_SK + g * 4) == P_SPLIT - 1;
        nbar_sync(barid, 128);
        if (!last) return;
        uint4 v[(P_SPLIT - 1) * NV];
#pragma unroll
        for (int j = 0; j < (P_SPLIT - 1) * NV; j++) v[j] = __ldcg(base + ((tk.c + 1 + j / NV) % P_SPLIT) * NV * 256 + (j % NV) * 128);
#pragma unroll
        for (int j = 0; j < (P_SPLIT - 1) * NV; j++) {
            float* e = d + 8 * (j % NV);
            e[0] += __uint_as_float(v[j].x << 16); e[1] += __uint_as_float(v[j].x & 0xFFFF0000u);
            e[2] += __uint_as_float(v[j].y << 16); e[3] += __uint_as_float(v[j].y & 0xFFFF0000u);
            e[4] += __uint_as_float(v[j].z << 16); e[5] += __uint_as_float(v[j].z & 0xFFFF0000u);
            e[6] += __uint_as_float(v[j].w << 16); e[7] += __uint_as_float(v[j].w & 0xFFFF0000u);
        }
    }
    const bool qh = BN == 128 && tk.kind == K_QH;
    const POut o = {qh ? &mp.cq : &mp.cout, tk.a * 128 + g * 64, tk.b * BN, 0, qh};
    uint32_t q[BN / 4];
#pragma unroll
    for (int j = 0; j < BN / 4; j++) q[j] = pack_bf16(d[2 * j], d[2 * j + 1]);
    if (BN == 64 && elected) bulk_wait_read();
#pragma unroll
    for (int c = 0; c < BN / 64; c++) p_store(q + 16 * c, o, c, sb + PS_STG + g * 16384, warp, tid & 31, barid, elected);
    if (BN == 64 && elected) bulk_wait_read();
    if (elected && qh) { bulk_wait_all(); p_signal(sb, g, tk.b == 0 ? C_QH : C_Q, nsig); }
}
DEVI void post_consumer(const PMaps& mp, uint32_t sb, int g, int warp) {
    const int barid = 1 + g, tid = threadIdx.x, lane = tid & 31;
    const bool elected = (tid & 127) == 0;
    const uint32_t stg = sb + PS_STG + g * 16384;
    int nsig = 0;
    PRing r = {0, 0, 0};
    uint32_t pk[64];
    POut out;
    bool pend = false;
#pragma unroll
    for (int i = 0; i < 64; i++) pk[i] = 0u;
    for (int i = 0;; i++) {
        const uint32_t bTF = sb + PB_TF + (i & 1) * 8;
        if (pend) {
            uint32_t now;
            asm volatile("{.reg .pred p, q; mbarrier.test_wait.parity.shared::cta.b64 p, [%1], %2; bar.red.and.pred q, %3, 128, p; selp.u32 %0, 1, 0, q;}"
                         : "=r"(now) : "r"(bTF), "r"((i >> 1) & 1), "r"(barid) : "memory");
            if (!now || (lds32(sb + PS_T + (i & 1) * 16) & 255u) > K_A4) {
#pragma unroll
                for (int c = 0; c < 4; c++) p_store(pk + 16 * c, out, c, stg, warp, lane, barid, elected);
                if (elected && out.cnt != C_NONE) { bulk_wait_all(); p_signal(sb, g, out.cnt, nsig); }
                pend = false;
            }
        }
        mbar_wait(bTF, (i >> 1) & 1);
        const uint4 tw = lds128(sb + PS_T + (i & 1) * 16);
        mbar_arrive(sb + PB_TE + (i & 1) * 8);
        const PTask tk = {(int)(tw.x & 255u), (int)tw.y, (int)tw.z, (int)tw.w};
        if (tk.kind == K_END) break;
        if (tk.kind <= K_A4) {
            float d[128];
            const int nk = tk.kind == K_A4 ? HD / 64 : DM / 64;
            p_kblock<256, true>(d, sb, g, r);
            if (pend) p_store(pk, out, 0, stg, warp, lane, barid, elected);
#pragma unroll
            for (int c = 1; c < 4; c++) {
                p_kblock<256, false>(d, sb, g, r);
                if (pend) p_store(pk + 16 * c, out, c, stg, warp, lane, barid, elected);
            }
#pragma unroll 1
            for (int kb = 4; kb < nk; kb++) {
                p_kblock<256, false>(d, sb, g, r);
                if (kb == 6 && pend && elected && out.cnt != C_NONE) { bulk_wait_all(); p_signal(sb, g, out.cnt, nsig); }
            }
            wg_wait<0>();
            reg_fence<128>(d);
            p_release(sb, r);
#pragma unroll
            for (int j = 0; j < 64; j++) pk[j] = pack_bf16(d[2 * j], d[2 * j + 1]);
            out.map = tk.kind == K_Q ? &mp.cq : (tk.kind == K_B1 ? &mp.cb : &mp.cout);
            out.col = tk.a * 128 + g * 64 + (tk.kind == K_B3 ? DM : 0);
            out.tok = tk.b * 256;
            out.cnt = tk.kind == K_Q ? C_Q + tk.b : (tk.kind == K_B1 ? C_B1 + tk.b : C_NONE);
            out.blocked = tk.kind == K_Q;
            pend = true;
        } else if (tk.kind == K_B2) {
#pragma unroll 2
            for (int j = 0; j < 16; j++) {
                mbar_wait(sb + PB_F + r.st * 8, r.ph);
                const uint32_t a = sb + (g ? r.x(false) : r.w(false));
                battn_warp(a, sb + PB_E + r.st * 8, tk.b * 32, g, j * 2 + (warp >> 1), warp >> 1, warp & 1, lane);
                r.next(2);
            }
            nbar_sync(barid, 128);
            if (elected) p_signal(sb, g, C_B2 + (tk.b >> 2), nsig);
#pragma unroll
            for (int j = 0; j < 64; j++) pk[j] = 0u;
        } else {
            if (tk.kind == K_SN) p_narrow<64>(mp, tk, sb, g, warp, r, nsig); else p_narrow<128>(mp, tk, sb, g, warp, r, nsig);
#pragma unroll
            for (int j = 0; j < 64; j++) pk[j] = 0u;
        }
    }
    if (elected) { bulk_wait_all(); p_signal(sb, g, -1, nsig); }
}
DEVI void post_init(uint32_t sb) {
    for (int i = 0; i < P_STAGES; i++) { mbar_init(sb + PB_F + i * 8, 1); mbar_init(sb + PB_E + i * 8, 8); }
    for (int i = 0; i < 2; i++) { mbar_init(sb + PB_TF + i * 8, 1); mbar_init(sb + PB_TE + i * 8, 256); mbar_init(sb + PB_S + i * 8, 1); }
    fence_mbar_init();
}

constexpr unsigned long long R_TORD_PACK = 0xf5ea4937dc1826b0ull;
__host__ __device__ constexpr int r_tord(int pos) { return (int)((R_TORD_PACK >> (4 * pos)) & 15ull); }
__host__ __device__ constexpr int r_tinv(int T) { for (int p = 0; p < 16; p++) if (r_tord(p) == T) return p; return 0; }
__host__ __device__ constexpr bool r_pos_ss(int pos) { return pos % 3 == 2; }
__host__ __device__ constexpr int r_ss(int pos) { return pos / 3; }
__host__ __device__ constexpr int r_rs(int pos) { return pos - pos / 3; }
constexpr int R_NRS = 11, R_NSS = 5;
constexpr int R_G1 = 3, R_G2 = 9;
#define REG_KB 232
constexpr int X_SLOTS = 4;
constexpr int X_NST = 8;

constexpr int RS_WSS  = 0;
constexpr int RS_WO   = RS_WSS + R_NSS * 16384;
constexpr int RS_MEM  = RS_WO + 5 * 16384;
constexpr int RS_O    = RS_MEM + 16384;
constexpr int RS_SX   = RS_O + 2048;
constexpr int RS_BAR  = RS_SX + 2048;
constexpr int RS_TAIL = RS_BAR + 1024;
constexpr int RS_WO5  = RS_TAIL;
constexpr int RS_K    = RS_WO5 + 16384;
constexpr int RS_V    = RS_K + 10240;
constexpr int RS_Q    = RS_V + 10240;
constexpr int RS_QX   = RS_Q + 2048;
constexpr int RS_QEND = RS_QX + 8192;
constexpr int RS_X    = RS_TAIL;
constexpr int X_PITCH = X_SLOTS * 4096;
constexpr int RS_XD   = RS_X + 2 * X_PITCH;
constexpr int RS_WX   = RS_XD + 8192;
constexpr int RS_XE   = RS_WX + 4096;
constexpr int RS_KEND = RS_XE + 2048;
constexpr int RS_EV   = RS_BAR + 256;
constexpr int R_SMEM  = RS_KEND > RS_QEND ? RS_KEND : RS_QEND;
static_assert(R_SMEM <= 232448 && P_SMEM <= R_SMEM, "smem");
static_assert(RS_TAIL % 1024 == 0 && RS_MEM % 1024 == 0, "alignment");

constexpr int RB_G = RS_BAR, RB_K = RS_BAR + 24, RB_V = RS_BAR + 32, RB_KV = RS_BAR + 40, RB_QX = RS_BAR + 48, RB_O = RS_BAR + 56;
constexpr int RB_ATT = RS_BAR + 64, RB_W = RS_BAR + 72, RB_SF = RS_BAR + 80, RB_SE = RB_SF + 40, RB_XF = RB_SE + 40;
constexpr int RB_VX = RB_XF + 48, RB_WO = RB_XF + 56, RB_T = RB_XF + 64, RS_INV = RB_XF + 16;
static_assert(RB_T + 8 <= RS_EV, "barriers");
constexpr uint32_t SB0 = 1024;
__host__ __device__ constexpr uint32_t cdesc(uint32_t off, uint32_t lbo) { return ((SB0 + off) >> 4) | ((lbo >> 4) << 16); }
#define SCHED_FENCE() __syncwarp()
constexpr int NB_BIG = 1, NB_Q = 2, NB_AUX = 3, NB_WO = 4, NB_XS = 5, NB_WG = 6, NB_PAIR = 8, NB_PRO = 12;

DEVI int tid_now() { int t; asm volatile("mov.u32 %0, %%tid.x;" : "=r"(t)); return t; }
DEVI uint32_t a_frag_off(int lane, int warp) { return (uint32_t)((((lane >> 4) * 8 + (lane & 7)) * 128) + (((2 * warp + ((lane >> 3) & 1)) ^ (lane & 7)) * 16)); }
DEVI uint32_t b_frag_off(int lane) { return (uint32_t)((lane & 3) * 64 + (((lane >> 2) * 8) ^ ((lane & 2) * 16))); }
DEVI void lds_b(uint32_t* b, uint32_t a) {
    asm volatile("ld.shared.v2.u32 {%0,%1}, [%2];" : "=r"(b[0]), "=r"(b[1]) : "r"(a) : "memory");
    asm volatile("ld.shared.v2.u32 {%0,%1}, [%2];" : "=r"(b[2]), "=r"(b[3]) : "r"(a + 256) : "memory");
}
DEVI uint32_t clk32() { unsigned long long c; asm volatile("mov.u64 %0, %%clock64;" : "=l"(c)); return (uint32_t)c; }

__host__ __device__ constexpr int x_pair(int j) { return j == 0 || j > 3 ? j : (j == 3 ? 1 : j + 1); }
DEVI void x_load(uint32_t sb, int seg, int j, int g, const CUtensorMap* tmX) {
    const uint32_t bar = sb + RB_XF + g * 8;
    mbar_expect_tx(bar, 4096);
    tma_load_3d(sb + RS_X + g * X_PITCH + (j % X_SLOTS) * 4096, tmX + (j == 3), g * 32, seg * 32, x_pair(j) * 2, bar);
    if (j == 3) tma_load_3d(sb + RS_SX + g * (RS_XE - RS_SX), tmX + 1, g * 32, seg * 32, x_pair(3) * 2 + 1, bar);
}
DEVI void x_refill(uint32_t sb, int seg, int j, int g, int warp, const CUtensorMap* tmX) {
    const int sn = j + X_SLOTS < X_NST ? seg : seg + 1;
    if (warp == (j & 3) && sn < NSEG) {
        if (elect_one()) x_load(sb, sn, (j + X_SLOTS) % X_NST, g, tmX);
    }
}
template <int J, int Q0, int Q1, int DQ>
DEVI void x_steps(float* xa, const uint32_t* w, int g0) {
    const int g = (int)opaque((uint32_t)g0);
    const uint32_t dW0 = cdesc(RS_WSS, 16) + g * 768, dW1 = cdesc(RS_WSS + 8192, 16) - g * 256;
#pragma unroll
    for (int q = Q0; q < Q1; q += DQ) {
        const int pos = r_tinv(2 * x_pair(J) + (q >> 2)), kk = (q >> 1) & 1, mt = q & 1;
        const uint32_t db = (J == 3 && q >= 4 ? cdesc(RS_SX, 16) + g * ((RS_XE - RS_SX) >> 4)
                                                    : cdesc(RS_X + (J % X_SLOTS) * 4096, 16) + g * (X_PITCH >> 4) + (q >> 2) * 128) + kk * 2;
        if (J == 0 && q < 2)   wgmma_n32_rs_first(xa + 16 * mt, &w[((r_rs(pos) * 2 + kk) * 2 + mt) * 4], db);
        else if (J == 0 && q == 3) wgmma_n32_ss(xa + 16, cdesc(RS_WX, 16) + g * 128, db);
        else if (r_pos_ss(pos)) wgmma_n32_ss(xa + 16 * mt, (mt ? dW1 : dW0) + r_ss(pos) * 1024 + kk * 128, db);
        else                   wgmma_n32_rs(xa + 16 * mt, &w[((r_rs(pos) * 2 + kk) * 2 + mt) * 4], db);
    }
}
DEVI void x_first(float* xa, const uint32_t* w, uint32_t sb, int seg, int g0, int warp, const CUtensorMap* tmX) {
    wg_fence();
    x_steps<0, 0, 8, 1>(xa, w, g0); wg_commit();
    x_steps<1, 0, 8, 1>(xa, w, g0); wg_commit();
    x_steps<2, 0, 8, 1>(xa, w, g0); wg_commit();
    x_steps<3, 0, 4, 1>(xa, w, g0); wg_commit();
    const int g = (int)opaque((uint32_t)g0);
    wg_wait<3>(); x_refill(sb, seg, 0, g, warp, tmX);
    wg_wait<2>(); x_refill(sb, seg, 1, g, warp, tmX);
    wg_wait<1>(); x_refill(sb, seg, 2, g, warp, tmX);
    wg_wait<0>(); x_refill(sb, seg, 3, g, warp, tmX);
    reg_fence<32>(xa);
    mbar_wait(sb + RB_XF + g * 8, 1);
}
DEVI void x_second(float* xa, uint32_t* a, uint32_t aA0, const uint32_t* w, uint32_t sb, int seg, int g0, int warp, const CUtensorMap* tmX) {
    wg_fence();
    x_steps<4, 0, 8, 1>(xa, w, g0); wg_commit();
    x_steps<5, 0, 8, 1>(xa, w, g0); wg_commit();
    x_steps<3, 4, 8, 1>(xa, w, g0);
    x_steps<6, 1, 8, 2>(xa, w, g0); x_steps<7, 1, 8, 2>(xa, w, g0); wg_commit();
    x_steps<6, 0, 8, 2>(xa, w, g0); x_steps<7, 0, 8, 2>(xa, w, g0); wg_commit();
    const int g = (int)opaque((uint32_t)g0);
    wg_wait<3>(); x_refill(sb, seg, 4, g, warp, tmX);
    SCHED_FENCE();
#pragma unroll
    for (int q = 0; q < 4; q++) ldsm4t(a + 4 * q, aA0 + (q & 1) * (8192 - g * 16384) + (q >> 1) * 2048);
    SCHED_FENCE();
    wg_wait<2>(); x_refill(sb, seg, 5, g, warp, tmX);
    wg_wait<1>();
    reg_fence<16>(xa + 16);
}
DEVI void x_finish(float* xa, uint32_t sb, int seg, int g, int warp, int lane, const CUtensorMap* tmX) {
    const uint32_t d = sb + RS_XD + (lane >> 4) * 2048 + warp * 256 + (lane & 15) * 16;
#pragma unroll
    for (int i = 0; i < 2; i++) {
        const float* x = xa + 16 + 8 * i;
        sts128(d + (g ^ 1) * 1024 + i * 4096, make_uint4(pack_bf16(x[0], x[1]), pack_bf16(x[2], x[3]), pack_bf16(x[4], x[5]), pack_bf16(x[6], x[7])));
    }
    nbar_sync(NB_PAIR + warp, 64);
    float y[16];
#pragma unroll
    for (int i = 0; i < 2; i++) {
        const uint4 v = lds128(d + g * 1024 + i * 4096);
        const uint32_t u[4] = {v.x, v.y, v.z, v.w};
#pragma unroll
        for (int j = 0; j < 4; j++) { y[8 * i + 2 * j] = __uint_as_float(u[j] << 16); y[8 * i + 2 * j + 1] = __uint_as_float(u[j] & 0xFFFF0000u); }
    }
    reg_fence<16>(y);
    wg_wait<0>();
    reg_fence<16>(xa);
    uint32_t p[8];
#pragma unroll
    for (int j = 0; j < 8; j++) p[j] = pack_bf16(xa[2 * j] + y[2 * j], xa[2 * j + 1] + y[2 * j + 1]);
    __syncwarp();
    stsm4(d + g * 1024, p[0], p[1], p[2], p[3]);
    stsm4(d + g * 1024 + 4096, p[4], p[5], p[6], p[7]);
    nbar_arrive(NB_XS, 256 + 32);
    x_refill(sb, seg, X_NST - 2, g, warp, tmX);
    x_refill(sb, seg, X_NST - 1, g, warp, tmX);
}
DEVI void x_send(uint32_t sb, int seg, uint32_t rank, int vdelay) {
    mbar_wait(sb + RB_ATT, (seg - 1) & 1);
    nbar_sync(NB_XS, 256 + 32);
    if (rank == 2) { const uint32_t t = clk32() + vdelay; while ((int)(clk32() - t) < 0) { } }
    if (elect_one()) {
        fence_proxy_async();
        bulk_copy_s2c(mapa(sb + (rank == 1 ? RS_K : RS_V) + 2048, 0), sb + RS_XD, 8192, mapa(sb + (rank == 1 ? RB_KV : RB_VX), 0));
    }
    __syncwarp();
}

template <bool XP>
DEVI void mem_pass(float* c0, float* c1, uint32_t* a, const uint32_t* w, uint32_t sb, uint32_t aA0, uint32_t aB, int g, int warp, int s) {
    const uint32_t aA1 = aA0 + 8192 - g * 16384, par = (s - 1) & 1;
    uint32_t b[2][4], e[4];
    float d0[4], d1[4];
    if (XP) ldsm4t(e, aA0 + opaque((RS_WX - RS_WSS) - g * (8192 + 2048)));
#pragma unroll
    for (int q = XP ? 4 : 0; q < 4; q++) ldsm4t(a + 4 * q, ((q & 1) ? aA1 : aA0) + (q >> 1) * 2048);
#pragma unroll
    for (int i = 0; i < 4; i++) { c0[i] = 0.f; c1[i] = 0.f; d0[i] = 0.f; d1[i] = 0.f; }
    EV(EV_BIG0, s, 0);
    mbar_wait(sb + RB_G, par);
    EV(EV_BIG0, s, 1);
    lds_b(b[0], aB + r_tord(0) * 1024);
    bool in = false;
#pragma unroll
    for (int pos = 0; pos < 16; pos++) {
        if (pos + 1 < 16) {
            if (pos + 1 == R_G1 && !in) mbar_wait(sb + RB_G + 8, par);
            if (pos + 1 == R_G2) { if (!in) mbar_wait(sb + RB_G + 16, par); EV(EV_BIG0, s, 2); }
            lds_b(b[(pos + 1) & 1], aB + r_tord(pos + 1) * 1024);
        }
        if (pos + 2 == R_G1) in = mbar_try(sb + RB_G + 8, par);
        if (pos + 2 == R_G2) in = mbar_try(sb + RB_G + 16, par);
        if (XP && pos == 12) in = s == NSEG - 1 || mbar_try(sb + RB_XF + g * 8, 0);
        if (XP && pos == 14) { if (!in) mbar_wait(sb + RB_XF + g * 8, 0); in = mbar_try(sb + RB_ATT, par); }
        const uint32_t* bb = b[pos & 1];
        const uint32_t* aa = r_pos_ss(pos) ? a : &w[r_rs(pos) * 16];
        mma16816(c1, aa + 4, bb[0], bb[1]);
        mma16816(d1, XP && pos == 0 ? e : aa + 12, bb[2], bb[3]);
        mma16816(c0, aa, bb[0], bb[1]);
        mma16816(d0, aa + 8, bb[2], bb[3]);
        if (r_pos_ss(pos) && pos + 3 < 16) {
#pragma unroll
            for (int q = 0; q < 4; q++) ldsm4t(a + 4 * q, ((q & 1) ? aA1 : aA0) + (r_ss(pos) + 1) * 16384 + (q >> 1) * 2048);
        }
        SCHED_FENCE();
    }
    if (XP && !in) mbar_wait(sb + RB_ATT, par);
#pragma unroll
    for (int i = 0; i < 4; i++) { c1[i] += d1[i]; c0[i] += d0[i]; }
}

DEVI uint32_t k_frag_off(int lane) { return (uint32_t)((((lane >> 3) & 1) * 16 + (lane >> 4) * 8 + (lane & 7)) * 16); }
DEVI uint32_t v_frag_off(int lane) { return (uint32_t)(((lane >> 3) & 1) * 2048 + ((lane >> 4) * 8 + (lane & 7)) * 16); }
DEVI void pv_pair(float (*o)[4], const uint32_t* p, const uint32_t* v) {
#pragma unroll
    for (int n = 0; n < 4; n++) mma16816(o[n], p, v[2 * n], v[2 * n + 1]);
}
DEVI void pv_single(float (*o)[4], const uint32_t* p, const uint32_t* v) {
#pragma unroll
    for (int n = 0; n < 4; n++) mma1688(o[n], p[0], p[1], v[n]);
}
DEVI void s_tile(const uint32_t* qa, const uint32_t* k, float& s0, float& s1) {
    float c[4][4];
#pragma unroll
    for (int q = 0; q < 4; q++) { c[q][0] = c[q][1] = c[q][2] = c[q][3] = 0.f; }
#pragma unroll
    for (int q = 0; q < 4; q++) {
        mma16816(c[2 * (q & 1)], qa + 4 * q, k[4 * q], k[4 * q + 1]);
        mma16816(c[2 * (q & 1) + 1], qa + 4 * q, k[4 * q + 2], k[4 * q + 3]);
    }
    s0 = (c[0][0] + c[1][2]) + (c[2][0] + c[3][2]);
    s1 = (c[0][1] + c[1][3]) + (c[2][1] + c[3][3]);
}
DEVI void mem_scores(uint32_t sb, int s, int lane) {
    const uint32_t ka = sb + RS_K + k_frag_off(lane), sa = sb + RS_SX + 1024 + lane * 8;
    uint32_t qa[16], km[16];
    nbar_sync(NB_Q, 256);
#pragma unroll
    for (int q = 0; q < 4; q++) ldsm4t(qa + 4 * q, sb + RS_Q + q * 512 + lane * 16);
    mbar_wait(sb + RB_K, s & 1);
#pragma unroll
    for (int q = 0; q < 4; q++) ldsm4t(km + 4 * q, ka + q * 512);
    SCHED_FENCE();
    float s0, s1;
    s_tile(qa, km, s0, s1);
    asm volatile("st.shared.v2.f32 [%0], {%1,%2};" :: "r"(sa), "f"(s0 * SCALE_LOG2E), "f"(s1 * SCALE_LOG2E) : "memory");
    nbar_arrive(NB_XS, 128 + 32);
}
DEVI float quad_max(float m) {
    return fmaxf(fmaxf(m, __shfl_xor_sync(0xffffffffu, m, 1)), fmaxf(__shfl_xor_sync(0xffffffffu, m, 2), __shfl_xor_sync(0xffffffffu, m, 3)));
}
DEVI void mem_attn(uint32_t sb, int s, int warp, int lane) {
    const uint32_t va = sb + RS_V + warp * 512, sa = sb + RS_SX + lane * 8;
    [[maybe_unused]] constexpr int g = 0;
    float o[4][4], mx, l = 0.f;
    {
        const uint32_t ka = sb + RS_K + k_frag_off(lane) + (1 + warp) * 2048;
        uint32_t qa[16], kx[16];
        const bool in = mbar_try(sb + RB_KV, s & 1);
        nbar_sync(NB_Q, 256);
        EV(EV_BIG0 && lds32(sb + RS_Q) != 0x12345678u, s, 8);
#pragma unroll
        for (int q = 0; q < 4; q++) ldsm4t(qa + 4 * q, sb + RS_Q + q * 512 + lane * 16);
        if (!in) mbar_wait(sb + RB_KV, s & 1);
#pragma unroll
        for (int q = 0; q < 4; q++) ldsm4t(kx + 4 * q, ka + q * 512);
        const bool vin = mbar_try(sb + RB_VX, s & 1);
        SCHED_FENCE();
        float s0, s1;
        s_tile(qa, kx, s0, s1);
        asm volatile("st.shared.v2.f32 [%0], {%1,%2};" :: "r"(sa + warp * 256), "f"(s0), "f"(s1) : "memory");
        nbar_sync(NB_WG, 128);
        float sc[8];
#pragma unroll
        for (int n = 0; n < 4; n++) { const float2 v = lds64f(sa + n * 256); sc[2 * n] = v.x; sc[2 * n + 1] = v.y; }
        if (!vin) mbar_wait(sb + RB_VX, s & 1);
        mx = quad_max(fmaxf(fmaxf(fmaxf(sc[0], sc[1]), fmaxf(sc[2], sc[3])), fmaxf(fmaxf(sc[4], sc[5]), fmaxf(sc[6], sc[7])))) * SCALE_LOG2E;
        uint32_t vx[16], p[8];
#pragma unroll
        for (int q = 0; q < 4; q++) ldsm4(vx + 4 * q, va + 2048 + (q >> 1) * 4096 + (q & 1) * 256 + v_frag_off(lane));
#pragma unroll
        for (int n = 0; n < 4; n++) {
            const float e0 = ex2(fmaf(sc[2 * n], SCALE_LOG2E, -mx)), e1 = ex2(fmaf(sc[2 * n + 1], SCALE_LOG2E, -mx));
            l += e0 + e1;
            p[2 * n] = pack_bf16(e0, e1); p[2 * n + 1] = __float_as_uint(e0);
        }
#pragma unroll
        for (int n = 0; n < 4; n++) { o[n][0] = o[n][1] = o[n][2] = o[n][3] = 0.f; }
        pv_pair(o, p, vx);
        pv_pair(o, p + 4, vx + 8);
    }
    const uint32_t dst = sb + RS_O + warp * 512 + (lane & 3) * 128 + (lane >> 2) * 16, dl = sb + RS_INV + (lane & 28);
    EV(EV_BIG0, s, 5);
    mbar_wait(sb + RB_V, s & 1);
    uint32_t vm[4], p[2];
    ldsm4(vm, va + lane * 16);
    nbar_sync(NB_XS, 128 + 32);
    EV(EV_BIG0 && lds32(sb + RS_Q) != 0x12345678u, s, 9);
    const float2 sm = lds64f(sa + 1024);
    const float s0 = sm.x, s1 = sm.y;
    const float m = quad_max(fmaxf(mx, fmaxf(s0, s1)));
    const float e0 = ex2(s0 - m), e1 = ex2(s1 - m), f = ex2(mx - m);
    p[0] = pack_bf16(e0, e1); p[1] = __float_as_uint(e0);
#pragma unroll
    for (int n = 0; n < 4; n++) { o[n][0] *= f; o[n][1] *= f; }
    pv_single(o, p, vm);
    l = fmaf(l, f, e0 + e1);
    l = (l + __shfl_xor_sync(0xffffffffu, l, 1)) + (__shfl_xor_sync(0xffffffffu, l, 2) + __shfl_xor_sync(0xffffffffu, l, 3));
    const uint4 u = make_uint4(pack_bf16(o[0][0], o[0][1]), pack_bf16(o[1][0], o[1][1]), pack_bf16(o[2][0], o[2][1]), pack_bf16(o[3][0], o[3][1]));
    st_async128(mapa(dst, 1), u.x, u.y, u.z, u.w, mapa(sb + RB_O, 1));
    st_async128(mapa(dst, 2), u.x, u.y, u.z, u.w, mapa(sb + RB_O, 2));
    st_async32(mapa(dl, 1 + (warp & 1)), __float_as_uint(l), mapa(sb + RB_O, 1 + (warp & 1)));
    sts128(dst, u);
    sts32(dl, __float_as_uint(l));
    __syncwarp();
    if (elect_one()) mbar_arrive(sb + RB_O);
    EV(EV_BIG0, s, 15);
}

DEVI void ta_mask(float* c, int cw, int lane) {
    const int mt = cw >= 3, over = 8 * (cw - 3 * mt - 1) + 2 * (lane & 3) - 16 * mt - (lane >> 2);
    if (over > 0) c[0] = -INFINITY;
    if (over >= 0) c[1] = -INFINITY;
    if (over > 8) c[2] = -INFINITY;
    if (over >= 8) c[3] = -INFINITY;
}
DEVI void ta_scores(uint32_t sb, int seg, int warp, int lane) {
    const int tx = warp == 3 ? 0 : (warp == 2 ? 1 : 4 + 2 * warp), ty = warp == 3 ? 3 : tx + 1;
    const uint32_t qa = sb + RS_QX + ((warp < 2 ? 2 : 0) + ((lane >> 3) & 1)) * 2048 + ((lane >> 4) * 8 + (lane & 7)) * 16;
    const uint32_t ka = sb + RS_K + (warp < 2 ? tx - 3 : tx) * 2048 + lane * 16;
    float x[4] = {0.f, 0.f, 0.f, 0.f}, y[4] = {0.f, 0.f, 0.f, 0.f};
    mbar_wait(sb + RB_QX, seg & 1);
    if (warp < 3) {
#pragma unroll
        for (int j = 0; j < 4; j++) {
            uint32_t a0[4], a1[4], bx[4], by[4];
            ldsm4t(a0, qa + j * 512); ldsm4t(bx, ka + j * 512); ldsm4t(by, ka + 2048 + j * 512); ldsm4t(a1, qa + j * 512 + 256);
            mma16816(x, a0, bx[0], bx[1]); mma16816(y, a0, by[0], by[1]);
            mma16816(x, a1, bx[2], bx[3]); mma16816(y, a1, by[2], by[3]);
        }
        ta_mask(x, tx, lane); ta_mask(y, ty, lane);
    } else {
        mbar_wait(sb + RB_K, seg & 1);
#pragma unroll
        for (int j = 0; j < 4; j++) {
            uint32_t a0[4], a1[4], a2[4], a3[4], b[4];
            ldsm4t(a0, qa + j * 512); ldsm4t(b, ka + j * 512); ldsm4t(a2, qa + 4096 + j * 512);
            ldsm4t(a1, qa + j * 512 + 256); ldsm4t(a3, qa + 4096 + j * 512 + 256);
            mma16816(x, a0, b[0], b[1]); mma16816(y, a2, b[0], b[1]);
            mma16816(x, a1, b[2], b[3]); mma16816(y, a3, b[2], b[3]);
        }
    }
    nbar_sync(NB_WG + 1, 128);
    asm volatile("st.shared.v2.f32 [%0], {%1,%2};" :: "r"(sb + RS_QX + 4096 + tx * 256 + lane * 8), "f"(fmaxf(x[0], x[1])), "f"(fmaxf(x[2], x[3])) : "memory");
    asm volatile("st.shared.v2.f32 [%0], {%1,%2};" :: "r"(sb + RS_QX + 4096 + ty * 256 + lane * 8), "f"(fmaxf(y[0], y[1])), "f"(fmaxf(y[2], y[3])) : "memory");
    nbar_sync(NB_WG + 1, 128);
    float m[4] = {-INFINITY, -INFINITY, -INFINITY, -INFINITY};
#pragma unroll
    for (int n = 0; n < 8; n++) {
        if (n < 3 ? warp >= 2 : warp != 2) {
            const float2 v = lds64f(sb + RS_QX + 4096 + n * 256 + lane * 8);
            m[n < 3 ? 0 : 2] = fmaxf(m[n < 3 ? 0 : 2], v.x); m[n < 3 ? 1 : 3] = fmaxf(m[n < 3 ? 1 : 3], v.y);
        }
    }
#pragma unroll
    for (int o = 1; o < 4; o <<= 1) {
#pragma unroll
        for (int i = 0; i < 4; i++) m[i] = fmaxf(m[i], __shfl_xor_sync(0xffffffffu, m[i], o));
    }
    const float x0 = (warp < 2 ? m[2] : m[0]) * -SCALE_LOG2E, x1 = (warp < 2 ? m[3] : m[1]) * -SCALE_LOG2E;
    const float y0 = (warp == 2 ? m[0] : m[2]) * -SCALE_LOG2E, y1 = (warp == 2 ? m[1] : m[3]) * -SCALE_LOG2E;
    sts64(sb + RS_QX + tx * 256 + lane * 8, pack_bf16(ex2(fmaf(x[0], SCALE_LOG2E, x0)), ex2(fmaf(x[1], SCALE_LOG2E, x0))),
                                            pack_bf16(ex2(fmaf(x[2], SCALE_LOG2E, x1)), ex2(fmaf(x[3], SCALE_LOG2E, x1))));
    sts64(sb + RS_QX + ty * 256 + lane * 8, pack_bf16(ex2(fmaf(y[0], SCALE_LOG2E, y0)), ex2(fmaf(y[1], SCALE_LOG2E, y0))),
                                            pack_bf16(ex2(fmaf(y[2], SCALE_LOG2E, y1)), ex2(fmaf(y[3], SCALE_LOG2E, y1))));
}
template <int MT>
DEVI void ta_output(uint32_t sb, int seg, int head, int j, int lane) {
    const uint32_t pa = sb + RS_QX + MT * 768 + lane * 8, vb = sb + RS_V + j * 512;
    uint32_t p[6 + 4 * MT], v[12 + 8 * MT];
#pragma unroll
    for (int n = 0; n < 3 + 2 * MT; n++)
        asm volatile("ld.shared.v2.u32 {%0,%1}, [%2];" : "=r"(p[2 * n]), "=r"(p[2 * n + 1]) : "r"(pa + n * 256) : "memory");
#pragma unroll
    for (int q = 0; q < 2 + 2 * MT; q++) ldsm4(v + 4 * q, vb + (q >> 1) * 4096 + (q & 1) * 256 + v_frag_off(lane));
    ldsm4(v + 8 + 8 * MT, vb + 4096 + MT * 4096 + lane * 16);
    float o[4][4], l[4] = {0.f, 0.f, 0.f, 0.f};
#pragma unroll
    for (int n = 0; n < 4; n++) { o[n][0] = o[n][1] = o[n][2] = o[n][3] = 0.f; }
    mma16816(l, p, 0x3F803F80u, 0x3F803F80u);
    pv_pair(o, p, v);
    if (MT) { mma16816(l, p + 4, 0x3F803F80u, 0x3F803F80u); pv_pair(o, p + 4, v + 8); }
    mma1688(l, p[4 + 4 * MT], p[5 + 4 * MT], 0x3F803F80u);
    pv_single(o, p + 4 + 4 * MT, v + 8 + 8 * MT);
    const float i0 = rcp_fast(l[0]), i1 = rcp_fast(l[2]);
    bf16* dst = g_ox + (uint32_t)((seg * 32 + MT * 16 + (lane >> 2)) * HD + head * DH + j * 32 + (lane & 3) * 8);
    asm volatile("st.global.v4.u32 [%0], {%1,%2,%3,%4};" :: "l"(dst), "r"(pack_bf16(o[0][0] * i0, o[0][1] * i0)), "r"(pack_bf16(o[1][0] * i0, o[1][1] * i0)),
                 "r"(pack_bf16(o[2][0] * i0, o[2][1] * i0)), "r"(pack_bf16(o[3][0] * i0, o[3][1] * i0)) : "memory");
    asm volatile("st.global.v4.u32 [%0], {%1,%2,%3,%4};" :: "l"(dst + 8 * HD), "r"(pack_bf16(o[0][2] * i1, o[0][3] * i1)), "r"(pack_bf16(o[1][2] * i1, o[1][3] * i1)),
                 "r"(pack_bf16(o[2][2] * i1, o[2][3] * i1)), "r"(pack_bf16(o[3][2] * i1, o[3][3] * i1)) : "memory");
}

template <bool XP>
DEVI void big_main(const uint32_t* w, const uint32_t sb, const int g, const int warp, const uint32_t rank, const int head,
                   const CUtensorMap* tmX, const bf16* xg, const unsigned E) {
    float xa[32];
    uint32_t a[16];
    const uint32_t aB = __shfl_sync(0xffffffffu, sb + RS_MEM + (g * 32 + (tid_now() & 31)) * 16, tid_now() & 31);
#define lane0 ((int)(opaque(aB) >> 4) & 31)
    const uint32_t aA0 = sb + RS_WSS + g * (8192 + 4096) + a_frag_off(lane0, warp);
    const uint32_t aBf = sb + RS_MEM + g * 512 + b_frag_off(lane0);
    if constexpr (XP) {
        mbar_wait(sb + RB_XF + g * 8, 0);
        x_first(xa, w, sb, 0, g, warp, tmX);
        x_second(xa, a, aA0, w, sb, 0, g, warp, tmX);
        x_finish(xa, sb, 0, g, warp, lane0, tmX);
    }
    nbar_sync(NB_BIG, 256);
    for (int s = 0; s < NSEG; s++) {
        float c0[4], c1[4];
        mem_pass<XP>(c0, c1, a, w, sb, aA0, aBf, g, warp, s);
        EV(EV_BIG0 && c0[0] != 1.2345e30f, s, 3);
        const uint32_t xs = sb + RS_O + warp * 256 + lane0 * 8;
        sts64(xs + g * 1024, pack_bf16(c1[0], c1[1]), pack_bf16(c1[2], c1[3]));
        {
            const uint32_t d = sb + (XP ? (rank == 1 ? RS_K : RS_V) : RS_Q) + (g * 4 + warp) * 256 + lane0 * 4;
            const uint32_t rbar = XP ? mapa(sb + (rank == 1 ? RB_K : RB_V), 0) : 0u;
            nbar_sync(NB_PAIR + warp, 64);
            const float2 v = lds64f(xs + (g ^ 1) * 1024);
            const uint32_t v0 = __float_as_uint(v.x), v1 = __float_as_uint(v.y);
            const uint32_t p0 = pack_bf16(c0[0] + __uint_as_float(v0 << 16), c0[1] + __uint_as_float(v0 & 0xFFFF0000u));
            const uint32_t p1 = pack_bf16(c0[2] + __uint_as_float(v1 << 16), c0[3] + __uint_as_float(v1 & 0xFFFF0000u));
            if constexpr (XP) { st_async32(mapa(d, 0), p0, rbar); st_async32(mapa(d + 128, 0), p1, rbar); }
            else { sts32(d, p0); sts32(d + 128, p1); }
            EV(EV_BIG0, s, 4);
        }
        if constexpr (XP) {
            if (s == NSEG - 1) break;
            x_first(xa, w, sb, s + 1, g, warp, tmX);
            EV(EV_BIG0, s, 5);
            EVCAL(s);
            nbar_sync(NB_WO, 384);
            EV(EV_BIG0 && lds32(sb + RS_O) != 0x12345678u, s, 6);
            x_second(xa, a, aA0, w, sb, s + 1, g, warp, tmX);
            EV(EV_BIG0, s, 7);
            x_finish(xa, sb, s + 1, g, warp, lane0, tmX);
        } else {
            if (g == 0) {
                if (s < NSEG - 1) mem_attn(sb, s, warp, lane0);
            } else {
                if (s < NSEG - 1) { if (warp == 3) mem_scores(sb, s, lane0); else nbar_arrive(NB_Q, 256); }
                mbar_wait(sb + RB_KV, s & 1);
                if (s == 0 && warp == 0) {
                    wait_count_warp(&g_cnt[C_QH], 64 * E);
                    if (elect_one()) {
                        fence_proxy_global();
                        mbar_expect_tx(sb + RB_QX, 8192);
                        bulk_load(sb + RS_QX, g_qx + (uint32_t)(head * 4096), 8192, sb + RB_QX);
                    }
                    __syncwarp();
                }
                ta_scores(sb, s, warp, lane0);
            }
            EVCAL(s);
            mbar_wait(sb + RB_V, s & 1);
            mbar_wait(sb + RB_VX, s & 1);
            if (s < NSEG - 1) nbar_sync(NB_WO, 384); else nbar_sync(NB_BIG, 256);
            EV(EV_BIG0 && lds32(sb + RS_O) != 0x12345678u, s, 6);
            if (g == 0) ta_output<0>(sb, s, head, warp, lane0); else ta_output<1>(sb, s, head, warp, lane0);
            nbar_sync(NB_BIG, 256);
            EV(EV_BIG0 && lds32(sb + RS_O) != 0x12345678u, s, 7);
            if (g == 0 && warp == 0 && s + 1 < NSEG) {
                if (elect_one()) {
                    mbar_arrive_remote(mapa(sb + RB_ATT, 1));
                    mbar_arrive_remote(mapa(sb + RB_ATT, 2));
                    mbar_expect_tx(sb + RB_KV, 8192);
                    mbar_expect_tx(sb + RB_K, 2048);
                    mbar_expect_tx(sb + RB_V, 2048); mbar_expect_tx(sb + RB_VX, 8192);
                    mbar_arrive(sb + RB_T);
                }
                __syncwarp();
            }
        }
    }
    if constexpr (!XP) { if (tid_now() == 0) signal_count(&g_prog[(NSEG - 1) >> 2]); }
#undef lane0
}

template <int T, int K0, int K1>
DEVI void wo_part(float* acc) {
    constexpr uint32_t dWo = cdesc(T < 5 ? RS_WO + T * 16384 : RS_WO5, 16), dO = cdesc(RS_O, 128);
#pragma unroll
    for (int kk = K0; kk < K1; kk++) {
        if (kk == 0) { if (T < 3) wgmma_n8_ss_first<0>(acc, dWo, dO); else wgmma_n8_ss<0, 0>(acc, dWo, dO); }
        else wgmma_n8_ss<0, 1>(acc, dWo + kk * 128, dO + kk * 16);
    }
    wg_commit();
}
DEVI void red3(uint8_t* p, uint32_t a, uint32_t b, uint32_t c, uint32_t one) {
    asm volatile("red.relaxed.gpu.global.add.noftz.v4.bf16x2 [%0], {%1,%2,%3,%4};" :: "l"(p), "r"(a), "r"(b), "r"(c), "r"(one) : "memory");
}
constexpr int ACC_CH = 3 * 16 * 1024;
template <bool Q>
DEVI void wo_phase(uint32_t sb, int s, int warp, uint8_t* p, uint32_t ainv, int gap) {
    float a0[4], a1[4], a2[4];
    fence_proxy_async();
    const float2 iv = lds64f(ainv);
    SCHED_FENCE();
    const float i0 = rcp_fast(iv.x), i1 = rcp_fast(iv.y);
#define WORD(a, h) pack_bf16(a[2 * h] * i0, a[2 * h + 1] * i1)
    wg_fence();
    wo_part<0, 0, 8>(a0); wo_part<1, 0, 8>(a1); wo_part<2, 0, 8>(a2);
    wg_wait<1>(); reg_fence<4>(a0); reg_fence<4>(a1);
    red3(p, WORD(a0, 0), WORD(a0, 1), WORD(a1, 0), 0x3F80u);
    SCHED_FENCE();
    EV(warp == 0 && elect_one(), s, 11);
    wg_wait<0>(); reg_fence<4>(a2);
    red3(p + ACC_CH, WORD(a2, 0), WORD(a2, 1), WORD(a1, 1), 0x3F80u);
    SCHED_FENCE();
    { const uint32_t t = clk32() + gap; while ((int)(clk32() - t) < 0) { } }
    wg_fence();
    wo_part<3, 0, 8>(a0); wo_part<4, 0, 8>(a1);
    if (Q) {
        wo_part<5, 0, 8>(a2);
        wg_wait<1>(); reg_fence<4>(a0); reg_fence<4>(a1);
        red3(p + 2 * ACC_CH, WORD(a0, 0), WORD(a0, 1), WORD(a1, 0), 0x3F80u);
        SCHED_FENCE();
        wg_wait<0>(); reg_fence<4>(a2);
        red3(p + 3 * ACC_CH, WORD(a2, 0), WORD(a2, 1), WORD(a1, 1), 0x3F80u);
        nbar_arrive(NB_WO, 384);
    } else {
        wg_wait<1>();
        nbar_arrive(NB_WO, 384);
        wg_wait<0>(); reg_fence<4>(a0); reg_fence<4>(a1);
        red3(p + 2 * ACC_CH, WORD(a0, 0), WORD(a0, 1), WORD(a1, 0), 0x3F80u);
        red3(p + 3 * ACC_CH, 0u, 0u, WORD(a1, 1), 0x3F80u);
    }
#undef WORD
}
DEVI void unit_pack(uint32_t* u, uint32_t x0, uint32_t x1, uint32_t x2, uint32_t x3) {
    u[0] = __byte_perm(x0, x1, 0x5410); u[1] = __byte_perm(x2, x3, 0x5410); u[2] = __byte_perm(x0, x1, 0x7632); u[3] = __byte_perm(x2, x3, 0x7632);
}
DEVI void unit_send(uint32_t d, const uint32_t* u, uint32_t bar, uint32_t r1, uint32_t r2) {
    st_async128(mapa(d, r1), u[0], u[1], u[2], u[3], mapa(bar, r1));
    st_async128(mapa(d, r2), u[0], u[1], u[2], u[3], mapa(bar, r2));
}
template <bool Q>
DEVI void stage_sums(uint32_t sb, int s, uint32_t rank, int warp, const uint8_t* src, uint32_t l, uint32_t gate) {
    uint4 v[4];
    while ((int)(clk32() - gate) < 0) { }
    EV(elect_one(), s, 16 + warp);
#pragma unroll
    for (int j = 0; j < 4; j++) v[j] = ld_rlx4(src + j * 1024);
    const uint32_t col = sb + RS_MEM + ((Q ? 0 : (rank == 1 ? 6 : 11)) + 3 * (warp >> 1)) * 1024 + ((l >> 2) & 0x300) + (l & 0x70);
    const uint32_t d0 = col + (warp & 1) * 2048, d1 = d0 ^ 160, d2 = (col ^ ((warp & 1) * 160)) + 1024;
    const uint32_t r1 = Q ? 1 : 0, r2 = Q ? 2 : 3 - rank, bar = sb + RB_G + 8 * (warp < 2 ? warp : 2);
    int n = 0;
    while (!__all_sync(0xffffffffu, v[0].w == 0x4200u && v[1].w == 0x4200u && v[2].w == 0x4200u && v[3].w == 0x4200u)) {
#pragma unroll
        for (int j = 0; j < 4; j++) v[j] = ld_rlx4(src + j * 1024);
        if (++n > SPIN_LIMIT) TRAP(0x20000000u | (s << 8) | warp);
    }
    EV(elect_one(), s, 24 + warp);
    uint32_t u[12];
    unit_pack(u + 8, v[0].z, v[1].z, v[2].z, v[3].z);
    unit_send(d2, u + 8, bar, r1, r2);
    if (Q || warp < 3) {
        unit_pack(u, v[0].x, v[1].x, v[2].x, v[3].x);
        unit_pack(u + 4, v[0].y, v[1].y, v[2].y, v[3].y);
        unit_send(d0, u, bar, r1, r2);
        unit_send(d1, u + 4, bar, r1, r2);
        sts128(d0, make_uint4(u[0], u[1], u[2], u[3]));
        sts128(d1, make_uint4(u[4], u[5], u[6], u[7]));
    }
    sts128(d2, make_uint4(u[8], u[9], u[10], u[11]));
    __syncwarp();
    if (elect_one()) mbar_expect_tx(bar, warp < 2 ? 3072u : (warp == 3 ? 0u : (Q ? 4096u : 5120u)));
    EV(elect_one(), s, 20 + warp);
}
DEVI void wo_permute(uint32_t tile, int t) {
    const uint32_t a = tile + t * 32 + ((t >> 2) & 1) * 16;
#pragma unroll
    for (int h = 0; h < 2; h++) {
        uint4 v[3], u[3];
#pragma unroll
        for (int i = 0; i < 3; i++) if (3 * h + i < 5 || t < 32) { v[i] = lds128(a + (3 * h + i) * 3072); u[i] = lds128((a ^ 16) + (3 * h + i) * 3072); }
#pragma unroll
        for (int i = 0; i < 3; i++) if (3 * h + i < 5 || t < 32) {
            sts128(a + (3 * h + i) * 3072, make_uint4(__byte_perm(v[i].x, v[i].y, 0x5410), __byte_perm(v[i].x, v[i].y, 0x7632),
                                                      __byte_perm(u[i].x, u[i].y, 0x5410), __byte_perm(u[i].x, u[i].y, 0x7632)));
            sts128((a ^ 16) + (3 * h + i) * 3072, make_uint4(__byte_perm(v[i].z, v[i].w, 0x5410), __byte_perm(v[i].z, v[i].w, 0x7632),
                                                             __byte_perm(u[i].z, u[i].w, 0x5410), __byte_perm(u[i].z, u[i].w, 0x7632)));
        }
    }
}
DEVI uint32_t acc_clear(int slot, int idx, uint32_t lo) {
    uint8_t* p = g_acc + (uint32_t)(slot * 128 + idx * 3072 + (lo < 3072 ? lo : lo - 1024));
    st_rlx4(p, 0u, 0u, 0u, 0u);
    uint32_t z; asm volatile("ld.relaxed.gpu.global.u32 %0, [%1];" : "=r"(z) : "l"(p) : "memory");
    return z;
}

template <bool Q>
DEVI void aux_main(uint32_t sb, int warp, uint32_t rank, int head, const CUtensorMap* tmX, const bf16* xg, unsigned E, const int delay, const int gap, const int vdelay) {
    const uint32_t lo = __shfl_sync(0xffffffffu, ((tid_now() >> 3) & 3) * 1024 + (tid_now() & 7) * 16, tid_now() & 31);
    for (int s = 0; s < NSEG - 1; s++) {
        if (!Q && warp == 0 && elect_one()) mbar_expect_tx(sb + RB_O, 2048 + 256);
        __syncwarp();
        const uint32_t slot = (s & 3) * 128;
        mbar_wait(sb + RB_O, s & 1);
        EV(warp == 0 && elect_one(), s, 10);
        wo_phase<Q>(sb, s, warp, g_acc + (uint32_t)(slot + (rank * 4 + warp) * 4096 + opaque(lo)), sb + RS_INV + ((opaque(lo) >> 1) & 24), gap);
        SCHED_FENCE();
        const uint32_t t_o = clk32();
        EV(warp == 0 && elect_one(), s, 12);
        {
            const uint32_t l = opaque(lo);
            stage_sums<Q>(sb, s, rank, warp, g_acc + (uint32_t)(slot + rank * 16384 + warp * ACC_CH + (l & 0xC00) * 4 + (l & 0x70)), l, t_o + delay);
        }
        EV(warp == 2 && elect_one(), s, 14);
        if (warp == 3) {
            if (Q) {
                mbar_wait(sb + RB_T, s & 1);
                if (s == 3) wait_count_warp(&g_cnt[C_Q], 64 * E);
                if (elect_one()) {
                    if (s == 3) fence_proxy_global();
                    fence_proxy_async();
                    mbar_expect_tx(sb + RB_QX, 8192);
                    bulk_load(sb + RS_QX, g_qx + (uint32_t)(((s + 1) * NH + head) * 4096), 8192, sb + RB_QX);
                    if (head == 0) { TLOG(1400 + s, 0, gtime()); TLOG(1400 + s, 1, clock64()); }
                }
                __syncwarp();
                const bool fresh = (s & 7) == 6 && s + 2 < NSEG;
                if (fresh) wait_count_warp(&g_cnt[C_Q + ((s + 2) >> 3)], 64 * E);
                if (elect_one()) {
                    if (fresh) fence_proxy_global();
                    if (s + 2 < NSEG && s != 2) l2_prefetch(g_qx + (uint32_t)(((s + 2) * NH + head) * 4096), 8192);
                    if (s + 4 < NSEG) l2_prefetch(xg + (uint32_t)(((s + 4) * 32 + head) * DM), 2048);
                    signal_count(&g_prog[s >> 2]);
                }
                __syncwarp();
            } else {
                const uint32_t zero = acc_clear((s + 2) & 3, 2 * head + (int)rank - 1, opaque(lo));
                mbar_wait(sb + RB_G + 16, s & 1);
                x_send(sb, s + 1, rank, vdelay);
                if (__any_sync(0xffffffffu, zero != 0u)) __trap();
            }
        }
    }
}

DEVI void load_weights(uint32_t sb, const CUtensorMap* tmW, const CUtensorMap* tmWo, int head, uint32_t rank, int2 t0) {
    const uint32_t c0 = clk32();
    if (rank == 0) while ((int)(clk32() - c0) < t0.x) { }
    const uint32_t bW = sb + RB_W, bSF = sb + RB_SF, bSE = sb + RB_SE;
    const int tile0 = rank == 0 ? 0 : (rank == 1 ? 6 : 11);
    mbar_expect_tx(bW, R_NSS * 16384);
    for (int pass = 0; pass < 2; pass++) {
        for (int pos = 0; pos < 16; pos++) {
            const int k = (int)((R_TORD_PACK >> (4 * pos)) & 15ull) * 64, rd = pos - pos / 3, slot = rd % 5;
            if (r_pos_ss(pos)) {
                if (pass) continue;
                const uint32_t dst = sb + RS_WSS + (pos / 3) * 16384;
                tma_load_2d(dst, tmW, head * DH, k, bW);
                tma_load_2d(dst + 8192, tmW, head * DH + 64, k, bW);
            } else if (pass == (rd >= 5)) {
                if (rd >= 5) mbar_wait(bSE + 8 * slot, ((rd / 5) - 1) & 1);
                mbar_expect_tx(bSF + 8 * slot, 16384);
                const uint32_t dst = sb + RS_WO + slot * 16384;
                tma_load_2d(dst, tmW, head * DH, k, bSF + 8 * slot);
                tma_load_2d(dst + 8192, tmW, head * DH + 64, k, bSF + 8 * slot);
            }
        }
    }
    while ((int)(clk32() - c0) < t0.y) { }
    if (rank == 0) { mbar_expect_tx(sb + RB_WO, 16384); tma_load_wo(sb + RS_WO5, tmWo, 5 * 64, head * 4, sb + RB_WO); }
    for (int i = 1; i <= 5; i++) {
        const int slot = i % 5, last = slot + 10 < R_NRS ? slot + 10 : slot + 5;
        mbar_wait(bSE + 8 * slot, (last / 5) & 1);
        mbar_expect_tx(bSF + 8 * slot, 16384);
        tma_load_wo(sb + RS_WO + slot * 16384, tmWo, (tile0 + slot) * 64, head * 4, bSF + 8 * slot);
    }
}
template <bool XP>
DEVI void big_prologue(uint32_t* w, uint32_t sb, int g, int warp, const bf16* __restrict__ mem0) {
    const int tid = tid_now(), lane = tid & 31;
    {
        const uint32_t* m = (const uint32_t*)(mem0 + (lane >> 2) * DM + (tid >> 5) * 16) + (lane & 3);
        uint32_t u[16];
#pragma unroll
        for (int j = 0; j < 8; j++) { u[2 * j] = m[j * 64]; u[2 * j + 1] = m[j * 64 + 4]; }
#pragma unroll
        for (int j = 0; j < 8; j++) sts64(sb + RS_MEM + ((tid >> 5) + j * 8) * 256 + b_frag_off(lane), u[2 * j], u[2 * j + 1]);
    }
    const uint32_t a0 = sb + RS_WO + g * (8192 + 4096) + a_frag_off(lane, warp), a1 = a0 + 8192 - g * 16384;
#pragma unroll
    for (int rd = 0; rd < R_NRS; rd++) {
        const int slot = rd % 5;
        mbar_wait(sb + RB_SF + 8 * slot, (rd / 5) & 1);
#pragma unroll
        for (int q = 0; q < 4; q++) {
            if (XP && rd == 0 && q == 3) {
                sts128(sb + RS_WX + g * 2048 + (tid & 127) * 16, lds128(sb + RS_WO + 8192 - g * 4096 + 2048 + (tid & 127) * 16));
                fence_proxy_async();
                nbar_sync(NB_WG + g, 128);
            } else ldsm4t(&w[rd * 16 + q * 4], ((q & 1) ? a1 : a0) + slot * 16384 + (q >> 1) * 2048);
        }
        mbar_arrive(sb + RB_SE + 8 * slot);
    }
    mbar_wait(sb + RB_W, 0);
    if (tid == 0) TLOG(1500 + blockIdx.x, 2, gtime());
}

#define REC_END() do { if (tid_now() == 0) TLOG(1024 + blockIdx.x, 1, gtime()); } while (0)
struct XMaps { CUtensorMap m[2]; };
__global__ void __launch_bounds__(384, 1)
k_rec(const __grid_constant__ PMaps mp, const __grid_constant__ CUtensorMap tmWk, const __grid_constant__ CUtensorMap tmWv,
      const __grid_constant__ CUtensorMap tmWo, const __grid_constant__ XMaps xm, const bf16* __restrict__ mem0, const bf16* __restrict__ xg,
      int4 tq, int4 tk, int2 t0, int rec) {
    extern __shared__ __align__(1024) uint8_t smem_raw[];
    const uint32_t sb = smem_u32(smem_raw);
    if ((sb & 0x3FFFFu) != SB0) __trap();
    const int tid = threadIdx.x;
    const int wg = __shfl_sync(0xffffffffu, tid >> 7, 0), warp = __shfl_sync(0xffffffffu, (tid >> 5) & 3, 0);
    uint32_t rank; asm("mov.u32 %0, %%cluster_ctarank;" : "=r"(rank));
    int head; asm("mov.u32 %0, %%clusterid.x;" : "=r"(head));
    asm volatile("griddepcontrol.launch_dependents;");
    if (tid == 0 && rec) {
        mbar_init(sb + RB_G, 1);
        mbar_init(sb + RB_G + 8, 1);
        mbar_init(sb + RB_G + 16, 2);
        mbar_init(sb + RB_T, 1); mbar_init(sb + RB_VX, 1); mbar_init(sb + RB_WO, 1);
        mbar_init(sb + RB_K, 1); mbar_init(sb + RB_V, 1); mbar_init(sb + RB_KV, 1); mbar_init(sb + RB_QX, 1);
        mbar_init(sb + RB_O, rank == 0 ? 4 : 1); mbar_init(sb + RB_ATT, 1); mbar_init(sb + RB_W, 1);
        for (int i = 0; i < 5; i++) { mbar_init(sb + RB_SF + 8 * i, 1); mbar_init(sb + RB_SE + 8 * i, 256); }
        for (int i = 0; i < 2; i++) mbar_init(sb + RB_XF + 8 * i, X_SLOTS);
        fence_mbar_init();
        if (rank == 0) { mbar_expect_tx(sb + RB_KV, 8192); mbar_expect_tx(sb + RB_K, 2048); mbar_expect_tx(sb + RB_V, 2048); mbar_expect_tx(sb + RB_VX, 8192); }
    }
    __syncthreads();
    asm volatile("barrier.cluster.arrive.release.aligned;" ::: "memory");

    if (wg < 2) {
        reg_inc<REG_KB>();
        if (rank != 0) {
            uint32_t w[R_NRS * 16];
            if ((tid & 127) == 0) for (int j = 0; j < X_SLOTS; j++) x_load(sb, 0, j, wg, xm.m);
            __syncwarp();
            cluster_wait();
            big_prologue<true>(w, sb, wg, warp, mem0);
            big_main<true>(w, sb, wg, warp, rank, head, xm.m, xg, 0u);
            REC_END();
        } else if (rec) {
            uint32_t w[R_NRS * 16];
            cluster_wait();
            big_prologue<false>(w, sb, wg, warp, mem0);
            big_main<false>(w, sb, wg, warp, rank, head, xm.m, xg, *(volatile unsigned*)&g_epoch + 1);
            REC_END();
        } else cluster_wait();
        nbar_sync(0, 384);
        nbar_sync(0, 384);
        post_consumer(mp, sb, wg, warp);
    } else {
        reg_dec<504 - 2 * REG_KB>();
        if (rec) {
            if (tid == 256) {
                if (rank == 0) l2_prefetch(xg + (uint32_t)(head * 8 * DM), 16384);
                load_weights(sb, rank == 0 ? &mp.wq : (rank == 1 ? &tmWk : &tmWv), &tmWo, head, rank, t0);
            }
            if (warp == 3 && rank != 0) {
                const uint32_t lo = ((tid >> 3) & 3) * 1024 + (tid & 7) * 16;
                acc_clear(0, 2 * head + (int)rank - 1, lo); acc_clear(1, 2 * head + (int)rank - 1, lo);
                __threadfence();
                __syncwarp();
                if (tid == 256 + 96) atomicAdd(&g_zero, 1u);
            }
            __syncwarp();
        }
        cluster_wait();
        const unsigned E = __shfl_sync(0xffffffffu, *(volatile unsigned*)&g_epoch + 1, 0);
        if (rec) {
            if (warp == 1) wait_count_warp(&g_zero, E * 64u);
            if (warp == 3) { if (rank != 0) x_send(sb, 0, rank, 0); }
            else {
                nbar_sync(NB_PRO, 96);
#pragma unroll 1
                for (int i = rank == 0 ? 0 : 1; i <= 5; i++) {
                    mbar_wait(sb + (i == 0 ? RB_WO : RB_SF + 8 * (i % 5)), i == 5);
                    if (i == 5 && tid == 288) TLOG(1500 + blockIdx.x, 0, gtime());
                    wo_permute(sb + (i == 0 ? RS_WO5 : RS_WO + (i % 5) * 16384), tid & 127);
                }
            }
            fence_proxy_async();
            nbar_sync(NB_AUX, 128);
            if (tid == 288) { TLOG(1500 + blockIdx.x, 1, gtime()); }
            if (rank == 0) aux_main<true>(sb, warp, rank, head, xm.m, xg, E, warp == 0 ? tq.x : (warp == 1 ? tq.y : tq.z), tq.w, 0);
            else           aux_main<false>(sb, warp, rank, head, xm.m, xg, E, warp == 0 ? tk.x : (warp == 1 ? tk.y : tk.z), tq.w, tk.w);
        }
        const int t = tid_now();
        int id = 0;
        if (t >= 288 && t < 288 + 13) asm volatile("prefetch.tensormap [%0];" :: "l"(&mp.wq + (t - 288)) : "memory");
        if (warp == 0 && rank != 0) id = post_claim(mp, E);
        nbar_sync(0, 384);
        if (warp == 0) { if (elect_one()) post_init(sb); fence_proxy_async(); }
        __syncwarp();
        nbar_sync(0, 384);
        if (warp == 0) post_producer(mp, sb, E, rank != 0 ? id : post_claim(mp, E));
        else if (t == 288 || t == 320) post_helper(sb, warp - 1);
    }
    __syncthreads();
    asm volatile("griddepcontrol.wait;" ::: "memory");
}

typedef CUresult (*EncodeFn)(CUtensorMap*, CUtensorMapDataType, cuuint32_t, void*, const cuuint64_t*, const cuuint64_t*,
                             const cuuint32_t*, const cuuint32_t*, CUtensorMapInterleave, CUtensorMapSwizzle,
                             CUtensorMapL2promotion, CUtensorMapFloatOOBfill);

static CUtensorMap make_map(EncodeFn fn, const void* ptr, uint64_t inner, uint64_t outer, uint32_t box_inner, uint32_t box_outer) {
    CUtensorMap m;
    cuuint64_t dims[2] = {inner, outer};
    cuuint64_t strides[1] = {inner * 2};
    cuuint32_t box[2] = {box_inner, box_outer};
    cuuint32_t es[2] = {1, 1};
    fn(&m, CU_TENSOR_MAP_DATA_TYPE_BFLOAT16, 2, const_cast<void*>(ptr), dims, strides, box, es,
       CU_TENSOR_MAP_INTERLEAVE_NONE, CU_TENSOR_MAP_SWIZZLE_128B, CU_TENSOR_MAP_L2_PROMOTION_L2_256B, CU_TENSOR_MAP_FLOAT_OOB_FILL_NONE);
    return m;
}

static CUtensorMap make_wo_map(EncodeFn fn, const void* ptr, uint64_t rows, uint32_t ngrp) {
    CUtensorMap m;
    cuuint64_t dims[5] = {DM, 2, 4, 4, rows / 32};
    cuuint64_t strides[4] = {DM * 2, 8 * DM * 2, 2 * DM * 2, 32 * DM * 2};
    cuuint32_t box[5] = {64, 2, 4, 4, ngrp};
    cuuint32_t es[5] = {1, 1, 1, 1, 1};
    fn(&m, CU_TENSOR_MAP_DATA_TYPE_BFLOAT16, 5, const_cast<void*>(ptr), dims, strides, box, es,
       CU_TENSOR_MAP_INTERLEAVE_NONE, CU_TENSOR_MAP_SWIZZLE_128B, CU_TENSOR_MAP_L2_PROMOTION_L2_256B, CU_TENSOR_MAP_FLOAT_OOB_FILL_NONE);
    return m;
}

struct Maps {
    PMaps post;
    CUtensorMap wk16, wv16, wo128;
    XMaps x32;
};

extern "C" void kernel_launch(void* const* d_in, const int* in_sizes, int n_in, void* d_out, int out_size) {
    const bf16* A_x   = (const bf16*)d_in[0];
    const bf16* A_mem = (const bf16*)d_in[1];
    const bf16* A_Wq  = (const bf16*)d_in[2];
    const bf16* A_Wk  = (const bf16*)d_in[3];
    const bf16* A_Wv  = (const bf16*)d_in[4];
    const bf16* A_Wo  = (const bf16*)d_in[5];
    const bf16* B_x   = (const bf16*)d_in[7];
    const bf16* B_w   = (const bf16*)d_in[8];
    const bf16* B_wo  = (const bf16*)d_in[9];

    static EncodeFn fn = nullptr;
    static Maps mp;
    static const void* cached[10];
    const void* cur[10] = {A_x, A_mem, A_Wq, A_Wk, A_Wv, A_Wo, B_x, B_w, B_wo, d_out};
    bool same = fn != nullptr;
    for (int i = 0; i < 10 && same; i++) same = cached[i] == cur[i];
    if (!same) {
        if (!fn) {
            void* p = nullptr; cudaDriverEntryPointQueryResult qr;
            cudaGetDriverEntryPoint("cuTensorMapEncodeTiled", &p, cudaEnableDefault, &qr);
            fn = (EncodeFn)p;
            cudaFuncSetAttribute(k_rec, cudaFuncAttributeMaxDynamicSharedMemorySize, R_SMEM);
        }
        void *p_ox, *p_bqkv, *p_bo, *p_qx;
        cudaGetSymbolAddress(&p_qx, g_qx);
        cudaGetSymbolAddress(&p_ox, g_ox); cudaGetSymbolAddress(&p_bqkv, g_bqkv); cudaGetSymbolAddress(&p_bo, g_bo);
        mp.post.wq   = make_map(fn, A_Wq, HD, DM, 64, 64);
        mp.post.wo   = make_wo_map(fn, A_Wo, HD, 2);
        mp.post.bw   = make_map(fn, B_w, 3 * DM, DM, 64, 64);
        mp.post.bwo  = make_wo_map(fn, B_wo, DM, 2);
        mp.post.x    = make_map(fn, A_x, DM, S_TOK, 64, 128);
        mp.post.bx   = make_map(fn, B_x, DM, S_TOK, 64, 128);
        mp.post.bo   = make_map(fn, p_bo, DM, S_TOK, 64, 128);
        mp.post.ox   = make_map(fn, p_ox, HD, S_TOK, 64, 128);
        mp.post.ox64 = make_map(fn, p_ox, HD, S_TOK, 64, 64);
        mp.post.cb   = make_map(fn, p_bqkv, 3 * DM, S_TOK, 64, 64);
        mp.post.cout = make_map(fn, d_out, 2 * DM, S_TOK, 64, 64);
        {
            cuuint64_t dims[4] = {256, 4, NH * 4, NSEG};
            cuuint64_t strides[3] = {512, 2048, NH * 8192};
            cuuint32_t box[4] = {256, 2, 4, 2};
            cuuint32_t es[4] = {1, 1, 1, 1};
            fn(&mp.post.cq, CU_TENSOR_MAP_DATA_TYPE_BFLOAT16, 4, p_qx, dims, strides, box, es,
               CU_TENSOR_MAP_INTERLEAVE_NONE, CU_TENSOR_MAP_SWIZZLE_NONE, CU_TENSOR_MAP_L2_PROMOTION_NONE, CU_TENSOR_MAP_FLOAT_OOB_FILL_NONE);
        }
        {
            int runs[48] = {K_QH, 0, 2, K_Q, 1, 7, K_B1, 0, 8, K_A4, 0, 4, K_B2, 0, 32, K_A4, 4, 2, K_B3, 0, 4, K_A3, 12, 1, K_B3, 4, 1, K_A3, 13, 1,
                            K_B3, 5, 3, K_SN, 28, 4, -1};
            const int per[9] = {32, 24, 8, 8, 32, 8, 8 * P_SPLIT, 1, 8 * P_SPLIT};
            int n = 0, id = 0;
            for (; runs[3 * n] >= 0; n++) {
                mp.post.list.run[n] = make_int4(runs[3 * n], runs[3 * n + 1], id, id + runs[3 * n + 2] * per[runs[3 * n]]);
                id = mp.post.list.run[n].w;
            }
            mp.post.list.n = n;
            int dev = 0, nsm = 132;
            cudaGetDevice(&dev);
            cudaDeviceGetAttribute(&nsm, cudaDevAttrMultiProcessorCount, dev);
            mp.post.list.nworker = nsm > 96 ? nsm : 97;
        }
        {
            cuuint64_t dims[4] = {DM, 3, 2, S_TOK / 2};
            cuuint64_t strides[3] = {DM * 2, 3 * DM * 2, 3 * DM * 4};
            cuuint32_t box[4] = {64, 3, 1, 40};
            cuuint32_t es[4] = {1, 1, 1, 1};
            fn(&mp.post.b40, CU_TENSOR_MAP_DATA_TYPE_BFLOAT16, 4, p_bqkv, dims, strides, box, es,
               CU_TENSOR_MAP_INTERLEAVE_NONE, CU_TENSOR_MAP_SWIZZLE_128B, CU_TENSOR_MAP_L2_PROMOTION_L2_256B, CU_TENSOR_MAP_FLOAT_OOB_FILL_NONE);
        }
        mp.wk16 = make_map(fn, A_Wk, HD, DM, 64, 64);
        mp.wv16 = make_map(fn, A_Wv, HD, DM, 64, 64);
        mp.wo128 = make_wo_map(fn, A_Wo, HD, 4);
        for (int i = 0; i < 2; i++) {
            cuuint64_t dims[3] = {64, S_TOK, DM / 64};
            cuuint64_t strides[2] = {DM * 2, 128};
            cuuint32_t box[3] = {32, 32, 2u - i};
            cuuint32_t es[3] = {1, 1, 1};
            fn(&mp.x32.m[i], CU_TENSOR_MAP_DATA_TYPE_BFLOAT16, 3, const_cast<bf16*>(A_x), dims, strides, box, es,
               CU_TENSOR_MAP_INTERLEAVE_NONE, CU_TENSOR_MAP_SWIZZLE_64B, CU_TENSOR_MAP_L2_PROMOTION_L2_128B, CU_TENSOR_MAP_FLOAT_OOB_FILL_NONE);
        }
        for (int i = 0; i < 10; i++) cached[i] = cur[i];
    }

    cudaStream_t st = cudaStreamPerThread;
    int4 tq = make_int4(50, 150, 700, 80), tk = make_int4(100, 250, 750, 100);
    int2 t0 = make_int2(13000, 16000);
    cudaLaunchConfig_t cfg = {};
    cfg.gridDim = dim3(96); cfg.blockDim = dim3(384); cfg.dynamicSmemBytes = R_SMEM; cfg.stream = st;
    cudaLaunchAttribute at[1];
    at[0].id = cudaLaunchAttributeClusterDimension;
    at[0].val.clusterDim.x = 3; at[0].val.clusterDim.y = 1; at[0].val.clusterDim.z = 1;
    cfg.attrs = at; cfg.numAttrs = 1;
    cudaLaunchKernelEx(&cfg, k_rec, mp.post, mp.wk16, mp.wv16, mp.wo128, mp.x32, A_mem, A_x, tq, tk, t0, 1);
    cfg.gridDim = dim3(mp.post.list.nworker - 96);
    at[0].id = cudaLaunchAttributeProgrammaticStreamSerialization;
    at[0].val.programmaticStreamSerializationAllowed = 1;
    cudaLaunchKernelEx(&cfg, k_rec, mp.post, mp.wk16, mp.wv16, mp.wo128, mp.x32, A_mem, A_x, tq, tk, t0, 0);
}
```

```cpp
#include <cuda_runtime.h>
#include <cuda_bf16.h>
#include <cuda.h>
#include <stdint.h>

typedef __nv_bfloat16 bf16;

constexpr int S_TOK = 2048;
constexpr int DM    = 1024;
constexpr int NH    = 32;
constexpr int DH    = 128;
constexpr int NSEG  = 64;
constexpr int HD    = NH * DH;

__device__ __align__(1024) bf16 g_qx[NSEG * NH * 4 * DH * 8];
__device__ __align__(1024) bf16 g_ox[S_TOK * HD];
__device__ __align__(1024) bf16 g_bqkv[S_TOK * 3 * DM];
__device__ __align__(1024) bf16 g_bo[S_TOK * DM];
__device__ __align__(1024) uint8_t g_acc[192 * 1024];

#define EV(cond, s, k) do {} while (0)
#define EVCAL(s) do {} while (0)

constexpr int P_NSK = 4;
__device__ unsigned g_epoch, g_qctr, g_done, g_zero;
enum { C_B1 = 0, C_B2 = 8, C_Q = 16, C_QH = 24, C_NONE = 31 };
__device__ unsigned g_cnt[32], g_prog[16], g_cnt_sk[P_NSK * 32];
constexpr int P_SPLIT = 4;
__device__ __align__(1024) uint4 g_skp[P_NSK * 8 * P_SPLIT * 2 * 8 * 128];
#define TLOG(i, k, v) do {} while (0)

#define DEVI __device__ __forceinline__

DEVI uint32_t opaque(uint32_t v) { uint32_t r; asm volatile("mov.u32 %0, %1;" : "=r"(r) : "r"(v)); return r; }
DEVI uint32_t smem_u32(const void* p) { return (uint32_t)__cvta_generic_to_shared(p); }

#define TRAP(code) __trap()
constexpr int SPIN_LIMIT = 1 << 22;
#define MBAR_HINT_NS 20000u
constexpr int SPIN_LIMIT_MBAR = 1 << 17;

DEVI void mbar_init(uint32_t bar, uint32_t cnt) { asm volatile("mbarrier.init.shared::cta.b64 [%0], %1;" :: "r"(bar), "r"(cnt)); }
DEVI void mbar_expect_tx(uint32_t bar, uint32_t bytes) {
    asm volatile("mbarrier.arrive.expect_tx.shared::cta.b64 _, [%0], %1;" :: "r"(bar), "r"(bytes) : "memory");
}
DEVI void mbar_arrive(uint32_t bar) { asm volatile("mbarrier.arrive.shared::cta.b64 _, [%0];" :: "r"(bar) : "memory"); }
DEVI bool mbar_try(uint32_t bar, uint32_t parity) {
    uint32_t ok;
    asm volatile("{.reg .pred p; mbarrier.try_wait.parity.shared::cta.b64 p, [%1], %2; selp.u32 %0, 1, 0, p;}"
                 : "=r"(ok) : "r"(bar), "r"(parity) : "memory");
    return ok;
}
DEVI bool mbar_try_cluster(uint32_t bar, uint32_t parity) {
    uint32_t ok;
    asm volatile("{.reg .pred p; mbarrier.try_wait.parity.acquire.cluster.shared::cta.b64 p, [%1], %2; selp.u32 %0, 1, 0, p;}"
                 : "=r"(ok) : "r"(bar), "r"(parity) : "memory");
    return ok;
}
DEVI bool mbar_try_hint(uint32_t bar, uint32_t parity) {
    uint32_t ok;
    asm volatile("{.reg .pred p; mbarrier.try_wait.parity.shared::cta.b64 p, [%1], %2, %3; selp.u32 %0, 1, 0, p;}"
                 : "=r"(ok) : "r"(bar), "r"(parity), "r"(MBAR_HINT_NS) : "memory");
    return ok;
}
DEVI void mbar_wait(uint32_t bar, uint32_t parity) {
    int n = 0;
    while (!mbar_try(bar, parity)) { if (++n > SPIN_LIMIT) TRAP(bar | (parity << 31)); }
}
DEVI void mbar_wait_sleepy(uint32_t bar, uint32_t parity) {
    int n = 0;
    while (!mbar_try_hint(bar, parity)) { if (++n > SPIN_LIMIT_MBAR) __trap(); }
}
DEVI void mbar_wait_cluster(uint32_t bar, uint32_t parity) {
    int n = 0;
    while (!mbar_try_cluster(bar, parity)) { if (++n > SPIN_LIMIT) __trap(); }
}
DEVI void mbar_spin(uint32_t bar, uint32_t parity) {
    uint32_t ok; int n = 0;
    do {
        asm volatile("{.reg .pred p; mbarrier.test_wait.parity.shared::cta.b64 p, [%1], %2; selp.u32 %0, 1, 0, p;}"
                     : "=r"(ok) : "r"(bar), "r"(parity) : "memory");
        if (++n > SPIN_LIMIT) __trap();
    } while (!ok);
}
DEVI void fence_mbar_init() { asm volatile("fence.mbarrier_init.release.cluster;" ::: "memory"); }
DEVI void fence_proxy_async() { asm volatile("fence.proxy.async.shared::cta;" ::: "memory"); }
DEVI void cluster_sync() {
    asm volatile("barrier.cluster.arrive.release.aligned;\n barrier.cluster.wait.acquire.aligned;" ::: "memory");
}
DEVI bool elect_one() {
    uint32_t e; asm volatile("{.reg .pred p; elect.sync _|p, 0xffffffff; selp.u32 %0, 1, 0, p;}" : "=r"(e)); return e;
}
DEVI void fence_proxy_global() { asm volatile("fence.proxy.async.global;" ::: "memory"); }
DEVI void cluster_wait() { asm volatile("barrier.cluster.wait.acquire.aligned;" ::: "memory"); }
DEVI void nbar_sync(int id, int n) { asm volatile("bar.sync %0, %1;" :: "r"(id), "r"(n) : "memory"); }
DEVI void nbar_arrive(int id, int n) { asm volatile("bar.arrive %0, %1;" :: "r"(id), "r"(n) : "memory"); }

DEVI void tma_load_2d(uint32_t dst, const CUtensorMap* map, int x, int y, uint32_t bar) {
    asm volatile("cp.async.bulk.tensor.2d.shared::cluster.global.mbarrier::complete_tx::bytes [%0], [%1, {%3, %4}], [%2];"
                 :: "r"(dst), "l"(map), "r"(bar), "r"(x), "r"(y) : "memory");
}
DEVI void tma_load_3d(uint32_t dst, const CUtensorMap* map, int x, int y, int z, uint32_t bar) {
    asm volatile("cp.async.bulk.tensor.3d.shared::cluster.global.mbarrier::complete_tx::bytes [%0], [%1, {%3, %4, %5}], [%2];"
                 :: "r"(dst), "l"(map), "r"(bar), "r"(x), "r"(y), "r"(z) : "memory");
}
DEVI void tma_load_wo(uint32_t dst, const CUtensorMap* map, int col, int k32, uint32_t bar) {
    asm volatile("cp.async.bulk.tensor.5d.shared::cluster.global.mbarrier::complete_tx::bytes [%0], [%1, {%3, %5, %5, %5, %4}], [%2];"
                 :: "r"(dst), "l"(map), "r"(bar), "r"(col), "r"(k32), "r"(0) : "memory");
}
DEVI void tma_store_2d(const CUtensorMap* map, uint32_t src, int x, int y) {
    asm volatile("cp.async.bulk.tensor.2d.global.shared::cta.bulk_group [%0, {%2, %3}], [%1];"
                 :: "l"(map), "r"(src), "r"(x), "r"(y) : "memory");
}
DEVI void bulk_load(uint32_t dst, const void* src, uint32_t bytes, uint32_t bar) {
    asm volatile("cp.async.bulk.shared::cluster.global.mbarrier::complete_tx::bytes [%0], [%1], %2, [%3];"
                 :: "r"(dst), "l"(src), "r"(bytes), "r"(bar) : "memory");
}
DEVI void tma_load_2d_mc(uint32_t dst, const CUtensorMap* map, int x, int y, uint32_t bar, uint16_t mask) {
    asm volatile("cp.async.bulk.tensor.2d.shared::cluster.global.mbarrier::complete_tx::bytes.multicast::cluster [%0], [%1, {%3, %4}], [%2], %5;"
                 :: "r"(dst), "l"(map), "r"(bar), "r"(x), "r"(y), "h"(mask) : "memory");
}
DEVI void bulk_copy_s2c(uint32_t dst_cluster, uint32_t src, uint32_t bytes, uint32_t bar_cluster) {
    asm volatile("cp.async.bulk.shared::cluster.shared::cta.mbarrier::complete_tx::bytes [%0], [%1], %2, [%3];"
                 :: "r"(dst_cluster), "r"(src), "r"(bytes), "r"(bar_cluster) : "memory");
}
DEVI void bulk_store(void* dst, uint32_t src, uint32_t bytes) {
    asm volatile("cp.async.bulk.global.shared::cta.bulk_group [%0], [%1], %2;" :: "l"(dst), "r"(src), "r"(bytes) : "memory");
}
DEVI void bulk_wait_read() { asm volatile("cp.async.bulk.wait_group.read 0;" ::: "memory"); }
DEVI void mbar_arrive_remote(uint32_t bar_cluster) {
    asm volatile("mbarrier.arrive.shared::cluster.b64 _, [%0];" :: "r"(bar_cluster) : "memory");
}
DEVI void mbar_expect_tx_remote(uint32_t bar_cluster, uint32_t bytes) {
    asm volatile("mbarrier.arrive.expect_tx.shared::cluster.b64 _, [%0], %1;" :: "r"(bar_cluster), "r"(bytes) : "memory");
}
DEVI void l2_prefetch(const void* p, uint32_t bytes) {
    asm volatile("cp.async.bulk.prefetch.L2.global [%0], %1;" :: "l"(p), "r"(bytes) : "memory");
}
DEVI void bulk_commit() { asm volatile("cp.async.bulk.commit_group;" ::: "memory"); }
DEVI void bulk_wait_all() { asm volatile("cp.async.bulk.wait_group 0;" ::: "memory"); }

DEVI void wg_fence() { asm volatile("wgmma.fence.sync.aligned;" ::: "memory"); }
DEVI void wg_commit() { asm volatile("wgmma.commit_group.sync.aligned;" ::: "memory"); }
template <int N> DEVI void wg_wait() { asm volatile("wgmma.wait_group.sync.aligned %0;" :: "n"(N) : "memory"); }

template <int R> DEVI void reg_dec() { asm volatile("setmaxnreg.dec.sync.aligned.u32 %0;" :: "n"(R)); }
template <int R> DEVI void reg_inc() { asm volatile("setmaxnreg.inc.sync.aligned.u32 %0;" :: "n"(R)); }

DEVI uint64_t mk_desc(uint32_t addr, uint32_t lbo, uint32_t sbo, uint32_t sw) {
    return (uint64_t)((addr & 0x3FFFF) >> 4) | ((uint64_t)(lbo >> 4) << 16) | ((uint64_t)(sbo >> 4) << 32) | ((uint64_t)sw << 62);
}

DEVI uint32_t desc_lo(uint32_t addr, uint32_t lbo) { return ((addr & 0x3FFFF) >> 4) | ((lbo >> 4) << 16); }
constexpr uint32_t DHI_SW128 = (1024u >> 4) | (1u << 30);
constexpr uint32_t DHI_SW64  = (512u >> 4) | (2u << 30);
constexpr uint32_t DHI_NONE  = (128u >> 4);

template <int TB, int SCALE_D>
DEVI void wgmma_n8_ss(float* d, uint32_t alo, uint32_t blo) {
    asm volatile("{.reg .b64 da, db; mov.b64 da, {%4, %6}; mov.b64 db, {%5, %7};\n"
                 "wgmma.mma_async.sync.aligned.m64n8k16.f32.bf16.bf16 {%0,%1,%2,%3}, da, db, %8, 1, 1, 1, %9;}"
                 : "+f"(d[0]), "+f"(d[1]), "+f"(d[2]), "+f"(d[3])
                 : "r"(alo), "r"(blo), "n"(DHI_SW128), "n"(DHI_NONE), "n"(SCALE_D), "n"(TB));
}

template <int TB>
DEVI void wgmma_n8_ss_first(float* d, uint32_t alo, uint32_t blo) {
    asm volatile("{.reg .b64 da, db; mov.b64 da, {%4, %6}; mov.b64 db, {%5, %7};\n"
                 "wgmma.mma_async.sync.aligned.m64n8k16.f32.bf16.bf16 {%0,%1,%2,%3}, da, db, 0, 1, 1, 1, %8;}"
                 : "=f"(d[0]), "=f"(d[1]), "=f"(d[2]), "=f"(d[3])
                 : "r"(alo), "r"(blo), "n"(DHI_SW128), "n"(DHI_NONE), "n"(TB));
}
DEVI void wgmma_n32_rs_first(float* d, const uint32_t* a, uint32_t blo) {
    asm volatile("{.reg .b64 db; mov.b64 db, {%20, %21};\n"
                 "wgmma.mma_async.sync.aligned.m64n32k16.f32.bf16.bf16 {%0,%1,%2,%3,%4,%5,%6,%7,%8,%9,%10,%11,%12,%13,%14,%15}, "
                 "{%16,%17,%18,%19}, db, 0, 1, 1, 0;}"
                 : "=f"(d[0]), "=f"(d[1]), "=f"(d[2]), "=f"(d[3]), "=f"(d[4]), "=f"(d[5]), "=f"(d[6]), "=f"(d[7]),
                   "=f"(d[8]), "=f"(d[9]), "=f"(d[10]), "=f"(d[11]), "=f"(d[12]), "=f"(d[13]), "=f"(d[14]), "=f"(d[15])
                 : "r"(a[0]), "r"(a[1]), "r"(a[2]), "r"(a[3]), "r"(blo), "n"(DHI_SW64));
}
template <int N> DEVI void reg_fence(float* d) {
#pragma unroll
    for (int i = 0; i < N; i++) asm volatile("" : "+f"(d[i]) :: "memory");
}
DEVI void wgmma_n32_rs(float* d, const uint32_t* a, uint32_t blo) {
    asm volatile("{.reg .b64 db; mov.b64 db, {%20, %21};\n"
                 "wgmma.mma_async.sync.aligned.m64n32k16.f32.bf16.bf16 {%0,%1,%2,%3,%4,%5,%6,%7,%8,%9,%10,%11,%12,%13,%14,%15}, "
                 "{%16,%17,%18,%19}, db, 1, 1, 1, 0;}"
                 : "+f"(d[0]), "+f"(d[1]), "+f"(d[2]), "+f"(d[3]), "+f"(d[4]), "+f"(d[5]), "+f"(d[6]), "+f"(d[7]),
                   "+f"(d[8]), "+f"(d[9]), "+f"(d[10]), "+f"(d[11]), "+f"(d[12]), "+f"(d[13]), "+f"(d[14]), "+f"(d[15])
                 : "r"(a[0]), "r"(a[1]), "r"(a[2]), "r"(a[3]), "r"(blo), "n"(DHI_SW64));
}
DEVI void wgmma_n32_ss(float* d, uint32_t alo, uint32_t blo) {
    asm volatile("{.reg .b64 da, db; mov.b64 da, {%16, %18}; mov.b64 db, {%17, %19};\n"
                 "wgmma.mma_async.sync.aligned.m64n32k16.f32.bf16.bf16 {%0,%1,%2,%3,%4,%5,%6,%7,%8,%9,%10,%11,%12,%13,%14,%15}, "
                 "da, db, 1, 1, 1, 1, 0;}"
                 : "+f"(d[0]), "+f"(d[1]), "+f"(d[2]), "+f"(d[3]), "+f"(d[4]), "+f"(d[5]), "+f"(d[6]), "+f"(d[7]),
                   "+f"(d[8]), "+f"(d[9]), "+f"(d[10]), "+f"(d[11]), "+f"(d[12]), "+f"(d[13]), "+f"(d[14]), "+f"(d[15])
                 : "r"(alo), "r"(blo), "n"(DHI_SW128), "n"(DHI_SW64));
}

template <bool FIRST>
DEVI void wgmma_n256_ss(float* d, uint64_t a, uint64_t b) {
    if (FIRST)
        asm volatile("wgmma.mma_async.sync.aligned.m64n256k16.f32.bf16.bf16 {%0,%1,%2,%3,%4,%5,%6,%7,%8,%9,%10,%11,%12,%13,%14,%15,%16,%17,%18,%19,%20,%21,%22,%23,%24,%25,%26,%27,%28,%29,%30,%31,%32,%33,%34,%35,%36,%37,%38,%39,%40,%41,%42,%43,%44,%45,%46,%47,%48,%49,%50,%51,%52,%53,%54,%55,%56,%57,%58,%59,%60,%61,%62,%63,%64,%65,%66,%67,%68,%69,%70,%71,%72,%73,%74,%75,%76,%77,%78,%79,%80,%81,%82,%83,%84,%85,%86,%87,%88,%89,%90,%91,%92,%93,%94,%95,%96,%97,%98,%99,%100,%101,%102,%103,%104,%105,%106,%107,%108,%109,%110,%111,%112,%113,%114,%115,%116,%117,%118,%119,%120,%121,%122,%123,%124,%125,%126,%127}, %128, %129, 0, 1, 1, 1, 0;"
            : "=f"(d[0]), "=f"(d[1]), "=f"(d[2]), "=f"(d[3]), "=f"(d[4]), "=f"(d[5]), "=f"(d[6]), "=f"(d[7]), "=f"(d[8]), "=f"(d[9]), "=f"(d[10]), "=f"(d[11]), "=f"(d[12]), "=f"(d[13]), "=f"(d[14]), "=f"(d[15]), "=f"(d[16]), "=f"(d[17]), "=f"(d[18]), "=f"(d[19]), "=f"(d[20]), "=f"(d[21]), "=f"(d[22]), "=f"(d[23]), "=f"(d[24]), "=f"(d[25]), "=f"(d[26]), "=f"(d[27]), "=f"(d[28]), "=f"(d[29]), "=f"(d[30]), "=f"(d[31]), "=f"(d[32]), "=f"(d[33]), "=f"(d[34]), "=f"(d[35]), "=f"(d[36]), "=f"(d[37]), "=f"(d[38]), "=f"(d[39]), "=f"(d[40]), "=f"(d[41]), "=f"(d[42]), "=f"(d[43]), "=f"(d[44]), "=f"(d[45]), "=f"(d[46]), "=f"(d[47]), "=f"(d[48]), "=f"(d[49]), "=f"(d[50]), "=f"(d[51]), "=f"(d[52]), "=f"(d[53]), "=f"(d[54]), "=f"(d[55]), "=f"(d[56]), "=f"(d[57]), "=f"(d[58]), "=f"(d[59]), "=f"(d[60]), "=f"(d[61]), "=f"(d[62]), "=f"(d[63]), "=f"(d[64]), "=f"(d[65]), "=f"(d[66]), "=f"(d[67]), "=f"(d[68]), "=f"(d[69]), "=f"(d[70]), "=f"(d[71]), "=f"(d[72]), "=f"(d[73]), "=f"(d[74]), "=f"(d[75]), "=f"(d[76]), "=f"(d[77]), "=f"(d[78]), "=f"(d[79]), "=f"(d[80]), "=f"(d[81]), "=f"(d[82]), "=f"(d[83]), "=f"(d[84]), "=f"(d[85]), "=f"(d[86]), "=f"(d[87]), "=f"(d[88]), "=f"(d[89]), "=f"(d[90]), "=f"(d[91]), "=f"(d[92]), "=f"(d[93]), "=f"(d[94]), "=f"(d[95]), "=f"(d[96]), "=f"(d[97]), "=f"(d[98]), "=f"(d[99]), "=f"(d[100]), "=f"(d[101]), "=f"(d[102]), "=f"(d[103]), "=f"(d[104]), "=f"(d[105]), "=f"(d[106]), "=f"(d[107]), "=f"(d[108]), "=f"(d[109]), "=f"(d[110]), "=f"(d[111]), "=f"(d[112]), "=f"(d[113]), "=f"(d[114]), "=f"(d[115]), "=f"(d[116]), "=f"(d[117]), "=f"(d[118]), "=f"(d[119]), "=f"(d[120]), "=f"(d[121]), "=f"(d[122]), "=f"(d[123]), "=f"(d[124]), "=f"(d[125]), "=f"(d[126]), "=f"(d[127]) : "l"(a), "l"(b));
    else
        asm volatile("wgmma.mma_async.sync.aligned.m64n256k16.f32.bf16.bf16 {%0,%1,%2,%3,%4,%5,%6,%7,%8,%9,%10,%11,%12,%13,%14,%15,%16,%17,%18,%19,%20,%21,%22,%23,%24,%25,%26,%27,%28,%29,%30,%31,%32,%33,%34,%35,%36,%37,%38,%39,%40,%41,%42,%43,%44,%45,%46,%47,%48,%49,%50,%51,%52,%53,%54,%55,%56,%57,%58,%59,%60,%61,%62,%63,%64,%65,%66,%67,%68,%69,%70,%71,%72,%73,%74,%75,%76,%77,%78,%79,%80,%81,%82,%83,%84,%85,%86,%87,%88,%89,%90,%91,%92,%93,%94,%95,%96,%97,%98,%99,%100,%101,%102,%103,%104,%105,%106,%107,%108,%109,%110,%111,%112,%113,%114,%115,%116,%117,%118,%119,%120,%121,%122,%123,%124,%125,%126,%127}, %128, %129, 1, 1, 1, 1, 0;"
            : "+f"(d[0]), "+f"(d[1]), "+f"(d[2]), "+f"(d[3]), "+f"(d[4]), "+f"(d[5]), "+f"(d[6]), "+f"(d[7]), "+f"(d[8]), "+f"(d[9]), "+f"(d[10]), "+f"(d[11]), "+f"(d[12]), "+f"(d[13]), "+f"(d[14]), "+f"(d[15]), "+f"(d[16]), "+f"(d[17]), "+f"(d[18]), "+f"(d[19]), "+f"(d[20]), "+f"(d[21]), "+f"(d[22]), "+f"(d[23]), "+f"(d[24]), "+f"(d[25]), "+f"(d[26]), "+f"(d[27]), "+f"(d[28]), "+f"(d[29]), "+f"(d[30]), "+f"(d[31]), "+f"(d[32]), "+f"(d[33]), "+f"(d[34]), "+f"(d[35]), "+f"(d[36]), "+f"(d[37]), "+f"(d[38]), "+f"(d[39]), "+f"(d[40]), "+f"(d[41]), "+f"(d[42]), "+f"(d[43]), "+f"(d[44]), "+f"(d[45]), "+f"(d[46]), "+f"(d[47]), "+f"(d[48]), "+f"(d[49]), "+f"(d[50]), "+f"(d[51]), "+f"(d[52]), "+f"(d[53]), "+f"(d[54]), "+f"(d[55]), "+f"(d[56]), "+f"(d[57]), "+f"(d[58]), "+f"(d[59]), "+f"(d[60]), "+f"(d[61]), "+f"(d[62]), "+f"(d[63]), "+f"(d[64]), "+f"(d[65]), "+f"(d[66]), "+f"(d[67]), "+f"(d[68]), "+f"(d[69]), "+f"(d[70]), "+f"(d[71]), "+f"(d[72]), "+f"(d[73]), "+f"(d[74]), "+f"(d[75]), "+f"(d[76]), "+f"(d[77]), "+f"(d[78]), "+f"(d[79]), "+f"(d[80]), "+f"(d[81]), "+f"(d[82]), "+f"(d[83]), "+f"(d[84]), "+f"(d[85]), "+f"(d[86]), "+f"(d[87]), "+f"(d[88]), "+f"(d[89]), "+f"(d[90]), "+f"(d[91]), "+f"(d[92]), "+f"(d[93]), "+f"(d[94]), "+f"(d[95]), "+f"(d[96]), "+f"(d[97]), "+f"(d[98]), "+f"(d[99]), "+f"(d[100]), "+f"(d[101]), "+f"(d[102]), "+f"(d[103]), "+f"(d[104]), "+f"(d[105]), "+f"(d[106]), "+f"(d[107]), "+f"(d[108]), "+f"(d[109]), "+f"(d[110]), "+f"(d[111]), "+f"(d[112]), "+f"(d[113]), "+f"(d[114]), "+f"(d[115]), "+f"(d[116]), "+f"(d[117]), "+f"(d[118]), "+f"(d[119]), "+f"(d[120]), "+f"(d[121]), "+f"(d[122]), "+f"(d[123]), "+f"(d[124]), "+f"(d[125]), "+f"(d[126]), "+f"(d[127]) : "l"(a), "l"(b));
}
template <bool FIRST>
DEVI void wgmma_n128_ss(float* d, uint64_t a, uint64_t b) {
    if (FIRST)
        asm volatile("wgmma.mma_async.sync.aligned.m64n128k16.f32.bf16.bf16 {%0,%1,%2,%3,%4,%5,%6,%7,%8,%9,%10,%11,%12,%13,%14,%15,%16,%17,%18,%19,%20,%21,%22,%23,%24,%25,%26,%27,%28,%29,%30,%31,%32,%33,%34,%35,%36,%37,%38,%39,%40,%41,%42,%43,%44,%45,%46,%47,%48,%49,%50,%51,%52,%53,%54,%55,%56,%57,%58,%59,%60,%61,%62,%63}, %64, %65, 0, 1, 1, 1, 0;"
            : "=f"(d[0]), "=f"(d[1]), "=f"(d[2]), "=f"(d[3]), "=f"(d[4]), "=f"(d[5]), "=f"(d[6]), "=f"(d[7]), "=f"(d[8]), "=f"(d[9]), "=f"(d[10]), "=f"(d[11]), "=f"(d[12]), "=f"(d[13]), "=f"(d[14]), "=f"(d[15]), "=f"(d[16]), "=f"(d[17]), "=f"(d[18]), "=f"(d[19]), "=f"(d[20]), "=f"(d[21]), "=f"(d[22]), "=f"(d[23]), "=f"(d[24]), "=f"(d[25]), "=f"(d[26]), "=f"(d[27]), "=f"(d[28]), "=f"(d[29]), "=f"(d[30]), "=f"(d[31]), "=f"(d[32]), "=f"(d[33]), "=f"(d[34]), "=f"(d[35]), "=f"(d[36]), "=f"(d[37]), "=f"(d[38]), "=f"(d[39]), "=f"(d[40]), "=f"(d[41]), "=f"(d[42]), "=f"(d[43]), "=f"(d[44]), "=f"(d[45]), "=f"(d[46]), "=f"(d[47]), "=f"(d[48]), "=f"(d[49]), "=f"(d[50]), "=f"(d[51]), "=f"(d[52]), "=f"(d[53]), "=f"(d[54]), "=f"(d[55]), "=f"(d[56]), "=f"(d[57]), "=f"(d[58]), "=f"(d[59]), "=f"(d[60]), "=f"(d[61]), "=f"(d[62]), "=f"(d[63]) : "l"(a), "l"(b));
    else
        asm volatile("wgmma.mma_async.sync.aligned.m64n128k16.f32.bf16.bf16 {%0,%1,%2,%3,%4,%5,%6,%7,%8,%9,%10,%11,%12,%13,%14,%15,%16,%17,%18,%19,%20,%21,%22,%23,%24,%25,%26,%27,%28,%29,%30,%31,%32,%33,%34,%35,%36,%37,%38,%39,%40,%41,%42,%43,%44,%45,%46,%47,%48,%49,%50,%51,%52,%53,%54,%55,%56,%57,%58,%59,%60,%61,%62,%63}, %64, %65, 1, 1, 1, 1, 0;"
            : "+f"(d[0]), "+f"(d[1]), "+f"(d[2]), "+f"(d[3]), "+f"(d[4]), "+f"(d[5]), "+f"(d[6]), "+f"(d[7]), "+f"(d[8]), "+f"(d[9]), "+f"(d[10]), "+f"(d[11]), "+f"(d[12]), "+f"(d[13]), "+f"(d[14]), "+f"(d[15]), "+f"(d[16]), "+f"(d[17]), "+f"(d[18]), "+f"(d[19]), "+f"(d[20]), "+f"(d[21]), "+f"(d[22]), "+f"(d[23]), "+f"(d[24]), "+f"(d[25]), "+f"(d[26]), "+f"(d[27]), "+f"(d[28]), "+f"(d[29]), "+f"(d[30]), "+f"(d[31]), "+f"(d[32]), "+f"(d[33]), "+f"(d[34]), "+f"(d[35]), "+f"(d[36]), "+f"(d[37]), "+f"(d[38]), "+f"(d[39]), "+f"(d[40]), "+f"(d[41]), "+f"(d[42]), "+f"(d[43]), "+f"(d[44]), "+f"(d[45]), "+f"(d[46]), "+f"(d[47]), "+f"(d[48]), "+f"(d[49]), "+f"(d[50]), "+f"(d[51]), "+f"(d[52]), "+f"(d[53]), "+f"(d[54]), "+f"(d[55]), "+f"(d[56]), "+f"(d[57]), "+f"(d[58]), "+f"(d[59]), "+f"(d[60]), "+f"(d[61]), "+f"(d[62]), "+f"(d[63]) : "l"(a), "l"(b));
}

template <bool FIRST>
DEVI void wgmma_n64_ss(float* d, uint64_t a, uint64_t b) {
    if (FIRST)
        asm volatile("wgmma.mma_async.sync.aligned.m64n64k16.f32.bf16.bf16 {%0,%1,%2,%3,%4,%5,%6,%7,%8,%9,%10,%11,%12,%13,%14,%15,%16,%17,%18,%19,%20,%21,%22,%23,%24,%25,%26,%27,%28,%29,%30,%31}, %32, %33, 0, 1, 1, 1, 0;"
            : "=f"(d[0]), "=f"(d[1]), "=f"(d[2]), "=f"(d[3]), "=f"(d[4]), "=f"(d[5]), "=f"(d[6]), "=f"(d[7]), "=f"(d[8]), "=f"(d[9]), "=f"(d[10]), "=f"(d[11]), "=f"(d[12]), "=f"(d[13]), "=f"(d[14]), "=f"(d[15]), "=f"(d[16]), "=f"(d[17]), "=f"(d[18]), "=f"(d[19]), "=f"(d[20]), "=f"(d[21]), "=f"(d[22]), "=f"(d[23]), "=f"(d[24]), "=f"(d[25]), "=f"(d[26]), "=f"(d[27]), "=f"(d[28]), "=f"(d[29]), "=f"(d[30]), "=f"(d[31]) : "l"(a), "l"(b));
    else
        asm volatile("wgmma.mma_async.sync.aligned.m64n64k16.f32.bf16.bf16 {%0,%1,%2,%3,%4,%5,%6,%7,%8,%9,%10,%11,%12,%13,%14,%15,%16,%17,%18,%19,%20,%21,%22,%23,%24,%25,%26,%27,%28,%29,%30,%31}, %32, %33, 1, 1, 1, 1, 0;"
            : "+f"(d[0]), "+f"(d[1]), "+f"(d[2]), "+f"(d[3]), "+f"(d[4]), "+f"(d[5]), "+f"(d[6]), "+f"(d[7]), "+f"(d[8]), "+f"(d[9]), "+f"(d[10]), "+f"(d[11]), "+f"(d[12]), "+f"(d[13]), "+f"(d[14]), "+f"(d[15]), "+f"(d[16]), "+f"(d[17]), "+f"(d[18]), "+f"(d[19]), "+f"(d[20]), "+f"(d[21]), "+f"(d[22]), "+f"(d[23]), "+f"(d[24]), "+f"(d[25]), "+f"(d[26]), "+f"(d[27]), "+f"(d[28]), "+f"(d[29]), "+f"(d[30]), "+f"(d[31]) : "l"(a), "l"(b));
}

DEVI void mma16816(float* d, const uint32_t* a, uint32_t b0, uint32_t b1) {
    asm volatile("mma.sync.aligned.m16n8k16.row.col.f32.bf16.bf16.f32 {%0,%1,%2,%3}, {%4,%5,%6,%7}, {%8,%9}, {%0,%1,%2,%3};"
                 : "+f"(d[0]), "+f"(d[1]), "+f"(d[2]), "+f"(d[3])
                 : "r"(a[0]), "r"(a[1]), "r"(a[2]), "r"(a[3]), "r"(b0), "r"(b1));
}
DEVI void mma1688(float* d, uint32_t a0, uint32_t a1, uint32_t b0) {
    asm volatile("mma.sync.aligned.m16n8k8.row.col.f32.bf16.bf16.f32 {%0,%1,%2,%3}, {%4,%5}, {%6}, {%0,%1,%2,%3};"
                 : "+f"(d[0]), "+f"(d[1]), "+f"(d[2]), "+f"(d[3]) : "r"(a0), "r"(a1), "r"(b0));
}
DEVI void ldsm4(uint32_t* r, uint32_t addr) {
    asm volatile("ldmatrix.sync.aligned.m8n8.x4.shared.b16 {%0,%1,%2,%3}, [%4];"
                 : "=r"(r[0]), "=r"(r[1]), "=r"(r[2]), "=r"(r[3]) : "r"(addr) : "memory");
}
DEVI void ldsm4t(uint32_t* r, uint32_t addr) {
    asm volatile("ldmatrix.sync.aligned.m8n8.x4.trans.shared.b16 {%0,%1,%2,%3}, [%4];"
                 : "=r"(r[0]), "=r"(r[1]), "=r"(r[2]), "=r"(r[3]) : "r"(addr) : "memory");
}
DEVI void ldsm2(uint32_t* r, uint32_t addr) {
    asm volatile("ldmatrix.sync.aligned.m8n8.x2.shared.b16 {%0,%1}, [%2];" : "=r"(r[0]), "=r"(r[1]) : "r"(addr) : "memory");
}
DEVI void ldsm1t(uint32_t& r, uint32_t addr) {
    asm volatile("ldmatrix.sync.aligned.m8n8.x1.trans.shared.b16 {%0}, [%1];" : "=r"(r) : "r"(addr) : "memory");
}
DEVI void stsm4(uint32_t addr, uint32_t r0, uint32_t r1, uint32_t r2, uint32_t r3) {
    asm volatile("stmatrix.sync.aligned.m8n8.x4.shared.b16 [%0], {%1,%2,%3,%4};" :: "r"(addr), "r"(r0), "r"(r1), "r"(r2), "r"(r3) : "memory");
}
DEVI void stsm4t(uint32_t addr, uint32_t r0, uint32_t r1, uint32_t r2, uint32_t r3) {
    asm volatile("stmatrix.sync.aligned.m8n8.x4.trans.shared.b16 [%0], {%1,%2,%3,%4};" :: "r"(addr), "r"(r0), "r"(r1), "r"(r2), "r"(r3) : "memory");
}
DEVI uint32_t movm_t(uint32_t a) {
    uint32_t d; asm volatile("movmatrix.sync.aligned.m8n8.trans.b16 %0, %1;" : "=r"(d) : "r"(a)); return d;
}
DEVI uint32_t pack_bf16(float lo, float hi) {
    uint32_t r; asm("cvt.rn.bf16x2.f32 %0, %1, %2;" : "=r"(r) : "f"(hi), "f"(lo)); return r;
}
DEVI float ex2(float x) { float y; asm("ex2.approx.ftz.f32 %0, %1;" : "=f"(y) : "f"(x)); return y; }

DEVI uint4 ld_rlx4(const void* p) {
    uint4 v;
    asm volatile("ld.relaxed.gpu.global.v4.u32 {%0,%1,%2,%3}, [%4];" : "=r"(v.x), "=r"(v.y), "=r"(v.z), "=r"(v.w) : "l"(p) : "memory");
    return v;
}
DEVI void ld_rlx4f(float* d, const void* p) {
    asm volatile("ld.relaxed.gpu.global.v4.f32 {%0,%1,%2,%3}, [%4];" : "=f"(d[0]), "=f"(d[1]), "=f"(d[2]), "=f"(d[3]) : "l"(p) : "memory");
}
DEVI bool all_nzf(const float* d) { return __float_as_uint(d[0]) && __float_as_uint(d[1]) && __float_as_uint(d[2]) && __float_as_uint(d[3]); }
DEVI void sts128f(uint32_t addr, const float* d) {
    asm volatile("st.shared.v4.f32 [%0], {%1,%2,%3,%4};" :: "r"(addr), "f"(d[0]), "f"(d[1]), "f"(d[2]), "f"(d[3]) : "memory");
}
DEVI void st_rlx4(void* p, uint32_t a, uint32_t b, uint32_t c, uint32_t d) {
    asm volatile("st.relaxed.gpu.global.v4.u32 [%0], {%1,%2,%3,%4};" :: "l"(p), "r"(a), "r"(b), "r"(c), "r"(d) : "memory");
}
DEVI void st_rlx(void* p, uint32_t v) { asm volatile("st.relaxed.gpu.global.u32 [%0], %1;" :: "l"(p), "r"(v) : "memory"); }
DEVI void sts128(uint32_t addr, uint4 v) {
    asm volatile("st.shared.v4.u32 [%0], {%1,%2,%3,%4};" :: "r"(addr), "r"(v.x), "r"(v.y), "r"(v.z), "r"(v.w) : "memory");
}
DEVI void sts64(uint32_t addr, uint32_t a, uint32_t b) { asm volatile("st.shared.v2.u32 [%0], {%1,%2};" :: "r"(addr), "r"(a), "r"(b) : "memory"); }
DEVI void sts32(uint32_t addr, uint32_t v) { asm volatile("st.shared.u32 [%0], %1;" :: "r"(addr), "r"(v) : "memory"); }
DEVI uint4 lds128(uint32_t addr) {
    uint4 v; asm volatile("ld.shared.v4.u32 {%0,%1,%2,%3}, [%4];" : "=r"(v.x), "=r"(v.y), "=r"(v.z), "=r"(v.w) : "r"(addr) : "memory"); return v;
}
DEVI float2 lds64f(uint32_t addr) {
    float2 v; asm volatile("ld.shared.v2.f32 {%0,%1}, [%2];" : "=f"(v.x), "=f"(v.y) : "r"(addr) : "memory"); return v;
}
DEVI void cp_async16(uint32_t dst, const void* src) {
    asm volatile("cp.async.cg.shared.global [%0], [%1], 16;" :: "r"(dst), "l"(src) : "memory");
}
DEVI void cp_async_commit() { asm volatile("cp.async.commit_group;" ::: "memory"); }
DEVI void cp_async_wait0() { asm volatile("cp.async.wait_group 0;" ::: "memory"); }
DEVI uint32_t lds32(uint32_t addr) { uint32_t v; asm volatile("ld.shared.u32 %0, [%1];" : "=r"(v) : "r"(addr) : "memory"); return v; }
DEVI float rcp_fast(float x) { float y; asm("rcp.approx.ftz.f32 %0, %1;" : "=f"(y) : "f"(x)); return y; }
DEVI bool all_nz(const uint4& v) { return v.x && v.y && v.z && v.w; }
DEVI uint32_t mapa(uint32_t addr, uint32_t rank) {
    uint32_t r; asm("mapa.shared::cluster.u32 %0, %1, %2;" : "=r"(r) : "r"(addr), "r"(rank)); return r;
}
DEVI void st_async32(uint32_t dst, uint32_t a, uint32_t bar) {
    asm volatile("st.async.weak.shared::cluster.mbarrier::complete_tx::bytes.b32 [%0], %1, [%2];" :: "r"(dst), "r"(a), "r"(bar) : "memory");
}
DEVI void st_async64(uint32_t dst, uint32_t a, uint32_t b, uint32_t bar) {
    asm volatile("st.async.weak.shared::cluster.mbarrier::complete_tx::bytes.v2.b32 [%0], {%1,%2}, [%3];"
                 :: "r"(dst), "r"(a), "r"(b), "r"(bar) : "memory");
}

DEVI void st_async128(uint32_t dst, uint32_t a, uint32_t b, uint32_t c, uint32_t d, uint32_t bar) {
    asm volatile("st.async.weak.shared::cluster.mbarrier::complete_tx::bytes.v4.b32 [%0], {%1,%2,%3,%4}, [%5];"
                 :: "r"(dst), "r"(a), "r"(b), "r"(c), "r"(d), "r"(bar) : "memory");
}

DEVI uint32_t b_addr(uint32_t sb, int row, int which, int chunk) { const int l = 3 * row + which; return sb + l * 128 + ((chunk ^ (l & 7)) * 16); }
DEVI void battn_warp(uint32_t st, uint32_t ebar, int i0, int par, int head, int hh, int mt, int lane) {
    const int gq = lane >> 2, t = lane & 3, r = 16 * mt + (lane & 7), b3 = (lane >> 3) & 1, b4 = lane >> 4;
    uint32_t a[8], k[8], k2[4], v[8], v2[4];
#pragma unroll
    for (int ks = 0; ks < 2; ks++) {
        ldsm4(a + 4 * ks, b_addr(st, 8 + r + b3 * 8, 0, hh * 4 + ks * 2 + b4));
        ldsm4(k + 4 * ks, b_addr(st, r + b4 * 8, 1, hh * 4 + ks * 2 + b3));
    }
    ldsm4(k2, b_addr(st, r + 16, 1, hh * 4 + (lane >> 3)));
#pragma unroll
    for (int n = 0; n < 2; n++) ldsm4t(v + 4 * n, b_addr(st, r + b3 * 8, 2, hh * 4 + 2 * n + b4));
    ldsm4t(v2, b_addr(st, r + 16, 2, hh * 4 + (lane >> 3)));
    float s[3][4];
#pragma unroll
    for (int n = 0; n < 3; n++) { s[n][0] = s[n][1] = s[n][2] = s[n][3] = 0.f; }
#pragma unroll
    for (int ks = 0; ks < 2; ks++) {
        mma16816(s[0], a + 4 * ks, k[4 * ks], k[4 * ks + 1]);
        mma16816(s[1], a + 4 * ks, k[4 * ks + 2], k[4 * ks + 3]);
        mma16816(s[2], a + 4 * ks, k2[2 * ks], k2[2 * ks + 1]);
    }
    const bool ex = i0 + 16 * mt > 0;
    float x[4], y[4];
#pragma unroll
    for (int c = 0; c < 2; c++) {
        const bool low = 2 * t + c <= gq;
        x[c] = !low && ex ? s[0][c] : -INFINITY; x[2 + c] = low ? s[1][c] : -INFINITY;
        y[c] = !low ? s[1][2 + c] : -INFINITY;   y[2 + c] = low ? s[2][2 + c] : -INFINITY;
    }
    float m0 = fmaxf(fmaxf(x[0], x[1]), fmaxf(x[2], x[3])), m1 = fmaxf(fmaxf(y[0], y[1]), fmaxf(y[2], y[3]));
    m0 = fmaxf(fmaxf(m0, __shfl_xor_sync(0xffffffffu, m0, 1)), fmaxf(__shfl_xor_sync(0xffffffffu, m0, 2), __shfl_xor_sync(0xffffffffu, m0, 3)));
    m1 = fmaxf(fmaxf(m1, __shfl_xor_sync(0xffffffffu, m1, 1)), fmaxf(__shfl_xor_sync(0xffffffffu, m1, 2), __shfl_xor_sync(0xffffffffu, m1, 3)));
    constexpr float C = 0.17677669529663687f * 1.4426950408889634f;
    m0 *= -C; m1 *= -C;
    const uint32_t p0[4] = {pack_bf16(ex2(fmaf(x[0], C, m0)), ex2(fmaf(x[1], C, m0))), 0u,
                            pack_bf16(ex2(fmaf(x[2], C, m0)), ex2(fmaf(x[3], C, m0))), pack_bf16(ex2(fmaf(y[0], C, m1)), ex2(fmaf(y[1], C, m1)))};
    const uint32_t p1 = pack_bf16(ex2(fmaf(y[2], C, m1)), ex2(fmaf(y[3], C, m1)));
    float o[4][4], l[4] = {0.f, 0.f, 0.f, 0.f};
#pragma unroll
    for (int n = 0; n < 4; n++) { o[n][0] = o[n][1] = o[n][2] = o[n][3] = 0.f; }
    mma16816(l, p0, 0x3F803F80u, 0x3F803F80u);
#pragma unroll
    for (int n = 0; n < 4; n++) mma16816(o[n], p0, v[2 * n], v[2 * n + 1]);
    mma1688(l, 0u, p1, 0x3F803F80u);
#pragma unroll
    for (int n = 0; n < 4; n++) mma1688(o[n], 0u, p1, v2[n]);
    if (lane == 0) mbar_arrive(ebar);
    const float i0f = rcp_fast(l[0]), i1f = rcp_fast(l[2]);
    uint4* dst = (uint4*)(g_bo + (uint32_t)((2 * (i0 + 16 * mt + gq) + par) * DM + head * 32 + t * 8));
    dst[0] = make_uint4(pack_bf16(o[0][0] * i0f, o[0][1] * i0f), pack_bf16(o[1][0] * i0f, o[1][1] * i0f),
                        pack_bf16(o[2][0] * i0f, o[2][1] * i0f), pack_bf16(o[3][0] * i0f, o[3][1] * i0f));
    dst[16 * DM / 8] = make_uint4(pack_bf16(o[0][2] * i1f, o[0][3] * i1f), pack_bf16(o[1][2] * i1f, o[1][3] * i1f),
                                  pack_bf16(o[2][2] * i1f, o[2][3] * i1f), pack_bf16(o[3][2] * i1f, o[3][3] * i1f));
}

constexpr float SCALE_LOG2E = 0.08838834764831845f * 1.4426950408889634f;

constexpr int P_UNITS = 12, P_STAGES = 6;
constexpr int PS_STG = P_UNITS * 16384;
constexpr int PS_BAR = PS_STG + 32768;
constexpr int P_SMEM = PS_BAR + 256;
static_assert(P_SMEM <= 232448, "smem");
enum { K_Q, K_B1, K_B3, K_A4, K_QH, K_A3, K_SK, K_B2, K_SN, K_END };
struct PList { int n, nworker; int4 run[16]; };
struct PTask { int kind, a, b, c; };
DEVI PTask p_decode(const PList& pl, int id) {
    for (int i = 0; i < pl.n; i++) {
        const int4 r = pl.run[i];
        if (id < r.w) {
            const int j = id - r.z;
            if (r.x == K_Q || r.x == K_QH) return {r.x, j & 31, r.y + (j >> 5), 0};
            if (r.x == K_B1) return {r.x, j % 24, r.y + j / 24, 0};
            if (r.x == K_B2) return {r.x, 0, r.y + j, 0};
            if (r.x == K_SK || r.x == K_SN) return {r.x, (j / P_SPLIT) & 7, r.y + j / (8 * P_SPLIT), j % P_SPLIT};
            return {r.x, j & 7, r.y + (j >> 3), 0};
        }
    }
    return {K_END, 0, 0, 0};
}
DEVI void wait_count(const unsigned* p, unsigned target) {
    int n = 0;
    while (true) {
        unsigned v; asm volatile("ld.acquire.gpu.global.u32 %0, [%1];" : "=r"(v) : "l"(p) : "memory");
        if ((int)(v - target) >= 0) break;
        __nanosleep(100);
        if (++n > SPIN_LIMIT) TRAP(0x10000000u | ((unsigned)(size_t)p & 0xFFFFu));
    }
}
DEVI void wait_count_warp(const unsigned* p, unsigned target) {
    int n = 0;
    while (true) {
        unsigned v; asm volatile("ld.acquire.gpu.global.u32 %0, [%1];" : "=r"(v) : "l"(p) : "memory");
        if (__all_sync(0xffffffffu, (int)(v - target) >= 0)) break;
        __nanosleep(100);
        if (++n > SPIN_LIMIT) TRAP(0x10000000u | ((unsigned)(size_t)p & 0xFFFFu));
    }
}
DEVI void signal_count(unsigned* p) { __threadfence(); atomicAdd(p, 1u); }

struct PMaps { CUtensorMap wq, bw, bwo, wo, x, bx, bo, ox, ox64, cb, cout, cq, b40; PList list; };
constexpr int PB_F = PS_BAR, PB_E = PB_F + 48, PB_TF = PB_F + 96, PB_TE = PB_F + 112, PB_S = PB_F + 128;
constexpr int PS_T = PB_F + 144, PS_SIG = PS_T + 32, PS_SK = PS_SIG + 16;

struct PRing {
    int st, ph, u;
    DEVI void next(int n) { u += n; if (u >= P_UNITS) u -= P_UNITS; if (++st == P_STAGES) { st = 0; ph ^= 1; } }
    DEVI uint32_t w(bool wide) const { return wide && u == P_UNITS - 2 ? 0u : u * 16384u; }
    DEVI uint32_t x(bool wide) const { return wide && u == P_UNITS - 2 ? u * 16384u : (u == P_UNITS - 1 ? 0u : (u + 1) * 16384u); }
};
struct POut { const CUtensorMap* map; int col, tok, cnt; bool blocked; };
DEVI void p_store(const uint32_t* pk, const POut& o, int c, uint32_t stg, int warp, int lane_, int barid, bool elected) {
    const int lane = (int)opaque((uint32_t)lane_);
    const int mi = lane >> 3, r = lane & 7;
    const uint32_t buf = stg + (c & 1) * 8192;
    if (elected) asm volatile("cp.async.bulk.wait_group.read 1;" ::: "memory");
    nbar_sync(barid, 128);
    if (o.blocked) {
#pragma unroll
        for (int j = 0; j < 8; j += 2)
            stsm4(buf + (j + (mi >> 1)) * 1024 + (warp * 16 + (mi & 1) * 8 + r) * 16, pk[2 * j], pk[2 * j + 1], pk[2 * j + 2], pk[2 * j + 3]);
    } else {
#pragma unroll
        for (int j = 0; j < 8; j += 2)
            stsm4t(buf + (8 * (j + (mi >> 1)) + r) * 128 + ((2 * warp + (mi & 1)) ^ r) * 16, pk[2 * j], pk[2 * j + 1], pk[2 * j + 2], pk[2 * j + 3]);
    }
    fence_proxy_async();
    nbar_sync(barid, 128);
    if (elected) {
        if (o.blocked)
            asm volatile("cp.async.bulk.tensor.4d.global.shared::cta.bulk_group [%0, {%2, %3, %4, %5}], [%1];"
                         :: "l"(o.map), "r"(buf), "r"(0), "r"((o.col >> 5) & 2), "r"((o.col >> 7) * 4), "r"((o.tok >> 5) + 2 * c) : "memory");
        else tma_store_2d(o.map, buf, o.col, o.tok + c * 64);
        bulk_commit();
    }
}
DEVI void p_signal(uint32_t sb, int g, int cnt, int& nsig) {
    sts32(sb + PS_SIG + g * 8 + (nsig & 1) * 4, (uint32_t)cnt);
    mbar_arrive(sb + PB_S + g * 8);
    nsig++;
}
DEVI void p_release(uint32_t sb, const PRing& r) {
    if (elect_one()) mbar_arrive(sb + PB_E + (r.st ? r.st - 1 : P_STAGES - 1) * 8);
}
template <int BN, bool FIRST>
DEVI void p_kblock(float* d, uint32_t sb, int g, PRing& r) {
    mbar_wait(sb + PB_F + r.st * 8, r.ph);
    const uint64_t da = mk_desc(sb + r.w(BN == 256) + g * 8192, 16, 1024, 1), db = mk_desc(sb + r.x(BN == 256), 16, 1024, 1);
    wg_fence();
#pragma unroll
    for (int kk = 0; kk < 4; kk++) {
        if (BN == 256) { if (FIRST && kk == 0) wgmma_n256_ss<true>(d, da, db); else wgmma_n256_ss<false>(d, da + (uint64_t)(kk * 128), db + (uint64_t)(kk * 2)); }
        if (BN == 128) { if (FIRST && kk == 0) wgmma_n128_ss<true>(d, da, db); else wgmma_n128_ss<false>(d, da + (uint64_t)(kk * 128), db + (uint64_t)(kk * 2)); }
        if (BN == 64)  { if (FIRST && kk == 0) wgmma_n64_ss<true>(d, da, db); else wgmma_n64_ss<false>(d, da + (uint64_t)(kk * 128), db + (uint64_t)(kk * 2)); }
    }
    wg_commit();
    if (!FIRST) {
        wg_wait<1>();
        p_release(sb, r);
    }
    r.next(BN == 256 ? 3 : 2);
}

DEVI int post_claim(const PMaps& mp, unsigned E) {
    unsigned v = 0;
    if ((threadIdx.x & 31) == 0) v = atomicAdd(&g_qctr, 1u);
    return (int)(__shfl_sync(0xffffffffu, v, 0) - (E - 1) * (unsigned)(mp.list.run[mp.list.n - 1].w + mp.list.nworker));
}
DEVI void post_producer(const PMaps& mp, uint32_t sb, unsigned E, int id) {
    PRing r = {0, 0, 0};
    int ts = 0, tp = 0, used = 0;
    uint32_t big = 0;
    auto reserve = [&](int n) {
        while (used + n > P_UNITS) {
            mbar_wait(sb + PB_E + ts * 8, tp);
            used -= 2 + ((big >> ts) & 1);
            if (++ts == P_STAGES) { ts = 0; tp ^= 1; }
        }
        used += n;
        big = (big & ~(1u << r.st)) | ((uint32_t)(n & 1) << r.st);
    };
    for (int i = 0;; i++) {
        mbar_wait(sb + PB_TE + (i & 1) * 8, ((i >> 1) & 1) ^ 1);
        if (i > 0) id = post_claim(mp, E);
        const PTask tk = p_decode(mp.list, id);
        const bool sn = tk.kind == K_SN, split = tk.kind == K_SK || sn, wide = tk.kind <= K_A4;
        const bool qk = tk.kind == K_Q || tk.kind == K_QH, ak = tk.kind == K_A4 || tk.kind == K_A3 || split;
        const int nk = split ? HD / 64 / P_SPLIT : (ak ? HD / 64 : DM / 64), kb0 = tk.c * (HD / 64 / P_SPLIT);
        const int tok0 = tk.b * (wide ? 256 : (sn ? 64 : 128)), grp = (tok0 >> 7) + (wide ? 1 : 0);
        const uint32_t bytes = wide ? 49152 : (sn ? 24576 : 32768);
        const CUtensorMap* tx = tk.kind == K_B1 ? &mp.bx : (qk ? &mp.x : (sn ? &mp.ox64 : (ak ? &mp.ox : &mp.bo)));
        const int npre = split && (i == 0 || __any_sync(0xffffffffu, (int)(*(volatile unsigned*)&g_prog[grp] - 128 * E) < 0)) ? P_STAGES : 0;
        PRing rp = r;
        for (int kb = kb0; kb < kb0 + npre; kb++) {
            reserve(2);
            const uint32_t bar = sb + PB_F + r.st * 8;
            if (elect_one()) {
                mbar_expect_tx(bar, bytes);
                tma_load_wo(sb + r.w(false), &mp.wo, tk.a * 128, kb * 2, bar);
                tma_load_wo(sb + r.w(false) + 8192, &mp.wo, tk.a * 128 + 64, kb * 2, bar);
            }
            r.next(2);
        }
        if (tk.kind == K_B2) {
            wait_count_warp(&g_cnt[C_B1 + (tk.b >> 2)], 48 * E);
            if ((tk.b & 3) == 0 && tk.b > 0) wait_count_warp(&g_cnt[C_B1 + (tk.b >> 2) - 1], 48 * E);
        } else if (tk.kind == K_B3) wait_count_warp(&g_cnt[C_B2 + tk.b], 8 * E);
        else if (ak) wait_count_warp(&g_prog[grp], 128 * E);
        fence_proxy_global();
        for (int kb = kb0; kb < kb0 + npre; kb++) {
            if (elect_one()) tma_load_2d(sb + rp.x(false), tx, kb * 64, tok0, sb + PB_F + rp.st * 8);
            rp.next(2);
        }
        if (elect_one()) {
            sts128(sb + PS_T + (i & 1) * 16, make_uint4((uint32_t)tk.kind | ((uint32_t)id << 8), (uint32_t)tk.a, (uint32_t)tk.b, (uint32_t)tk.c));
            mbar_arrive(sb + PB_TF + (i & 1) * 8);
        }
        if (tk.kind == K_END) break;
        if (tk.kind == K_B2) {
            for (int j = 0; j < 16; j++) {
                reserve(2);
                const uint32_t bar = sb + PB_F + r.st * 8;
                if (elect_one()) {
                    mbar_expect_tx(bar, 2 * 15360);
#pragma unroll
                    for (int u = 0; u < 2; u++) asm volatile("cp.async.bulk.tensor.4d.shared::cluster.global.mbarrier::complete_tx::bytes [%0], [%1, {%3, %4, %5, %6}], [%2];"
                                 :: "r"(sb + (u ? r.x(false) : r.w(false))), "l"(&mp.b40), "r"(bar), "r"(j * 64), "r"(0), "r"(u), "r"(tk.b * 32 - 8) : "memory");
                }
                r.next(2);
            }
            continue;
        }
        const CUtensorMap* tw = tk.kind == K_B1 ? &mp.bw : (qk ? &mp.wq : (ak ? &mp.wo : &mp.bwo));
        for (int kb = kb0 + npre; kb < kb0 + nk; kb++) {
            reserve(wide ? 3 : 2);
            const uint32_t aw = sb + r.w(wide), ax = sb + r.x(wide), bar = sb + PB_F + r.st * 8;
            if (elect_one()) {
                mbar_expect_tx(bar, bytes);
                if (ak || tk.kind == K_B3) {
                    tma_load_wo(aw, tw, tk.a * 128, kb * 2, bar);
                    tma_load_wo(aw + 8192, tw, tk.a * 128 + 64, kb * 2, bar);
                } else {
                    tma_load_2d(aw, tw, tk.a * 128, kb * 64, bar);
                    tma_load_2d(aw + 8192, tw, tk.a * 128 + 64, kb * 64, bar);
                }
                tma_load_2d(ax, tx, kb * 64, tok0, bar);
                if (wide) tma_load_2d(ax + 16384, tx, kb * 64, tok0 + 128, bar);
            }
            r.next(wide ? 3 : 2);
        }
    }
    if (elect_one()) {
        __threadfence();
        if (atomicAdd(&g_done, 1u) == E * mp.list.nworker - 1) { __threadfence(); *(volatile unsigned*)&g_epoch = E; }
    }
}
DEVI void post_helper(uint32_t sb, int g) {
    for (int n = 0;; n++) {
        mbar_wait_sleepy(sb + PB_S + g * 8, n & 1);
        const int cnt = (int)lds32(sb + PS_SIG + g * 8 + (n & 1) * 4);
        if (cnt < 0) break;
        signal_count(&g_cnt[cnt]);
    }
}
template <int BN>
DEVI void p_narrow(const PMaps& mp, const PTask& tk, uint32_t sb, int g, int warp, PRing& r, int& nsig) {
    const int barid = 1 + g, tid = threadIdx.x;
    const bool elected = (tid & 127) == 0, split = BN == 64 || tk.kind == K_SK;
    constexpr int NV = BN / 16;
    float d[BN / 2];
    const int nk = split ? HD / 64 / P_SPLIT : (tk.kind == K_A3 ? HD / 64 : DM / 64);
    p_kblock<BN, true>(d, sb, g, r);
#pragma unroll 1
    for (int kb = 1; kb < nk; kb++) p_kblock<BN, false>(d, sb, g, r);
    wg_wait<0>();
    reg_fence<BN / 2>(d);
    p_release(sb, r);
    if (split) {
        const int tile = (tk.b * (BN / 64) - 2 * (16 - P_NSK)) * 8 + tk.a * (BN / 64);
        uint4* const base = g_skp + (uint32_t)(tile * P_SPLIT * 1024 + g * NV * 128 + (tid & 127));
#pragma unroll
        for (int j = 0; j < NV; j++)
            base[tk.c * NV * 256 + j * 128] = make_uint4(pack_bf16(d[8 * j], d[8 * j + 1]), pack_bf16(d[8 * j + 2], d[8 * j + 3]),
                                                         pack_bf16(d[8 * j + 4], d[8 * j + 5]), pack_bf16(d[8 * j + 6], d[8 * j + 7]));
        nbar_sync(barid, 128);
        if (elected) {
            unsigned old;
            asm volatile("atom.acq_rel.gpu.global.add.u32 %0, [%1], 1;" : "=r"(old) : "l"(&g_cnt_sk[tile * 2 + g]) : "memory");
            sts32(sb + PS_SK + g * 4, old % P_SPLIT);
        }
        nbar_sync(barid, 128);
        const bool last = lds32(sb + PS_SK + g * 4) == P_SPLIT - 1;
        nbar_sync(barid, 128);
        if (!last) return;
        uint4 v[(P_SPLIT - 1) * NV];
#pragma unroll
        for (int j = 0; j < (P_SPLIT - 1) * NV; j++) v[j] = __ldcg(base + ((tk.c + 1 + j / NV) % P_SPLIT) * NV * 256 + (j % NV) * 128);
#pragma unroll
        for (int j = 0; j < (P_SPLIT - 1) * NV; j++) {
            float* e = d + 8 * (j % NV);
            e[0] += __uint_as_float(v[j].x << 16); e[1] += __uint_as_float(v[j].x & 0xFFFF0000u);
            e[2] += __uint_as_float(v[j].y << 16); e[3] += __uint_as_float(v[j].y & 0xFFFF0000u);
            e[4] += __uint_as_float(v[j].z << 16); e[5] += __uint_as_float(v[j].z & 0xFFFF0000u);
            e[6] += __uint_as_float(v[j].w << 16); e[7] += __uint_as_float(v[j].w & 0xFFFF0000u);
        }
    }
    const bool qh = BN == 128 && tk.kind == K_QH;
    const POut o = {qh ? &mp.cq : &mp.cout, tk.a * 128 + g * 64, tk.b * BN, 0, qh};
    uint32_t q[BN / 4];
#pragma unroll
    for (int j = 0; j < BN / 4; j++) q[j] = pack_bf16(d[2 * j], d[2 * j + 1]);
    if (BN == 64 && elected) bulk_wait_read();
#pragma unroll
    for (int c = 0; c < BN / 64; c++) p_store(q + 16 * c, o, c, sb + PS_STG + g * 16384, warp, tid & 31, barid, elected);
    if (BN == 64 && elected) bulk_wait_read();
    if (elected && qh) { bulk_wait_all(); p_signal(sb, g, tk.b == 0 ? C_QH : C_Q, nsig); }
}
DEVI void post_consumer(const PMaps& mp, uint32_t sb, int g, int warp) {
    const int barid = 1 + g, tid = threadIdx.x, lane = tid & 31;
    const bool elected = (tid & 127) == 0;
    const uint32_t stg = sb + PS_STG + g * 16384;
    int nsig = 0;
    PRing r = {0, 0, 0};
    uint32_t pk[64];
    POut out;
    bool pend = false;
#pragma unroll
    for (int i = 0; i < 64; i++) pk[i] = 0u;
    for (int i = 0;; i++) {
        const uint32_t bTF = sb + PB_TF + (i & 1) * 8;
        if (pend) {
            uint32_t now;
            asm volatile("{.reg .pred p, q; mbarrier.test_wait.parity.shared::cta.b64 p, [%1], %2; bar.red.and.pred q, %3, 128, p; selp.u32 %0, 1, 0, q;}"
                         : "=r"(now) : "r"(bTF), "r"((i >> 1) & 1), "r"(barid) : "memory");
            if (!now || (lds32(sb + PS_T + (i & 1) * 16) & 255u) > K_A4) {
#pragma unroll
                for (int c = 0; c < 4; c++) p_store(pk + 16 * c, out, c, stg, warp, lane, barid, elected);
                if (elected && out.cnt != C_NONE) { bulk_wait_all(); p_signal(sb, g, out.cnt, nsig); }
                pend = false;
            }
        }
        mbar_wait(bTF, (i >> 1) & 1);
        const uint4 tw = lds128(sb + PS_T + (i & 1) * 16);
        mbar_arrive(sb + PB_TE + (i & 1) * 8);
        const PTask tk = {(int)(tw.x & 255u), (int)tw.y, (int)tw.z, (int)tw.w};
        if (tk.kind == K_END) break;
        if (tk.kind <= K_A4) {
            float d[128];
            const int nk = tk.kind == K_A4 ? HD / 64 : DM / 64;
            p_kblock<256, true>(d, sb, g, r);
            if (pend) p_store(pk, out, 0, stg, warp, lane, barid, elected);
#pragma unroll
            for (int c = 1; c < 4; c++) {
                p_kblock<256, false>(d, sb, g, r);
                if (pend) p_store(pk + 16 * c, out, c, stg, warp, lane, barid, elected);
            }
#pragma unroll 1
            for (int kb = 4; kb < nk; kb++) {
                p_kblock<256, false>(d, sb, g, r);
                if (kb == 6 && pend && elected && out.cnt != C_NONE) { bulk_wait_all(); p_signal(sb, g, out.cnt, nsig); }
            }
            wg_wait<0>();
            reg_fence<128>(d);
            p_release(sb, r);
#pragma unroll
            for (int j = 0; j < 64; j++) pk[j] = pack_bf16(d[2 * j], d[2 * j + 1]);
            out.map = tk.kind == K_Q ? &mp.cq : (tk.kind == K_B1 ? &mp.cb : &mp.cout);
            out.col = tk.a * 128 + g * 64 + (tk.kind == K_B3 ? DM : 0);
            out.tok = tk.b * 256;
            out.cnt = tk.kind == K_Q ? C_Q + tk.b : (tk.kind == K_B1 ? C_B1 + tk.b : C_NONE);
            out.blocked = tk.kind == K_Q;
            pend = true;
        } else if (tk.kind == K_B2) {
#pragma unroll 2
            for (int j = 0; j < 16; j++) {
                mbar_wait(sb + PB_F + r.st * 8, r.ph);
                const uint32_t a = sb + (g ? r.x(false) : r.w(false));
                battn_warp(a, sb + PB_E + r.st * 8, tk.b * 32, g, j * 2 + (warp >> 1), warp >> 1, warp & 1, lane);
                r.next(2);
            }
            nbar_sync(barid, 128);
            if (elected) p_signal(sb, g, C_B2 + (tk.b >> 2), nsig);
#pragma unroll
            for (int j = 0; j < 64; j++) pk[j] = 0u;
        } else {
            if (tk.kind == K_SN) p_narrow<64>(mp, tk, sb, g, warp, r, nsig); else p_narrow<128>(mp, tk, sb, g, warp, r, nsig);
#pragma unroll
            for (int j = 0; j < 64; j++) pk[j] = 0u;
        }
    }
    if (elected) { bulk_wait_all(); p_signal(sb, g, -1, nsig); }
}
DEVI void post_init(uint32_t sb) {
    for (int i = 0; i < P_STAGES; i++) { mbar_init(sb + PB_F + i * 8, 1); mbar_init(sb + PB_E + i * 8, 8); }
    for (int i = 0; i < 2; i++) { mbar_init(sb + PB_TF + i * 8, 1); mbar_init(sb + PB_TE + i * 8, 256); mbar_init(sb + PB_S + i * 8, 1); }
    fence_mbar_init();
}

constexpr unsigned long long R_TORD_PACK = 0xfae93542dc187b60ull;
__host__ __device__ constexpr int r_tord(int pos) { return (int)((R_TORD_PACK >> (4 * pos)) & 15ull); }
__host__ __device__ constexpr int r_tinv(int T) { for (int p = 0; p < 16; p++) if (r_tord(p) == T) return p; return 0; }
__host__ __device__ constexpr bool r_pos_ss(int pos) { return pos % 3 == 2; }
__host__ __device__ constexpr int r_ss(int pos) { return pos / 3; }
__host__ __device__ constexpr int r_rs(int pos) { return pos - pos / 3; }
constexpr int R_NRS = 11, R_NSS = 5;
constexpr int R_G1 = 3, R_G2 = 9, R_G3 = 12;
#define REG_KB 232
constexpr int X_SLOTS = 4;
constexpr int X_NST = 8;

constexpr int RS_WSS  = 0;
constexpr int RS_WO   = RS_WSS + R_NSS * 16384;
constexpr int RS_MEM  = RS_WO + 5 * 16384;
constexpr int RS_O    = RS_MEM + 16384;
constexpr int RS_SX   = RS_O + 2048;
constexpr int RS_BAR  = RS_SX + 2048;
constexpr int RS_TAIL = RS_BAR + 1024;
constexpr int RS_WO5  = RS_TAIL;
constexpr int RS_K    = RS_WO5 + 16384;
constexpr int RS_V    = RS_K + 10240;
constexpr int RS_Q    = RS_V + 10240;
constexpr int RS_QX   = RS_Q + 2048;
constexpr int RS_QEND = RS_QX + 8192;
constexpr int RS_X    = RS_TAIL;
constexpr int X_PITCH = X_SLOTS * 4096;
constexpr int RS_XD   = RS_X + 2 * X_PITCH;
constexpr int RS_WX   = RS_XD + 8192;
constexpr int RS_XE   = RS_WX + 4096;
constexpr int RS_KEND = RS_XE + 2048;
constexpr int RS_EV   = RS_BAR + 256;
constexpr int R_SMEM  = RS_KEND > RS_QEND ? RS_KEND : RS_QEND;
static_assert(R_SMEM <= 232448 && P_SMEM <= R_SMEM, "smem");
static_assert(RS_TAIL % 1024 == 0 && RS_MEM % 1024 == 0, "alignment");

constexpr int RB_G = RS_BAR, RB_K = RS_BAR + 24, RB_V = RS_BAR + 32, RB_KV = RS_BAR + 40, RB_QX = RS_BAR + 48, RB_O = RS_BAR + 56;
constexpr int RB_ATT = RS_BAR + 64, RB_W = RS_BAR + 72, RB_SF = RS_BAR + 80, RB_SE = RB_SF + 40, RB_XF = RB_SE + 40;
constexpr int RB_VX = RB_XF + 48, RB_WO = RB_XF + 56, RB_T = RB_XF + 64, RB_G3 = RB_XF + 72, RS_INV = RB_XF + 16;
static_assert(RB_G3 + 8 <= RS_EV, "barriers");
constexpr uint32_t SB0 = 1024;
__host__ __device__ constexpr uint32_t cdesc(uint32_t off, uint32_t lbo) { return ((SB0 + off) >> 4) | ((lbo >> 4) << 16); }
#define SCHED_FENCE() __syncwarp()
constexpr int NB_BIG = 1, NB_Q = 2, NB_AUX = 3, NB_WO = 4, NB_XS = 5, NB_WG = 6, NB_PAIR = 8, NB_PRO = 12;

DEVI int tid_now() { int t; asm volatile("mov.u32 %0, %%tid.x;" : "=r"(t)); return t; }
DEVI uint32_t a_frag_off(int lane, int warp) { return (uint32_t)((((lane >> 4) * 8 + (lane & 7)) * 128) + (((2 * warp + ((lane >> 3) & 1)) ^ (lane & 7)) * 16)); }
DEVI uint32_t b_frag_off(int lane) { return (uint32_t)((lane & 3) * 64 + (((lane >> 2) * 8) ^ ((lane & 2) * 16))); }
DEVI void lds_b(uint32_t* b, uint32_t a) {
    asm volatile("ld.shared.v2.u32 {%0,%1}, [%2];" : "=r"(b[0]), "=r"(b[1]) : "r"(a) : "memory");
    asm volatile("ld.shared.v2.u32 {%0,%1}, [%2];" : "=r"(b[2]), "=r"(b[3]) : "r"(a + 256) : "memory");
}
DEVI uint32_t clk32() { unsigned long long c; asm volatile("mov.u64 %0, %%clock64;" : "=l"(c)); return (uint32_t)c; }

__host__ __device__ constexpr int x_pair(int j) { return j < 2 || j > 5 ? j : (j == 2 ? 5 : j - 1); }
DEVI void x_load(uint32_t sb, int seg, int j, int g, const CUtensorMap* tmX) {
    const uint32_t bar = sb + RB_XF + g * 8;
    mbar_expect_tx(bar, 4096);
    tma_load_3d(sb + RS_X + g * X_PITCH + (j % X_SLOTS) * 4096, tmX + (j == 3), g * 32, seg * 32, x_pair(j) * 2, bar);
    if (j == 3) tma_load_3d(sb + RS_SX + g * (RS_XE - RS_SX), tmX + 1, g * 32, seg * 32, x_pair(3) * 2 + 1, bar);
}
DEVI void x_refill(uint32_t sb, int seg, int j, int g, int warp, const CUtensorMap* tmX) {
    const int sn = j + X_SLOTS < X_NST ? seg : seg + 1;
    if (warp == (j & 3) && sn < NSEG) {
        if (elect_one()) x_load(sb, sn, (j + X_SLOTS) % X_NST, g, tmX);
    }
}
template <int J, int Q0, int Q1, int DQ>
DEVI void x_steps(float* xa, const uint32_t* w, int g0) {
    const int g = (int)opaque((uint32_t)g0);
    const uint32_t dW0 = cdesc(RS_WSS, 16) + g * 768, dW1 = cdesc(RS_WSS + 8192, 16) - g * 256;
#pragma unroll
    for (int q = Q0; q < Q1; q += DQ) {
        const int pos = r_tinv(2 * x_pair(J) + (q >> 2)), kk = (q >> 1) & 1, mt = q & 1;
        const uint32_t db = (J == 3 && q >= 4 ? cdesc(RS_SX, 16) + g * ((RS_XE - RS_SX) >> 4)
                                                    : cdesc(RS_X + (J % X_SLOTS) * 4096, 16) + g * (X_PITCH >> 4) + (q >> 2) * 128) + kk * 2;
        if (J == 0 && q < 2)   wgmma_n32_rs_first(xa + 16 * mt, &w[((r_rs(pos) * 2 + kk) * 2 + mt) * 4], db);
        else if (J == 0 && q == 3) wgmma_n32_ss(xa + 16, cdesc(RS_WX, 16) + g * 128, db);
        else if (r_pos_ss(pos)) wgmma_n32_ss(xa + 16 * mt, (mt ? dW1 : dW0) + r_ss(pos) * 1024 + kk * 128, db);
        else                   wgmma_n32_rs(xa + 16 * mt, &w[((r_rs(pos) * 2 + kk) * 2 + mt) * 4], db);
    }
}
DEVI void x_first(float* xa, const uint32_t* w, uint32_t sb, int seg, int g0, int warp, const CUtensorMap* tmX) {
    wg_fence();
    x_steps<0, 0, 8, 1>(xa, w, g0); wg_commit();
    x_steps<1, 0, 8, 1>(xa, w, g0); wg_commit();
    x_steps<2, 0, 8, 1>(xa, w, g0); wg_commit();
    x_steps<3, 0, 4, 1>(xa, w, g0); wg_commit();
    const int g = (int)opaque((uint32_t)g0);
    wg_wait<3>(); x_refill(sb, seg, 0, g, warp, tmX);
    wg_wait<2>(); x_refill(sb, seg, 1, g, warp, tmX);
    wg_wait<1>(); x_refill(sb, seg, 2, g, warp, tmX);
    wg_wait<0>(); x_refill(sb, seg, 3, g, warp, tmX);
    reg_fence<32>(xa);
    mbar_wait(sb + RB_XF + g * 8, 1);
}
DEVI void x_second(float* xa, uint32_t* a, uint32_t aA0, const uint32_t* w, uint32_t sb, int seg, int g0, int warp, const CUtensorMap* tmX) {
    wg_fence();
    x_steps<4, 0, 8, 1>(xa, w, g0); wg_commit();
    x_steps<5, 0, 8, 1>(xa, w, g0); wg_commit();
    x_steps<3, 4, 8, 1>(xa, w, g0);
    x_steps<6, 1, 8, 2>(xa, w, g0); x_steps<7, 1, 8, 2>(xa, w, g0); wg_commit();
    x_steps<6, 0, 8, 2>(xa, w, g0); x_steps<7, 0, 8, 2>(xa, w, g0); wg_commit();
    const int g = (int)opaque((uint32_t)g0);
    wg_wait<3>(); x_refill(sb, seg, 4, g, warp, tmX);
    SCHED_FENCE();
#pragma unroll
    for (int q = 0; q < 4; q++) ldsm4t(a + 4 * q, aA0 + (q & 1) * (8192 - g * 16384) + (q >> 1) * 2048);
    SCHED_FENCE();
    wg_wait<2>(); x_refill(sb, seg, 5, g, warp, tmX);
    wg_wait<1>();
    reg_fence<16>(xa + 16);
}
DEVI void x_finish(float* xa, uint32_t sb, int seg, int g, int warp, int lane, const CUtensorMap* tmX) {
    const uint32_t d = sb + RS_XD + (lane >> 4) * 2048 + warp * 256 + (lane & 15) * 16;
#pragma unroll
    for (int i = 0; i < 2; i++) {
        const float* x = xa + 16 + 8 * i;
        sts128(d + (g ^ 1) * 1024 + i * 4096, make_uint4(pack_bf16(x[0], x[1]), pack_bf16(x[2], x[3]), pack_bf16(x[4], x[5]), pack_bf16(x[6], x[7])));
    }
    nbar_sync(NB_PAIR + warp, 64);
    float y[16];
#pragma unroll
    for (int i = 0; i < 2; i++) {
        const uint4 v = lds128(d + g * 1024 + i * 4096);
        const uint32_t u[4] = {v.x, v.y, v.z, v.w};
#pragma unroll
        for (int j = 0; j < 4; j++) { y[8 * i + 2 * j] = __uint_as_float(u[j] << 16); y[8 * i + 2 * j + 1] = __uint_as_float(u[j] & 0xFFFF0000u); }
    }
    reg_fence<16>(y);
    wg_wait<0>();
    reg_fence<16>(xa);
    uint32_t p[8];
#pragma unroll
    for (int j = 0; j < 8; j++) p[j] = pack_bf16(xa[2 * j] + y[2 * j], xa[2 * j + 1] + y[2 * j + 1]);
    __syncwarp();
    stsm4(d + g * 1024, p[0], p[1], p[2], p[3]);
    stsm4(d + g * 1024 + 4096, p[4], p[5], p[6], p[7]);
    nbar_arrive(NB_XS, 256 + 32);
    x_refill(sb, seg, X_NST - 2, g, warp, tmX);
    x_refill(sb, seg, X_NST - 1, g, warp, tmX);
}
DEVI void x_send(uint32_t sb, int seg, uint32_t rank) {
    mbar_wait(sb + RB_ATT, (seg - 1) & 1);
    nbar_sync(NB_XS, 256 + 32);
    if (elect_one()) {
        fence_proxy_async();
        bulk_copy_s2c(mapa(sb + (rank == 1 ? RS_K : RS_V) + 2048, 0), sb + RS_XD, 8192, mapa(sb + (rank == 1 ? RB_KV : RB_VX), 0));
    }
    __syncwarp();
}

template <bool XP>
DEVI void mem_pass(float* c0, float* c1, uint32_t* a, const uint32_t* w, uint32_t sb, uint32_t aA0, uint32_t aB, int g, int warp, int s) {
    const uint32_t aA1 = aA0 + 8192 - g * 16384, par = (s - 1) & 1;
    uint32_t b[2][4], e[4];
    float d0[4], d1[4];
    if (XP) ldsm4t(e, aA0 + opaque((RS_WX - RS_WSS) - g * (8192 + 2048)));
#pragma unroll
    for (int q = XP ? 4 : 0; q < 4; q++) ldsm4t(a + 4 * q, ((q & 1) ? aA1 : aA0) + (q >> 1) * 2048);
#pragma unroll
    for (int i = 0; i < 4; i++) { c0[i] = 0.f; c1[i] = 0.f; d0[i] = 0.f; d1[i] = 0.f; }
    EV(EV_BIG0, s, 0);
    mbar_wait(sb + RB_G, par);
    EV(EV_BIG0, s, 1);
    lds_b(b[0], aB + r_tord(0) * 1024);
    bool in = false;
#pragma unroll
    for (int pos = 0; pos < 16; pos++) {
        if (pos + 1 < 16) {
            if (pos + 1 == R_G1 && !in) mbar_wait(sb + RB_G + 8, par);
            if (pos + 1 == R_G2 && !in) mbar_wait(sb + RB_G + 16, par);
            if (pos + 1 == R_G3) { if (!in) mbar_wait(sb + RB_G3, par); EV(EV_BIG0, s, 2); }
            lds_b(b[(pos + 1) & 1], aB + r_tord(pos + 1) * 1024);
        }
        if (pos + 2 == R_G1) in = mbar_try(sb + RB_G + 8, par);
        if (pos + 2 == R_G2) in = mbar_try(sb + RB_G + 16, par);
        if (pos + 2 == R_G3) in = mbar_try(sb + RB_G3, par);
        if (XP && pos == 12) in = s == NSEG - 1 || mbar_try(sb + RB_XF + g * 8, 0);
        if (XP && pos == 14) { if (!in) mbar_wait(sb + RB_XF + g * 8, 0); in = mbar_try(sb + RB_ATT, par); }
        const uint32_t* bb = b[pos & 1];
        const uint32_t* aa = r_pos_ss(pos) ? a : &w[r_rs(pos) * 16];
        mma16816(c1, aa + 4, bb[0], bb[1]);
        mma16816(d1, XP && pos == 0 ? e : aa + 12, bb[2], bb[3]);
        mma16816(c0, aa, bb[0], bb[1]);
        mma16816(d0, aa + 8, bb[2], bb[3]);
        if (r_pos_ss(pos) && pos + 3 < 16) {
#pragma unroll
            for (int q = 0; q < 4; q++) ldsm4t(a + 4 * q, ((q & 1) ? aA1 : aA0) + (r_ss(pos) + 1) * 16384 + (q >> 1) * 2048);
        }
        SCHED_FENCE();
    }
    if (XP && !in) mbar_wait(sb + RB_ATT, par);
#pragma unroll
    for (int i = 0; i < 4; i++) { c1[i] += d1[i]; c0[i] += d0[i]; }
}

DEVI uint32_t k_frag_off(int lane) { return (uint32_t)((((lane >> 3) & 1) * 16 + (lane >> 4) * 8 + (lane & 7)) * 16); }
DEVI uint32_t v_frag_off(int lane) { return (uint32_t)(((lane >> 3) & 1) * 2048 + ((lane >> 4) * 8 + (lane & 7)) * 16); }
DEVI void pv_pair(float (*o)[4], const uint32_t* p, const uint32_t* v) {
#pragma unroll
    for (int n = 0; n < 4; n++) mma16816(o[n], p, v[2 * n], v[2 * n + 1]);
}
DEVI void pv_single(float (*o)[4], const uint32_t* p, const uint32_t* v) {
#pragma unroll
    for (int n = 0; n < 4; n++) mma1688(o[n], p[0], p[1], v[n]);
}
DEVI void s_tile(const uint32_t* qa, const uint32_t* k, float& s0, float& s1) {
    float c[4][4];
#pragma unroll
    for (int q = 0; q < 4; q++) { c[q][0] = c[q][1] = c[q][2] = c[q][3] = 0.f; }
#pragma unroll
    for (int q = 0; q < 4; q++) {
        mma16816(c[2 * (q & 1)], qa + 4 * q, k[4 * q], k[4 * q + 1]);
        mma16816(c[2 * (q & 1) + 1], qa + 4 * q, k[4 * q + 2], k[4 * q + 3]);
    }
    s0 = (c[0][0] + c[1][2]) + (c[2][0] + c[3][2]);
    s1 = (c[0][1] + c[1][3]) + (c[2][1] + c[3][3]);
}
DEVI void mem_scores(uint32_t sb, int s, int lane) {
    const uint32_t ka = sb + RS_K + k_frag_off(lane), sa = sb + RS_SX + 1024 + lane * 8;
    uint32_t qa[16], km[16];
    nbar_sync(NB_Q, 256);
#pragma unroll
    for (int q = 0; q < 4; q++) ldsm4t(qa + 4 * q, sb + RS_Q + q * 512 + lane * 16);
    mbar_wait(sb + RB_K, s & 1);
#pragma unroll
    for (int q = 0; q < 4; q++) ldsm4t(km + 4 * q, ka + q * 512);
    SCHED_FENCE();
    float s0, s1;
    s_tile(qa, km, s0, s1);
    asm volatile("st.shared.v2.f32 [%0], {%1,%2};" :: "r"(sa), "f"(s0 * SCALE_LOG2E), "f"(s1 * SCALE_LOG2E) : "memory");
    nbar_arrive(NB_XS, 128 + 32);
}
DEVI float quad_max(float m) {
    return fmaxf(fmaxf(m, __shfl_xor_sync(0xffffffffu, m, 1)), fmaxf(__shfl_xor_sync(0xffffffffu, m, 2), __shfl_xor_sync(0xffffffffu, m, 3)));
}
DEVI void mem_attn(uint32_t sb, int s, int warp, int lane) {
    const uint32_t va = sb + RS_V + warp * 512, sa = sb + RS_SX + lane * 8;
    [[maybe_unused]] constexpr int g = 0;
    float o[4][4], mx, l = 0.f;
    {
        const uint32_t ka = sb + RS_K + k_frag_off(lane) + (1 + warp) * 2048;
        uint32_t qa[16], kx[16];
        const bool in = mbar_try(sb + RB_KV, s & 1);
        nbar_sync(NB_Q, 256);
        EV(EV_BIG0 && lds32(sb + RS_Q) != 0x12345678u, s, 8);
#pragma unroll
        for (int q = 0; q < 4; q++) ldsm4t(qa + 4 * q, sb + RS_Q + q * 512 + lane * 16);
        if (!in) mbar_wait(sb + RB_KV, s & 1);
#pragma unroll
        for (int q = 0; q < 4; q++) ldsm4t(kx + 4 * q, ka + q * 512);
        const bool vin = mbar_try(sb + RB_VX, s & 1);
        SCHED_FENCE();
        float s0, s1;
        s_tile(qa, kx, s0, s1);
        asm volatile("st.shared.v2.f32 [%0], {%1,%2};" :: "r"(sa + warp * 256), "f"(s0), "f"(s1) : "memory");
        nbar_sync(NB_WG, 128);
        float sc[8];
#pragma unroll
        for (int n = 0; n < 4; n++) { const float2 v = lds64f(sa + n * 256); sc[2 * n] = v.x; sc[2 * n + 1] = v.y; }
        if (!vin) mbar_wait(sb + RB_VX, s & 1);
        mx = quad_max(fmaxf(fmaxf(fmaxf(sc[0], sc[1]), fmaxf(sc[2], sc[3])), fmaxf(fmaxf(sc[4], sc[5]), fmaxf(sc[6], sc[7])))) * SCALE_LOG2E;
        uint32_t vx[16], p[8];
#pragma unroll
        for (int q = 0; q < 4; q++) ldsm4(vx + 4 * q, va + 2048 + (q >> 1) * 4096 + (q & 1) * 256 + v_frag_off(lane));
#pragma unroll
        for (int n = 0; n < 4; n++) {
            const float e0 = ex2(fmaf(sc[2 * n], SCALE_LOG2E, -mx)), e1 = ex2(fmaf(sc[2 * n + 1], SCALE_LOG2E, -mx));
            l += e0 + e1;
            p[2 * n] = pack_bf16(e0, e1); p[2 * n + 1] = __float_as_uint(e0);
        }
#pragma unroll
        for (int n = 0; n < 4; n++) { o[n][0] = o[n][1] = o[n][2] = o[n][3] = 0.f; }
        pv_pair(o, p, vx);
        pv_pair(o, p + 4, vx + 8);
    }
    const uint32_t dst = sb + RS_O + warp * 512 + (lane & 3) * 128 + (lane >> 2) * 16, dl = sb + RS_INV + (lane & 28);
    EV(EV_BIG0, s, 5);
    mbar_wait(sb + RB_V, s & 1);
    uint32_t vm[4], p[2];
    ldsm4(vm, va + lane * 16);
    nbar_sync(NB_XS, 128 + 32);
    EV(EV_BIG0 && lds32(sb + RS_Q) != 0x12345678u, s, 9);
    const float2 sm = lds64f(sa + 1024);
    const float s0 = sm.x, s1 = sm.y;
    const float m = quad_max(fmaxf(mx, fmaxf(s0, s1)));
    const float e0 = ex2(s0 - m), e1 = ex2(s1 - m), f = ex2(mx - m);
    p[0] = pack_bf16(e0, e1); p[1] = __float_as_uint(e0);
#pragma unroll
    for (int n = 0; n < 4; n++) { o[n][0] *= f; o[n][1] *= f; }
    pv_single(o, p, vm);
    l = fmaf(l, f, e0 + e1);
    l = (l + __shfl_xor_sync(0xffffffffu, l, 1)) + (__shfl_xor_sync(0xffffffffu, l, 2) + __shfl_xor_sync(0xffffffffu, l, 3));
    const uint4 u = make_uint4(pack_bf16(o[0][0], o[0][1]), pack_bf16(o[1][0], o[1][1]), pack_bf16(o[2][0], o[2][1]), pack_bf16(o[3][0], o[3][1]));
    st_async128(mapa(dst, 1), u.x, u.y, u.z, u.w, mapa(sb + RB_O, 1));
    st_async128(mapa(dst, 2), u.x, u.y, u.z, u.w, mapa(sb + RB_O, 2));
    st_async32(mapa(dl, 1 + (warp & 1)), __float_as_uint(l), mapa(sb + RB_O, 1 + (warp & 1)));
    sts128(dst, u);
    sts32(dl, __float_as_uint(l));
    __syncwarp();
    if (elect_one()) mbar_arrive(sb + RB_O);
    EV(EV_BIG0, s, 15);
}

DEVI void ta_mask(float* c, int cw, int lane) {
    const int mt = cw >= 3, over = 8 * (cw - 3 * mt - 1) + 2 * (lane & 3) - 16 * mt - (lane >> 2);
    if (over > 0) c[0] = -INFINITY;
    if (over >= 0) c[1] = -INFINITY;
    if (over > 8) c[2] = -INFINITY;
    if (over >= 8) c[3] = -INFINITY;
}
DEVI void ta_scores(uint32_t sb, int seg, int warp, int lane) {
    const int tx = warp == 3 ? 0 : (warp == 2 ? 1 : 4 + 2 * warp), ty = warp == 3 ? 3 : tx + 1;
    const uint32_t qa = sb + RS_QX + ((warp < 2 ? 2 : 0) + ((lane >> 3) & 1)) * 2048 + ((lane >> 4) * 8 + (lane & 7)) * 16;
    const uint32_t ka = sb + RS_K + (warp < 2 ? tx - 3 : tx) * 2048 + lane * 16;
    float x[4] = {0.f, 0.f, 0.f, 0.f}, y[4] = {0.f, 0.f, 0.f, 0.f};
    mbar_wait(sb + RB_QX, seg & 1);
    if (warp < 3) {
#pragma unroll
        for (int j = 0; j < 4; j++) {
            uint32_t a0[4], a1[4], bx[4], by[4];
            ldsm4t(a0, qa + j * 512); ldsm4t(bx, ka + j * 512); ldsm4t(by, ka + 2048 + j * 512); ldsm4t(a1, qa + j * 512 + 256);
            mma16816(x, a0, bx[0], bx[1]); mma16816(y, a0, by[0], by[1]);
            mma16816(x, a1, bx[2], bx[3]); mma16816(y, a1, by[2], by[3]);
        }
        ta_mask(x, tx, lane); ta_mask(y, ty, lane);
    } else {
        mbar_wait(sb + RB_K, seg & 1);
#pragma unroll
        for (int j = 0; j < 4; j++) {
            uint32_t a0[4], a1[4], a2[4], a3[4], b[4];
            ldsm4t(a0, qa + j * 512); ldsm4t(b, ka + j * 512); ldsm4t(a2, qa + 4096 + j * 512);
            ldsm4t(a1, qa + j * 512 + 256); ldsm4t(a3, qa + 4096 + j * 512 + 256);
            mma16816(x, a0, b[0], b[1]); mma16816(y, a2, b[0], b[1]);
            mma16816(x, a1, b[2], b[3]); mma16816(y, a3, b[2], b[3]);
        }
    }
    nbar_sync(NB_WG + 1, 128);
    asm volatile("st.shared.v2.f32 [%0], {%1,%2};" :: "r"(sb + RS_QX + 4096 + tx * 256 + lane * 8), "f"(fmaxf(x[0], x[1])), "f"(fmaxf(x[2], x[3])) : "memory");
    asm volatile("st.shared.v2.f32 [%0], {%1,%2};" :: "r"(sb + RS_QX + 4096 + ty * 256 + lane * 8), "f"(fmaxf(y[0], y[1])), "f"(fmaxf(y[2], y[3])) : "memory");
    nbar_sync(NB_WG + 1, 128);
    float m[4] = {-INFINITY, -INFINITY, -INFINITY, -INFINITY};
#pragma unroll
    for (int n = 0; n < 8; n++) {
        if (n < 3 ? warp >= 2 : warp != 2) {
            const float2 v = lds64f(sb + RS_QX + 4096 + n * 256 + lane * 8);
            m[n < 3 ? 0 : 2] = fmaxf(m[n < 3 ? 0 : 2], v.x); m[n < 3 ? 1 : 3] = fmaxf(m[n < 3 ? 1 : 3], v.y);
        }
    }
#pragma unroll
    for (int o = 1; o < 4; o <<= 1) {
#pragma unroll
        for (int i = 0; i < 4; i++) m[i] = fmaxf(m[i], __shfl_xor_sync(0xffffffffu, m[i], o));
    }
    const float x0 = (warp < 2 ? m[2] : m[0]) * -SCALE_LOG2E, x1 = (warp < 2 ? m[3] : m[1]) * -SCALE_LOG2E;
    const float y0 = (warp == 2 ? m[0] : m[2]) * -SCALE_LOG2E, y1 = (warp == 2 ? m[1] : m[3]) * -SCALE_LOG2E;
    sts64(sb + RS_QX + tx * 256 + lane * 8, pack_bf16(ex2(fmaf(x[0], SCALE_LOG2E, x0)), ex2(fmaf(x[1], SCALE_LOG2E, x0))),
                                            pack_bf16(ex2(fmaf(x[2], SCALE_LOG2E, x1)), ex2(fmaf(x[3], SCALE_LOG2E, x1))));
    sts64(sb + RS_QX + ty * 256 + lane * 8, pack_bf16(ex2(fmaf(y[0], SCALE_LOG2E, y0)), ex2(fmaf(y[1], SCALE_LOG2E, y0))),
                                            pack_bf16(ex2(fmaf(y[2], SCALE_LOG2E, y1)), ex2(fmaf(y[3], SCALE_LOG2E, y1))));
}
template <int MT>
DEVI void ta_output(uint32_t sb, int seg, int head, int j, int lane) {
    const uint32_t pa = sb + RS_QX + MT * 768 + lane * 8, vb = sb + RS_V + j * 512;
    uint32_t p[6 + 4 * MT], v[12 + 8 * MT];
#pragma unroll
    for (int n = 0; n < 3 + 2 * MT; n++)
        asm volatile("ld.shared.v2.u32 {%0,%1}, [%2];" : "=r"(p[2 * n]), "=r"(p[2 * n + 1]) : "r"(pa + n * 256) : "memory");
#pragma unroll
    for (int q = 0; q < 2 + 2 * MT; q++) ldsm4(v + 4 * q, vb + (q >> 1) * 4096 + (q & 1) * 256 + v_frag_off(lane));
    ldsm4(v + 8 + 8 * MT, vb + 4096 + MT * 4096 + lane * 16);
    float o[4][4], l[4] = {0.f, 0.f, 0.f, 0.f};
#pragma unroll
    for (int n = 0; n < 4; n++) { o[n][0] = o[n][1] = o[n][2] = o[n][3] = 0.f; }
    mma16816(l, p, 0x3F803F80u, 0x3F803F80u);
    pv_pair(o, p, v);
    if (MT) { mma16816(l, p + 4, 0x3F803F80u, 0x3F803F80u); pv_pair(o, p + 4, v + 8); }
    mma1688(l, p[4 + 4 * MT], p[5 + 4 * MT], 0x3F803F80u);
    pv_single(o, p + 4 + 4 * MT, v + 8 + 8 * MT);
    const float i0 = rcp_fast(l[0]), i1 = rcp_fast(l[2]);
    bf16* dst = g_ox + (uint32_t)((seg * 32 + MT * 16 + (lane >> 2)) * HD + head * DH + j * 32 + (lane & 3) * 8);
    asm volatile("st.global.v4.u32 [%0], {%1,%2,%3,%4};" :: "l"(dst), "r"(pack_bf16(o[0][0] * i0, o[0][1] * i0)), "r"(pack_bf16(o[1][0] * i0, o[1][1] * i0)),
                 "r"(pack_bf16(o[2][0] * i0, o[2][1] * i0)), "r"(pack_bf16(o[3][0] * i0, o[3][1] * i0)) : "memory");
    asm volatile("st.global.v4.u32 [%0], {%1,%2,%3,%4};" :: "l"(dst + 8 * HD), "r"(pack_bf16(o[0][2] * i1, o[0][3] * i1)), "r"(pack_bf16(o[1][2] * i1, o[1][3] * i1)),
                 "r"(pack_bf16(o[2][2] * i1, o[2][3] * i1)), "r"(pack_bf16(o[3][2] * i1, o[3][3] * i1)) : "memory");
}

template <bool XP>
DEVI void big_main(const uint32_t* w, const uint32_t sb, const int g, const int warp, const uint32_t rank, const int head,
                   const CUtensorMap* tmX, const bf16* xg, const unsigned E) {
    float xa[32];
    uint32_t a[16];
    const uint32_t aB = __shfl_sync(0xffffffffu, sb + RS_MEM + (g * 32 + (tid_now() & 31)) * 16, tid_now() & 31);
#define lane0 ((int)(opaque(aB) >> 4) & 31)
    const uint32_t aA0 = sb + RS_WSS + g * (8192 + 4096) + a_frag_off(lane0, warp);
    const uint32_t aBf = sb + RS_MEM + g * 512 + b_frag_off(lane0);
    if constexpr (XP) {
        mbar_wait(sb + RB_XF + g * 8, 0);
        x_first(xa, w, sb, 0, g, warp, tmX);
        x_second(xa, a, aA0, w, sb, 0, g, warp, tmX);
        x_finish(xa, sb, 0, g, warp, lane0, tmX);
    }
    nbar_sync(NB_BIG, 256);
    for (int s = 0; s < NSEG; s++) {
        float c0[4], c1[4];
        mem_pass<XP>(c0, c1, a, w, sb, aA0, aBf, g, warp, s);
        EV(EV_BIG0 && c0[0] != 1.2345e30f, s, 3);
        const uint32_t xs = sb + RS_O + warp * 256 + lane0 * 8;
        sts64(xs + g * 1024, pack_bf16(c1[0], c1[1]), pack_bf16(c1[2], c1[3]));
        {
            const uint32_t d = sb + (XP ? (rank == 1 ? RS_K : RS_V) : RS_Q) + (g * 4 + warp) * 256 + lane0 * 4;
            const uint32_t rbar = XP ? mapa(sb + (rank == 1 ? RB_K : RB_V), 0) : 0u;
            nbar_sync(NB_PAIR + warp, 64);
            const float2 v = lds64f(xs + (g ^ 1) * 1024);
            const uint32_t v0 = __float_as_uint(v.x), v1 = __float_as_uint(v.y);
            const uint32_t p0 = pack_bf16(c0[0] + __uint_as_float(v0 << 16), c0[1] + __uint_as_float(v0 & 0xFFFF0000u));
            const uint32_t p1 = pack_bf16(c0[2] + __uint_as_float(v1 << 16), c0[3] + __uint_as_float(v1 & 0xFFFF0000u));
            if constexpr (XP) { st_async32(mapa(d, 0), p0, rbar); st_async32(mapa(d + 128, 0), p1, rbar); }
            else { sts32(d, p0); sts32(d + 128, p1); }
            EV(EV_BIG0, s, 4);
        }
        if constexpr (XP) {
            if (s == NSEG - 1) break;
            x_first(xa, w, sb, s + 1, g, warp, tmX);
            EV(EV_BIG0, s, 5);
            EVCAL(s);
            nbar_sync(NB_WO, 384);
            EV(EV_BIG0 && lds32(sb + RS_O) != 0x12345678u, s, 6);
            x_second(xa, a, aA0, w, sb, s + 1, g, warp, tmX);
            EV(EV_BIG0, s, 7);
            x_finish(xa, sb, s + 1, g, warp, lane0, tmX);
        } else {
            if (g == 0) {
                if (s < NSEG - 1) mem_attn(sb, s, warp, lane0);
            } else {
                if (s < NSEG - 1) { if (warp == 3) mem_scores(sb, s, lane0); else nbar_arrive(NB_Q, 256); }
                mbar_wait(sb + RB_KV, s & 1);
                if (s == 0 && warp == 0) {
                    wait_count_warp(&g_cnt[C_QH], 64 * E);
                    if (elect_one()) {
                        fence_proxy_global();
                        mbar_expect_tx(sb + RB_QX, 8192);
                        bulk_load(sb + RS_QX, g_qx + (uint32_t)(head * 4096), 8192, sb + RB_QX);
                    }
                    __syncwarp();
                }
                ta_scores(sb, s, warp, lane0);
            }
            EVCAL(s);
            mbar_wait(sb + RB_V, s & 1);
            mbar_wait(sb + RB_VX, s & 1);
            if (s < NSEG - 1) nbar_sync(NB_WO, 384); else nbar_sync(NB_BIG, 256);
            EV(EV_BIG0 && lds32(sb + RS_O) != 0x12345678u, s, 6);
            if (g == 0) ta_output<0>(sb, s, head, warp, lane0); else ta_output<1>(sb, s, head, warp, lane0);
            nbar_sync(NB_BIG, 256);
            EV(EV_BIG0 && lds32(sb + RS_O) != 0x12345678u, s, 7);
            if (g == 0 && warp == 0 && s + 1 < NSEG) {
                if (elect_one()) {
                    mbar_arrive_remote(mapa(sb + RB_ATT, 1));
                    mbar_arrive_remote(mapa(sb + RB_ATT, 2));
                    mbar_expect_tx(sb + RB_KV, 8192);
                    mbar_expect_tx(sb + RB_K, 2048);
                    mbar_expect_tx(sb + RB_V, 2048); mbar_expect_tx(sb + RB_VX, 8192);
                    mbar_arrive(sb + RB_T);
                }
                __syncwarp();
            }
        }
    }
    if constexpr (!XP) { if (tid_now() == 0) signal_count(&g_prog[(NSEG - 1) >> 2]); }
#undef lane0
}

template <int T, int K0, int K1>
DEVI void wo_part(float* acc) {
    constexpr uint32_t dWo = cdesc(T < 5 ? RS_WO + T * 16384 : RS_WO5, 16), dO = cdesc(RS_O, 128);
#pragma unroll
    for (int kk = K0; kk < K1; kk++) {
        if (kk == 0) { if (T < 3) wgmma_n8_ss_first<0>(acc, dWo, dO); else wgmma_n8_ss<0, 0>(acc, dWo, dO); }
        else wgmma_n8_ss<0, 1>(acc, dWo + kk * 128, dO + kk * 16);
    }
    wg_commit();
}
DEVI void red3(uint8_t* p, uint32_t a, uint32_t b, uint32_t c, uint32_t one) {
    asm volatile("red.relaxed.gpu.global.add.noftz.v4.bf16x2 [%0], {%1,%2,%3,%4};" :: "l"(p), "r"(a), "r"(b), "r"(c), "r"(one) : "memory");
}
constexpr int ACC_CH = 3 * 16 * 1024;
template <bool Q>
DEVI void wo_phase(uint32_t sb, int s, int warp, uint8_t* p, uint32_t ainv, int gap) {
    float a0[4], a1[4], a2[4];
    fence_proxy_async();
    const float2 iv = lds64f(ainv);
    SCHED_FENCE();
    const float i0 = rcp_fast(iv.x), i1 = rcp_fast(iv.y);
#define WORD(a, h) pack_bf16(a[2 * h] * i0, a[2 * h + 1] * i1)
    wg_fence();
    wo_part<0, 0, 8>(a0); wo_part<1, 0, 8>(a1); wo_part<2, 0, 8>(a2);
    wg_wait<1>(); reg_fence<4>(a0); reg_fence<4>(a1);
    red3(p, WORD(a0, 0), WORD(a0, 1), WORD(a1, 0), 0x3F80u);
    SCHED_FENCE();
    EV(warp == 0 && elect_one(), s, 11);
    wg_wait<0>(); reg_fence<4>(a2);
    red3(p + ACC_CH, WORD(a2, 0), WORD(a2, 1), WORD(a1, 1), 0x3F80u);
    SCHED_FENCE();
    { const uint32_t t = clk32() + gap; while ((int)(clk32() - t) < 0) { } }
    wg_fence();
    wo_part<3, 0, 8>(a0); wo_part<4, 0, 8>(a1);
    if (Q) {
        wo_part<5, 0, 8>(a2);
        wg_wait<1>(); reg_fence<4>(a0); reg_fence<4>(a1);
        red3(p + 2 * ACC_CH, WORD(a0, 0), WORD(a0, 1), WORD(a1, 0), 0x3F80u);
        SCHED_FENCE();
        wg_wait<0>(); reg_fence<4>(a2);
        red3(p + 3 * ACC_CH, WORD(a2, 0), WORD(a2, 1), WORD(a1, 1), 0x3F80u);
        nbar_arrive(NB_WO, 384);
    } else {
        wg_wait<1>();
        nbar_arrive(NB_WO, 384);
        wg_wait<0>(); reg_fence<4>(a0); reg_fence<4>(a1);
        red3(p + 2 * ACC_CH, WORD(a0, 0), WORD(a0, 1), WORD(a1, 0), 0x3F80u);
        red3(p + 3 * ACC_CH, 0u, 0u, WORD(a1, 1), 0x3F80u);
    }
#undef WORD
}
DEVI void unit_pack(uint32_t* u, uint32_t x0, uint32_t x1, uint32_t x2, uint32_t x3) {
    u[0] = __byte_perm(x0, x1, 0x5410); u[1] = __byte_perm(x2, x3, 0x5410); u[2] = __byte_perm(x0, x1, 0x7632); u[3] = __byte_perm(x2, x3, 0x7632);
}
DEVI void unit_send(uint32_t d, const uint32_t* u, uint32_t bar, uint32_t r1, uint32_t r2) {
    st_async128(mapa(d, r1), u[0], u[1], u[2], u[3], mapa(bar, r1));
    st_async128(mapa(d, r2), u[0], u[1], u[2], u[3], mapa(bar, r2));
}
template <bool Q>
DEVI void stage_sums(uint32_t sb, int s, uint32_t rank, int warp, const uint8_t* src, uint32_t l, uint32_t gate) {
    uint4 v[4];
    while ((int)(clk32() - gate) < 0) { }
    EV(elect_one(), s, 16 + warp);
#pragma unroll
    for (int j = 0; j < 4; j++) v[j] = ld_rlx4(src + j * 1024);
    const uint32_t col = sb + RS_MEM + ((Q ? 0 : (rank == 1 ? 6 : 11)) + 3 * (warp >> 1)) * 1024 + ((l >> 2) & 0x300) + (l & 0x70);
    const uint32_t d0 = col + (warp & 1) * 2048, d1 = d0 ^ 160, d2 = (col ^ ((warp & 1) * 160)) + 1024;
    const uint32_t r1 = Q ? 1 : 0, r2 = Q ? 2 : 3 - rank, bar = sb + (warp < 2 ? RB_G + 8 * warp : (Q ? RB_G + 16 : RB_G3));
    int n = 0;
    while (!__all_sync(0xffffffffu, v[0].w == 0x4200u && v[1].w == 0x4200u && v[2].w == 0x4200u && v[3].w == 0x4200u)) {
#pragma unroll
        for (int j = 0; j < 4; j++) v[j] = ld_rlx4(src + j * 1024);
        if (++n > SPIN_LIMIT) TRAP(0x20000000u | (s << 8) | warp);
    }
    EV(elect_one(), s, 24 + warp);
    uint32_t u[12];
    unit_pack(u + 8, v[0].z, v[1].z, v[2].z, v[3].z);
    unit_send(d2, u + 8, bar, r1, r2);
    if (Q || warp < 3) {
        unit_pack(u, v[0].x, v[1].x, v[2].x, v[3].x);
        unit_pack(u + 4, v[0].y, v[1].y, v[2].y, v[3].y);
        unit_send(d0, u, bar, r1, r2);
        unit_send(d1, u + 4, bar, r1, r2);
        sts128(d0, make_uint4(u[0], u[1], u[2], u[3]));
        sts128(d1, make_uint4(u[4], u[5], u[6], u[7]));
    }
    sts128(d2, make_uint4(u[8], u[9], u[10], u[11]));
    __syncwarp();
    if (elect_one()) {
        mbar_expect_tx(bar, warp < 2 ? 3072u : (Q ? 0u : 1024u));
        if (warp == 0) mbar_expect_tx(sb + (Q ? RB_G3 : RB_G + 16), Q ? 4096u : 3072u);
    }
    EV(elect_one(), s, 20 + warp);
}
DEVI void wo_permute(uint32_t tile, int t) {
    const uint32_t a = tile + t * 32 + ((t >> 2) & 1) * 16;
#pragma unroll
    for (int h = 0; h < 2; h++) {
        uint4 v[3], u[3];
#pragma unroll
        for (int i = 0; i < 3; i++) if (3 * h + i < 5 || t < 32) { v[i] = lds128(a + (3 * h + i) * 3072); u[i] = lds128((a ^ 16) + (3 * h + i) * 3072); }
#pragma unroll
        for (int i = 0; i < 3; i++) if (3 * h + i < 5 || t < 32) {
            sts128(a + (3 * h + i) * 3072, make_uint4(__byte_perm(v[i].x, v[i].y, 0x5410), __byte_perm(v[i].x, v[i].y, 0x7632),
                                                      __byte_perm(u[i].x, u[i].y, 0x5410), __byte_perm(u[i].x, u[i].y, 0x7632)));
            sts128((a ^ 16) + (3 * h + i) * 3072, make_uint4(__byte_perm(v[i].z, v[i].w, 0x5410), __byte_perm(v[i].z, v[i].w, 0x7632),
                                                             __byte_perm(u[i].z, u[i].w, 0x5410), __byte_perm(u[i].z, u[i].w, 0x7632)));
        }
    }
}
DEVI uint32_t acc_clear(int slot, int idx, uint32_t lo) {
    uint8_t* p = g_acc + (uint32_t)(slot * 128 + idx * 3072 + (lo < 3072 ? lo : lo - 1024));
    st_rlx4(p, 0u, 0u, 0u, 0u);
    uint32_t z; asm volatile("ld.relaxed.gpu.global.u32 %0, [%1];" : "=r"(z) : "l"(p) : "memory");
    return z;
}

template <bool Q>
DEVI void aux_main(uint32_t sb, int warp, uint32_t rank, int head, const CUtensorMap* tmX, const bf16* xg, unsigned E, const int delay, const int gap) {
    const uint32_t lo = __shfl_sync(0xffffffffu, ((tid_now() >> 3) & 3) * 1024 + (tid_now() & 7) * 16, tid_now() & 31);
    for (int s = 0; s < NSEG - 1; s++) {
        if (!Q && warp == 0 && elect_one()) mbar_expect_tx(sb + RB_O, 2048 + 256);
        __syncwarp();
        const uint32_t slot = (s & 3) * 128;
        mbar_wait(sb + RB_O, s & 1);
        EV(warp == 0 && elect_one(), s, 10);
        wo_phase<Q>(sb, s, warp, g_acc + (uint32_t)(slot + (rank * 4 + warp) * 4096 + opaque(lo)), sb + RS_INV + ((opaque(lo) >> 1) & 24), gap);
        SCHED_FENCE();
        const uint32_t t_o = clk32();
        EV(warp == 0 && elect_one(), s, 12);
        {
            const uint32_t l = opaque(lo);
            stage_sums<Q>(sb, s, rank, warp, g_acc + (uint32_t)(slot + rank * 16384 + warp * ACC_CH + (l & 0xC00) * 4 + (l & 0x70)), l, t_o + delay);
        }
        EV(warp == 2 && elect_one(), s, 14);
        if (warp == (Q ? 3 : 1)) {
            if (Q) {
                mbar_wait(sb + RB_T, s & 1);
                if (s == 3) wait_count_warp(&g_cnt[C_Q], 64 * E);
                if (elect_one()) {
                    if (s == 3) fence_proxy_global();
                    fence_proxy_async();
                    mbar_expect_tx(sb + RB_QX, 8192);
                    bulk_load(sb + RS_QX, g_qx + (uint32_t)(((s + 1) * NH + head) * 4096), 8192, sb + RB_QX);
                    if (head == 0) { TLOG(1400 + s, 0, gtime()); TLOG(1400 + s, 1, clock64()); }
                }
                __syncwarp();
                const bool fresh = (s & 7) == 6 && s + 2 < NSEG;
                if (fresh) wait_count_warp(&g_cnt[C_Q + ((s + 2) >> 3)], 64 * E);
                if (elect_one()) {
                    if (fresh) fence_proxy_global();
                    if (s + 2 < NSEG && s != 2) l2_prefetch(g_qx + (uint32_t)(((s + 2) * NH + head) * 4096), 8192);
                    if (s + 4 < NSEG) l2_prefetch(xg + (uint32_t)(((s + 4) * 32 + head) * DM), 2048);
                    signal_count(&g_prog[s >> 2]);
                }
                __syncwarp();
            } else {
                const uint32_t zero = acc_clear((s + 2) & 3, 2 * head + (int)rank - 1, opaque(lo));
                if (rank == 2) mbar_wait(sb + RB_G3, s & 1);
                x_send(sb, s + 1, rank);
                if (__any_sync(0xffffffffu, zero != 0u)) __trap();
            }
        }
    }
}

DEVI void load_weights(uint32_t sb, const CUtensorMap* tmW, const CUtensorMap* tmWo, int head, uint32_t rank, int2 t0) {
    const uint32_t c0 = clk32();
    if (rank == 0) while ((int)(clk32() - c0) < t0.x) { }
    const uint32_t bW = sb + RB_W, bSF = sb + RB_SF, bSE = sb + RB_SE;
    const int tile0 = rank == 0 ? 0 : (rank == 1 ? 6 : 11);
    mbar_expect_tx(bW, R_NSS * 16384);
    for (int pass = 0; pass < 2; pass++) {
        for (int pos = 0; pos < 16; pos++) {
            const int k = (int)((R_TORD_PACK >> (4 * pos)) & 15ull) * 64, rd = pos - pos / 3, slot = rd % 5;
            if (r_pos_ss(pos)) {
                if (pass) continue;
                const uint32_t dst = sb + RS_WSS + (pos / 3) * 16384;
                tma_load_2d(dst, tmW, head * DH, k, bW);
                tma_load_2d(dst + 8192, tmW, head * DH + 64, k, bW);
            } else if (pass == (rd >= 5)) {
                if (rd >= 5) mbar_wait(bSE + 8 * slot, ((rd / 5) - 1) & 1);
                mbar_expect_tx(bSF + 8 * slot, 16384);
                const uint32_t dst = sb + RS_WO + slot * 16384;
                tma_load_2d(dst, tmW, head * DH, k, bSF + 8 * slot);
                tma_load_2d(dst + 8192, tmW, head * DH + 64, k, bSF + 8 * slot);
            }
        }
    }
    while ((int)(clk32() - c0) < t0.y) { }
    if (rank == 0) { mbar_expect_tx(sb + RB_WO, 16384); tma_load_wo(sb + RS_WO5, tmWo, 5 * 64, head * 4, sb + RB_WO); }
    for (int i = 1; i <= 5; i++) {
        const int slot = i % 5, last = slot + 10 < R_NRS ? slot + 10 : slot + 5;
        mbar_wait(bSE + 8 * slot, (last / 5) & 1);
        mbar_expect_tx(bSF + 8 * slot, 16384);
        tma_load_wo(sb + RS_WO + slot * 16384, tmWo, (tile0 + slot) * 64, head * 4, bSF + 8 * slot);
    }
}
template <bool XP>
DEVI void big_prologue(uint32_t* w, uint32_t sb, int g, int warp, const bf16* __restrict__ mem0) {
    const int tid = tid_now(), lane = tid & 31;
    {
        const uint32_t* m = (const uint32_t*)(mem0 + (lane >> 2) * DM + (tid >> 5) * 16) + (lane & 3);
        uint32_t u[16];
#pragma unroll
        for (int j = 0; j < 8; j++) { u[2 * j] = m[j * 64]; u[2 * j + 1] = m[j * 64 + 4]; }
#pragma unroll
        for (int j = 0; j < 8; j++) sts64(sb + RS_MEM + ((tid >> 5) + j * 8) * 256 + b_frag_off(lane), u[2 * j], u[2 * j + 1]);
    }
    const uint32_t a0 = sb + RS_WO + g * (8192 + 4096) + a_frag_off(lane, warp), a1 = a0 + 8192 - g * 16384;
#pragma unroll
    for (int rd = 0; rd < R_NRS; rd++) {
        const int slot = rd % 5;
        mbar_wait(sb + RB_SF + 8 * slot, (rd / 5) & 1);
#pragma unroll
        for (int q = 0; q < 4; q++) {
            if (XP && rd == 0 && q == 3) {
                sts128(sb + RS_WX + g * 2048 + (tid & 127) * 16, lds128(sb + RS_WO + 8192 - g * 4096 + 2048 + (tid & 127) * 16));
                fence_proxy_async();
                nbar_sync(NB_WG + g, 128);
            } else ldsm4t(&w[rd * 16 + q * 4], ((q & 1) ? a1 : a0) + slot * 16384 + (q >> 1) * 2048);
        }
        mbar_arrive(sb + RB_SE + 8 * slot);
    }
    mbar_wait(sb + RB_W, 0);
    if (tid == 0) TLOG(1500 + blockIdx.x, 2, gtime());
}

#define REC_END() do { if (tid_now() == 0) TLOG(1024 + blockIdx.x, 1, gtime()); } while (0)
struct XMaps { CUtensorMap m[2]; };
__global__ void __launch_bounds__(384, 1)
k_rec(const __grid_constant__ PMaps mp, const __grid_constant__ CUtensorMap tmWk, const __grid_constant__ CUtensorMap tmWv,
      const __grid_constant__ CUtensorMap tmWo, const __grid_constant__ XMaps xm, const bf16* __restrict__ mem0, const bf16* __restrict__ xg,
      int4 tq, int4 tk, int2 t0, int rec) {
    extern __shared__ __align__(1024) uint8_t smem_raw[];
    const uint32_t sb = smem_u32(smem_raw);
    if ((sb & 0x3FFFFu) != SB0) __trap();
    const int tid = threadIdx.x;
    const int wg = __shfl_sync(0xffffffffu, tid >> 7, 0), warp = __shfl_sync(0xffffffffu, (tid >> 5) & 3, 0);
    uint32_t rank; asm("mov.u32 %0, %%cluster_ctarank;" : "=r"(rank));
    int head; asm("mov.u32 %0, %%clusterid.x;" : "=r"(head));
    asm volatile("griddepcontrol.launch_dependents;");
    if (tid == 0 && rec) {
        mbar_init(sb + RB_G, 1);
        mbar_init(sb + RB_G + 8, 1);
        mbar_init(sb + RB_G + 16, rank == 0 ? 2 : 1);
        mbar_init(sb + RB_G3, rank == 0 ? 1 : 2);
        mbar_init(sb + RB_T, 1); mbar_init(sb + RB_VX, 1); mbar_init(sb + RB_WO, 1);
        mbar_init(sb + RB_K, 1); mbar_init(sb + RB_V, 1); mbar_init(sb + RB_KV, 1); mbar_init(sb + RB_QX, 1);
        mbar_init(sb + RB_O, rank == 0 ? 4 : 1); mbar_init(sb + RB_ATT, 1); mbar_init(sb + RB_W, 1);
        for (int i = 0; i < 5; i++) { mbar_init(sb + RB_SF + 8 * i, 1); mbar_init(sb + RB_SE + 8 * i, 256); }
        for (int i = 0; i < 2; i++) mbar_init(sb + RB_XF + 8 * i, X_SLOTS);
        fence_mbar_init();
        if (rank == 0) { mbar_expect_tx(sb + RB_KV, 8192); mbar_expect_tx(sb + RB_K, 2048); mbar_expect_tx(sb + RB_V, 2048); mbar_expect_tx(sb + RB_VX, 8192); }
    }
    __syncthreads();
    asm volatile("barrier.cluster.arrive.release.aligned;" ::: "memory");

    if (wg < 2) {
        reg_inc<REG_KB>();
        if (rank != 0) {
            uint32_t w[R_NRS * 16];
            if ((tid & 127) == 0) for (int j = 0; j < X_SLOTS; j++) x_load(sb, 0, j, wg, xm.m);
            __syncwarp();
            cluster_wait();
            big_prologue<true>(w, sb, wg, warp, mem0);
            big_main<true>(w, sb, wg, warp, rank, head, xm.m, xg, 0u);
            REC_END();
        } else if (rec) {
            uint32_t w[R_NRS * 16];
            cluster_wait();
            big_prologue<false>(w, sb, wg, warp, mem0);
            big_main<false>(w, sb, wg, warp, rank, head, xm.m, xg, *(volatile unsigned*)&g_epoch + 1);
            REC_END();
        } else cluster_wait();
        nbar_sync(0, 384);
        nbar_sync(0, 384);
        post_consumer(mp, sb, wg, warp);
    } else {
        reg_dec<504 - 2 * REG_KB>();
        if (rec) {
            if (tid == 256) {
                if (rank == 0) l2_prefetch(xg + (uint32_t)(head * 8 * DM), 16384);
                load_weights(sb, rank == 0 ? &mp.wq : (rank == 1 ? &tmWk : &tmWv), &tmWo, head, rank, t0);
            }
            if (warp == 3 && rank != 0) {
                const uint32_t lo = ((tid >> 3) & 3) * 1024 + (tid & 7) * 16;
                acc_clear(0, 2 * head + (int)rank - 1, lo); acc_clear(1, 2 * head + (int)rank - 1, lo);
                __threadfence();
                __syncwarp();
                if (tid == 256 + 96) atomicAdd(&g_zero, 1u);
            }
            __syncwarp();
        }
        cluster_wait();
        const unsigned E = __shfl_sync(0xffffffffu, *(volatile unsigned*)&g_epoch + 1, 0);
        if (rec) {
            if (warp == 1) wait_count_warp(&g_zero, E * 64u);
            if (warp == 3) { if (rank != 0) x_send(sb, 0, rank); }
            else {
                nbar_sync(NB_PRO, 96);
#pragma unroll 1
                for (int i = rank == 0 ? 0 : 1; i <= 5; i++) {
                    mbar_wait(sb + (i == 0 ? RB_WO : RB_SF + 8 * (i % 5)), i == 5);
                    if (i == 5 && tid == 288) TLOG(1500 + blockIdx.x, 0, gtime());
                    wo_permute(sb + (i == 0 ? RS_WO5 : RS_WO + (i % 5) * 16384), tid & 127);
                }
            }
            fence_proxy_async();
            nbar_sync(NB_AUX, 128);
            if (tid == 288) { TLOG(1500 + blockIdx.x, 1, gtime()); }
            if (rank == 0) aux_main<true>(sb, warp, rank, head, xm.m, xg, E, warp == 0 ? tq.x : (warp == 1 ? tq.y : tq.z), tq.w);
            else           aux_main<false>(sb, warp, rank, head, xm.m, xg, E, warp == 0 ? tk.x : (warp == 1 ? tk.y : tk.z), tk.w);
        }
        const int t = tid_now();
        int id = 0;
        if (t >= 288 && t < 288 + 13) asm volatile("prefetch.tensormap [%0];" :: "l"(&mp.wq + (t - 288)) : "memory");
        if (warp == 0 && rank != 0) id = post_claim(mp, E);
        nbar_sync(0, 384);
        if (warp == 0) { if (elect_one()) post_init(sb); fence_proxy_async(); }
        __syncwarp();
        nbar_sync(0, 384);
        if (warp == 0) post_producer(mp, sb, E, rank != 0 ? id : post_claim(mp, E));
        else if (t == 288 || t == 320) post_helper(sb, warp - 1);
    }
    __syncthreads();
    asm volatile("griddepcontrol.wait;" ::: "memory");
}

typedef CUresult (*EncodeFn)(CUtensorMap*, CUtensorMapDataType, cuuint32_t, void*, const cuuint64_t*, const cuuint64_t*,
                             const cuuint32_t*, const cuuint32_t*, CUtensorMapInterleave, CUtensorMapSwizzle,
                             CUtensorMapL2promotion, CUtensorMapFloatOOBfill);

static CUtensorMap make_map(EncodeFn fn, const void* ptr, uint64_t inner, uint64_t outer, uint32_t box_inner, uint32_t box_outer) {
    CUtensorMap m;
    cuuint64_t dims[2] = {inner, outer};
    cuuint64_t strides[1] = {inner * 2};
    cuuint32_t box[2] = {box_inner, box_outer};
    cuuint32_t es[2] = {1, 1};
    fn(&m, CU_TENSOR_MAP_DATA_TYPE_BFLOAT16, 2, const_cast<void*>(ptr), dims, strides, box, es,
       CU_TENSOR_MAP_INTERLEAVE_NONE, CU_TENSOR_MAP_SWIZZLE_128B, CU_TENSOR_MAP_L2_PROMOTION_L2_256B, CU_TENSOR_MAP_FLOAT_OOB_FILL_NONE);
    return m;
}

static CUtensorMap make_wo_map(EncodeFn fn, const void* ptr, uint64_t rows, uint32_t ngrp) {
    CUtensorMap m;
    cuuint64_t dims[5] = {DM, 2, 4, 4, rows / 32};
    cuuint64_t strides[4] = {DM * 2, 8 * DM * 2, 2 * DM * 2, 32 * DM * 2};
    cuuint32_t box[5] = {64, 2, 4, 4, ngrp};
    cuuint32_t es[5] = {1, 1, 1, 1, 1};
    fn(&m, CU_TENSOR_MAP_DATA_TYPE_BFLOAT16, 5, const_cast<void*>(ptr), dims, strides, box, es,
       CU_TENSOR_MAP_INTERLEAVE_NONE, CU_TENSOR_MAP_SWIZZLE_128B, CU_TENSOR_MAP_L2_PROMOTION_L2_256B, CU_TENSOR_MAP_FLOAT_OOB_FILL_NONE);
    return m;
}

struct Maps {
    PMaps post;
    CUtensorMap wk16, wv16, wo128;
    XMaps x32;
};

extern "C" void kernel_launch(void* const* d_in, const int* in_sizes, int n_in, void* d_out, int out_size) {
    const bf16* A_x   = (const bf16*)d_in[0];
    const bf16* A_mem = (const bf16*)d_in[1];
    const bf16* A_Wq  = (const bf16*)d_in[2];
    const bf16* A_Wk  = (const bf16*)d_in[3];
    const bf16* A_Wv  = (const bf16*)d_in[4];
    const bf16* A_Wo  = (const bf16*)d_in[5];
    const bf16* B_x   = (const bf16*)d_in[7];
    const bf16* B_w   = (const bf16*)d_in[8];
    const bf16* B_wo  = (const bf16*)d_in[9];

    static EncodeFn fn = nullptr;
    static Maps mp;
    static const void* cached[10];
    const void* cur[10] = {A_x, A_mem, A_Wq, A_Wk, A_Wv, A_Wo, B_x, B_w, B_wo, d_out};
    bool same = fn != nullptr;
    for (int i = 0; i < 10 && same; i++) same = cached[i] == cur[i];
    if (!same) {
        if (!fn) {
            void* p = nullptr; cudaDriverEntryPointQueryResult qr;
            cudaGetDriverEntryPoint("cuTensorMapEncodeTiled", &p, cudaEnableDefault, &qr);
            fn = (EncodeFn)p;
            cudaFuncSetAttribute(k_rec, cudaFuncAttributeMaxDynamicSharedMemorySize, R_SMEM);
        }
        void *p_ox, *p_bqkv, *p_bo, *p_qx;
        cudaGetSymbolAddress(&p_qx, g_qx);
        cudaGetSymbolAddress(&p_ox, g_ox); cudaGetSymbolAddress(&p_bqkv, g_bqkv); cudaGetSymbolAddress(&p_bo, g_bo);
        mp.post.wq   = make_map(fn, A_Wq, HD, DM, 64, 64);
        mp.post.wo   = make_wo_map(fn, A_Wo, HD, 2);
        mp.post.bw   = make_map(fn, B_w, 3 * DM, DM, 64, 64);
        mp.post.bwo  = make_wo_map(fn, B_wo, DM, 2);
        mp.post.x    = make_map(fn, A_x, DM, S_TOK, 64, 128);
        mp.post.bx   = make_map(fn, B_x, DM, S_TOK, 64, 128);
        mp.post.bo   = make_map(fn, p_bo, DM, S_TOK, 64, 128);
        mp.post.ox   = make_map(fn, p_ox, HD, S_TOK, 64, 128);
        mp.post.ox64 = make_map(fn, p_ox, HD, S_TOK, 64, 64);
        mp.post.cb   = make_map(fn, p_bqkv, 3 * DM, S_TOK, 64, 64);
        mp.post.cout = make_map(fn, d_out, 2 * DM, S_TOK, 64, 64);
        {
            cuuint64_t dims[4] = {256, 4, NH * 4, NSEG};
            cuuint64_t strides[3] = {512, 2048, NH * 8192};
            cuuint32_t box[4] = {256, 2, 4, 2};
            cuuint32_t es[4] = {1, 1, 1, 1};
            fn(&mp.post.cq, CU_TENSOR_MAP_DATA_TYPE_BFLOAT16, 4, p_qx, dims, strides, box, es,
               CU_TENSOR_MAP_INTERLEAVE_NONE, CU_TENSOR_MAP_SWIZZLE_NONE, CU_TENSOR_MAP_L2_PROMOTION_NONE, CU_TENSOR_MAP_FLOAT_OOB_FILL_NONE);
        }
        {
            int runs[48] = {K_QH, 0, 2, K_Q, 1, 7, K_B1, 0, 8, K_A4, 0, 4, K_B2, 0, 32, K_A4, 4, 2, K_B3, 0, 4, K_A3, 12, 1, K_B3, 4, 1, K_A3, 13, 1,
                            K_B3, 5, 3, K_SN, 28, 4, -1};
            const int per[9] = {32, 24, 8, 8, 32, 8, 8 * P_SPLIT, 1, 8 * P_SPLIT};
            int n = 0, id = 0;
            for (; runs[3 * n] >= 0; n++) {
                mp.post.list.run[n] = make_int4(runs[3 * n], runs[3 * n + 1], id, id + runs[3 * n + 2] * per[runs[3 * n]]);
                id = mp.post.list.run[n].w;
            }
            mp.post.list.n = n;
            int dev = 0, nsm = 132;
            cudaGetDevice(&dev);
            cudaDeviceGetAttribute(&nsm, cudaDevAttrMultiProcessorCount, dev);
            mp.post.list.nworker = nsm > 96 ? nsm : 97;
        }
        {
            cuuint64_t dims[4] = {DM, 3, 2, S_TOK / 2};
            cuuint64_t strides[3] = {DM * 2, 3 * DM * 2, 3 * DM * 4};
            cuuint32_t box[4] = {64, 3, 1, 40};
            cuuint32_t es[4] = {1, 1, 1, 1};
            fn(&mp.post.b40, CU_TENSOR_MAP_DATA_TYPE_BFLOAT16, 4, p_bqkv, dims, strides, box, es,
               CU_TENSOR_MAP_INTERLEAVE_NONE, CU_TENSOR_MAP_SWIZZLE_128B, CU_TENSOR_MAP_L2_PROMOTION_L2_256B, CU_TENSOR_MAP_FLOAT_OOB_FILL_NONE);
        }
        mp.wk16 = make_map(fn, A_Wk, HD, DM, 64, 64);
        mp.wv16 = make_map(fn, A_Wv, HD, DM, 64, 64);
        mp.wo128 = make_wo_map(fn, A_Wo, HD, 4);
        for (int i = 0; i < 2; i++) {
            cuuint64_t dims[3] = {64, S_TOK, DM / 64};
            cuuint64_t strides[2] = {DM * 2, 128};
            cuuint32_t box[3] = {32, 32, 2u - i};
            cuuint32_t es[3] = {1, 1, 1};
            fn(&mp.x32.m[i], CU_TENSOR_MAP_DATA_TYPE_BFLOAT16, 3, const_cast<bf16*>(A_x), dims, strides, box, es,
               CU_TENSOR_MAP_INTERLEAVE_NONE, CU_TENSOR_MAP_SWIZZLE_64B, CU_TENSOR_MAP_L2_PROMOTION_L2_128B, CU_TENSOR_MAP_FLOAT_OOB_FILL_NONE);
        }
        for (int i = 0; i < 10; i++) cached[i] = cur[i];
    }

    cudaStream_t st = cudaStreamPerThread;
    int4 tq = make_int4(100, 200, 700, 60), tk = make_int4(50, 250, 850, 60);
    int2 t0 = make_int2(13000, 16000);
    cudaLaunchConfig_t cfg = {};
    cfg.gridDim = dim3(96); cfg.blockDim = dim3(384); cfg.dynamicSmemBytes = R_SMEM; cfg.stream = st;
    cudaLaunchAttribute at[1];
    at[0].id = cudaLaunchAttributeClusterDimension;
    at[0].val.clusterDim.x = 3; at[0].val.clusterDim.y = 1; at[0].val.clusterDim.z = 1;
    cfg.attrs = at; cfg.numAttrs = 1;
    cudaLaunchKernelEx(&cfg, k_rec, mp.post, mp.wk16, mp.wv16, mp.wo128, mp.x32, A_mem, A_x, tq, tk, t0, 1);
    cfg.gridDim = dim3(mp.post.list.nworker - 96);
    at[0].id = cudaLaunchAttributeProgrammaticStreamSerialization;
    at[0].val.programmaticStreamSerializationAllowed = 1;
    cudaLaunchKernelEx(&cfg, k_rec, mp.post, mp.wk16, mp.wv16, mp.wo128, mp.x32, A_mem, A_x, tq, tk, t0, 0);
}
```

```cpp
#include <cuda_runtime.h>
#include <cuda_bf16.h>
#include <cuda.h>
#include <stdint.h>

typedef __nv_bfloat16 bf16;

constexpr int S_TOK = 2048;
constexpr int DM    = 1024;
constexpr int NH    = 32;
constexpr int DH    = 128;
constexpr int NSEG  = 64;
constexpr int HD    = NH * DH;

__device__ __align__(1024) bf16 g_qx[NSEG * NH * 4 * DH * 8];
__device__ __align__(1024) bf16 g_ox[S_TOK * HD];
__device__ __align__(1024) bf16 g_bqkv[S_TOK * 3 * DM];
__device__ __align__(1024) bf16 g_bo[S_TOK * DM];
__device__ __align__(1024) uint8_t g_acc[192 * 1024];

#define EV(cond, s, k) do {} while (0)
#define EVCAL(s) do {} while (0)

constexpr int P_NSK = 4;
__device__ unsigned g_epoch, g_qctr, g_done, g_zero;
enum { C_B1 = 0, C_B2 = 8, C_Q = 16, C_QH = 24, C_NONE = 31 };
__device__ unsigned g_cnt[32], g_prog[16], g_cnt_sk[P_NSK * 32];
constexpr int P_SPLIT = 4;
__device__ __align__(1024) uint4 g_skp[P_NSK * 8 * P_SPLIT * 2 * 8 * 128];
#define TLOG(i, k, v) do {} while (0)

#define DEVI __device__ __forceinline__

DEVI uint32_t opaque(uint32_t v) { uint32_t r; asm volatile("mov.u32 %0, %1;" : "=r"(r) : "r"(v)); return r; }
DEVI uint32_t smem_u32(const void* p) { return (uint32_t)__cvta_generic_to_shared(p); }

#define TRAP(code) __trap()
constexpr int SPIN_LIMIT = 1 << 22;
#define MBAR_HINT_NS 20000u
constexpr int SPIN_LIMIT_MBAR = 1 << 17;

DEVI void mbar_init(uint32_t bar, uint32_t cnt) { asm volatile("mbarrier.init.shared::cta.b64 [%0], %1;" :: "r"(bar), "r"(cnt)); }
DEVI void mbar_expect_tx(uint32_t bar, uint32_t bytes) {
    asm volatile("mbarrier.arrive.expect_tx.shared::cta.b64 _, [%0], %1;" :: "r"(bar), "r"(bytes) : "memory");
}
DEVI void mbar_arrive(uint32_t bar) { asm volatile("mbarrier.arrive.shared::cta.b64 _, [%0];" :: "r"(bar) : "memory"); }
DEVI bool mbar_try(uint32_t bar, uint32_t parity) {
    uint32_t ok;
    asm volatile("{.reg .pred p; mbarrier.try_wait.parity.shared::cta.b64 p, [%1], %2; selp.u32 %0, 1, 0, p;}"
                 : "=r"(ok) : "r"(bar), "r"(parity) : "memory");
    return ok;
}
DEVI bool mbar_try_cluster(uint32_t bar, uint32_t parity) {
    uint32_t ok;
    asm volatile("{.reg .pred p; mbarrier.try_wait.parity.acquire.cluster.shared::cta.b64 p, [%1], %2; selp.u32 %0, 1, 0, p;}"
                 : "=r"(ok) : "r"(bar), "r"(parity) : "memory");
    return ok;
}
DEVI bool mbar_try_hint(uint32_t bar, uint32_t parity) {
    uint32_t ok;
    asm volatile("{.reg .pred p; mbarrier.try_wait.parity.shared::cta.b64 p, [%1], %2, %3; selp.u32 %0, 1, 0, p;}"
                 : "=r"(ok) : "r"(bar), "r"(parity), "r"(MBAR_HINT_NS) : "memory");
    return ok;
}
DEVI bool mbar_test(uint32_t bar, uint32_t parity) {
    uint32_t ok;
    asm volatile("{.reg .pred p; mbarrier.test_wait.parity.shared::cta.b64 p, [%1], %2; selp.u32 %0, 1, 0, p;}"
                 : "=r"(ok) : "r"(bar), "r"(parity) : "memory");
    return ok;
}
DEVI void mbar_wait(uint32_t bar, uint32_t parity) {
    int n = 0;
    while (!mbar_try(bar, parity)) { if (++n > SPIN_LIMIT) TRAP(bar | (parity << 31)); }
}
DEVI void mbar_wait_sleepy(uint32_t bar, uint32_t parity) {
    int n = 0;
    while (!mbar_try_hint(bar, parity)) { if (++n > SPIN_LIMIT_MBAR) __trap(); }
}
DEVI void mbar_wait_cluster(uint32_t bar, uint32_t parity) {
    int n = 0;
    while (!mbar_try_cluster(bar, parity)) { if (++n > SPIN_LIMIT) __trap(); }
}
DEVI void mbar_spin(uint32_t bar, uint32_t parity) {
    uint32_t ok; int n = 0;
    do {
        asm volatile("{.reg .pred p; mbarrier.test_wait.parity.shared::cta.b64 p, [%1], %2; selp.u32 %0, 1, 0, p;}"
                     : "=r"(ok) : "r"(bar), "r"(parity) : "memory");
        if (++n > SPIN_LIMIT) __trap();
    } while (!ok);
}
DEVI void fence_mbar_init() { asm volatile("fence.mbarrier_init.release.cluster;" ::: "memory"); }
DEVI void fence_proxy_async() { asm volatile("fence.proxy.async.shared::cta;" ::: "memory"); }
DEVI void cluster_sync() {
    asm volatile("barrier.cluster.arrive.release.aligned;\n barrier.cluster.wait.acquire.aligned;" ::: "memory");
}
DEVI bool elect_one() {
    uint32_t e; asm volatile("{.reg .pred p; elect.sync _|p, 0xffffffff; selp.u32 %0, 1, 0, p;}" : "=r"(e)); return e;
}
DEVI void fence_proxy_global() { asm volatile("fence.proxy.async.global;" ::: "memory"); }
DEVI void cluster_wait() { asm volatile("barrier.cluster.wait.acquire.aligned;" ::: "memory"); }
DEVI void nbar_sync(int id, int n) { asm volatile("bar.sync %0, %1;" :: "r"(id), "r"(n) : "memory"); }
DEVI void nbar_arrive(int id, int n) { asm volatile("bar.arrive %0, %1;" :: "r"(id), "r"(n) : "memory"); }

DEVI void tma_load_2d(uint32_t dst, const CUtensorMap* map, int x, int y, uint32_t bar) {
    asm volatile("cp.async.bulk.tensor.2d.shared::cluster.global.mbarrier::complete_tx::bytes [%0], [%1, {%3, %4}], [%2];"
                 :: "r"(dst), "l"(map), "r"(bar), "r"(x), "r"(y) : "memory");
}
DEVI void tma_load_3d(uint32_t dst, const CUtensorMap* map, int x, int y, int z, uint32_t bar) {
    asm volatile("cp.async.bulk.tensor.3d.shared::cluster.global.mbarrier::complete_tx::bytes [%0], [%1, {%3, %4, %5}], [%2];"
                 :: "r"(dst), "l"(map), "r"(bar), "r"(x), "r"(y), "r"(z) : "memory");
}
DEVI void tma_load_wo(uint32_t dst, const CUtensorMap* map, int col, int k32, uint32_t bar) {
    asm volatile("cp.async.bulk.tensor.5d.shared::cluster.global.mbarrier::complete_tx::bytes [%0], [%1, {%3, %5, %5, %5, %4}], [%2];"
                 :: "r"(dst), "l"(map), "r"(bar), "r"(col), "r"(k32), "r"(0) : "memory");
}
DEVI void tma_store_2d(const CUtensorMap* map, uint32_t src, int x, int y) {
    asm volatile("cp.async.bulk.tensor.2d.global.shared::cta.bulk_group [%0, {%2, %3}], [%1];"
                 :: "l"(map), "r"(src), "r"(x), "r"(y) : "memory");
}
DEVI void bulk_load(uint32_t dst, const void* src, uint32_t bytes, uint32_t bar) {
    asm volatile("cp.async.bulk.shared::cluster.global.mbarrier::complete_tx::bytes [%0], [%1], %2, [%3];"
                 :: "r"(dst), "l"(src), "r"(bytes), "r"(bar) : "memory");
}
DEVI void tma_load_2d_mc(uint32_t dst, const CUtensorMap* map, int x, int y, uint32_t bar, uint16_t mask) {
    asm volatile("cp.async.bulk.tensor.2d.shared::cluster.global.mbarrier::complete_tx::bytes.multicast::cluster [%0], [%1, {%3, %4}], [%2], %5;"
                 :: "r"(dst), "l"(map), "r"(bar), "r"(x), "r"(y), "h"(mask) : "memory");
}
DEVI void bulk_copy_s2c(uint32_t dst_cluster, uint32_t src, uint32_t bytes, uint32_t bar_cluster) {
    asm volatile("cp.async.bulk.shared::cluster.shared::cta.mbarrier::complete_tx::bytes [%0], [%1], %2, [%3];"
                 :: "r"(dst_cluster), "r"(src), "r"(bytes), "r"(bar_cluster) : "memory");
}
DEVI void bulk_store(void* dst, uint32_t src, uint32_t bytes) {
    asm volatile("cp.async.bulk.global.shared::cta.bulk_group [%0], [%1], %2;" :: "l"(dst), "r"(src), "r"(bytes) : "memory");
}
DEVI void bulk_wait_read() { asm volatile("cp.async.bulk.wait_group.read 0;" ::: "memory"); }
DEVI void mbar_arrive_remote(uint32_t bar_cluster) {
    asm volatile("mbarrier.arrive.shared::cluster.b64 _, [%0];" :: "r"(bar_cluster) : "memory");
}
DEVI void mbar_expect_tx_remote(uint32_t bar_cluster, uint32_t bytes) {
    asm volatile("mbarrier.arrive.expect_tx.shared::cluster.b64 _, [%0], %1;" :: "r"(bar_cluster), "r"(bytes) : "memory");
}
DEVI void l2_prefetch(const void* p, uint32_t bytes) {
    asm volatile("cp.async.bulk.prefetch.L2.global [%0], %1;" :: "l"(p), "r"(bytes) : "memory");
}
DEVI void bulk_commit() { asm volatile("cp.async.bulk.commit_group;" ::: "memory"); }
DEVI void bulk_wait_all() { asm volatile("cp.async.bulk.wait_group 0;" ::: "memory"); }

DEVI void wg_fence() { asm volatile("wgmma.fence.sync.aligned;" ::: "memory"); }
DEVI void wg_commit() { asm volatile("wgmma.commit_group.sync.aligned;" ::: "memory"); }
template <int N> DEVI void wg_wait() { asm volatile("wgmma.wait_group.sync.aligned %0;" :: "n"(N) : "memory"); }

template <int R> DEVI void reg_dec() { asm volatile("setmaxnreg.dec.sync.aligned.u32 %0;" :: "n"(R)); }
template <int R> DEVI void reg_inc() { asm volatile("setmaxnreg.inc.sync.aligned.u32 %0;" :: "n"(R)); }

DEVI uint64_t mk_desc(uint32_t addr, uint32_t lbo, uint32_t sbo, uint32_t sw) {
    return (uint64_t)((addr & 0x3FFFF) >> 4) | ((uint64_t)(lbo >> 4) << 16) | ((uint64_t)(sbo >> 4) << 32) | ((uint64_t)sw << 62);
}

DEVI uint32_t desc_lo(uint32_t addr, uint32_t lbo) { return ((addr & 0x3FFFF) >> 4) | ((lbo >> 4) << 16); }
constexpr uint32_t DHI_SW128 = (1024u >> 4) | (1u << 30);
constexpr uint32_t DHI_SW64  = (512u >> 4) | (2u << 30);
constexpr uint32_t DHI_NONE  = (128u >> 4);

template <int TB, int SCALE_D>
DEVI void wgmma_n8_ss(float* d, uint32_t alo, uint32_t blo) {
    asm volatile("{.reg .b64 da, db; mov.b64 da, {%4, %6}; mov.b64 db, {%5, %7};\n"
                 "wgmma.mma_async.sync.aligned.m64n8k16.f32.bf16.bf16 {%0,%1,%2,%3}, da, db, %8, 1, 1, 1, %9;}"
                 : "+f"(d[0]), "+f"(d[1]), "+f"(d[2]), "+f"(d[3])
                 : "r"(alo), "r"(blo), "n"(DHI_SW128), "n"(DHI_NONE), "n"(SCALE_D), "n"(TB));
}

template <int TB>
DEVI void wgmma_n8_ss_first(float* d, uint32_t alo, uint32_t blo) {
    asm volatile("{.reg .b64 da, db; mov.b64 da, {%4, %6}; mov.b64 db, {%5, %7};\n"
                 "wgmma.mma_async.sync.aligned.m64n8k16.f32.bf16.bf16 {%0,%1,%2,%3}, da, db, 0, 1, 1, 1, %8;}"
                 : "=f"(d[0]), "=f"(d[1]), "=f"(d[2]), "=f"(d[3])
                 : "r"(alo), "r"(blo), "n"(DHI_SW128), "n"(DHI_NONE), "n"(TB));
}
DEVI void wgmma_n32_rs_first(float* d, const uint32_t* a, uint32_t blo) {
    asm volatile("{.reg .b64 db; mov.b64 db, {%20, %21};\n"
                 "wgmma.mma_async.sync.aligned.m64n32k16.f32.bf16.bf16 {%0,%1,%2,%3,%4,%5,%6,%7,%8,%9,%10,%11,%12,%13,%14,%15}, "
                 "{%16,%17,%18,%19}, db, 0, 1, 1, 0;}"
                 : "=f"(d[0]), "=f"(d[1]), "=f"(d[2]), "=f"(d[3]), "=f"(d[4]), "=f"(d[5]), "=f"(d[6]), "=f"(d[7]),
                   "=f"(d[8]), "=f"(d[9]), "=f"(d[10]), "=f"(d[11]), "=f"(d[12]), "=f"(d[13]), "=f"(d[14]), "=f"(d[15])
                 : "r"(a[0]), "r"(a[1]), "r"(a[2]), "r"(a[3]), "r"(blo), "n"(DHI_SW64));
}
template <int N> DEVI void reg_fence(float* d) {
#pragma unroll
    for (int i = 0; i < N; i++) asm volatile("" : "+f"(d[i]) :: "memory");
}
DEVI void wgmma_n32_rs(float* d, const uint32_t* a, uint32_t blo) {
    asm volatile("{.reg .b64 db; mov.b64 db, {%20, %21};\n"
                 "wgmma.mma_async.sync.aligned.m64n32k16.f32.bf16.bf16 {%0,%1,%2,%3,%4,%5,%6,%7,%8,%9,%10,%11,%12,%13,%14,%15}, "
                 "{%16,%17,%18,%19}, db, 1, 1, 1, 0;}"
                 : "+f"(d[0]), "+f"(d[1]), "+f"(d[2]), "+f"(d[3]), "+f"(d[4]), "+f"(d[5]), "+f"(d[6]), "+f"(d[7]),
                   "+f"(d[8]), "+f"(d[9]), "+f"(d[10]), "+f"(d[11]), "+f"(d[12]), "+f"(d[13]), "+f"(d[14]), "+f"(d[15])
                 : "r"(a[0]), "r"(a[1]), "r"(a[2]), "r"(a[3]), "r"(blo), "n"(DHI_SW64));
}
DEVI void wgmma_n32_ss(float* d, uint32_t alo, uint32_t blo) {
    asm volatile("{.reg .b64 da, db; mov.b64 da, {%16, %18}; mov.b64 db, {%17, %19};\n"
                 "wgmma.mma_async.sync.aligned.m64n32k16.f32.bf16.bf16 {%0,%1,%2,%3,%4,%5,%6,%7,%8,%9,%10,%11,%12,%13,%14,%15}, "
                 "da, db, 1, 1, 1, 1, 0;}"
                 : "+f"(d[0]), "+f"(d[1]), "+f"(d[2]), "+f"(d[3]), "+f"(d[4]), "+f"(d[5]), "+f"(d[6]), "+f"(d[7]),
                   "+f"(d[8]), "+f"(d[9]), "+f"(d[10]), "+f"(d[11]), "+f"(d[12]), "+f"(d[13]), "+f"(d[14]), "+f"(d[15])
                 : "r"(alo), "r"(blo), "n"(DHI_SW128), "n"(DHI_SW64));
}

template <bool FIRST>
DEVI void wgmma_n256_ss(float* d, uint64_t a, uint64_t b) {
    if (FIRST)
        asm volatile("wgmma.mma_async.sync.aligned.m64n256k16.f32.bf16.bf16 {%0,%1,%2,%3,%4,%5,%6,%7,%8,%9,%10,%11,%12,%13,%14,%15,%16,%17,%18,%19,%20,%21,%22,%23,%24,%25,%26,%27,%28,%29,%30,%31,%32,%33,%34,%35,%36,%37,%38,%39,%40,%41,%42,%43,%44,%45,%46,%47,%48,%49,%50,%51,%52,%53,%54,%55,%56,%57,%58,%59,%60,%61,%62,%63,%64,%65,%66,%67,%68,%69,%70,%71,%72,%73,%74,%75,%76,%77,%78,%79,%80,%81,%82,%83,%84,%85,%86,%87,%88,%89,%90,%91,%92,%93,%94,%95,%96,%97,%98,%99,%100,%101,%102,%103,%104,%105,%106,%107,%108,%109,%110,%111,%112,%113,%114,%115,%116,%117,%118,%119,%120,%121,%122,%123,%124,%125,%126,%127}, %128, %129, 0, 1, 1, 1, 0;"
            : "=f"(d[0]), "=f"(d[1]), "=f"(d[2]), "=f"(d[3]), "=f"(d[4]), "=f"(d[5]), "=f"(d[6]), "=f"(d[7]), "=f"(d[8]), "=f"(d[9]), "=f"(d[10]), "=f"(d[11]), "=f"(d[12]), "=f"(d[13]), "=f"(d[14]), "=f"(d[15]), "=f"(d[16]), "=f"(d[17]), "=f"(d[18]), "=f"(d[19]), "=f"(d[20]), "=f"(d[21]), "=f"(d[22]), "=f"(d[23]), "=f"(d[24]), "=f"(d[25]), "=f"(d[26]), "=f"(d[27]), "=f"(d[28]), "=f"(d[29]), "=f"(d[30]), "=f"(d[31]), "=f"(d[32]), "=f"(d[33]), "=f"(d[34]), "=f"(d[35]), "=f"(d[36]), "=f"(d[37]), "=f"(d[38]), "=f"(d[39]), "=f"(d[40]), "=f"(d[41]), "=f"(d[42]), "=f"(d[43]), "=f"(d[44]), "=f"(d[45]), "=f"(d[46]), "=f"(d[47]), "=f"(d[48]), "=f"(d[49]), "=f"(d[50]), "=f"(d[51]), "=f"(d[52]), "=f"(d[53]), "=f"(d[54]), "=f"(d[55]), "=f"(d[56]), "=f"(d[57]), "=f"(d[58]), "=f"(d[59]), "=f"(d[60]), "=f"(d[61]), "=f"(d[62]), "=f"(d[63]), "=f"(d[64]), "=f"(d[65]), "=f"(d[66]), "=f"(d[67]), "=f"(d[68]), "=f"(d[69]), "=f"(d[70]), "=f"(d[71]), "=f"(d[72]), "=f"(d[73]), "=f"(d[74]), "=f"(d[75]), "=f"(d[76]), "=f"(d[77]), "=f"(d[78]), "=f"(d[79]), "=f"(d[80]), "=f"(d[81]), "=f"(d[82]), "=f"(d[83]), "=f"(d[84]), "=f"(d[85]), "=f"(d[86]), "=f"(d[87]), "=f"(d[88]), "=f"(d[89]), "=f"(d[90]), "=f"(d[91]), "=f"(d[92]), "=f"(d[93]), "=f"(d[94]), "=f"(d[95]), "=f"(d[96]), "=f"(d[97]), "=f"(d[98]), "=f"(d[99]), "=f"(d[100]), "=f"(d[101]), "=f"(d[102]), "=f"(d[103]), "=f"(d[104]), "=f"(d[105]), "=f"(d[106]), "=f"(d[107]), "=f"(d[108]), "=f"(d[109]), "=f"(d[110]), "=f"(d[111]), "=f"(d[112]), "=f"(d[113]), "=f"(d[114]), "=f"(d[115]), "=f"(d[116]), "=f"(d[117]), "=f"(d[118]), "=f"(d[119]), "=f"(d[120]), "=f"(d[121]), "=f"(d[122]), "=f"(d[123]), "=f"(d[124]), "=f"(d[125]), "=f"(d[126]), "=f"(d[127]) : "l"(a), "l"(b));
    else
        asm volatile("wgmma.mma_async.sync.aligned.m64n256k16.f32.bf16.bf16 {%0,%1,%2,%3,%4,%5,%6,%7,%8,%9,%10,%11,%12,%13,%14,%15,%16,%17,%18,%19,%20,%21,%22,%23,%24,%25,%26,%27,%28,%29,%30,%31,%32,%33,%34,%35,%36,%37,%38,%39,%40,%41,%42,%43,%44,%45,%46,%47,%48,%49,%50,%51,%52,%53,%54,%55,%56,%57,%58,%59,%60,%61,%62,%63,%64,%65,%66,%67,%68,%69,%70,%71,%72,%73,%74,%75,%76,%77,%78,%79,%80,%81,%82,%83,%84,%85,%86,%87,%88,%89,%90,%91,%92,%93,%94,%95,%96,%97,%98,%99,%100,%101,%102,%103,%104,%105,%106,%107,%108,%109,%110,%111,%112,%113,%114,%115,%116,%117,%118,%119,%120,%121,%122,%123,%124,%125,%126,%127}, %128, %129, 1, 1, 1, 1, 0;"
            : "+f"(d[0]), "+f"(d[1]), "+f"(d[2]), "+f"(d[3]), "+f"(d[4]), "+f"(d[5]), "+f"(d[6]), "+f"(d[7]), "+f"(d[8]), "+f"(d[9]), "+f"(d[10]), "+f"(d[11]), "+f"(d[12]), "+f"(d[13]), "+f"(d[14]), "+f"(d[15]), "+f"(d[16]), "+f"(d[17]), "+f"(d[18]), "+f"(d[19]), "+f"(d[20]), "+f"(d[21]), "+f"(d[22]), "+f"(d[23]), "+f"(d[24]), "+f"(d[25]), "+f"(d[26]), "+f"(d[27]), "+f"(d[28]), "+f"(d[29]), "+f"(d[30]), "+f"(d[31]), "+f"(d[32]), "+f"(d[33]), "+f"(d[34]), "+f"(d[35]), "+f"(d[36]), "+f"(d[37]), "+f"(d[38]), "+f"(d[39]), "+f"(d[40]), "+f"(d[41]), "+f"(d[42]), "+f"(d[43]), "+f"(d[44]), "+f"(d[45]), "+f"(d[46]), "+f"(d[47]), "+f"(d[48]), "+f"(d[49]), "+f"(d[50]), "+f"(d[51]), "+f"(d[52]), "+f"(d[53]), "+f"(d[54]), "+f"(d[55]), "+f"(d[56]), "+f"(d[57]), "+f"(d[58]), "+f"(d[59]), "+f"(d[60]), "+f"(d[61]), "+f"(d[62]), "+f"(d[63]), "+f"(d[64]), "+f"(d[65]), "+f"(d[66]), "+f"(d[67]), "+f"(d[68]), "+f"(d[69]), "+f"(d[70]), "+f"(d[71]), "+f"(d[72]), "+f"(d[73]), "+f"(d[74]), "+f"(d[75]), "+f"(d[76]), "+f"(d[77]), "+f"(d[78]), "+f"(d[79]), "+f"(d[80]), "+f"(d[81]), "+f"(d[82]), "+f"(d[83]), "+f"(d[84]), "+f"(d[85]), "+f"(d[86]), "+f"(d[87]), "+f"(d[88]), "+f"(d[89]), "+f"(d[90]), "+f"(d[91]), "+f"(d[92]), "+f"(d[93]), "+f"(d[94]), "+f"(d[95]), "+f"(d[96]), "+f"(d[97]), "+f"(d[98]), "+f"(d[99]), "+f"(d[100]), "+f"(d[101]), "+f"(d[102]), "+f"(d[103]), "+f"(d[104]), "+f"(d[105]), "+f"(d[106]), "+f"(d[107]), "+f"(d[108]), "+f"(d[109]), "+f"(d[110]), "+f"(d[111]), "+f"(d[112]), "+f"(d[113]), "+f"(d[114]), "+f"(d[115]), "+f"(d[116]), "+f"(d[117]), "+f"(d[118]), "+f"(d[119]), "+f"(d[120]), "+f"(d[121]), "+f"(d[122]), "+f"(d[123]), "+f"(d[124]), "+f"(d[125]), "+f"(d[126]), "+f"(d[127]) : "l"(a), "l"(b));
}
template <bool FIRST>
DEVI void wgmma_n128_ss(float* d, uint64_t a, uint64_t b) {
    if (FIRST)
        asm volatile("wgmma.mma_async.sync.aligned.m64n128k16.f32.bf16.bf16 {%0,%1,%2,%3,%4,%5,%6,%7,%8,%9,%10,%11,%12,%13,%14,%15,%16,%17,%18,%19,%20,%21,%22,%23,%24,%25,%26,%27,%28,%29,%30,%31,%32,%33,%34,%35,%36,%37,%38,%39,%40,%41,%42,%43,%44,%45,%46,%47,%48,%49,%50,%51,%52,%53,%54,%55,%56,%57,%58,%59,%60,%61,%62,%63}, %64, %65, 0, 1, 1, 1, 0;"
            : "=f"(d[0]), "=f"(d[1]), "=f"(d[2]), "=f"(d[3]), "=f"(d[4]), "=f"(d[5]), "=f"(d[6]), "=f"(d[7]), "=f"(d[8]), "=f"(d[9]), "=f"(d[10]), "=f"(d[11]), "=f"(d[12]), "=f"(d[13]), "=f"(d[14]), "=f"(d[15]), "=f"(d[16]), "=f"(d[17]), "=f"(d[18]), "=f"(d[19]), "=f"(d[20]), "=f"(d[21]), "=f"(d[22]), "=f"(d[23]), "=f"(d[24]), "=f"(d[25]), "=f"(d[26]), "=f"(d[27]), "=f"(d[28]), "=f"(d[29]), "=f"(d[30]), "=f"(d[31]), "=f"(d[32]), "=f"(d[33]), "=f"(d[34]), "=f"(d[35]), "=f"(d[36]), "=f"(d[37]), "=f"(d[38]), "=f"(d[39]), "=f"(d[40]), "=f"(d[41]), "=f"(d[42]), "=f"(d[43]), "=f"(d[44]), "=f"(d[45]), "=f"(d[46]), "=f"(d[47]), "=f"(d[48]), "=f"(d[49]), "=f"(d[50]), "=f"(d[51]), "=f"(d[52]), "=f"(d[53]), "=f"(d[54]), "=f"(d[55]), "=f"(d[56]), "=f"(d[57]), "=f"(d[58]), "=f"(d[59]), "=f"(d[60]), "=f"(d[61]), "=f"(d[62]), "=f"(d[63]) : "l"(a), "l"(b));
    else
        asm volatile("wgmma.mma_async.sync.aligned.m64n128k16.f32.bf16.bf16 {%0,%1,%2,%3,%4,%5,%6,%7,%8,%9,%10,%11,%12,%13,%14,%15,%16,%17,%18,%19,%20,%21,%22,%23,%24,%25,%26,%27,%28,%29,%30,%31,%32,%33,%34,%35,%36,%37,%38,%39,%40,%41,%42,%43,%44,%45,%46,%47,%48,%49,%50,%51,%52,%53,%54,%55,%56,%57,%58,%59,%60,%61,%62,%63}, %64, %65, 1, 1, 1, 1, 0;"
            : "+f"(d[0]), "+f"(d[1]), "+f"(d[2]), "+f"(d[3]), "+f"(d[4]), "+f"(d[5]), "+f"(d[6]), "+f"(d[7]), "+f"(d[8]), "+f"(d[9]), "+f"(d[10]), "+f"(d[11]), "+f"(d[12]), "+f"(d[13]), "+f"(d[14]), "+f"(d[15]), "+f"(d[16]), "+f"(d[17]), "+f"(d[18]), "+f"(d[19]), "+f"(d[20]), "+f"(d[21]), "+f"(d[22]), "+f"(d[23]), "+f"(d[24]), "+f"(d[25]), "+f"(d[26]), "+f"(d[27]), "+f"(d[28]), "+f"(d[29]), "+f"(d[30]), "+f"(d[31]), "+f"(d[32]), "+f"(d[33]), "+f"(d[34]), "+f"(d[35]), "+f"(d[36]), "+f"(d[37]), "+f"(d[38]), "+f"(d[39]), "+f"(d[40]), "+f"(d[41]), "+f"(d[42]), "+f"(d[43]), "+f"(d[44]), "+f"(d[45]), "+f"(d[46]), "+f"(d[47]), "+f"(d[48]), "+f"(d[49]), "+f"(d[50]), "+f"(d[51]), "+f"(d[52]), "+f"(d[53]), "+f"(d[54]), "+f"(d[55]), "+f"(d[56]), "+f"(d[57]), "+f"(d[58]), "+f"(d[59]), "+f"(d[60]), "+f"(d[61]), "+f"(d[62]), "+f"(d[63]) : "l"(a), "l"(b));
}

template <bool FIRST>
DEVI void wgmma_n64_ss(float* d, uint64_t a, uint64_t b) {
    if (FIRST)
        asm volatile("wgmma.mma_async.sync.aligned.m64n64k16.f32.bf16.bf16 {%0,%1,%2,%3,%4,%5,%6,%7,%8,%9,%10,%11,%12,%13,%14,%15,%16,%17,%18,%19,%20,%21,%22,%23,%24,%25,%26,%27,%28,%29,%30,%31}, %32, %33, 0, 1, 1, 1, 0;"
            : "=f"(d[0]), "=f"(d[1]), "=f"(d[2]), "=f"(d[3]), "=f"(d[4]), "=f"(d[5]), "=f"(d[6]), "=f"(d[7]), "=f"(d[8]), "=f"(d[9]), "=f"(d[10]), "=f"(d[11]), "=f"(d[12]), "=f"(d[13]), "=f"(d[14]), "=f"(d[15]), "=f"(d[16]), "=f"(d[17]), "=f"(d[18]), "=f"(d[19]), "=f"(d[20]), "=f"(d[21]), "=f"(d[22]), "=f"(d[23]), "=f"(d[24]), "=f"(d[25]), "=f"(d[26]), "=f"(d[27]), "=f"(d[28]), "=f"(d[29]), "=f"(d[30]), "=f"(d[31]) : "l"(a), "l"(b));
    else
        asm volatile("wgmma.mma_async.sync.aligned.m64n64k16.f32.bf16.bf16 {%0,%1,%2,%3,%4,%5,%6,%7,%8,%9,%10,%11,%12,%13,%14,%15,%16,%17,%18,%19,%20,%21,%22,%23,%24,%25,%26,%27,%28,%29,%30,%31}, %32, %33, 1, 1, 1, 1, 0;"
            : "+f"(d[0]), "+f"(d[1]), "+f"(d[2]), "+f"(d[3]), "+f"(d[4]), "+f"(d[5]), "+f"(d[6]), "+f"(d[7]), "+f"(d[8]), "+f"(d[9]), "+f"(d[10]), "+f"(d[11]), "+f"(d[12]), "+f"(d[13]), "+f"(d[14]), "+f"(d[15]), "+f"(d[16]), "+f"(d[17]), "+f"(d[18]), "+f"(d[19]), "+f"(d[20]), "+f"(d[21]), "+f"(d[22]), "+f"(d[23]), "+f"(d[24]), "+f"(d[25]), "+f"(d[26]), "+f"(d[27]), "+f"(d[28]), "+f"(d[29]), "+f"(d[30]), "+f"(d[31]) : "l"(a), "l"(b));
}

DEVI void mma16816(float* d, const uint32_t* a, uint32_t b0, uint32_t b1) {
    asm volatile("mma.sync.aligned.m16n8k16.row.col.f32.bf16.bf16.f32 {%0,%1,%2,%3}, {%4,%5,%6,%7}, {%8,%9}, {%0,%1,%2,%3};"
                 : "+f"(d[0]), "+f"(d[1]), "+f"(d[2]), "+f"(d[3])
                 : "r"(a[0]), "r"(a[1]), "r"(a[2]), "r"(a[3]), "r"(b0), "r"(b1));
}
DEVI void mma1688(float* d, uint32_t a0, uint32_t a1, uint32_t b0) {
    asm volatile("mma.sync.aligned.m16n8k8.row.col.f32.bf16.bf16.f32 {%0,%1,%2,%3}, {%4,%5}, {%6}, {%0,%1,%2,%3};"
                 : "+f"(d[0]), "+f"(d[1]), "+f"(d[2]), "+f"(d[3]) : "r"(a0), "r"(a1), "r"(b0));
}
DEVI void ldsm4(uint32_t* r, uint32_t addr) {
    asm volatile("ldmatrix.sync.aligned.m8n8.x4.shared.b16 {%0,%1,%2,%3}, [%4];"
                 : "=r"(r[0]), "=r"(r[1]), "=r"(r[2]), "=r"(r[3]) : "r"(addr) : "memory");
}
DEVI void ldsm4t(uint32_t* r, uint32_t addr) {
    asm volatile("ldmatrix.sync.aligned.m8n8.x4.trans.shared.b16 {%0,%1,%2,%3}, [%4];"
                 : "=r"(r[0]), "=r"(r[1]), "=r"(r[2]), "=r"(r[3]) : "r"(addr) : "memory");
}
DEVI void ldsm2(uint32_t* r, uint32_t addr) {
    asm volatile("ldmatrix.sync.aligned.m8n8.x2.shared.b16 {%0,%1}, [%2];" : "=r"(r[0]), "=r"(r[1]) : "r"(addr) : "memory");
}
DEVI void ldsm1t(uint32_t& r, uint32_t addr) {
    asm volatile("ldmatrix.sync.aligned.m8n8.x1.trans.shared.b16 {%0}, [%1];" : "=r"(r) : "r"(addr) : "memory");
}
DEVI void stsm4(uint32_t addr, uint32_t r0, uint32_t r1, uint32_t r2, uint32_t r3) {
    asm volatile("stmatrix.sync.aligned.m8n8.x4.shared.b16 [%0], {%1,%2,%3,%4};" :: "r"(addr), "r"(r0), "r"(r1), "r"(r2), "r"(r3) : "memory");
}
DEVI void stsm4t(uint32_t addr, uint32_t r0, uint32_t r1, uint32_t r2, uint32_t r3) {
    asm volatile("stmatrix.sync.aligned.m8n8.x4.trans.shared.b16 [%0], {%1,%2,%3,%4};" :: "r"(addr), "r"(r0), "r"(r1), "r"(r2), "r"(r3) : "memory");
}
DEVI uint32_t movm_t(uint32_t a) {
    uint32_t d; asm volatile("movmatrix.sync.aligned.m8n8.trans.b16 %0, %1;" : "=r"(d) : "r"(a)); return d;
}
DEVI uint32_t pack_bf16(float lo, float hi) {
    uint32_t r; asm("cvt.rn.bf16x2.f32 %0, %1, %2;" : "=r"(r) : "f"(hi), "f"(lo)); return r;
}
DEVI float ex2(float x) { float y; asm("ex2.approx.ftz.f32 %0, %1;" : "=f"(y) : "f"(x)); return y; }

DEVI uint4 ld_rlx4(const void* p) {
    uint4 v;
    asm volatile("ld.relaxed.gpu.global.v4.u32 {%0,%1,%2,%3}, [%4];" : "=r"(v.x), "=r"(v.y), "=r"(v.z), "=r"(v.w) : "l"(p) : "memory");
    return v;
}
DEVI void ld_rlx4f(float* d, const void* p) {
    asm volatile("ld.relaxed.gpu.global.v4.f32 {%0,%1,%2,%3}, [%4];" : "=f"(d[0]), "=f"(d[1]), "=f"(d[2]), "=f"(d[3]) : "l"(p) : "memory");
}
DEVI bool all_nzf(const float* d) { return __float_as_uint(d[0]) && __float_as_uint(d[1]) && __float_as_uint(d[2]) && __float_as_uint(d[3]); }
DEVI void sts128f(uint32_t addr, const float* d) {
    asm volatile("st.shared.v4.f32 [%0], {%1,%2,%3,%4};" :: "r"(addr), "f"(d[0]), "f"(d[1]), "f"(d[2]), "f"(d[3]) : "memory");
}
DEVI void st_rlx4(void* p, uint32_t a, uint32_t b, uint32_t c, uint32_t d) {
    asm volatile("st.relaxed.gpu.global.v4.u32 [%0], {%1,%2,%3,%4};" :: "l"(p), "r"(a), "r"(b), "r"(c), "r"(d) : "memory");
}
DEVI void st_rlx(void* p, uint32_t v) { asm volatile("st.relaxed.gpu.global.u32 [%0], %1;" :: "l"(p), "r"(v) : "memory"); }
DEVI void sts128(uint32_t addr, uint4 v) {
    asm volatile("st.shared.v4.u32 [%0], {%1,%2,%3,%4};" :: "r"(addr), "r"(v.x), "r"(v.y), "r"(v.z), "r"(v.w) : "memory");
}
DEVI void sts64(uint32_t addr, uint32_t a, uint32_t b) { asm volatile("st.shared.v2.u32 [%0], {%1,%2};" :: "r"(addr), "r"(a), "r"(b) : "memory"); }
DEVI void sts32(uint32_t addr, uint32_t v) { asm volatile("st.shared.u32 [%0], %1;" :: "r"(addr), "r"(v) : "memory"); }
DEVI uint4 lds128(uint32_t addr) {
    uint4 v; asm volatile("ld.shared.v4.u32 {%0,%1,%2,%3}, [%4];" : "=r"(v.x), "=r"(v.y), "=r"(v.z), "=r"(v.w) : "r"(addr) : "memory"); return v;
}
DEVI float2 lds64f(uint32_t addr) {
    float2 v; asm volatile("ld.shared.v2.f32 {%0,%1}, [%2];" : "=f"(v.x), "=f"(v.y) : "r"(addr) : "memory"); return v;
}
DEVI void cp_async16(uint32_t dst, const void* src) {
    asm volatile("cp.async.cg.shared.global [%0], [%1], 16;" :: "r"(dst), "l"(src) : "memory");
}
DEVI void cp_async_commit() { asm volatile("cp.async.commit_group;" ::: "memory"); }
DEVI void cp_async_wait0() { asm volatile("cp.async.wait_group 0;" ::: "memory"); }
DEVI uint32_t lds32(uint32_t addr) { uint32_t v; asm volatile("ld.shared.u32 %0, [%1];" : "=r"(v) : "r"(addr) : "memory"); return v; }
DEVI float rcp_fast(float x) { float y; asm("rcp.approx.ftz.f32 %0, %1;" : "=f"(y) : "f"(x)); return y; }
DEVI bool all_nz(const uint4& v) { return v.x && v.y && v.z && v.w; }
DEVI uint32_t mapa(uint32_t addr, uint32_t rank) {
    uint32_t r; asm("mapa.shared::cluster.u32 %0, %1, %2;" : "=r"(r) : "r"(addr), "r"(rank)); return r;
}
DEVI void st_async32(uint32_t dst, uint32_t a, uint32_t bar) {
    asm volatile("st.async.weak.shared::cluster.mbarrier::complete_tx::bytes.b32 [%0], %1, [%2];" :: "r"(dst), "r"(a), "r"(bar) : "memory");
}
DEVI void st_async64(uint32_t dst, uint32_t a, uint32_t b, uint32_t bar) {
    asm volatile("st.async.weak.shared::cluster.mbarrier::complete_tx::bytes.v2.b32 [%0], {%1,%2}, [%3];"
                 :: "r"(dst), "r"(a), "r"(b), "r"(bar) : "memory");
}

DEVI void st_async128(uint32_t dst, uint32_t a, uint32_t b, uint32_t c, uint32_t d, uint32_t bar) {
    asm volatile("st.async.weak.shared::cluster.mbarrier::complete_tx::bytes.v4.b32 [%0], {%1,%2,%3,%4}, [%5];"
                 :: "r"(dst), "r"(a), "r"(b), "r"(c), "r"(d), "r"(bar) : "memory");
}

DEVI uint32_t b_addr(uint32_t sb, int row, int which, int chunk) { const int l = 3 * row + which; return sb + l * 128 + ((chunk ^ (l & 7)) * 16); }
DEVI void battn_warp(uint32_t st, uint32_t ebar, int i0, int par, int head, int hh, int mt, int lane) {
    const int gq = lane >> 2, t = lane & 3, r = 16 * mt + (lane & 7), b3 = (lane >> 3) & 1, b4 = lane >> 4;
    uint32_t a[8], k[8], k2[4], v[8], v2[4];
#pragma unroll
    for (int ks = 0; ks < 2; ks++) {
        ldsm4(a + 4 * ks, b_addr(st, 8 + r + b3 * 8, 0, hh * 4 + ks * 2 + b4));
        ldsm4(k + 4 * ks, b_addr(st, r + b4 * 8, 1, hh * 4 + ks * 2 + b3));
    }
    ldsm4(k2, b_addr(st, r + 16, 1, hh * 4 + (lane >> 3)));
#pragma unroll
    for (int n = 0; n < 2; n++) ldsm4t(v + 4 * n, b_addr(st, r + b3 * 8, 2, hh * 4 + 2 * n + b4));
    ldsm4t(v2, b_addr(st, r + 16, 2, hh * 4 + (lane >> 3)));
    float s[3][4];
#pragma unroll
    for (int n = 0; n < 3; n++) { s[n][0] = s[n][1] = s[n][2] = s[n][3] = 0.f; }
#pragma unroll
    for (int ks = 0; ks < 2; ks++) {
        mma16816(s[0], a + 4 * ks, k[4 * ks], k[4 * ks + 1]);
        mma16816(s[1], a + 4 * ks, k[4 * ks + 2], k[4 * ks + 3]);
        mma16816(s[2], a + 4 * ks, k2[2 * ks], k2[2 * ks + 1]);
    }
    const bool ex = i0 + 16 * mt > 0;
    float x[4], y[4];
#pragma unroll
    for (int c = 0; c < 2; c++) {
        const bool low = 2 * t + c <= gq;
        x[c] = !low && ex ? s[0][c] : -INFINITY; x[2 + c] = low ? s[1][c] : -INFINITY;
        y[c] = !low ? s[1][2 + c] : -INFINITY;   y[2 + c] = low ? s[2][2 + c] : -INFINITY;
    }
    float m0 = fmaxf(fmaxf(x[0], x[1]), fmaxf(x[2], x[3])), m1 = fmaxf(fmaxf(y[0], y[1]), fmaxf(y[2], y[3]));
    m0 = fmaxf(fmaxf(m0, __shfl_xor_sync(0xffffffffu, m0, 1)), fmaxf(__shfl_xor_sync(0xffffffffu, m0, 2), __shfl_xor_sync(0xffffffffu, m0, 3)));
    m1 = fmaxf(fmaxf(m1, __shfl_xor_sync(0xffffffffu, m1, 1)), fmaxf(__shfl_xor_sync(0xffffffffu, m1, 2), __shfl_xor_sync(0xffffffffu, m1, 3)));
    constexpr float C = 0.17677669529663687f * 1.4426950408889634f;
    m0 *= -C; m1 *= -C;
    const uint32_t p0[4] = {pack_bf16(ex2(fmaf(x[0], C, m0)), ex2(fmaf(x[1], C, m0))), 0u,
                            pack_bf16(ex2(fmaf(x[2], C, m0)), ex2(fmaf(x[3], C, m0))), pack_bf16(ex2(fmaf(y[0], C, m1)), ex2(fmaf(y[1], C, m1)))};
    const uint32_t p1 = pack_bf16(ex2(fmaf(y[2], C, m1)), ex2(fmaf(y[3], C, m1)));
    float o[4][4], l[4] = {0.f, 0.f, 0.f, 0.f};
#pragma unroll
    for (int n = 0; n < 4; n++) { o[n][0] = o[n][1] = o[n][2] = o[n][3] = 0.f; }
    mma16816(l, p0, 0x3F803F80u, 0x3F803F80u);
#pragma unroll
    for (int n = 0; n < 4; n++) mma16816(o[n], p0, v[2 * n], v[2 * n + 1]);
    mma1688(l, 0u, p1, 0x3F803F80u);
#pragma unroll
    for (int n = 0; n < 4; n++) mma1688(o[n], 0u, p1, v2[n]);
    if (lane == 0) mbar_arrive(ebar);
    const float i0f = rcp_fast(l[0]), i1f = rcp_fast(l[2]);
    uint4* dst = (uint4*)(g_bo + (uint32_t)((2 * (i0 + 16 * mt + gq) + par) * DM + head * 32 + t * 8));
    dst[0] = make_uint4(pack_bf16(o[0][0] * i0f, o[0][1] * i0f), pack_bf16(o[1][0] * i0f, o[1][1] * i0f),
                        pack_bf16(o[2][0] * i0f, o[2][1] * i0f), pack_bf16(o[3][0] * i0f, o[3][1] * i0f));
    dst[16 * DM / 8] = make_uint4(pack_bf16(o[0][2] * i1f, o[0][3] * i1f), pack_bf16(o[1][2] * i1f, o[1][3] * i1f),
                                  pack_bf16(o[2][2] * i1f, o[2][3] * i1f), pack_bf16(o[3][2] * i1f, o[3][3] * i1f));
}

constexpr float SCALE_LOG2E = 0.08838834764831845f * 1.4426950408889634f;

constexpr int P_UNITS = 12, P_STAGES = 6;
constexpr int PS_STG = P_UNITS * 16384;
constexpr int PS_BAR = PS_STG + 32768;
constexpr int P_SMEM = PS_BAR + 256;
static_assert(P_SMEM <= 232448, "smem");
enum { K_Q, K_B1, K_B3, K_A4, K_QH, K_A3, K_SK, K_B2, K_SN, K_END };
struct PList { int n, nworker; int4 run[16]; };
struct PTask { int kind, a, b, c; };
DEVI PTask p_decode(const PList& pl, int id) {
    for (int i = 0; i < pl.n; i++) {
        const int4 r = pl.run[i];
        if (id < r.w) {
            const int j = id - r.z;
            if (r.x == K_Q || r.x == K_QH) return {r.x, j & 31, r.y + (j >> 5), 0};
            if (r.x == K_B1) return {r.x, j % 24, r.y + j / 24, 0};
            if (r.x == K_B2) return {r.x, 0, r.y + j, 0};
            if (r.x == K_SK || r.x == K_SN) return {r.x, (j / P_SPLIT) & 7, r.y + j / (8 * P_SPLIT), j % P_SPLIT};
            return {r.x, j & 7, r.y + (j >> 3), 0};
        }
    }
    return {K_END, 0, 0, 0};
}
DEVI void wait_count(const unsigned* p, unsigned target) {
    int n = 0;
    while (true) {
        unsigned v; asm volatile("ld.acquire.gpu.global.u32 %0, [%1];" : "=r"(v) : "l"(p) : "memory");
        if ((int)(v - target) >= 0) break;
        __nanosleep(100);
        if (++n > SPIN_LIMIT) TRAP(0x10000000u | ((unsigned)(size_t)p & 0xFFFFu));
    }
}
DEVI void wait_count_warp(const unsigned* p, unsigned target) {
    int n = 0;
    while (true) {
        unsigned v; asm volatile("ld.acquire.gpu.global.u32 %0, [%1];" : "=r"(v) : "l"(p) : "memory");
        if (__all_sync(0xffffffffu, (int)(v - target) >= 0)) break;
        __nanosleep(100);
        if (++n > SPIN_LIMIT) TRAP(0x10000000u | ((unsigned)(size_t)p & 0xFFFFu));
    }
}
DEVI void signal_count(unsigned* p) { __threadfence(); atomicAdd(p, 1u); }

struct PMaps { CUtensorMap wq, bw, bwo, wo, x, bx, bo, ox, ox64, cb, cout, cq, b40; PList list; };
constexpr int PB_F = PS_BAR, PB_E = PB_F + 48, PB_TF = PB_F + 96, PB_TE = PB_F + 112, PB_S = PB_F + 128;
constexpr int PS_T = PB_F + 144, PS_SIG = PS_T + 32, PS_SK = PS_SIG + 16;

struct PRing {
    int st, ph, u;
    DEVI void next(int n) { u += n; if (u >= P_UNITS) u -= P_UNITS; if (++st == P_STAGES) { st = 0; ph ^= 1; } }
    DEVI uint32_t w(bool wide) const { return wide && u == P_UNITS - 2 ? 0u : u * 16384u; }
    DEVI uint32_t x(bool wide) const { return wide && u == P_UNITS - 2 ? u * 16384u : (u == P_UNITS - 1 ? 0u : (u + 1) * 16384u); }
};
struct POut { const CUtensorMap* map; int col, tok, cnt; bool blocked; };
DEVI void p_store(const uint32_t* pk, const POut& o, int c, uint32_t stg, int warp, int lane_, int barid, bool elected) {
    const int lane = (int)opaque((uint32_t)lane_);
    const int mi = lane >> 3, r = lane & 7;
    const uint32_t buf = stg + (c & 1) * 8192;
    if (elected) asm volatile("cp.async.bulk.wait_group.read 1;" ::: "memory");
    nbar_sync(barid, 128);
    if (o.blocked) {
#pragma unroll
        for (int j = 0; j < 8; j += 2)
            stsm4(buf + (j + (mi >> 1)) * 1024 + (warp * 16 + (mi & 1) * 8 + r) * 16, pk[2 * j], pk[2 * j + 1], pk[2 * j + 2], pk[2 * j + 3]);
    } else {
#pragma unroll
        for (int j = 0; j < 8; j += 2)
            stsm4t(buf + (8 * (j + (mi >> 1)) + r) * 128 + ((2 * warp + (mi & 1)) ^ r) * 16, pk[2 * j], pk[2 * j + 1], pk[2 * j + 2], pk[2 * j + 3]);
    }
    fence_proxy_async();
    nbar_sync(barid, 128);
    if (elected) {
        if (o.blocked)
            asm volatile("cp.async.bulk.tensor.4d.global.shared::cta.bulk_group [%0, {%2, %3, %4, %5}], [%1];"
                         :: "l"(o.map), "r"(buf), "r"(0), "r"((o.col >> 5) & 2), "r"((o.col >> 7) * 4), "r"((o.tok >> 5) + 2 * c) : "memory");
        else tma_store_2d(o.map, buf, o.col, o.tok + c * 64);
        bulk_commit();
    }
}
DEVI void p_signal(uint32_t sb, int g, int cnt, int& nsig) {
    sts32(sb + PS_SIG + g * 8 + (nsig & 1) * 4, (uint32_t)cnt);
    mbar_arrive(sb + PB_S + g * 8);
    nsig++;
}
DEVI void p_release(uint32_t sb, const PRing& r) {
    if (elect_one()) mbar_arrive(sb + PB_E + (r.st ? r.st - 1 : P_STAGES - 1) * 8);
}
template <int BN, bool FIRST>
DEVI void p_kblock(float* d, uint32_t sb, int g, PRing& r) {
    mbar_wait(sb + PB_F + r.st * 8, r.ph);
    const uint64_t da = mk_desc(sb + r.w(BN == 256) + g * 8192, 16, 1024, 1), db = mk_desc(sb + r.x(BN == 256), 16, 1024, 1);
    wg_fence();
#pragma unroll
    for (int kk = 0; kk < 4; kk++) {
        if (BN == 256) { if (FIRST && kk == 0) wgmma_n256_ss<true>(d, da, db); else wgmma_n256_ss<false>(d, da + (uint64_t)(kk * 128), db + (uint64_t)(kk * 2)); }
        if (BN == 128) { if (FIRST && kk == 0) wgmma_n128_ss<true>(d, da, db); else wgmma_n128_ss<false>(d, da + (uint64_t)(kk * 128), db + (uint64_t)(kk * 2)); }
        if (BN == 64)  { if (FIRST && kk == 0) wgmma_n64_ss<true>(d, da, db); else wgmma_n64_ss<false>(d, da + (uint64_t)(kk * 128), db + (uint64_t)(kk * 2)); }
    }
    wg_commit();
    if (!FIRST) {
        wg_wait<1>();
        p_release(sb, r);
    }
    r.next(BN == 256 ? 3 : 2);
}

DEVI int post_claim(const PMaps& mp, unsigned E) {
    unsigned v = 0;
    if ((threadIdx.x & 31) == 0) v = atomicAdd(&g_qctr, 1u);
    return (int)(__shfl_sync(0xffffffffu, v, 0) - (E - 1) * (unsigned)(mp.list.run[mp.list.n - 1].w + mp.list.nworker));
}
DEVI void post_producer(const PMaps& mp, uint32_t sb, unsigned E, int id) {
    PRing r = {0, 0, 0};
    int ts = 0, tp = 0, used = 0;
    uint32_t big = 0;
    auto reserve = [&](int n) {
        while (used + n > P_UNITS) {
            mbar_wait(sb + PB_E + ts * 8, tp);
            used -= 2 + ((big >> ts) & 1);
            if (++ts == P_STAGES) { ts = 0; tp ^= 1; }
        }
        used += n;
        big = (big & ~(1u << r.st)) | ((uint32_t)(n & 1) << r.st);
    };
    for (int i = 0;; i++) {
        mbar_wait(sb + PB_TE + (i & 1) * 8, ((i >> 1) & 1) ^ 1);
        if (i > 0) id = post_claim(mp, E);
        const PTask tk = p_decode(mp.list, id);
        const bool sn = tk.kind == K_SN, split = tk.kind == K_SK || sn, wide = tk.kind <= K_A4;
        const bool qk = tk.kind == K_Q || tk.kind == K_QH, ak = tk.kind == K_A4 || tk.kind == K_A3 || split;
        const int nk = split ? HD / 64 / P_SPLIT : (ak ? HD / 64 : DM / 64), kb0 = tk.c * (HD / 64 / P_SPLIT);
        const int tok0 = tk.b * (wide ? 256 : (sn ? 64 : 128)), grp = (tok0 >> 7) + (wide ? 1 : 0);
        const uint32_t bytes = wide ? 49152 : (sn ? 24576 : 32768);
        const CUtensorMap* tx = tk.kind == K_B1 ? &mp.bx : (qk ? &mp.x : (sn ? &mp.ox64 : (ak ? &mp.ox : &mp.bo)));
        const int npre = split && (i == 0 || __any_sync(0xffffffffu, (int)(*(volatile unsigned*)&g_prog[grp] - 128 * E) < 0)) ? P_STAGES : 0;
        PRing rp = r;
        for (int kb = kb0; kb < kb0 + npre; kb++) {
            reserve(2);
            const uint32_t bar = sb + PB_F + r.st * 8;
            if (elect_one()) {
                mbar_expect_tx(bar, bytes);
                tma_load_wo(sb + r.w(false), &mp.wo, tk.a * 128, kb * 2, bar);
                tma_load_wo(sb + r.w(false) + 8192, &mp.wo, tk.a * 128 + 64, kb * 2, bar);
            }
            r.next(2);
        }
        if (tk.kind == K_B2) {
            wait_count_warp(&g_cnt[C_B1 + (tk.b >> 2)], 48 * E);
            if ((tk.b & 3) == 0 && tk.b > 0) wait_count_warp(&g_cnt[C_B1 + (tk.b >> 2) - 1], 48 * E);
        } else if (tk.kind == K_B3) wait_count_warp(&g_cnt[C_B2 + tk.b], 8 * E);
        else if (ak) wait_count_warp(&g_prog[grp], 128 * E);
        fence_proxy_global();
        for (int kb = kb0; kb < kb0 + npre; kb++) {
            if (elect_one()) tma_load_2d(sb + rp.x(false), tx, kb * 64, tok0, sb + PB_F + rp.st * 8);
            rp.next(2);
        }
        if (elect_one()) {
            sts128(sb + PS_T + (i & 1) * 16, make_uint4((uint32_t)tk.kind | ((uint32_t)id << 8), (uint32_t)tk.a, (uint32_t)tk.b, (uint32_t)tk.c));
            mbar_arrive(sb + PB_TF + (i & 1) * 8);
        }
        if (tk.kind == K_END) break;
        if (tk.kind == K_B2) {
            for (int j = 0; j < 16; j++) {
                reserve(2);
                const uint32_t bar = sb + PB_F + r.st * 8;
                if (elect_one()) {
                    mbar_expect_tx(bar, 2 * 15360);
#pragma unroll
                    for (int u = 0; u < 2; u++) asm volatile("cp.async.bulk.tensor.4d.shared::cluster.global.mbarrier::complete_tx::bytes [%0], [%1, {%3, %4, %5, %6}], [%2];"
                                 :: "r"(sb + (u ? r.x(false) : r.w(false))), "l"(&mp.b40), "r"(bar), "r"(j * 64), "r"(0), "r"(u), "r"(tk.b * 32 - 8) : "memory");
                }
                r.next(2);
            }
            continue;
        }
        const CUtensorMap* tw = tk.kind == K_B1 ? &mp.bw : (qk ? &mp.wq : (ak ? &mp.wo : &mp.bwo));
        for (int kb = kb0 + npre; kb < kb0 + nk; kb++) {
            reserve(wide ? 3 : 2);
            const uint32_t aw = sb + r.w(wide), ax = sb + r.x(wide), bar = sb + PB_F + r.st * 8;
            if (elect_one()) {
                mbar_expect_tx(bar, bytes);
                if (ak || tk.kind == K_B3) {
                    tma_load_wo(aw, tw, tk.a * 128, kb * 2, bar);
                    tma_load_wo(aw + 8192, tw, tk.a * 128 + 64, kb * 2, bar);
                } else {
                    tma_load_2d(aw, tw, tk.a * 128, kb * 64, bar);
                    tma_load_2d(aw + 8192, tw, tk.a * 128 + 64, kb * 64, bar);
                }
                tma_load_2d(ax, tx, kb * 64, tok0, bar);
                if (wide) tma_load_2d(ax + 16384, tx, kb * 64, tok0 + 128, bar);
            }
            r.next(wide ? 3 : 2);
        }
    }
    if (elect_one()) {
        __threadfence();
        if (atomicAdd(&g_done, 1u) == E * mp.list.nworker - 1) { __threadfence(); *(volatile unsigned*)&g_epoch = E; }
    }
}
DEVI void post_helper(uint32_t sb, int g) {
    for (int n = 0;; n++) {
        mbar_wait_sleepy(sb + PB_S + g * 8, n & 1);
        const int cnt = (int)lds32(sb + PS_SIG + g * 8 + (n & 1) * 4);
        if (cnt < 0) break;
        signal_count(&g_cnt[cnt]);
    }
}
template <int BN>
DEVI void p_narrow(const PMaps& mp, const PTask& tk, uint32_t sb, int g, int warp, PRing& r, int& nsig) {
    const int barid = 1 + g, tid = threadIdx.x;
    const bool elected = (tid & 127) == 0, split = BN == 64 || tk.kind == K_SK;
    constexpr int NV = BN / 16;
    float d[BN / 2];
    const int nk = split ? HD / 64 / P_SPLIT : (tk.kind == K_A3 ? HD / 64 : DM / 64);
    p_kblock<BN, true>(d, sb, g, r);
#pragma unroll 1
    for (int kb = 1; kb < nk; kb++) p_kblock<BN, false>(d, sb, g, r);
    wg_wait<0>();
    reg_fence<BN / 2>(d);
    p_release(sb, r);
    if (split) {
        const int tile = (tk.b * (BN / 64) - 2 * (16 - P_NSK)) * 8 + tk.a * (BN / 64);
        uint4* const base = g_skp + (uint32_t)(tile * P_SPLIT * 1024 + g * NV * 128 + (tid & 127));
#pragma unroll
        for (int j = 0; j < NV; j++)
            base[tk.c * NV * 256 + j * 128] = make_uint4(pack_bf16(d[8 * j], d[8 * j + 1]), pack_bf16(d[8 * j + 2], d[8 * j + 3]),
                                                         pack_bf16(d[8 * j + 4], d[8 * j + 5]), pack_bf16(d[8 * j + 6], d[8 * j + 7]));
        nbar_sync(barid, 128);
        if (elected) {
            unsigned old;
            asm volatile("atom.acq_rel.gpu.global.add.u32 %0, [%1], 1;" : "=r"(old) : "l"(&g_cnt_sk[tile * 2 + g]) : "memory");
            sts32(sb + PS_SK + g * 4, old % P_SPLIT);
        }
        nbar_sync(barid, 128);
        const bool last = lds32(sb + PS_SK + g * 4) == P_SPLIT - 1;
        nbar_sync(barid, 128);
        if (!last) return;
        uint4 v[(P_SPLIT - 1) * NV];
#pragma unroll
        for (int j = 0; j < (P_SPLIT - 1) * NV; j++) v[j] = __ldcg(base + ((tk.c + 1 + j / NV) % P_SPLIT) * NV * 256 + (j % NV) * 128);
#pragma unroll
        for (int j = 0; j < (P_SPLIT - 1) * NV; j++) {
            float* e = d + 8 * (j % NV);
            e[0] += __uint_as_float(v[j].x << 16); e[1] += __uint_as_float(v[j].x & 0xFFFF0000u);
            e[2] += __uint_as_float(v[j].y << 16); e[3] += __uint_as_float(v[j].y & 0xFFFF0000u);
            e[4] += __uint_as_float(v[j].z << 16); e[5] += __uint_as_float(v[j].z & 0xFFFF0000u);
            e[6] += __uint_as_float(v[j].w << 16); e[7] += __uint_as_float(v[j].w & 0xFFFF0000u);
        }
    }
    const bool qh = BN == 128 && tk.kind == K_QH;
    const POut o = {qh ? &mp.cq : &mp.cout, tk.a * 128 + g * 64, tk.b * BN, 0, qh};
    uint32_t q[BN / 4];
#pragma unroll
    for (int j = 0; j < BN / 4; j++) q[j] = pack_bf16(d[2 * j], d[2 * j + 1]);
    if (BN == 64 && elected) bulk_wait_read();
#pragma unroll
    for (int c = 0; c < BN / 64; c++) p_store(q + 16 * c, o, c, sb + PS_STG + g * 16384, warp, tid & 31, barid, elected);
    if (BN == 64 && elected) bulk_wait_read();
    if (elected && qh) { bulk_wait_all(); p_signal(sb, g, tk.b == 0 ? C_QH : C_Q, nsig); }
}
DEVI void post_consumer(const PMaps& mp, uint32_t sb, int g, int warp) {
    const int barid = 1 + g, tid = threadIdx.x, lane = tid & 31;
    const bool elected = (tid & 127) == 0;
    const uint32_t stg = sb + PS_STG + g * 16384;
    int nsig = 0;
    PRing r = {0, 0, 0};
    uint32_t pk[64];
    POut out;
    bool pend = false;
#pragma unroll
    for (int i = 0; i < 64; i++) pk[i] = 0u;
    for (int i = 0;; i++) {
        const uint32_t bTF = sb + PB_TF + (i & 1) * 8;
        if (pend) {
            uint32_t now;
            asm volatile("{.reg .pred p, q; mbarrier.test_wait.parity.shared::cta.b64 p, [%1], %2; bar.red.and.pred q, %3, 128, p; selp.u32 %0, 1, 0, q;}"
                         : "=r"(now) : "r"(bTF), "r"((i >> 1) & 1), "r"(barid) : "memory");
            if (!now || (lds32(sb + PS_T + (i & 1) * 16) & 255u) > K_A4) {
#pragma unroll
                for (int c = 0; c < 4; c++) p_store(pk + 16 * c, out, c, stg, warp, lane, barid, elected);
                if (elected && out.cnt != C_NONE) { bulk_wait_all(); p_signal(sb, g, out.cnt, nsig); }
                pend = false;
            }
        }
        mbar_wait(bTF, (i >> 1) & 1);
        const uint4 tw = lds128(sb + PS_T + (i & 1) * 16);
        mbar_arrive(sb + PB_TE + (i & 1) * 8);
        const PTask tk = {(int)(tw.x & 255u), (int)tw.y, (int)tw.z, (int)tw.w};
        if (tk.kind == K_END) break;
        if (tk.kind <= K_A4) {
            float d[128];
            const int nk = tk.kind == K_A4 ? HD / 64 : DM / 64;
            p_kblock<256, true>(d, sb, g, r);
            if (pend) p_store(pk, out, 0, stg, warp, lane, barid, elected);
#pragma unroll
            for (int c = 1; c < 4; c++) {
                p_kblock<256, false>(d, sb, g, r);
                if (pend) p_store(pk + 16 * c, out, c, stg, warp, lane, barid, elected);
            }
#pragma unroll 1
            for (int kb = 4; kb < nk; kb++) {
                p_kblock<256, false>(d, sb, g, r);
                if (kb == 6 && pend && elected && out.cnt != C_NONE) { bulk_wait_all(); p_signal(sb, g, out.cnt, nsig); }
            }
            wg_wait<0>();
            reg_fence<128>(d);
            p_release(sb, r);
#pragma unroll
            for (int j = 0; j < 64; j++) pk[j] = pack_bf16(d[2 * j], d[2 * j + 1]);
            out.map = tk.kind == K_Q ? &mp.cq : (tk.kind == K_B1 ? &mp.cb : &mp.cout);
            out.col = tk.a * 128 + g * 64 + (tk.kind == K_B3 ? DM : 0);
            out.tok = tk.b * 256;
            out.cnt = tk.kind == K_Q ? C_Q + tk.b : (tk.kind == K_B1 ? C_B1 + tk.b : C_NONE);
            out.blocked = tk.kind == K_Q;
            pend = true;
        } else if (tk.kind == K_B2) {
#pragma unroll 2
            for (int j = 0; j < 16; j++) {
                mbar_wait(sb + PB_F + r.st * 8, r.ph);
                const uint32_t a = sb + (g ? r.x(false) : r.w(false));
                battn_warp(a, sb + PB_E + r.st * 8, tk.b * 32, g, j * 2 + (warp >> 1), warp >> 1, warp & 1, lane);
                r.next(2);
            }
            nbar_sync(barid, 128);
            if (elected) p_signal(sb, g, C_B2 + (tk.b >> 2), nsig);
#pragma unroll
            for (int j = 0; j < 64; j++) pk[j] = 0u;
        } else {
            if (tk.kind == K_SN) p_narrow<64>(mp, tk, sb, g, warp, r, nsig); else p_narrow<128>(mp, tk, sb, g, warp, r, nsig);
#pragma unroll
            for (int j = 0; j < 64; j++) pk[j] = 0u;
        }
    }
    if (elected) { bulk_wait_all(); p_signal(sb, g, -1, nsig); }
}
DEVI void post_init(uint32_t sb) {
    for (int i = 0; i < P_STAGES; i++) { mbar_init(sb + PB_F + i * 8, 1); mbar_init(sb + PB_E + i * 8, 8); }
    for (int i = 0; i < 2; i++) { mbar_init(sb + PB_TF + i * 8, 1); mbar_init(sb + PB_TE + i * 8, 256); mbar_init(sb + PB_S + i * 8, 1); }
    fence_mbar_init();
}

constexpr unsigned long long R_TORD_PACK = 0xfae93542dc187b60ull;
__host__ __device__ constexpr int r_tord(int pos) { return (int)((R_TORD_PACK >> (4 * pos)) & 15ull); }
__host__ __device__ constexpr int r_tinv(int T) { for (int p = 0; p < 16; p++) if (r_tord(p) == T) return p; return 0; }
__host__ __device__ constexpr bool r_pos_ss(int pos) { return pos % 3 == 2; }
__host__ __device__ constexpr int r_ss(int pos) { return pos / 3; }
__host__ __device__ constexpr int r_rs(int pos) { return pos - pos / 3; }
constexpr int R_NRS = 11, R_NSS = 5;
constexpr int R_G1 = 3, R_G2 = 9, R_G3 = 12;
#define REG_KB 232
constexpr int X_SLOTS = 4;
constexpr int X_NST = 8;

constexpr int RS_WSS  = 0;
constexpr int RS_WO   = RS_WSS + R_NSS * 16384;
constexpr int RS_MEM  = RS_WO + 5 * 16384;
constexpr int RS_O    = RS_MEM + 16384;
constexpr int RS_SX   = RS_O + 2048;
constexpr int RS_BAR  = RS_SX + 2048;
constexpr int RS_TAIL = RS_BAR + 1024;
constexpr int RS_WO5  = RS_TAIL;
constexpr int RS_K    = RS_WO5 + 16384;
constexpr int RS_V    = RS_K + 10240;
constexpr int RS_Q    = RS_V + 10240;
constexpr int RS_QX   = RS_Q + 2048;
constexpr int RS_QEND = RS_QX + 8192;
constexpr int RS_X    = RS_TAIL;
constexpr int X_PITCH = X_SLOTS * 4096;
constexpr int RS_XD   = RS_X + 2 * X_PITCH;
constexpr int RS_WX   = RS_XD + 8192;
constexpr int RS_XE   = RS_WX + 4096;
constexpr int RS_KEND = RS_XE + 2048;
constexpr int RS_EV   = RS_BAR + 256;
constexpr int R_SMEM  = RS_KEND > RS_QEND ? RS_KEND : RS_QEND;
static_assert(R_SMEM <= 232448 && P_SMEM <= R_SMEM, "smem");
static_assert(RS_TAIL % 1024 == 0 && RS_MEM % 1024 == 0, "alignment");

constexpr int RB_G = RS_BAR, RB_K = RS_BAR + 24, RB_V = RS_BAR + 32, RB_KV = RS_BAR + 40, RB_QX = RS_BAR + 48, RB_O = RS_BAR + 56;
constexpr int RB_ATT = RS_BAR + 64, RB_W = RS_BAR + 72, RB_SF = RS_BAR + 80, RB_SE = RB_SF + 40, RB_XF = RB_SE + 40;
constexpr int RB_VX = RB_XF + 48, RB_WO = RB_XF + 56, RB_T = RB_XF + 64, RB_G3 = RB_XF + 72, RS_INV = RB_XF + 16;
static_assert(RB_G3 + 8 <= RS_EV, "barriers");
constexpr uint32_t SB0 = 1024;
__host__ __device__ constexpr uint32_t cdesc(uint32_t off, uint32_t lbo) { return ((SB0 + off) >> 4) | ((lbo >> 4) << 16); }
#define SCHED_FENCE() __syncwarp()
constexpr int NB_BIG = 1, NB_Q = 2, NB_AUX = 3, NB_WO = 4, NB_XS = 5, NB_WG = 6, NB_PAIR = 8, NB_PRO = 12;

DEVI int tid_now() { int t; asm volatile("mov.u32 %0, %%tid.x;" : "=r"(t)); return t; }
DEVI uint32_t a_frag_off(int lane, int warp) { return (uint32_t)((((lane >> 4) * 8 + (lane & 7)) * 128) + (((2 * warp + ((lane >> 3) & 1)) ^ (lane & 7)) * 16)); }
DEVI uint32_t b_frag_off(int lane) { return (uint32_t)((lane & 3) * 64 + (((lane >> 2) * 8) ^ ((lane & 2) * 16))); }
DEVI void lds_b(uint32_t* b, uint32_t a) {
    asm volatile("ld.shared.v2.u32 {%0,%1}, [%2];" : "=r"(b[0]), "=r"(b[1]) : "r"(a) : "memory");
    asm volatile("ld.shared.v2.u32 {%0,%1}, [%2];" : "=r"(b[2]), "=r"(b[3]) : "r"(a + 256) : "memory");
}
DEVI uint32_t clk32() { unsigned long long c; asm volatile("mov.u64 %0, %%clock64;" : "=l"(c)); return (uint32_t)c; }

__host__ __device__ constexpr int x_pair(int j) { return j < 2 || j > 5 ? j : (j == 2 ? 5 : j - 1); }
DEVI void x_load(uint32_t sb, int seg, int j, int g, const CUtensorMap* tmX) {
    const uint32_t bar = sb + RB_XF + g * 8;
    mbar_expect_tx(bar, 4096);
    tma_load_3d(sb + RS_X + g * X_PITCH + (j % X_SLOTS) * 4096, tmX + (j == 3), g * 32, seg * 32, x_pair(j) * 2, bar);
    if (j == 3) tma_load_3d(sb + RS_SX + g * (RS_XE - RS_SX), tmX + 1, g * 32, seg * 32, x_pair(3) * 2 + 1, bar);
}
DEVI void x_refill(uint32_t sb, int seg, int j, int g, int warp, const CUtensorMap* tmX) {
    const int sn = j + X_SLOTS < X_NST ? seg : seg + 1;
    if (warp == (j & 3) && sn < NSEG) {
        if (elect_one()) x_load(sb, sn, (j + X_SLOTS) % X_NST, g, tmX);
    }
}
template <int J, int Q0, int Q1, int DQ>
DEVI void x_steps(float* xa, const uint32_t* w, int g0) {
    const int g = (int)opaque((uint32_t)g0);
    const uint32_t dW0 = cdesc(RS_WSS, 16) + g * 768, dW1 = cdesc(RS_WSS + 8192, 16) - g * 256;
#pragma unroll
    for (int q = Q0; q < Q1; q += DQ) {
        const int pos = r_tinv(2 * x_pair(J) + (q >> 2)), kk = (q >> 1) & 1, mt = q & 1;
        const uint32_t db = (J == 3 && q >= 4 ? cdesc(RS_SX, 16) + g * ((RS_XE - RS_SX) >> 4)
                                                    : cdesc(RS_X + (J % X_SLOTS) * 4096, 16) + g * (X_PITCH >> 4) + (q >> 2) * 128) + kk * 2;
        if (J == 0 && q < 2)   wgmma_n32_rs_first(xa + 16 * mt, &w[((r_rs(pos) * 2 + kk) * 2 + mt) * 4], db);
        else if (J == 0 && q == 3) wgmma_n32_ss(xa + 16, cdesc(RS_WX, 16) + g * 128, db);
        else if (r_pos_ss(pos)) wgmma_n32_ss(xa + 16 * mt, (mt ? dW1 : dW0) + r_ss(pos) * 1024 + kk * 128, db);
        else                   wgmma_n32_rs(xa + 16 * mt, &w[((r_rs(pos) * 2 + kk) * 2 + mt) * 4], db);
    }
}
DEVI void x_first(float* xa, const uint32_t* w, uint32_t sb, int seg, int g0, int warp, const CUtensorMap* tmX) {
    wg_fence();
    x_steps<0, 0, 8, 1>(xa, w, g0); wg_commit();
    x_steps<1, 0, 8, 1>(xa, w, g0); wg_commit();
    x_steps<2, 0, 8, 1>(xa, w, g0); wg_commit();
    x_steps<3, 0, 4, 1>(xa, w, g0); wg_commit();
    const int g = (int)opaque((uint32_t)g0);
    wg_wait<3>(); x_refill(sb, seg, 0, g, warp, tmX);
    wg_wait<2>(); x_refill(sb, seg, 1, g, warp, tmX);
    wg_wait<1>(); x_refill(sb, seg, 2, g, warp, tmX);
    wg_wait<0>(); x_refill(sb, seg, 3, g, warp, tmX);
    reg_fence<32>(xa);
    mbar_wait(sb + RB_XF + g * 8, 1);
}
DEVI void x_second(float* xa, uint32_t* a, uint32_t aA0, const uint32_t* w, uint32_t sb, int seg, int g0, int warp, const CUtensorMap* tmX) {
    wg_fence();
    x_steps<4, 0, 8, 1>(xa, w, g0); wg_commit();
    x_steps<3, 5, 8, 2>(xa, w, g0); x_steps<5, 1, 8, 2>(xa, w, g0); x_steps<6, 1, 8, 2>(xa, w, g0); x_steps<7, 1, 8, 2>(xa, w, g0); wg_commit();
    x_steps<3, 4, 8, 2>(xa, w, g0); x_steps<5, 0, 8, 2>(xa, w, g0); x_steps<6, 0, 8, 2>(xa, w, g0); x_steps<7, 0, 8, 2>(xa, w, g0); wg_commit();
    const int g = (int)opaque((uint32_t)g0);
    wg_wait<2>(); x_refill(sb, seg, 4, g, warp, tmX);
    SCHED_FENCE();
#pragma unroll
    for (int q = 0; q < 4; q++) ldsm4t(a + 4 * q, aA0 + (q & 1) * (8192 - g * 16384) + (q >> 1) * 2048);
    SCHED_FENCE();
    wg_wait<1>();
    reg_fence<16>(xa + 16);
}
DEVI void x_finish(float* xa, uint32_t sb, int g, int warp, int lane) {
    const uint32_t d = sb + RS_XD + (lane >> 4) * 2048 + warp * 256 + (lane & 15) * 16;
#pragma unroll
    for (int i = 0; i < 2; i++) {
        const float* x = xa + 16 + 8 * i;
        sts128(d + (g ^ 1) * 1024 + i * 4096, make_uint4(pack_bf16(x[0], x[1]), pack_bf16(x[2], x[3]), pack_bf16(x[4], x[5]), pack_bf16(x[6], x[7])));
    }
    nbar_sync(NB_PAIR + warp, 64);
    float y[16];
#pragma unroll
    for (int i = 0; i < 2; i++) {
        const uint4 v = lds128(d + g * 1024 + i * 4096);
        const uint32_t u[4] = {v.x, v.y, v.z, v.w};
#pragma unroll
        for (int j = 0; j < 4; j++) { y[8 * i + 2 * j] = __uint_as_float(u[j] << 16); y[8 * i + 2 * j + 1] = __uint_as_float(u[j] & 0xFFFF0000u); }
    }
    reg_fence<16>(y);
    wg_wait<0>();
    reg_fence<16>(xa);
    uint32_t p[8];
#pragma unroll
    for (int j = 0; j < 8; j++) p[j] = pack_bf16(xa[2 * j] + y[2 * j], xa[2 * j + 1] + y[2 * j + 1]);
    __syncwarp();
    stsm4(d + g * 1024, p[0], p[1], p[2], p[3]);
    stsm4(d + g * 1024 + 4096, p[4], p[5], p[6], p[7]);
    nbar_arrive(NB_XS, 256 + 32);
}
DEVI void x_send(uint32_t sb, int seg, uint32_t rank, const CUtensorMap* tmX) {
    auto refill = [&]() {
        if (seg + 1 < NSEG && elect_one()) {
#pragma unroll
            for (int j = 1; j < 4; j++) { x_load(sb, seg + 1, j, 0, tmX); x_load(sb, seg + 1, j, 1, tmX); }
        }
        __syncwarp();
    };
    mbar_wait(sb + RB_ATT, (seg - 1) & 1);
    nbar_sync(NB_XS, 256 + 32);
    if (rank == 2) { refill(); mbar_wait(sb + RB_G3, (seg - 1) & 1); }
    if (elect_one()) {
        fence_proxy_async();
        bulk_copy_s2c(mapa(sb + (rank == 1 ? RS_K : RS_V) + 2048, 0), sb + RS_XD, 8192, mapa(sb + (rank == 1 ? RB_KV : RB_VX), 0));
    }
    __syncwarp();
    if (rank == 1) refill();
}

template <bool XP>
DEVI void mem_pass(float* c0, float* c1, uint32_t* a, const uint32_t* w, uint32_t sb, uint32_t aA0, uint32_t aB, int g, int warp, int s) {
    const uint32_t aA1 = aA0 + 8192 - g * 16384, par = (s - 1) & 1;
    uint32_t b[2][4], e[4];
    float d0[4], d1[4];
    if (XP) ldsm4t(e, aA0 + opaque((RS_WX - RS_WSS) - g * (8192 + 2048)));
#pragma unroll
    for (int q = XP ? 4 : 0; q < 4; q++) ldsm4t(a + 4 * q, ((q & 1) ? aA1 : aA0) + (q >> 1) * 2048);
#pragma unroll
    for (int i = 0; i < 4; i++) { c0[i] = 0.f; c1[i] = 0.f; d0[i] = 0.f; d1[i] = 0.f; }
    EV(EV_BIG0, s, 0);
    mbar_wait(sb + RB_G, par);
    EV(EV_BIG0, s, 1);
    lds_b(b[0], aB + r_tord(0) * 1024);
    bool in = false;
#pragma unroll
    for (int pos = 0; pos < 16; pos++) {
        if (pos + 1 < 16) {
            if (pos + 1 == R_G1 && !in) mbar_wait(sb + RB_G + 8, par);
            if (pos + 1 == R_G2 && !in) mbar_wait(sb + RB_G + 16, par);
            if (pos + 1 == R_G3) { if (!in) mbar_wait(sb + RB_G3, par); EV(EV_BIG0, s, 2); }
            lds_b(b[(pos + 1) & 1], aB + r_tord(pos + 1) * 1024);
        }
        if (pos + 2 == R_G1) in = mbar_try(sb + RB_G + 8, par);
        if (pos + 2 == R_G2) in = mbar_try(sb + RB_G + 16, par);
        if (pos + 2 == R_G3) in = mbar_try(sb + RB_G3, par);
        if (XP && pos == 14) in = mbar_try(sb + RB_ATT, par);
        const uint32_t* bb = b[pos & 1];
        const uint32_t* aa = r_pos_ss(pos) ? a : &w[r_rs(pos) * 16];
        mma16816(c1, aa + 4, bb[0], bb[1]);
        mma16816(d1, XP && pos == 0 ? e : aa + 12, bb[2], bb[3]);
        mma16816(c0, aa, bb[0], bb[1]);
        mma16816(d0, aa + 8, bb[2], bb[3]);
        if (r_pos_ss(pos) && pos + 3 < 16) {
#pragma unroll
            for (int q = 0; q < 4; q++) ldsm4t(a + 4 * q, ((q & 1) ? aA1 : aA0) + (r_ss(pos) + 1) * 16384 + (q >> 1) * 2048);
        }
        SCHED_FENCE();
    }
    if (XP && !in) mbar_wait(sb + RB_ATT, par);
#pragma unroll
    for (int i = 0; i < 4; i++) { c1[i] += d1[i]; c0[i] += d0[i]; }
}

DEVI uint32_t k_frag_off(int lane) { return (uint32_t)((((lane >> 3) & 1) * 16 + (lane >> 4) * 8 + (lane & 7)) * 16); }
DEVI uint32_t v_frag_off(int lane) { return (uint32_t)(((lane >> 3) & 1) * 2048 + ((lane >> 4) * 8 + (lane & 7)) * 16); }
DEVI void pv_pair(float (*o)[4], const uint32_t* p, const uint32_t* v) {
#pragma unroll
    for (int n = 0; n < 4; n++) mma16816(o[n], p, v[2 * n], v[2 * n + 1]);
}
DEVI void pv_single(float (*o)[4], const uint32_t* p, const uint32_t* v) {
#pragma unroll
    for (int n = 0; n < 4; n++) mma1688(o[n], p[0], p[1], v[n]);
}
DEVI void s_tile(const uint32_t* qa, const uint32_t* k, float& s0, float& s1) {
    float c[4][4];
#pragma unroll
    for (int q = 0; q < 4; q++) { c[q][0] = c[q][1] = c[q][2] = c[q][3] = 0.f; }
#pragma unroll
    for (int q = 0; q < 4; q++) {
        mma16816(c[2 * (q & 1)], qa + 4 * q, k[4 * q], k[4 * q + 1]);
        mma16816(c[2 * (q & 1) + 1], qa + 4 * q, k[4 * q + 2], k[4 * q + 3]);
    }
    s0 = (c[0][0] + c[1][2]) + (c[2][0] + c[3][2]);
    s1 = (c[0][1] + c[1][3]) + (c[2][1] + c[3][3]);
}
DEVI void mem_scores(uint32_t sb, int s, int lane) {
    const uint32_t ka = sb + RS_K + k_frag_off(lane), sa = sb + RS_SX + 1024 + lane * 8;
    uint32_t qa[16], km[16];
    nbar_sync(NB_Q, 256);
#pragma unroll
    for (int q = 0; q < 4; q++) ldsm4t(qa + 4 * q, sb + RS_Q + q * 512 + lane * 16);
    mbar_wait(sb + RB_K, s & 1);
#pragma unroll
    for (int q = 0; q < 4; q++) ldsm4t(km + 4 * q, ka + q * 512);
    SCHED_FENCE();
    float s0, s1;
    s_tile(qa, km, s0, s1);
    asm volatile("st.shared.v2.f32 [%0], {%1,%2};" :: "r"(sa), "f"(s0 * SCALE_LOG2E), "f"(s1 * SCALE_LOG2E) : "memory");
    nbar_arrive(NB_XS, 128 + 32);
}
DEVI float quad_max(float m) {
    return fmaxf(fmaxf(m, __shfl_xor_sync(0xffffffffu, m, 1)), fmaxf(__shfl_xor_sync(0xffffffffu, m, 2), __shfl_xor_sync(0xffffffffu, m, 3)));
}
DEVI void mem_attn(uint32_t sb, int s, int warp, int lane) {
    const uint32_t va = sb + RS_V + warp * 512, sa = sb + RS_SX + lane * 8;
    [[maybe_unused]] constexpr int g = 0;
    float o[4][4], mx, l = 0.f;
    {
        const uint32_t ka = sb + RS_K + k_frag_off(lane) + (1 + warp) * 2048;
        uint32_t qa[16], kx[16];
        const bool in = mbar_try(sb + RB_KV, s & 1);
        nbar_sync(NB_Q, 256);
        EV(EV_BIG0 && lds32(sb + RS_Q) != 0x12345678u, s, 8);
#pragma unroll
        for (int q = 0; q < 4; q++) ldsm4t(qa + 4 * q, sb + RS_Q + q * 512 + lane * 16);
        if (!in) mbar_wait(sb + RB_KV, s & 1);
#pragma unroll
        for (int q = 0; q < 4; q++) ldsm4t(kx + 4 * q, ka + q * 512);
        const bool vin = mbar_try(sb + RB_VX, s & 1);
        SCHED_FENCE();
        float s0, s1;
        s_tile(qa, kx, s0, s1);
        asm volatile("st.shared.v2.f32 [%0], {%1,%2};" :: "r"(sa + warp * 256), "f"(s0), "f"(s1) : "memory");
        nbar_sync(NB_WG, 128);
        float sc[8];
#pragma unroll
        for (int n = 0; n < 4; n++) { const float2 v = lds64f(sa + n * 256); sc[2 * n] = v.x; sc[2 * n + 1] = v.y; }
        if (!vin) mbar_wait(sb + RB_VX, s & 1);
        mx = quad_max(fmaxf(fmaxf(fmaxf(sc[0], sc[1]), fmaxf(sc[2], sc[3])), fmaxf(fmaxf(sc[4], sc[5]), fmaxf(sc[6], sc[7])))) * SCALE_LOG2E;
        uint32_t vx[16], p[8];
#pragma unroll
        for (int q = 0; q < 4; q++) ldsm4(vx + 4 * q, va + 2048 + (q >> 1) * 4096 + (q & 1) * 256 + v_frag_off(lane));
#pragma unroll
        for (int n = 0; n < 4; n++) {
            const float e0 = ex2(fmaf(sc[2 * n], SCALE_LOG2E, -mx)), e1 = ex2(fmaf(sc[2 * n + 1], SCALE_LOG2E, -mx));
            l += e0 + e1;
            p[2 * n] = pack_bf16(e0, e1); p[2 * n + 1] = __float_as_uint(e0);
        }
#pragma unroll
        for (int n = 0; n < 4; n++) { o[n][0] = o[n][1] = o[n][2] = o[n][3] = 0.f; }
        pv_pair(o, p, vx);
        pv_pair(o, p + 4, vx + 8);
    }
    const uint32_t dst = sb + RS_O + warp * 512 + (lane & 3) * 128 + (lane >> 2) * 16, dl = sb + RS_INV + (lane & 28);
    EV(EV_BIG0, s, 5);
    mbar_wait(sb + RB_V, s & 1);
    uint32_t vm[4], p[2];
    ldsm4(vm, va + lane * 16);
    nbar_sync(NB_XS, 128 + 32);
    EV(EV_BIG0 && lds32(sb + RS_Q) != 0x12345678u, s, 9);
    const float2 sm = lds64f(sa + 1024);
    const float s0 = sm.x, s1 = sm.y;
    const float m = quad_max(fmaxf(mx, fmaxf(s0, s1)));
    const float e0 = ex2(s0 - m), e1 = ex2(s1 - m), f = ex2(mx - m);
    p[0] = pack_bf16(e0, e1); p[1] = __float_as_uint(e0);
#pragma unroll
    for (int n = 0; n < 4; n++) { o[n][0] *= f; o[n][1] *= f; }
    pv_single(o, p, vm);
    l = fmaf(l, f, e0 + e1);
    l = (l + __shfl_xor_sync(0xffffffffu, l, 1)) + (__shfl_xor_sync(0xffffffffu, l, 2) + __shfl_xor_sync(0xffffffffu, l, 3));
    const uint4 u = make_uint4(pack_bf16(o[0][0], o[0][1]), pack_bf16(o[1][0], o[1][1]), pack_bf16(o[2][0], o[2][1]), pack_bf16(o[3][0], o[3][1]));
    st_async128(mapa(dst, 1), u.x, u.y, u.z, u.w, mapa(sb + RB_O, 1));
    st_async128(mapa(dst, 2), u.x, u.y, u.z, u.w, mapa(sb + RB_O, 2));
    st_async32(mapa(dl, 1 + (warp & 1)), __float_as_uint(l), mapa(sb + RB_O, 1 + (warp & 1)));
    sts128(dst, u);
    sts32(dl, __float_as_uint(l));
    __syncwarp();
    if (elect_one()) mbar_arrive(sb + RB_O);
    EV(EV_BIG0, s, 15);
}

DEVI void ta_mask(float* c, int cw, int lane) {
    const int mt = cw >= 3, over = 8 * (cw - 3 * mt - 1) + 2 * (lane & 3) - 16 * mt - (lane >> 2);
    if (over > 0) c[0] = -INFINITY;
    if (over >= 0) c[1] = -INFINITY;
    if (over > 8) c[2] = -INFINITY;
    if (over >= 8) c[3] = -INFINITY;
}
DEVI void ta_scores(uint32_t sb, int seg, int warp, int lane) {
    const int tx = warp == 3 ? 0 : (warp == 2 ? 1 : 4 + 2 * warp), ty = warp == 3 ? 3 : tx + 1;
    const uint32_t qa = sb + RS_QX + ((warp < 2 ? 2 : 0) + ((lane >> 3) & 1)) * 2048 + ((lane >> 4) * 8 + (lane & 7)) * 16;
    const uint32_t ka = sb + RS_K + (warp < 2 ? tx - 3 : tx) * 2048 + lane * 16;
    float x[4] = {0.f, 0.f, 0.f, 0.f}, y[4] = {0.f, 0.f, 0.f, 0.f};
    mbar_wait(sb + RB_QX, seg & 1);
    if (warp < 3) {
#pragma unroll
        for (int j = 0; j < 4; j++) {
            uint32_t a0[4], a1[4], bx[4], by[4];
            ldsm4t(a0, qa + j * 512); ldsm4t(bx, ka + j * 512); ldsm4t(by, ka + 2048 + j * 512); ldsm4t(a1, qa + j * 512 + 256);
            mma16816(x, a0, bx[0], bx[1]); mma16816(y, a0, by[0], by[1]);
            mma16816(x, a1, bx[2], bx[3]); mma16816(y, a1, by[2], by[3]);
        }
        ta_mask(x, tx, lane); ta_mask(y, ty, lane);
    } else {
        mbar_wait(sb + RB_K, seg & 1);
#pragma unroll
        for (int j = 0; j < 4; j++) {
            uint32_t a0[4], a1[4], a2[4], a3[4], b[4];
            ldsm4t(a0, qa + j * 512); ldsm4t(b, ka + j * 512); ldsm4t(a2, qa + 4096 + j * 512);
            ldsm4t(a1, qa + j * 512 + 256); ldsm4t(a3, qa + 4096 + j * 512 + 256);
            mma16816(x, a0, b[0], b[1]); mma16816(y, a2, b[0], b[1]);
            mma16816(x, a1, b[2], b[3]); mma16816(y, a3, b[2], b[3]);
        }
    }
    nbar_sync(NB_WG + 1, 128);
    asm volatile("st.shared.v2.f32 [%0], {%1,%2};" :: "r"(sb + RS_QX + 4096 + tx * 256 + lane * 8), "f"(fmaxf(x[0], x[1])), "f"(fmaxf(x[2], x[3])) : "memory");
    asm volatile("st.shared.v2.f32 [%0], {%1,%2};" :: "r"(sb + RS_QX + 4096 + ty * 256 + lane * 8), "f"(fmaxf(y[0], y[1])), "f"(fmaxf(y[2], y[3])) : "memory");
    nbar_sync(NB_WG + 1, 128);
    float m[4] = {-INFINITY, -INFINITY, -INFINITY, -INFINITY};
#pragma unroll
    for (int n = 0; n < 8; n++) {
        if (n < 3 ? warp >= 2 : warp != 2) {
            const float2 v = lds64f(sb + RS_QX + 4096 + n * 256 + lane * 8);
            m[n < 3 ? 0 : 2] = fmaxf(m[n < 3 ? 0 : 2], v.x); m[n < 3 ? 1 : 3] = fmaxf(m[n < 3 ? 1 : 3], v.y);
        }
    }
#pragma unroll
    for (int o = 1; o < 4; o <<= 1) {
#pragma unroll
        for (int i = 0; i < 4; i++) m[i] = fmaxf(m[i], __shfl_xor_sync(0xffffffffu, m[i], o));
    }
    const float x0 = (warp < 2 ? m[2] : m[0]) * -SCALE_LOG2E, x1 = (warp < 2 ? m[3] : m[1]) * -SCALE_LOG2E;
    const float y0 = (warp == 2 ? m[0] : m[2]) * -SCALE_LOG2E, y1 = (warp == 2 ? m[1] : m[3]) * -SCALE_LOG2E;
    sts64(sb + RS_QX + tx * 256 + lane * 8, pack_bf16(ex2(fmaf(x[0], SCALE_LOG2E, x0)), ex2(fmaf(x[1], SCALE_LOG2E, x0))),
                                            pack_bf16(ex2(fmaf(x[2], SCALE_LOG2E, x1)), ex2(fmaf(x[3], SCALE_LOG2E, x1))));
    sts64(sb + RS_QX + ty * 256 + lane * 8, pack_bf16(ex2(fmaf(y[0], SCALE_LOG2E, y0)), ex2(fmaf(y[1], SCALE_LOG2E, y0))),
                                            pack_bf16(ex2(fmaf(y[2], SCALE_LOG2E, y1)), ex2(fmaf(y[3], SCALE_LOG2E, y1))));
}
template <int MT>
DEVI void ta_output(uint32_t sb, int seg, int head, int j, int lane) {
    const uint32_t pa = sb + RS_QX + MT * 768 + lane * 8, vb = sb + RS_V + j * 512;
    uint32_t p[6 + 4 * MT], v[12 + 8 * MT];
#pragma unroll
    for (int n = 0; n < 3 + 2 * MT; n++)
        asm volatile("ld.shared.v2.u32 {%0,%1}, [%2];" : "=r"(p[2 * n]), "=r"(p[2 * n + 1]) : "r"(pa + n * 256) : "memory");
#pragma unroll
    for (int q = 0; q < 2 + 2 * MT; q++) ldsm4(v + 4 * q, vb + (q >> 1) * 4096 + (q & 1) * 256 + v_frag_off(lane));
    ldsm4(v + 8 + 8 * MT, vb + 4096 + MT * 4096 + lane * 16);
    float o[4][4], l[4] = {0.f, 0.f, 0.f, 0.f};
#pragma unroll
    for (int n = 0; n < 4; n++) { o[n][0] = o[n][1] = o[n][2] = o[n][3] = 0.f; }
    mma16816(l, p, 0x3F803F80u, 0x3F803F80u);
    pv_pair(o, p, v);
    if (MT) { mma16816(l, p + 4, 0x3F803F80u, 0x3F803F80u); pv_pair(o, p + 4, v + 8); }
    mma1688(l, p[4 + 4 * MT], p[5 + 4 * MT], 0x3F803F80u);
    pv_single(o, p + 4 + 4 * MT, v + 8 + 8 * MT);
    const float i0 = rcp_fast(l[0]), i1 = rcp_fast(l[2]);
    bf16* dst = g_ox + (uint32_t)((seg * 32 + MT * 16 + (lane >> 2)) * HD + head * DH + j * 32 + (lane & 3) * 8);
    asm volatile("st.global.v4.u32 [%0], {%1,%2,%3,%4};" :: "l"(dst), "r"(pack_bf16(o[0][0] * i0, o[0][1] * i0)), "r"(pack_bf16(o[1][0] * i0, o[1][1] * i0)),
                 "r"(pack_bf16(o[2][0] * i0, o[2][1] * i0)), "r"(pack_bf16(o[3][0] * i0, o[3][1] * i0)) : "memory");
    asm volatile("st.global.v4.u32 [%0], {%1,%2,%3,%4};" :: "l"(dst + 8 * HD), "r"(pack_bf16(o[0][2] * i1, o[0][3] * i1)), "r"(pack_bf16(o[1][2] * i1, o[1][3] * i1)),
                 "r"(pack_bf16(o[2][2] * i1, o[2][3] * i1)), "r"(pack_bf16(o[3][2] * i1, o[3][3] * i1)) : "memory");
}

template <bool XP>
DEVI void big_main(const uint32_t* w, const uint32_t sb, const int g, const int warp, const uint32_t rank, const int head,
                   const CUtensorMap* tmX, const bf16* xg, const unsigned E) {
    float xa[32];
    uint32_t a[16];
    const uint32_t aB = __shfl_sync(0xffffffffu, sb + RS_MEM + (g * 32 + (tid_now() & 31)) * 16, tid_now() & 31);
#define lane0 ((int)(opaque(aB) >> 4) & 31)
    const uint32_t aA0 = sb + RS_WSS + g * (8192 + 4096) + a_frag_off(lane0, warp);
    const uint32_t aBf = sb + RS_MEM + g * 512 + b_frag_off(lane0);
    if constexpr (XP) {
        mbar_wait(sb + RB_XF + g * 8, 0);
        x_first(xa, w, sb, 0, g, warp, tmX);
        x_second(xa, a, aA0, w, sb, 0, g, warp, tmX);
        x_finish(xa, sb, g, warp, lane0);
    }
    nbar_sync(NB_BIG, 256);
    for (int s = 0; s < NSEG; s++) {
        float c0[4], c1[4];
        mem_pass<XP>(c0, c1, a, w, sb, aA0, aBf, g, warp, s);
        EV(EV_BIG0 && c0[0] != 1.2345e30f, s, 3);
        bool xin = true;
        const uint32_t xs = sb + RS_O + warp * 256 + lane0 * 8;
        sts64(xs + g * 1024, pack_bf16(c1[0], c1[1]), pack_bf16(c1[2], c1[3]));
        {
            const uint32_t d = sb + (XP ? (rank == 1 ? RS_K : RS_V) : RS_Q) + (g * 4 + warp) * 256 + lane0 * 4;
            const uint32_t rbar = XP ? mapa(sb + (rank == 1 ? RB_K : RB_V), 0) : 0u;
            nbar_sync(NB_PAIR + warp, 64);
            const float2 v = lds64f(xs + (g ^ 1) * 1024);
            if (XP) xin = mbar_test(sb + RB_XF + g * 8, 0);
            const uint32_t v0 = __float_as_uint(v.x), v1 = __float_as_uint(v.y);
            const uint32_t p0 = pack_bf16(c0[0] + __uint_as_float(v0 << 16), c0[1] + __uint_as_float(v0 & 0xFFFF0000u));
            const uint32_t p1 = pack_bf16(c0[2] + __uint_as_float(v1 << 16), c0[3] + __uint_as_float(v1 & 0xFFFF0000u));
            if constexpr (XP) { st_async32(mapa(d, 0), p0, rbar); st_async32(mapa(d + 128, 0), p1, rbar); }
            else { sts32(d, p0); sts32(d + 128, p1); }
            EV(EV_BIG0, s, 4);
        }
        if constexpr (XP) {
            if (s == NSEG - 1) break;
            if (!xin) mbar_wait(sb + RB_XF + g * 8, 0);
            x_first(xa, w, sb, s + 1, g, warp, tmX);
            EV(EV_BIG0, s, 5);
            EVCAL(s);
            nbar_sync(NB_WO, 384);
            EV(EV_BIG0 && lds32(sb + RS_O) != 0x12345678u, s, 6);
            x_second(xa, a, aA0, w, sb, s + 1, g, warp, tmX);
            EV(EV_BIG0, s, 7);
            x_finish(xa, sb, g, warp, lane0);
        } else {
            if (g == 0) {
                if (s < NSEG - 1) mem_attn(sb, s, warp, lane0);
            } else {
                if (s < NSEG - 1) { if (warp == 3) mem_scores(sb, s, lane0); else nbar_arrive(NB_Q, 256); }
                mbar_wait(sb + RB_KV, s & 1);
                if (s == 0 && warp == 0) {
                    wait_count_warp(&g_cnt[C_QH], 64 * E);
                    if (elect_one()) {
                        fence_proxy_global();
                        mbar_expect_tx(sb + RB_QX, 8192);
                        bulk_load(sb + RS_QX, g_qx + (uint32_t)(head * 4096), 8192, sb + RB_QX);
                    }
                    __syncwarp();
                }
                ta_scores(sb, s, warp, lane0);
            }
            EVCAL(s);
            mbar_wait(sb + RB_V, s & 1);
            mbar_wait(sb + RB_VX, s & 1);
            if (s < NSEG - 1) nbar_sync(NB_WO, 384); else nbar_sync(NB_BIG, 256);
            EV(EV_BIG0 && lds32(sb + RS_O) != 0x12345678u, s, 6);
            if (g == 0) ta_output<0>(sb, s, head, warp, lane0); else ta_output<1>(sb, s, head, warp, lane0);
            nbar_sync(NB_BIG, 256);
            EV(EV_BIG0 && lds32(sb + RS_O) != 0x12345678u, s, 7);
            if (g == 0 && warp == 0 && s + 1 < NSEG) {
                if (elect_one()) {
                    mbar_arrive_remote(mapa(sb + RB_ATT, 1));
                    mbar_arrive_remote(mapa(sb + RB_ATT, 2));
                    mbar_expect_tx(sb + RB_KV, 8192);
                    mbar_expect_tx(sb + RB_K, 2048);
                    mbar_expect_tx(sb + RB_V, 2048); mbar_expect_tx(sb + RB_VX, 8192);
                    mbar_arrive(sb + RB_T);
                }
                __syncwarp();
            }
        }
    }
    if constexpr (!XP) { if (tid_now() == 0) signal_count(&g_prog[(NSEG - 1) >> 2]); }
#undef lane0
}

template <int T, int K0, int K1>
DEVI void wo_part(float* acc) {
    constexpr uint32_t dWo = cdesc(T < 5 ? RS_WO + T * 16384 : RS_WO5, 16), dO = cdesc(RS_O, 128);
#pragma unroll
    for (int kk = K0; kk < K1; kk++) {
        if (kk == 0) { if (T < 3) wgmma_n8_ss_first<0>(acc, dWo, dO); else wgmma_n8_ss<0, 0>(acc, dWo, dO); }
        else wgmma_n8_ss<0, 1>(acc, dWo + kk * 128, dO + kk * 16);
    }
    wg_commit();
}
DEVI void red3(uint8_t* p, uint32_t a, uint32_t b, uint32_t c, uint32_t one) {
    asm volatile("red.relaxed.gpu.global.add.noftz.v4.bf16x2 [%0], {%1,%2,%3,%4};" :: "l"(p), "r"(a), "r"(b), "r"(c), "r"(one) : "memory");
}
constexpr int ACC_CH = 3 * 16 * 1024;
template <bool Q>
DEVI void wo_phase(uint32_t sb, int s, int warp, uint8_t* p, uint32_t ainv, int gap) {
    float a0[4], a1[4], a2[4];
    fence_proxy_async();
    const float2 iv = lds64f(ainv);
    SCHED_FENCE();
    const float i0 = rcp_fast(iv.x), i1 = rcp_fast(iv.y);
#define WORD(a, h) pack_bf16(a[2 * h] * i0, a[2 * h + 1] * i1)
    wg_fence();
    wo_part<0, 0, 8>(a0); wo_part<1, 0, 8>(a1); wo_part<2, 0, 8>(a2);
    wg_wait<1>(); reg_fence<4>(a0); reg_fence<4>(a1);
    red3(p, WORD(a0, 0), WORD(a0, 1), WORD(a1, 0), 0x3F80u);
    SCHED_FENCE();
    EV(warp == 0 && elect_one(), s, 11);
    wg_wait<0>(); reg_fence<4>(a2);
    red3(p + ACC_CH, WORD(a2, 0), WORD(a2, 1), WORD(a1, 1), 0x3F80u);
    SCHED_FENCE();
    { const uint32_t t = clk32() + gap; while ((int)(clk32() - t) < 0) { } }
    wg_fence();
    wo_part<3, 0, 8>(a0); wo_part<4, 0, 8>(a1);
    if (Q) {
        wo_part<5, 0, 8>(a2);
        wg_wait<1>(); reg_fence<4>(a0); reg_fence<4>(a1);
        red3(p + 2 * ACC_CH, WORD(a0, 0), WORD(a0, 1), WORD(a1, 0), 0x3F80u);
        SCHED_FENCE();
        wg_wait<0>(); reg_fence<4>(a2);
        red3(p + 3 * ACC_CH, WORD(a2, 0), WORD(a2, 1), WORD(a1, 1), 0x3F80u);
        nbar_arrive(NB_WO, 384);
    } else {
        wg_wait<1>();
        nbar_arrive(NB_WO, 384);
        wg_wait<0>(); reg_fence<4>(a0); reg_fence<4>(a1);
        red3(p + 2 * ACC_CH, WORD(a0, 0), WORD(a0, 1), WORD(a1, 0), 0x3F80u);
        red3(p + 3 * ACC_CH, 0u, 0u, WORD(a1, 1), 0x3F80u);
    }
#undef WORD
}
DEVI void unit_pack(uint32_t* u, uint32_t x0, uint32_t x1, uint32_t x2, uint32_t x3) {
    u[0] = __byte_perm(x0, x1, 0x5410); u[1] = __byte_perm(x2, x3, 0x5410); u[2] = __byte_perm(x0, x1, 0x7632); u[3] = __byte_perm(x2, x3, 0x7632);
}
DEVI void unit_send(uint32_t d, const uint32_t* u, uint32_t bar, uint32_t r1, uint32_t r2) {
    st_async128(mapa(d, r1), u[0], u[1], u[2], u[3], mapa(bar, r1));
    st_async128(mapa(d, r2), u[0], u[1], u[2], u[3], mapa(bar, r2));
}
template <bool Q>
DEVI void stage_sums(uint32_t sb, int s, uint32_t rank, int warp, const uint8_t* src, uint32_t l, uint32_t gate) {
    uint4 v[4];
    while ((int)(clk32() - gate) < 0) { }
    EV(elect_one(), s, 16 + warp);
#pragma unroll
    for (int j = 0; j < 4; j++) v[j] = ld_rlx4(src + j * 1024);
    const uint32_t col = sb + RS_MEM + ((Q ? 0 : (rank == 1 ? 6 : 11)) + 3 * (warp >> 1)) * 1024 + ((l >> 2) & 0x300) + (l & 0x70);
    const uint32_t d0 = col + (warp & 1) * 2048, d1 = d0 ^ 160, d2 = (col ^ ((warp & 1) * 160)) + 1024;
    const uint32_t r1 = Q ? 1 : 0, r2 = Q ? 2 : 3 - rank, bar = sb + (warp < 2 ? RB_G + 8 * warp : (Q ? RB_G + 16 : RB_G3));
    int n = 0;
    while (!__all_sync(0xffffffffu, v[0].w == 0x4200u && v[1].w == 0x4200u && v[2].w == 0x4200u && v[3].w == 0x4200u)) {
#pragma unroll
        for (int j = 0; j < 4; j++) v[j] = ld_rlx4(src + j * 1024);
        if (++n > SPIN_LIMIT) TRAP(0x20000000u | (s << 8) | warp);
    }
    EV(elect_one(), s, 24 + warp);
    uint32_t u[12];
    unit_pack(u + 8, v[0].z, v[1].z, v[2].z, v[3].z);
    unit_send(d2, u + 8, bar, r1, r2);
    if (Q || warp < 3) {
        unit_pack(u, v[0].x, v[1].x, v[2].x, v[3].x);
        unit_pack(u + 4, v[0].y, v[1].y, v[2].y, v[3].y);
        unit_send(d0, u, bar, r1, r2);
        unit_send(d1, u + 4, bar, r1, r2);
        sts128(d0, make_uint4(u[0], u[1], u[2], u[3]));
        sts128(d1, make_uint4(u[4], u[5], u[6], u[7]));
    }
    sts128(d2, make_uint4(u[8], u[9], u[10], u[11]));
    __syncwarp();
    if (elect_one()) {
        mbar_expect_tx(bar, warp < 2 ? 3072u : (Q ? 0u : 1024u));
        if (warp == 0) mbar_expect_tx(sb + (Q ? RB_G3 : RB_G + 16), Q ? 4096u : 3072u);
    }
    EV(elect_one(), s, 20 + warp);
}
DEVI void wo_permute(uint32_t tile, int t) {
    const uint32_t a = tile + t * 32 + ((t >> 2) & 1) * 16;
#pragma unroll
    for (int h = 0; h < 2; h++) {
        uint4 v[3], u[3];
#pragma unroll
        for (int i = 0; i < 3; i++) if (3 * h + i < 5 || t < 32) { v[i] = lds128(a + (3 * h + i) * 3072); u[i] = lds128((a ^ 16) + (3 * h + i) * 3072); }
#pragma unroll
        for (int i = 0; i < 3; i++) if (3 * h + i < 5 || t < 32) {
            sts128(a + (3 * h + i) * 3072, make_uint4(__byte_perm(v[i].x, v[i].y, 0x5410), __byte_perm(v[i].x, v[i].y, 0x7632),
                                                      __byte_perm(u[i].x, u[i].y, 0x5410), __byte_perm(u[i].x, u[i].y, 0x7632)));
            sts128((a ^ 16) + (3 * h + i) * 3072, make_uint4(__byte_perm(v[i].z, v[i].w, 0x5410), __byte_perm(v[i].z, v[i].w, 0x7632),
                                                             __byte_perm(u[i].z, u[i].w, 0x5410), __byte_perm(u[i].z, u[i].w, 0x7632)));
        }
    }
}
DEVI uint32_t acc_clear(int slot, int idx, uint32_t lo) {
    uint8_t* p = g_acc + (uint32_t)(slot * 128 + idx * 3072 + (lo < 3072 ? lo : lo - 1024));
    st_rlx4(p, 0u, 0u, 0u, 0u);
    uint32_t z; asm volatile("ld.relaxed.gpu.global.u32 %0, [%1];" : "=r"(z) : "l"(p) : "memory");
    return z;
}

template <bool Q>
DEVI void aux_main(uint32_t sb, int warp, uint32_t rank, int head, const CUtensorMap* tmX, const bf16* xg, unsigned E, const int delay, const int gap) {
    const uint32_t lo = __shfl_sync(0xffffffffu, ((tid_now() >> 3) & 3) * 1024 + (tid_now() & 7) * 16, tid_now() & 31);
    for (int s = 0; s < NSEG - 1; s++) {
        if (!Q && warp == 0 && elect_one()) mbar_expect_tx(sb + RB_O, 2048 + 256);
        __syncwarp();
        const uint32_t slot = (s & 3) * 128;
        mbar_wait(sb + RB_O, s & 1);
        EV(warp == 0 && elect_one(), s, 10);
        wo_phase<Q>(sb, s, warp, g_acc + (uint32_t)(slot + (rank * 4 + warp) * 4096 + opaque(lo)), sb + RS_INV + ((opaque(lo) >> 1) & 24), gap);
        SCHED_FENCE();
        const uint32_t t_o = clk32();
        EV(warp == 0 && elect_one(), s, 12);
        {
            const uint32_t l = opaque(lo);
            stage_sums<Q>(sb, s, rank, warp, g_acc + (uint32_t)(slot + rank * 16384 + warp * ACC_CH + (l & 0xC00) * 4 + (l & 0x70)), l, t_o + delay);
        }
        EV(warp == 2 && elect_one(), s, 14);
        if (warp == (Q ? 3 : 1)) {
            if (Q) {
                mbar_wait(sb + RB_T, s & 1);
                if (s == 3) wait_count_warp(&g_cnt[C_Q], 64 * E);
                if (elect_one()) {
                    if (s == 3) fence_proxy_global();
                    fence_proxy_async();
                    mbar_expect_tx(sb + RB_QX, 8192);
                    bulk_load(sb + RS_QX, g_qx + (uint32_t)(((s + 1) * NH + head) * 4096), 8192, sb + RB_QX);
                    if (head == 0) { TLOG(1400 + s, 0, gtime()); TLOG(1400 + s, 1, clock64()); }
                }
                __syncwarp();
                const bool fresh = (s & 7) == 6 && s + 2 < NSEG;
                if (fresh) wait_count_warp(&g_cnt[C_Q + ((s + 2) >> 3)], 64 * E);
                if (elect_one()) {
                    if (fresh) fence_proxy_global();
                    if (s + 2 < NSEG && s != 2) l2_prefetch(g_qx + (uint32_t)(((s + 2) * NH + head) * 4096), 8192);
                    if (s + 4 < NSEG) l2_prefetch(xg + (uint32_t)(((s + 4) * 32 + head) * DM), 2048);
                    signal_count(&g_prog[s >> 2]);
                }
                __syncwarp();
            } else {
                const uint32_t zero = acc_clear((s + 2) & 3, 2 * head + (int)rank - 1, opaque(lo));
                x_send(sb, s + 1, rank, tmX);
                if (__any_sync(0xffffffffu, zero != 0u)) __trap();
            }
        }
    }
}

DEVI void load_weights(uint32_t sb, const CUtensorMap* tmW, const CUtensorMap* tmWo, int head, uint32_t rank, int2 t0) {
    const uint32_t c0 = clk32();
    if (rank == 0) while ((int)(clk32() - c0) < t0.x) { }
    const uint32_t bW = sb + RB_W, bSF = sb + RB_SF, bSE = sb + RB_SE;
    const int tile0 = rank == 0 ? 0 : (rank == 1 ? 6 : 11);
    mbar_expect_tx(bW, R_NSS * 16384);
    for (int pass = 0; pass < 2; pass++) {
        for (int pos = 0; pos < 16; pos++) {
            const int k = (int)((R_TORD_PACK >> (4 * pos)) & 15ull) * 64, rd = pos - pos / 3, slot = rd % 5;
            if (r_pos_ss(pos)) {
                if (pass) continue;
                const uint32_t dst = sb + RS_WSS + (pos / 3) * 16384;
                tma_load_2d(dst, tmW, head * DH, k, bW);
                tma_load_2d(dst + 8192, tmW, head * DH + 64, k, bW);
            } else if (pass == (rd >= 5)) {
                if (rd >= 5) mbar_wait(bSE + 8 * slot, ((rd / 5) - 1) & 1);
                mbar_expect_tx(bSF + 8 * slot, 16384);
                const uint32_t dst = sb + RS_WO + slot * 16384;
                tma_load_2d(dst, tmW, head * DH, k, bSF + 8 * slot);
                tma_load_2d(dst + 8192, tmW, head * DH + 64, k, bSF + 8 * slot);
            }
        }
    }
    while ((int)(clk32() - c0) < t0.y) { }
    if (rank == 0) { mbar_expect_tx(sb + RB_WO, 16384); tma_load_wo(sb + RS_WO5, tmWo, 5 * 64, head * 4, sb + RB_WO); }
    for (int i = 1; i <= 5; i++) {
        const int slot = i % 5, last = slot + 10 < R_NRS ? slot + 10 : slot + 5;
        mbar_wait(bSE + 8 * slot, (last / 5) & 1);
        mbar_expect_tx(bSF + 8 * slot, 16384);
        tma_load_wo(sb + RS_WO + slot * 16384, tmWo, (tile0 + slot) * 64, head * 4, bSF + 8 * slot);
    }
}
template <bool XP>
DEVI void big_prologue(uint32_t* w, uint32_t sb, int g, int warp, const bf16* __restrict__ mem0) {
    const int tid = tid_now(), lane = tid & 31;
    {
        const uint32_t* m = (const uint32_t*)(mem0 + (lane >> 2) * DM + (tid >> 5) * 16) + (lane & 3);
        uint32_t u[16];
#pragma unroll
        for (int j = 0; j < 8; j++) { u[2 * j] = m[j * 64]; u[2 * j + 1] = m[j * 64 + 4]; }
#pragma unroll
        for (int j = 0; j < 8; j++) sts64(sb + RS_MEM + ((tid >> 5) + j * 8) * 256 + b_frag_off(lane), u[2 * j], u[2 * j + 1]);
    }
    const uint32_t a0 = sb + RS_WO + g * (8192 + 4096) + a_frag_off(lane, warp), a1 = a0 + 8192 - g * 16384;
#pragma unroll
    for (int rd = 0; rd < R_NRS; rd++) {
        const int slot = rd % 5;
        mbar_wait(sb + RB_SF + 8 * slot, (rd / 5) & 1);
#pragma unroll
        for (int q = 0; q < 4; q++) {
            if (XP && rd == 0 && q == 3) {
                sts128(sb + RS_WX + g * 2048 + (tid & 127) * 16, lds128(sb + RS_WO + 8192 - g * 4096 + 2048 + (tid & 127) * 16));
                fence_proxy_async();
                nbar_sync(NB_WG + g, 128);
            } else ldsm4t(&w[rd * 16 + q * 4], ((q & 1) ? a1 : a0) + slot * 16384 + (q >> 1) * 2048);
        }
        mbar_arrive(sb + RB_SE + 8 * slot);
    }
    mbar_wait(sb + RB_W, 0);
    if (tid == 0) TLOG(1500 + blockIdx.x, 2, gtime());
}

#define REC_END() do { if (tid_now() == 0) TLOG(1024 + blockIdx.x, 1, gtime()); } while (0)
struct XMaps { CUtensorMap m[2]; };
__global__ void __launch_bounds__(384, 1)
k_rec(const __grid_constant__ PMaps mp, const __grid_constant__ CUtensorMap tmWk, const __grid_constant__ CUtensorMap tmWv,
      const __grid_constant__ CUtensorMap tmWo, const __grid_constant__ XMaps xm, const bf16* __restrict__ mem0, const bf16* __restrict__ xg,
      int4 tq, int4 tk, int2 t0, int rec) {
    extern __shared__ __align__(1024) uint8_t smem_raw[];
    const uint32_t sb = smem_u32(smem_raw);
    if ((sb & 0x3FFFFu) != SB0) __trap();
    const int tid = threadIdx.x;
    const int wg = __shfl_sync(0xffffffffu, tid >> 7, 0), warp = __shfl_sync(0xffffffffu, (tid >> 5) & 3, 0);
    uint32_t rank; asm("mov.u32 %0, %%cluster_ctarank;" : "=r"(rank));
    int head; asm("mov.u32 %0, %%clusterid.x;" : "=r"(head));
    asm volatile("griddepcontrol.launch_dependents;");
    if (tid == 0 && rec) {
        mbar_init(sb + RB_G, 1);
        mbar_init(sb + RB_G + 8, 1);
        mbar_init(sb + RB_G + 16, rank == 0 ? 2 : 1);
        mbar_init(sb + RB_G3, rank == 0 ? 1 : 2);
        mbar_init(sb + RB_T, 1); mbar_init(sb + RB_VX, 1); mbar_init(sb + RB_WO, 1);
        mbar_init(sb + RB_K, 1); mbar_init(sb + RB_V, 1); mbar_init(sb + RB_KV, 1); mbar_init(sb + RB_QX, 1);
        mbar_init(sb + RB_O, rank == 0 ? 4 : 1); mbar_init(sb + RB_ATT, 1); mbar_init(sb + RB_W, 1);
        for (int i = 0; i < 5; i++) { mbar_init(sb + RB_SF + 8 * i, 1); mbar_init(sb + RB_SE + 8 * i, 256); }
        for (int i = 0; i < 2; i++) mbar_init(sb + RB_XF + 8 * i, X_SLOTS);
        fence_mbar_init();
        if (rank == 0) { mbar_expect_tx(sb + RB_KV, 8192); mbar_expect_tx(sb + RB_K, 2048); mbar_expect_tx(sb + RB_V, 2048); mbar_expect_tx(sb + RB_VX, 8192); }
    }
    __syncthreads();
    asm volatile("barrier.cluster.arrive.release.aligned;" ::: "memory");

    if (wg < 2) {
        reg_inc<REG_KB>();
        if (rank != 0) {
            uint32_t w[R_NRS * 16];
            if ((tid & 127) == 0) for (int j = 0; j < X_SLOTS; j++) x_load(sb, 0, j, wg, xm.m);
            __syncwarp();
            cluster_wait();
            big_prologue<true>(w, sb, wg, warp, mem0);
            big_main<true>(w, sb, wg, warp, rank, head, xm.m, xg, 0u);
            REC_END();
        } else if (rec) {
            uint32_t w[R_NRS * 16];
            cluster_wait();
            big_prologue<false>(w, sb, wg, warp, mem0);
            big_main<false>(w, sb, wg, warp, rank, head, xm.m, xg, *(volatile unsigned*)&g_epoch + 1);
            REC_END();
        } else cluster_wait();
        nbar_sync(0, 384);
        nbar_sync(0, 384);
        post_consumer(mp, sb, wg, warp);
    } else {
        reg_dec<504 - 2 * REG_KB>();
        if (rec) {
            if (tid == 256) {
                if (rank == 0) l2_prefetch(xg + (uint32_t)(head * 8 * DM), 16384);
                load_weights(sb, rank == 0 ? &mp.wq : (rank == 1 ? &tmWk : &tmWv), &tmWo, head, rank, t0);
            }
            if (warp == 3 && rank != 0) {
                const uint32_t lo = ((tid >> 3) & 3) * 1024 + (tid & 7) * 16;
                acc_clear(0, 2 * head + (int)rank - 1, lo); acc_clear(1, 2 * head + (int)rank - 1, lo);
                __threadfence();
                __syncwarp();
                if (tid == 256 + 96) atomicAdd(&g_zero, 1u);
            }
            __syncwarp();
        }
        cluster_wait();
        const unsigned E = __shfl_sync(0xffffffffu, *(volatile unsigned*)&g_epoch + 1, 0);
        if (rec) {
            if (warp == 1) wait_count_warp(&g_zero, E * 64u);
            if (warp == 3) { if (rank != 0) x_send(sb, 0, rank, xm.m); }
            else {
                nbar_sync(NB_PRO, 96);
#pragma unroll 1
                for (int i = rank == 0 ? 0 : 1; i <= 5; i++) {
                    mbar_wait(sb + (i == 0 ? RB_WO : RB_SF + 8 * (i % 5)), i == 5);
                    if (i == 5 && tid == 288) TLOG(1500 + blockIdx.x, 0, gtime());
                    wo_permute(sb + (i == 0 ? RS_WO5 : RS_WO + (i % 5) * 16384), tid & 127);
                }
            }
            fence_proxy_async();
            nbar_sync(NB_AUX, 128);
            if (tid == 288) { TLOG(1500 + blockIdx.x, 1, gtime()); }
            if (rank == 0) aux_main<true>(sb, warp, rank, head, xm.m, xg, E, warp == 0 ? tq.x : (warp == 1 ? tq.y : tq.z), tq.w);
            else           aux_main<false>(sb, warp, rank, head, xm.m, xg, E, warp == 0 ? tk.x : (warp == 1 ? tk.y : tk.z), tk.w);
        }
        const int t = tid_now();
        int id = 0;
        if (t >= 288 && t < 288 + 13) asm volatile("prefetch.tensormap [%0];" :: "l"(&mp.wq + (t - 288)) : "memory");
        if (warp == 0 && rank != 0) id = post_claim(mp, E);
        nbar_sync(0, 384);
        if (warp == 0) { if (elect_one()) post_init(sb); fence_proxy_async(); }
        __syncwarp();
        nbar_sync(0, 384);
        if (warp == 0) post_producer(mp, sb, E, rank != 0 ? id : post_claim(mp, E));
        else if (t == 288 || t == 320) post_helper(sb, warp - 1);
    }
    __syncthreads();
    asm volatile("griddepcontrol.wait;" ::: "memory");
}

typedef CUresult (*EncodeFn)(CUtensorMap*, CUtensorMapDataType, cuuint32_t, void*, const cuuint64_t*, const cuuint64_t*,
                             const cuuint32_t*, const cuuint32_t*, CUtensorMapInterleave, CUtensorMapSwizzle,
                             CUtensorMapL2promotion, CUtensorMapFloatOOBfill);

static CUtensorMap make_map(EncodeFn fn, const void* ptr, uint64_t inner, uint64_t outer, uint32_t box_inner, uint32_t box_outer) {
    CUtensorMap m;
    cuuint64_t dims[2] = {inner, outer};
    cuuint64_t strides[1] = {inner * 2};
    cuuint32_t box[2] = {box_inner, box_outer};
    cuuint32_t es[2] = {1, 1};
    fn(&m, CU_TENSOR_MAP_DATA_TYPE_BFLOAT16, 2, const_cast<void*>(ptr), dims, strides, box, es,
       CU_TENSOR_MAP_INTERLEAVE_NONE, CU_TENSOR_MAP_SWIZZLE_128B, CU_TENSOR_MAP_L2_PROMOTION_L2_256B, CU_TENSOR_MAP_FLOAT_OOB_FILL_NONE);
    return m;
}

static CUtensorMap make_wo_map(EncodeFn fn, const void* ptr, uint64_t rows, uint32_t ngrp) {
    CUtensorMap m;
    cuuint64_t dims[5] = {DM, 2, 4, 4, rows / 32};
    cuuint64_t strides[4] = {DM * 2, 8 * DM * 2, 2 * DM * 2, 32 * DM * 2};
    cuuint32_t box[5] = {64, 2, 4, 4, ngrp};
    cuuint32_t es[5] = {1, 1, 1, 1, 1};
    fn(&m, CU_TENSOR_MAP_DATA_TYPE_BFLOAT16, 5, const_cast<void*>(ptr), dims, strides, box, es,
       CU_TENSOR_MAP_INTERLEAVE_NONE, CU_TENSOR_MAP_SWIZZLE_128B, CU_TENSOR_MAP_L2_PROMOTION_L2_256B, CU_TENSOR_MAP_FLOAT_OOB_FILL_NONE);
    return m;
}

struct Maps {
    PMaps post;
    CUtensorMap wk16, wv16, wo128;
    XMaps x32;
};

extern "C" void kernel_launch(void* const* d_in, const int* in_sizes, int n_in, void* d_out, int out_size) {
    const bf16* A_x   = (const bf16*)d_in[0];
    const bf16* A_mem = (const bf16*)d_in[1];
    const bf16* A_Wq  = (const bf16*)d_in[2];
    const bf16* A_Wk  = (const bf16*)d_in[3];
    const bf16* A_Wv  = (const bf16*)d_in[4];
    const bf16* A_Wo  = (const bf16*)d_in[5];
    const bf16* B_x   = (const bf16*)d_in[7];
    const bf16* B_w   = (const bf16*)d_in[8];
    const bf16* B_wo  = (const bf16*)d_in[9];

    static EncodeFn fn = nullptr;
    static Maps mp;
    static const void* cached[10];
    const void* cur[10] = {A_x, A_mem, A_Wq, A_Wk, A_Wv, A_Wo, B_x, B_w, B_wo, d_out};
    bool same = fn != nullptr;
    for (int i = 0; i < 10 && same; i++) same = cached[i] == cur[i];
    if (!same) {
        if (!fn) {
            void* p = nullptr; cudaDriverEntryPointQueryResult qr;
            cudaGetDriverEntryPoint("cuTensorMapEncodeTiled", &p, cudaEnableDefault, &qr);
            fn = (EncodeFn)p;
            cudaFuncSetAttribute(k_rec, cudaFuncAttributeMaxDynamicSharedMemorySize, R_SMEM);
        }
        void *p_ox, *p_bqkv, *p_bo, *p_qx;
        cudaGetSymbolAddress(&p_qx, g_qx);
        cudaGetSymbolAddress(&p_ox, g_ox); cudaGetSymbolAddress(&p_bqkv, g_bqkv); cudaGetSymbolAddress(&p_bo, g_bo);
        mp.post.wq   = make_map(fn, A_Wq, HD, DM, 64, 64);
        mp.post.wo   = make_wo_map(fn, A_Wo, HD, 2);
        mp.post.bw   = make_map(fn, B_w, 3 * DM, DM, 64, 64);
        mp.post.bwo  = make_wo_map(fn, B_wo, DM, 2);
        mp.post.x    = make_map(fn, A_x, DM, S_TOK, 64, 128);
        mp.post.bx   = make_map(fn, B_x, DM, S_TOK, 64, 128);
        mp.post.bo   = make_map(fn, p_bo, DM, S_TOK, 64, 128);
        mp.post.ox   = make_map(fn, p_ox, HD, S_TOK, 64, 128);
        mp.post.ox64 = make_map(fn, p_ox, HD, S_TOK, 64, 64);
        mp.post.cb   = make_map(fn, p_bqkv, 3 * DM, S_TOK, 64, 64);
        mp.post.cout = make_map(fn, d_out, 2 * DM, S_TOK, 64, 64);
        {
            cuuint64_t dims[4] = {256, 4, NH * 4, NSEG};
            cuuint64_t strides[3] = {512, 2048, NH * 8192};
            cuuint32_t box[4] = {256, 2, 4, 2};
            cuuint32_t es[4] = {1, 1, 1, 1};
            fn(&mp.post.cq, CU_TENSOR_MAP_DATA_TYPE_BFLOAT16, 4, p_qx, dims, strides, box, es,
               CU_TENSOR_MAP_INTERLEAVE_NONE, CU_TENSOR_MAP_SWIZZLE_NONE, CU_TENSOR_MAP_L2_PROMOTION_NONE, CU_TENSOR_MAP_FLOAT_OOB_FILL_NONE);
        }
        {
            int runs[48] = {K_QH, 0, 2, K_Q, 1, 7, K_B1, 0, 8, K_A4, 0, 4, K_B2, 0, 32, K_A4, 4, 2, K_B3, 0, 4, K_A3, 12, 1, K_B3, 4, 1, K_A3, 13, 1,
                            K_B3, 5, 3, K_SN, 28, 4, -1};
            const int per[9] = {32, 24, 8, 8, 32, 8, 8 * P_SPLIT, 1, 8 * P_SPLIT};
            int n = 0, id = 0;
            for (; runs[3 * n] >= 0; n++) {
                mp.post.list.run[n] = make_int4(runs[3 * n], runs[3 * n + 1], id, id + runs[3 * n + 2] * per[runs[3 * n]]);
                id = mp.post.list.run[n].w;
            }
            mp.post.list.n = n;
            int dev = 0, nsm = 132;
            cudaGetDevice(&dev);
            cudaDeviceGetAttribute(&nsm, cudaDevAttrMultiProcessorCount, dev);
            mp.post.list.nworker = nsm > 96 ? nsm : 97;
        }
        {
            cuuint64_t dims[4] = {DM, 3, 2, S_TOK / 2};
            cuuint64_t strides[3] = {DM * 2, 3 * DM * 2, 3 * DM * 4};
            cuuint32_t box[4] = {64, 3, 1, 40};
            cuuint32_t es[4] = {1, 1, 1, 1};
            fn(&mp.post.b40, CU_TENSOR_MAP_DATA_TYPE_BFLOAT16, 4, p_bqkv, dims, strides, box, es,
               CU_TENSOR_MAP_INTERLEAVE_NONE, CU_TENSOR_MAP_SWIZZLE_128B, CU_TENSOR_MAP_L2_PROMOTION_L2_256B, CU_TENSOR_MAP_FLOAT_OOB_FILL_NONE);
        }
        mp.wk16 = make_map(fn, A_Wk, HD, DM, 64, 64);
        mp.wv16 = make_map(fn, A_Wv, HD, DM, 64, 64);
        mp.wo128 = make_wo_map(fn, A_Wo, HD, 4);
        for (int i = 0; i < 2; i++) {
            cuuint64_t dims[3] = {64, S_TOK, DM / 64};
            cuuint64_t strides[2] = {DM * 2, 128};
            cuuint32_t box[3] = {32, 32, 2u - i};
            cuuint32_t es[3] = {1, 1, 1};
            fn(&mp.x32.m[i], CU_TENSOR_MAP_DATA_TYPE_BFLOAT16, 3, const_cast<bf16*>(A_x), dims, strides, box, es,
               CU_TENSOR_MAP_INTERLEAVE_NONE, CU_TENSOR_MAP_SWIZZLE_64B, CU_TENSOR_MAP_L2_PROMOTION_L2_128B, CU_TENSOR_MAP_FLOAT_OOB_FILL_NONE);
        }
        for (int i = 0; i < 10; i++) cached[i] = cur[i];
    }

    cudaStream_t st = cudaStreamPerThread;
    int4 tq = make_int4(100, 200, 700, 60), tk = make_int4(50, 300, 800, 40);
    int2 t0 = make_int2(13000, 16000);
    cudaLaunchConfig_t cfg = {};
    cfg.gridDim = dim3(96); cfg.blockDim = dim3(384); cfg.dynamicSmemBytes = R_SMEM; cfg.stream = st;
    cudaLaunchAttribute at[1];
    at[0].id = cudaLaunchAttributeClusterDimension;
    at[0].val.clusterDim.x = 3; at[0].val.clusterDim.y = 1; at[0].val.clusterDim.z = 1;
    cfg.attrs = at; cfg.numAttrs = 1;
    cudaLaunchKernelEx(&cfg, k_rec, mp.post, mp.wk16, mp.wv16, mp.wo128, mp.x32, A_mem, A_x, tq, tk, t0, 1);
    cfg.gridDim = dim3(mp.post.list.nworker - 96);
    at[0].id = cudaLaunchAttributeProgrammaticStreamSerialization;
    at[0].val.programmaticStreamSerializationAllowed = 1;
    cudaLaunchKernelEx(&cfg, k_rec, mp.post, mp.wk16, mp.wv16, mp.wo128, mp.x32, A_mem, A_x, tq, tk, t0, 0);
}
```

```cpp
#include <cuda_runtime.h>
#include <cuda_bf16.h>
#include <cuda.h>
#include <stdint.h>

typedef __nv_bfloat16 bf16;

constexpr int S_TOK = 2048;
constexpr int DM    = 1024;
constexpr int NH    = 32;
constexpr int DH    = 128;
constexpr int NSEG  = 64;
constexpr int HD    = NH * DH;

__device__ __align__(1024) bf16 g_qx[NSEG * NH * 4 * DH * 8];
__device__ __align__(1024) bf16 g_ox[S_TOK * HD];
__device__ __align__(1024) bf16 g_bqkv[S_TOK * 3 * DM];
__device__ __align__(1024) bf16 g_bo[S_TOK * DM];
__device__ __align__(1024) uint8_t g_acc[192 * 1024];

#define EV(cond, s, k) do {} while (0)
#define EVCAL(s) do {} while (0)

constexpr int P_NSK = 4;
__device__ unsigned g_epoch, g_qctr, g_done, g_zero;
enum { C_B1 = 0, C_B2 = 8, C_Q = 16, C_QH = 24, C_NONE = 31 };
__device__ unsigned g_cnt[32], g_prog[32], g_cnt_sk[P_NSK * 32];
constexpr int P_SPLIT = 4;
__device__ __align__(1024) uint4 g_skp[P_NSK * 8 * P_SPLIT * 2 * 8 * 128];
#define TLOG(i, k, v) do {} while (0)

#define DEVI __device__ __forceinline__

DEVI uint32_t opaque(uint32_t v) { uint32_t r; asm volatile("mov.u32 %0, %1;" : "=r"(r) : "r"(v)); return r; }
DEVI uint32_t smem_u32(const void* p) { return (uint32_t)__cvta_generic_to_shared(p); }

constexpr int SPIN_LIMIT = 1 << 22;
#define MBAR_HINT_NS 20000u
constexpr int SPIN_LIMIT_MBAR = 1 << 17;

DEVI void mbar_init(uint32_t bar, uint32_t cnt) { asm volatile("mbarrier.init.shared::cta.b64 [%0], %1;" :: "r"(bar), "r"(cnt)); }
DEVI void mbar_expect_tx(uint32_t bar, uint32_t bytes) {
    asm volatile("mbarrier.arrive.expect_tx.shared::cta.b64 _, [%0], %1;" :: "r"(bar), "r"(bytes) : "memory");
}
DEVI void mbar_arrive(uint32_t bar) { asm volatile("mbarrier.arrive.shared::cta.b64 _, [%0];" :: "r"(bar) : "memory"); }
DEVI bool mbar_try(uint32_t bar, uint32_t parity) {
    uint32_t ok;
    asm volatile("{.reg .pred p; mbarrier.try_wait.parity.shared::cta.b64 p, [%1], %2; selp.u32 %0, 1, 0, p;}"
                 : "=r"(ok) : "r"(bar), "r"(parity) : "memory");
    return ok;
}
DEVI bool mbar_try_hint(uint32_t bar, uint32_t parity) {
    uint32_t ok;
    asm volatile("{.reg .pred p; mbarrier.try_wait.parity.shared::cta.b64 p, [%1], %2, %3; selp.u32 %0, 1, 0, p;}"
                 : "=r"(ok) : "r"(bar), "r"(parity), "r"(MBAR_HINT_NS) : "memory");
    return ok;
}
DEVI bool mbar_test(uint32_t bar, uint32_t parity) {
    uint32_t ok;
    asm volatile("{.reg .pred p; mbarrier.test_wait.parity.shared::cta.b64 p, [%1], %2; selp.u32 %0, 1, 0, p;}"
                 : "=r"(ok) : "r"(bar), "r"(parity) : "memory");
    return ok;
}
DEVI void mbar_wait(uint32_t bar, uint32_t parity) {
    int n = 0;
    while (!mbar_try(bar, parity)) { if (++n > SPIN_LIMIT) __trap(); }
}
DEVI void mbar_wait_sleepy(uint32_t bar, uint32_t parity) {
    int n = 0;
    while (!mbar_try_hint(bar, parity)) { if (++n > SPIN_LIMIT_MBAR) __trap(); }
}
DEVI void fence_mbar_init() { asm volatile("fence.mbarrier_init.release.cluster;" ::: "memory"); }
DEVI void fence_proxy_async() { asm volatile("fence.proxy.async.shared::cta;" ::: "memory"); }
DEVI bool elect_one() {
    uint32_t e; asm volatile("{.reg .pred p; elect.sync _|p, 0xffffffff; selp.u32 %0, 1, 0, p;}" : "=r"(e)); return e;
}
DEVI void fence_proxy_global() { asm volatile("fence.proxy.async.global;" ::: "memory"); }
DEVI void cluster_wait() { asm volatile("barrier.cluster.wait.acquire.aligned;" ::: "memory"); }
DEVI void nbar_sync(int id, int n) { asm volatile("bar.sync %0, %1;" :: "r"(id), "r"(n) : "memory"); }
DEVI void nbar_arrive(int id, int n) { asm volatile("bar.arrive %0, %1;" :: "r"(id), "r"(n) : "memory"); }

DEVI void tma_load_2d(uint32_t dst, const CUtensorMap* map, int x, int y, uint32_t bar) {
    asm volatile("cp.async.bulk.tensor.2d.shared::cluster.global.mbarrier::complete_tx::bytes [%0], [%1, {%3, %4}], [%2];"
                 :: "r"(dst), "l"(map), "r"(bar), "r"(x), "r"(y) : "memory");
}
DEVI void tma_load_3d(uint32_t dst, const CUtensorMap* map, int x, int y, int z, uint32_t bar) {
    asm volatile("cp.async.bulk.tensor.3d.shared::cluster.global.mbarrier::complete_tx::bytes [%0], [%1, {%3, %4, %5}], [%2];"
                 :: "r"(dst), "l"(map), "r"(bar), "r"(x), "r"(y), "r"(z) : "memory");
}
DEVI void tma_load_wo(uint32_t dst, const CUtensorMap* map, int col, int k32, uint32_t bar) {
    asm volatile("cp.async.bulk.tensor.5d.shared::cluster.global.mbarrier::complete_tx::bytes [%0], [%1, {%3, %5, %5, %5, %4}], [%2];"
                 :: "r"(dst), "l"(map), "r"(bar), "r"(col), "r"(k32), "r"(0) : "memory");
}
DEVI void tma_store_2d(const CUtensorMap* map, uint32_t src, int x, int y) {
    asm volatile("cp.async.bulk.tensor.2d.global.shared::cta.bulk_group [%0, {%2, %3}], [%1];"
                 :: "l"(map), "r"(src), "r"(x), "r"(y) : "memory");
}
DEVI void bulk_load(uint32_t dst, const void* src, uint32_t bytes, uint32_t bar) {
    asm volatile("cp.async.bulk.shared::cluster.global.mbarrier::complete_tx::bytes [%0], [%1], %2, [%3];"
                 :: "r"(dst), "l"(src), "r"(bytes), "r"(bar) : "memory");
}
DEVI void bulk_copy_s2c(uint32_t dst_cluster, uint32_t src, uint32_t bytes, uint32_t bar_cluster) {
    asm volatile("cp.async.bulk.shared::cluster.shared::cta.mbarrier::complete_tx::bytes [%0], [%1], %2, [%3];"
                 :: "r"(dst_cluster), "r"(src), "r"(bytes), "r"(bar_cluster) : "memory");
}
DEVI void bulk_wait_read() { asm volatile("cp.async.bulk.wait_group.read 0;" ::: "memory"); }
DEVI void mbar_arrive_remote(uint32_t bar_cluster) {
    asm volatile("mbarrier.arrive.shared::cluster.b64 _, [%0];" :: "r"(bar_cluster) : "memory");
}
DEVI void l2_prefetch(const void* p, uint32_t bytes) {
    asm volatile("cp.async.bulk.prefetch.L2.global [%0], %1;" :: "l"(p), "r"(bytes) : "memory");
}
DEVI void bulk_commit() { asm volatile("cp.async.bulk.commit_group;" ::: "memory"); }
DEVI void bulk_wait_all() { asm volatile("cp.async.bulk.wait_group 0;" ::: "memory"); }

DEVI void wg_fence() { asm volatile("wgmma.fence.sync.aligned;" ::: "memory"); }
DEVI void wg_commit() { asm volatile("wgmma.commit_group.sync.aligned;" ::: "memory"); }
template <int N> DEVI void wg_wait() { asm volatile("wgmma.wait_group.sync.aligned %0;" :: "n"(N) : "memory"); }

template <int R> DEVI void reg_dec() { asm volatile("setmaxnreg.dec.sync.aligned.u32 %0;" :: "n"(R)); }
template <int R> DEVI void reg_inc() { asm volatile("setmaxnreg.inc.sync.aligned.u32 %0;" :: "n"(R)); }

DEVI uint64_t mk_desc(uint32_t addr, uint32_t lbo, uint32_t sbo, uint32_t sw) {
    return (uint64_t)((addr & 0x3FFFF) >> 4) | ((uint64_t)(lbo >> 4) << 16) | ((uint64_t)(sbo >> 4) << 32) | ((uint64_t)sw << 62);
}

constexpr uint32_t DHI_SW128 = (1024u >> 4) | (1u << 30);
constexpr uint32_t DHI_SW64  = (512u >> 4) | (2u << 30);
constexpr uint32_t DHI_NONE  = (128u >> 4);

template <int TB, int SCALE_D>
DEVI void wgmma_n8_ss(float* d, uint32_t alo, uint32_t blo) {
    asm volatile("{.reg .b64 da, db; mov.b64 da, {%4, %6}; mov.b64 db, {%5, %7};\n"
                 "wgmma.mma_async.sync.aligned.m64n8k16.f32.bf16.bf16 {%0,%1,%2,%3}, da, db, %8, 1, 1, 1, %9;}"
                 : "+f"(d[0]), "+f"(d[1]), "+f"(d[2]), "+f"(d[3])
                 : "r"(alo), "r"(blo), "n"(DHI_SW128), "n"(DHI_NONE), "n"(SCALE_D), "n"(TB));
}

template <int TB>
DEVI void wgmma_n8_ss_first(float* d, uint32_t alo, uint32_t blo) {
    asm volatile("{.reg .b64 da, db; mov.b64 da, {%4, %6}; mov.b64 db, {%5, %7};\n"
                 "wgmma.mma_async.sync.aligned.m64n8k16.f32.bf16.bf16 {%0,%1,%2,%3}, da, db, 0, 1, 1, 1, %8;}"
                 : "=f"(d[0]), "=f"(d[1]), "=f"(d[2]), "=f"(d[3])
                 : "r"(alo), "r"(blo), "n"(DHI_SW128), "n"(DHI_NONE), "n"(TB));
}
DEVI void wgmma_n32_rs_first(float* d, const uint32_t* a, uint32_t blo) {
    asm volatile("{.reg .b64 db; mov.b64 db, {%20, %21};\n"
                 "wgmma.mma_async.sync.aligned.m64n32k16.f32.bf16.bf16 {%0,%1,%2,%3,%4,%5,%6,%7,%8,%9,%10,%11,%12,%13,%14,%15}, "
                 "{%16,%17,%18,%19}, db, 0, 1, 1, 0;}"
                 : "=f"(d[0]), "=f"(d[1]), "=f"(d[2]), "=f"(d[3]), "=f"(d[4]), "=f"(d[5]), "=f"(d[6]), "=f"(d[7]),
                   "=f"(d[8]), "=f"(d[9]), "=f"(d[10]), "=f"(d[11]), "=f"(d[12]), "=f"(d[13]), "=f"(d[14]), "=f"(d[15])
                 : "r"(a[0]), "r"(a[1]), "r"(a[2]), "r"(a[3]), "r"(blo), "n"(DHI_SW64));
}
template <int N> DEVI void reg_fence(float* d) {
#pragma unroll
    for (int i = 0; i < N; i++) asm volatile("" : "+f"(d[i]) :: "memory");
}
DEVI void wgmma_n32_rs(float* d, const uint32_t* a, uint32_t blo) {
    asm volatile("{.reg .b64 db; mov.b64 db, {%20, %21};\n"
                 "wgmma.mma_async.sync.aligned.m64n32k16.f32.bf16.bf16 {%0,%1,%2,%3,%4,%5,%6,%7,%8,%9,%10,%11,%12,%13,%14,%15}, "
                 "{%16,%17,%18,%19}, db, 1, 1, 1, 0;}"
                 : "+f"(d[0]), "+f"(d[1]), "+f"(d[2]), "+f"(d[3]), "+f"(d[4]), "+f"(d[5]), "+f"(d[6]), "+f"(d[7]),
                   "+f"(d[8]), "+f"(d[9]), "+f"(d[10]), "+f"(d[11]), "+f"(d[12]), "+f"(d[13]), "+f"(d[14]), "+f"(d[15])
                 : "r"(a[0]), "r"(a[1]), "r"(a[2]), "r"(a[3]), "r"(blo), "n"(DHI_SW64));
}
DEVI void wgmma_n32_ss(float* d, uint32_t alo, uint32_t blo) {
    asm volatile("{.reg .b64 da, db; mov.b64 da, {%16, %18}; mov.b64 db, {%17, %19};\n"
                 "wgmma.mma_async.sync.aligned.m64n32k16.f32.bf16.bf16 {%0,%1,%2,%3,%4,%5,%6,%7,%8,%9,%10,%11,%12,%13,%14,%15}, "
                 "da, db, 1, 1, 1, 1, 0;}"
                 : "+f"(d[0]), "+f"(d[1]), "+f"(d[2]), "+f"(d[3]), "+f"(d[4]), "+f"(d[5]), "+f"(d[6]), "+f"(d[7]),
                   "+f"(d[8]), "+f"(d[9]), "+f"(d[10]), "+f"(d[11]), "+f"(d[12]), "+f"(d[13]), "+f"(d[14]), "+f"(d[15])
                 : "r"(alo), "r"(blo), "n"(DHI_SW128), "n"(DHI_SW64));
}

template <bool FIRST>
DEVI void wgmma_n256_ss(float* d, uint64_t a, uint64_t b) {
    if (FIRST)
        asm volatile("wgmma.mma_async.sync.aligned.m64n256k16.f32.bf16.bf16 {%0,%1,%2,%3,%4,%5,%6,%7,%8,%9,%10,%11,%12,%13,%14,%15,%16,%17,%18,%19,%20,%21,%22,%23,%24,%25,%26,%27,%28,%29,%30,%31,%32,%33,%34,%35,%36,%37,%38,%39,%40,%41,%42,%43,%44,%45,%46,%47,%48,%49,%50,%51,%52,%53,%54,%55,%56,%57,%58,%59,%60,%61,%62,%63,%64,%65,%66,%67,%68,%69,%70,%71,%72,%73,%74,%75,%76,%77,%78,%79,%80,%81,%82,%83,%84,%85,%86,%87,%88,%89,%90,%91,%92,%93,%94,%95,%96,%97,%98,%99,%100,%101,%102,%103,%104,%105,%106,%107,%108,%109,%110,%111,%112,%113,%114,%115,%116,%117,%118,%119,%120,%121,%122,%123,%124,%125,%126,%127}, %128, %129, 0, 1, 1, 1, 0;"
            : "=f"(d[0]), "=f"(d[1]), "=f"(d[2]), "=f"(d[3]), "=f"(d[4]), "=f"(d[5]), "=f"(d[6]), "=f"(d[7]), "=f"(d[8]), "=f"(d[9]), "=f"(d[10]), "=f"(d[11]), "=f"(d[12]), "=f"(d[13]), "=f"(d[14]), "=f"(d[15]), "=f"(d[16]), "=f"(d[17]), "=f"(d[18]), "=f"(d[19]), "=f"(d[20]), "=f"(d[21]), "=f"(d[22]), "=f"(d[23]), "=f"(d[24]), "=f"(d[25]), "=f"(d[26]), "=f"(d[27]), "=f"(d[28]), "=f"(d[29]), "=f"(d[30]), "=f"(d[31]), "=f"(d[32]), "=f"(d[33]), "=f"(d[34]), "=f"(d[35]), "=f"(d[36]), "=f"(d[37]), "=f"(d[38]), "=f"(d[39]), "=f"(d[40]), "=f"(d[41]), "=f"(d[42]), "=f"(d[43]), "=f"(d[44]), "=f"(d[45]), "=f"(d[46]), "=f"(d[47]), "=f"(d[48]), "=f"(d[49]), "=f"(d[50]), "=f"(d[51]), "=f"(d[52]), "=f"(d[53]), "=f"(d[54]), "=f"(d[55]), "=f"(d[56]), "=f"(d[57]), "=f"(d[58]), "=f"(d[59]), "=f"(d[60]), "=f"(d[61]), "=f"(d[62]), "=f"(d[63]), "=f"(d[64]), "=f"(d[65]), "=f"(d[66]), "=f"(d[67]), "=f"(d[68]), "=f"(d[69]), "=f"(d[70]), "=f"(d[71]), "=f"(d[72]), "=f"(d[73]), "=f"(d[74]), "=f"(d[75]), "=f"(d[76]), "=f"(d[77]), "=f"(d[78]), "=f"(d[79]), "=f"(d[80]), "=f"(d[81]), "=f"(d[82]), "=f"(d[83]), "=f"(d[84]), "=f"(d[85]), "=f"(d[86]), "=f"(d[87]), "=f"(d[88]), "=f"(d[89]), "=f"(d[90]), "=f"(d[91]), "=f"(d[92]), "=f"(d[93]), "=f"(d[94]), "=f"(d[95]), "=f"(d[96]), "=f"(d[97]), "=f"(d[98]), "=f"(d[99]), "=f"(d[100]), "=f"(d[101]), "=f"(d[102]), "=f"(d[103]), "=f"(d[104]), "=f"(d[105]), "=f"(d[106]), "=f"(d[107]), "=f"(d[108]), "=f"(d[109]), "=f"(d[110]), "=f"(d[111]), "=f"(d[112]), "=f"(d[113]), "=f"(d[114]), "=f"(d[115]), "=f"(d[116]), "=f"(d[117]), "=f"(d[118]), "=f"(d[119]), "=f"(d[120]), "=f"(d[121]), "=f"(d[122]), "=f"(d[123]), "=f"(d[124]), "=f"(d[125]), "=f"(d[126]), "=f"(d[127]) : "l"(a), "l"(b));
    else
        asm volatile("wgmma.mma_async.sync.aligned.m64n256k16.f32.bf16.bf16 {%0,%1,%2,%3,%4,%5,%6,%7,%8,%9,%10,%11,%12,%13,%14,%15,%16,%17,%18,%19,%20,%21,%22,%23,%24,%25,%26,%27,%28,%29,%30,%31,%32,%33,%34,%35,%36,%37,%38,%39,%40,%41,%42,%43,%44,%45,%46,%47,%48,%49,%50,%51,%52,%53,%54,%55,%56,%57,%58,%59,%60,%61,%62,%63,%64,%65,%66,%67,%68,%69,%70,%71,%72,%73,%74,%75,%76,%77,%78,%79,%80,%81,%82,%83,%84,%85,%86,%87,%88,%89,%90,%91,%92,%93,%94,%95,%96,%97,%98,%99,%100,%101,%102,%103,%104,%105,%106,%107,%108,%109,%110,%111,%112,%113,%114,%115,%116,%117,%118,%119,%120,%121,%122,%123,%124,%125,%126,%127}, %128, %129, 1, 1, 1, 1, 0;"
            : "+f"(d[0]), "+f"(d[1]), "+f"(d[2]), "+f"(d[3]), "+f"(d[4]), "+f"(d[5]), "+f"(d[6]), "+f"(d[7]), "+f"(d[8]), "+f"(d[9]), "+f"(d[10]), "+f"(d[11]), "+f"(d[12]), "+f"(d[13]), "+f"(d[14]), "+f"(d[15]), "+f"(d[16]), "+f"(d[17]), "+f"(d[18]), "+f"(d[19]), "+f"(d[20]), "+f"(d[21]), "+f"(d[22]), "+f"(d[23]), "+f"(d[24]), "+f"(d[25]), "+f"(d[26]), "+f"(d[27]), "+f"(d[28]), "+f"(d[29]), "+f"(d[30]), "+f"(d[31]), "+f"(d[32]), "+f"(d[33]), "+f"(d[34]), "+f"(d[35]), "+f"(d[36]), "+f"(d[37]), "+f"(d[38]), "+f"(d[39]), "+f"(d[40]), "+f"(d[41]), "+f"(d[42]), "+f"(d[43]), "+f"(d[44]), "+f"(d[45]), "+f"(d[46]), "+f"(d[47]), "+f"(d[48]), "+f"(d[49]), "+f"(d[50]), "+f"(d[51]), "+f"(d[52]), "+f"(d[53]), "+f"(d[54]), "+f"(d[55]), "+f"(d[56]), "+f"(d[57]), "+f"(d[58]), "+f"(d[59]), "+f"(d[60]), "+f"(d[61]), "+f"(d[62]), "+f"(d[63]), "+f"(d[64]), "+f"(d[65]), "+f"(d[66]), "+f"(d[67]), "+f"(d[68]), "+f"(d[69]), "+f"(d[70]), "+f"(d[71]), "+f"(d[72]), "+f"(d[73]), "+f"(d[74]), "+f"(d[75]), "+f"(d[76]), "+f"(d[77]), "+f"(d[78]), "+f"(d[79]), "+f"(d[80]), "+f"(d[81]), "+f"(d[82]), "+f"(d[83]), "+f"(d[84]), "+f"(d[85]), "+f"(d[86]), "+f"(d[87]), "+f"(d[88]), "+f"(d[89]), "+f"(d[90]), "+f"(d[91]), "+f"(d[92]), "+f"(d[93]), "+f"(d[94]), "+f"(d[95]), "+f"(d[96]), "+f"(d[97]), "+f"(d[98]), "+f"(d[99]), "+f"(d[100]), "+f"(d[101]), "+f"(d[102]), "+f"(d[103]), "+f"(d[104]), "+f"(d[105]), "+f"(d[106]), "+f"(d[107]), "+f"(d[108]), "+f"(d[109]), "+f"(d[110]), "+f"(d[111]), "+f"(d[112]), "+f"(d[113]), "+f"(d[114]), "+f"(d[115]), "+f"(d[116]), "+f"(d[117]), "+f"(d[118]), "+f"(d[119]), "+f"(d[120]), "+f"(d[121]), "+f"(d[122]), "+f"(d[123]), "+f"(d[124]), "+f"(d[125]), "+f"(d[126]), "+f"(d[127]) : "l"(a), "l"(b));
}
template <bool FIRST>
DEVI void wgmma_n128_ss(float* d, uint64_t a, uint64_t b) {
    if (FIRST)
        asm volatile("wgmma.mma_async.sync.aligned.m64n128k16.f32.bf16.bf16 {%0,%1,%2,%3,%4,%5,%6,%7,%8,%9,%10,%11,%12,%13,%14,%15,%16,%17,%18,%19,%20,%21,%22,%23,%24,%25,%26,%27,%28,%29,%30,%31,%32,%33,%34,%35,%36,%37,%38,%39,%40,%41,%42,%43,%44,%45,%46,%47,%48,%49,%50,%51,%52,%53,%54,%55,%56,%57,%58,%59,%60,%61,%62,%63}, %64, %65, 0, 1, 1, 1, 0;"
            : "=f"(d[0]), "=f"(d[1]), "=f"(d[2]), "=f"(d[3]), "=f"(d[4]), "=f"(d[5]), "=f"(d[6]), "=f"(d[7]), "=f"(d[8]), "=f"(d[9]), "=f"(d[10]), "=f"(d[11]), "=f"(d[12]), "=f"(d[13]), "=f"(d[14]), "=f"(d[15]), "=f"(d[16]), "=f"(d[17]), "=f"(d[18]), "=f"(d[19]), "=f"(d[20]), "=f"(d[21]), "=f"(d[22]), "=f"(d[23]), "=f"(d[24]), "=f"(d[25]), "=f"(d[26]), "=f"(d[27]), "=f"(d[28]), "=f"(d[29]), "=f"(d[30]), "=f"(d[31]), "=f"(d[32]), "=f"(d[33]), "=f"(d[34]), "=f"(d[35]), "=f"(d[36]), "=f"(d[37]), "=f"(d[38]), "=f"(d[39]), "=f"(d[40]), "=f"(d[41]), "=f"(d[42]), "=f"(d[43]), "=f"(d[44]), "=f"(d[45]), "=f"(d[46]), "=f"(d[47]), "=f"(d[48]), "=f"(d[49]), "=f"(d[50]), "=f"(d[51]), "=f"(d[52]), "=f"(d[53]), "=f"(d[54]), "=f"(d[55]), "=f"(d[56]), "=f"(d[57]), "=f"(d[58]), "=f"(d[59]), "=f"(d[60]), "=f"(d[61]), "=f"(d[62]), "=f"(d[63]) : "l"(a), "l"(b));
    else
        asm volatile("wgmma.mma_async.sync.aligned.m64n128k16.f32.bf16.bf16 {%0,%1,%2,%3,%4,%5,%6,%7,%8,%9,%10,%11,%12,%13,%14,%15,%16,%17,%18,%19,%20,%21,%22,%23,%24,%25,%26,%27,%28,%29,%30,%31,%32,%33,%34,%35,%36,%37,%38,%39,%40,%41,%42,%43,%44,%45,%46,%47,%48,%49,%50,%51,%52,%53,%54,%55,%56,%57,%58,%59,%60,%61,%62,%63}, %64, %65, 1, 1, 1, 1, 0;"
            : "+f"(d[0]), "+f"(d[1]), "+f"(d[2]), "+f"(d[3]), "+f"(d[4]), "+f"(d[5]), "+f"(d[6]), "+f"(d[7]), "+f"(d[8]), "+f"(d[9]), "+f"(d[10]), "+f"(d[11]), "+f"(d[12]), "+f"(d[13]), "+f"(d[14]), "+f"(d[15]), "+f"(d[16]), "+f"(d[17]), "+f"(d[18]), "+f"(d[19]), "+f"(d[20]), "+f"(d[21]), "+f"(d[22]), "+f"(d[23]), "+f"(d[24]), "+f"(d[25]), "+f"(d[26]), "+f"(d[27]), "+f"(d[28]), "+f"(d[29]), "+f"(d[30]), "+f"(d[31]), "+f"(d[32]), "+f"(d[33]), "+f"(d[34]), "+f"(d[35]), "+f"(d[36]), "+f"(d[37]), "+f"(d[38]), "+f"(d[39]), "+f"(d[40]), "+f"(d[41]), "+f"(d[42]), "+f"(d[43]), "+f"(d[44]), "+f"(d[45]), "+f"(d[46]), "+f"(d[47]), "+f"(d[48]), "+f"(d[49]), "+f"(d[50]), "+f"(d[51]), "+f"(d[52]), "+f"(d[53]), "+f"(d[54]), "+f"(d[55]), "+f"(d[56]), "+f"(d[57]), "+f"(d[58]), "+f"(d[59]), "+f"(d[60]), "+f"(d[61]), "+f"(d[62]), "+f"(d[63]) : "l"(a), "l"(b));
}

template <bool FIRST>
DEVI void wgmma_n64_ss(float* d, uint64_t a, uint64_t b) {
    if (FIRST)
        asm volatile("wgmma.mma_async.sync.aligned.m64n64k16.f32.bf16.bf16 {%0,%1,%2,%3,%4,%5,%6,%7,%8,%9,%10,%11,%12,%13,%14,%15,%16,%17,%18,%19,%20,%21,%22,%23,%24,%25,%26,%27,%28,%29,%30,%31}, %32, %33, 0, 1, 1, 1, 0;"
            : "=f"(d[0]), "=f"(d[1]), "=f"(d[2]), "=f"(d[3]), "=f"(d[4]), "=f"(d[5]), "=f"(d[6]), "=f"(d[7]), "=f"(d[8]), "=f"(d[9]), "=f"(d[10]), "=f"(d[11]), "=f"(d[12]), "=f"(d[13]), "=f"(d[14]), "=f"(d[15]), "=f"(d[16]), "=f"(d[17]), "=f"(d[18]), "=f"(d[19]), "=f"(d[20]), "=f"(d[21]), "=f"(d[22]), "=f"(d[23]), "=f"(d[24]), "=f"(d[25]), "=f"(d[26]), "=f"(d[27]), "=f"(d[28]), "=f"(d[29]), "=f"(d[30]), "=f"(d[31]) : "l"(a), "l"(b));
    else
        asm volatile("wgmma.mma_async.sync.aligned.m64n64k16.f32.bf16.bf16 {%0,%1,%2,%3,%4,%5,%6,%7,%8,%9,%10,%11,%12,%13,%14,%15,%16,%17,%18,%19,%20,%21,%22,%23,%24,%25,%26,%27,%28,%29,%30,%31}, %32, %33, 1, 1, 1, 1, 0;"
            : "+f"(d[0]), "+f"(d[1]), "+f"(d[2]), "+f"(d[3]), "+f"(d[4]), "+f"(d[5]), "+f"(d[6]), "+f"(d[7]), "+f"(d[8]), "+f"(d[9]), "+f"(d[10]), "+f"(d[11]), "+f"(d[12]), "+f"(d[13]), "+f"(d[14]), "+f"(d[15]), "+f"(d[16]), "+f"(d[17]), "+f"(d[18]), "+f"(d[19]), "+f"(d[20]), "+f"(d[21]), "+f"(d[22]), "+f"(d[23]), "+f"(d[24]), "+f"(d[25]), "+f"(d[26]), "+f"(d[27]), "+f"(d[28]), "+f"(d[29]), "+f"(d[30]), "+f"(d[31]) : "l"(a), "l"(b));
}

DEVI void mma16816(float* d, const uint32_t* a, uint32_t b0, uint32_t b1) {
    asm volatile("mma.sync.aligned.m16n8k16.row.col.f32.bf16.bf16.f32 {%0,%1,%2,%3}, {%4,%5,%6,%7}, {%8,%9}, {%0,%1,%2,%3};"
                 : "+f"(d[0]), "+f"(d[1]), "+f"(d[2]), "+f"(d[3])
                 : "r"(a[0]), "r"(a[1]), "r"(a[2]), "r"(a[3]), "r"(b0), "r"(b1));
}
DEVI void mma1688(float* d, uint32_t a0, uint32_t a1, uint32_t b0) {
    asm volatile("mma.sync.aligned.m16n8k8.row.col.f32.bf16.bf16.f32 {%0,%1,%2,%3}, {%4,%5}, {%6}, {%0,%1,%2,%3};"
                 : "+f"(d[0]), "+f"(d[1]), "+f"(d[2]), "+f"(d[3]) : "r"(a0), "r"(a1), "r"(b0));
}
DEVI void ldsm4(uint32_t* r, uint32_t addr) {
    asm volatile("ldmatrix.sync.aligned.m8n8.x4.shared.b16 {%0,%1,%2,%3}, [%4];"
                 : "=r"(r[0]), "=r"(r[1]), "=r"(r[2]), "=r"(r[3]) : "r"(addr) : "memory");
}
DEVI void ldsm4t(uint32_t* r, uint32_t addr) {
    asm volatile("ldmatrix.sync.aligned.m8n8.x4.trans.shared.b16 {%0,%1,%2,%3}, [%4];"
                 : "=r"(r[0]), "=r"(r[1]), "=r"(r[2]), "=r"(r[3]) : "r"(addr) : "memory");
}
DEVI void stsm4(uint32_t addr, uint32_t r0, uint32_t r1, uint32_t r2, uint32_t r3) {
    asm volatile("stmatrix.sync.aligned.m8n8.x4.shared.b16 [%0], {%1,%2,%3,%4};" :: "r"(addr), "r"(r0), "r"(r1), "r"(r2), "r"(r3) : "memory");
}
DEVI void stsm4t(uint32_t addr, uint32_t r0, uint32_t r1, uint32_t r2, uint32_t r3) {
    asm volatile("stmatrix.sync.aligned.m8n8.x4.trans.shared.b16 [%0], {%1,%2,%3,%4};" :: "r"(addr), "r"(r0), "r"(r1), "r"(r2), "r"(r3) : "memory");
}
DEVI uint32_t pack_bf16(float lo, float hi) {
    uint32_t r; asm("cvt.rn.bf16x2.f32 %0, %1, %2;" : "=r"(r) : "f"(hi), "f"(lo)); return r;
}
DEVI float ex2(float x) { float y; asm("ex2.approx.ftz.f32 %0, %1;" : "=f"(y) : "f"(x)); return y; }

DEVI uint4 ld_rlx4(const void* p) {
    uint4 v;
    asm volatile("ld.relaxed.gpu.global.v4.u32 {%0,%1,%2,%3}, [%4];" : "=r"(v.x), "=r"(v.y), "=r"(v.z), "=r"(v.w) : "l"(p) : "memory");
    return v;
}
DEVI void st_rlx4(void* p, uint32_t a, uint32_t b, uint32_t c, uint32_t d) {
    asm volatile("st.relaxed.gpu.global.v4.u32 [%0], {%1,%2,%3,%4};" :: "l"(p), "r"(a), "r"(b), "r"(c), "r"(d) : "memory");
}
DEVI void sts128(uint32_t addr, uint4 v) {
    asm volatile("st.shared.v4.u32 [%0], {%1,%2,%3,%4};" :: "r"(addr), "r"(v.x), "r"(v.y), "r"(v.z), "r"(v.w) : "memory");
}
DEVI void sts64(uint32_t addr, uint32_t a, uint32_t b) { asm volatile("st.shared.v2.u32 [%0], {%1,%2};" :: "r"(addr), "r"(a), "r"(b) : "memory"); }
DEVI void sts32(uint32_t addr, uint32_t v) { asm volatile("st.shared.u32 [%0], %1;" :: "r"(addr), "r"(v) : "memory"); }
DEVI uint4 lds128(uint32_t addr) {
    uint4 v; asm volatile("ld.shared.v4.u32 {%0,%1,%2,%3}, [%4];" : "=r"(v.x), "=r"(v.y), "=r"(v.z), "=r"(v.w) : "r"(addr) : "memory"); return v;
}
DEVI float2 lds64f(uint32_t addr) {
    float2 v; asm volatile("ld.shared.v2.f32 {%0,%1}, [%2];" : "=f"(v.x), "=f"(v.y) : "r"(addr) : "memory"); return v;
}
DEVI uint32_t lds32(uint32_t addr) { uint32_t v; asm volatile("ld.shared.u32 %0, [%1];" : "=r"(v) : "r"(addr) : "memory"); return v; }
DEVI float rcp_fast(float x) { float y; asm("rcp.approx.ftz.f32 %0, %1;" : "=f"(y) : "f"(x)); return y; }
DEVI uint32_t mapa(uint32_t addr, uint32_t rank) {
    uint32_t r; asm("mapa.shared::cluster.u32 %0, %1, %2;" : "=r"(r) : "r"(addr), "r"(rank)); return r;
}
DEVI void st_async32(uint32_t dst, uint32_t a, uint32_t bar) {
    asm volatile("st.async.weak.shared::cluster.mbarrier::complete_tx::bytes.b32 [%0], %1, [%2];" :: "r"(dst), "r"(a), "r"(bar) : "memory");
}

DEVI void st_async128(uint32_t dst, uint32_t a, uint32_t b, uint32_t c, uint32_t d, uint32_t bar) {
    asm volatile("st.async.weak.shared::cluster.mbarrier::complete_tx::bytes.v4.b32 [%0], {%1,%2,%3,%4}, [%5];"
                 :: "r"(dst), "r"(a), "r"(b), "r"(c), "r"(d), "r"(bar) : "memory");
}

DEVI uint32_t b_addr(uint32_t sb, int row, int which, int chunk) { const int l = 3 * row + which; return sb + l * 128 + ((chunk ^ (l & 7)) * 16); }
DEVI void battn_warp(uint32_t st, uint32_t ebar, int i0, int par, int head, int hh, int mt, int lane) {
    const int gq = lane >> 2, t = lane & 3, r = 16 * mt + (lane & 7), b3 = (lane >> 3) & 1, b4 = lane >> 4;
    uint32_t a[8], k[8], k2[4], v[8], v2[4];
#pragma unroll
    for (int ks = 0; ks < 2; ks++) {
        ldsm4(a + 4 * ks, b_addr(st, 8 + r + b3 * 8, 0, hh * 4 + ks * 2 + b4));
        ldsm4(k + 4 * ks, b_addr(st, r + b4 * 8, 1, hh * 4 + ks * 2 + b3));
    }
    ldsm4(k2, b_addr(st, r + 16, 1, hh * 4 + (lane >> 3)));
#pragma unroll
    for (int n = 0; n < 2; n++) ldsm4t(v + 4 * n, b_addr(st, r + b3 * 8, 2, hh * 4 + 2 * n + b4));
    ldsm4t(v2, b_addr(st, r + 16, 2, hh * 4 + (lane >> 3)));
    float s[3][4];
#pragma unroll
    for (int n = 0; n < 3; n++) { s[n][0] = s[n][1] = s[n][2] = s[n][3] = 0.f; }
#pragma unroll
    for (int ks = 0; ks < 2; ks++) {
        mma16816(s[0], a + 4 * ks, k[4 * ks], k[4 * ks + 1]);
        mma16816(s[1], a + 4 * ks, k[4 * ks + 2], k[4 * ks + 3]);
        mma16816(s[2], a + 4 * ks, k2[2 * ks], k2[2 * ks + 1]);
    }
    const bool ex = i0 + 16 * mt > 0;
    float x[4], y[4];
#pragma unroll
    for (int c = 0; c < 2; c++) {
        const bool low = 2 * t + c <= gq;
        x[c] = !low && ex ? s[0][c] : -INFINITY; x[2 + c] = low ? s[1][c] : -INFINITY;
        y[c] = !low ? s[1][2 + c] : -INFINITY;   y[2 + c] = low ? s[2][2 + c] : -INFINITY;
    }
    float m0 = fmaxf(fmaxf(x[0], x[1]), fmaxf(x[2], x[3])), m1 = fmaxf(fmaxf(y[0], y[1]), fmaxf(y[2], y[3]));
    m0 = fmaxf(fmaxf(m0, __shfl_xor_sync(0xffffffffu, m0, 1)), fmaxf(__shfl_xor_sync(0xffffffffu, m0, 2), __shfl_xor_sync(0xffffffffu, m0, 3)));
    m1 = fmaxf(fmaxf(m1, __shfl_xor_sync(0xffffffffu, m1, 1)), fmaxf(__shfl_xor_sync(0xffffffffu, m1, 2), __shfl_xor_sync(0xffffffffu, m1, 3)));
    constexpr float C = 0.17677669529663687f * 1.4426950408889634f;
    m0 *= -C; m1 *= -C;
    const uint32_t p0[4] = {pack_bf16(ex2(fmaf(x[0], C, m0)), ex2(fmaf(x[1], C, m0))), 0u,
                            pack_bf16(ex2(fmaf(x[2], C, m0)), ex2(fmaf(x[3], C, m0))), pack_bf16(ex2(fmaf(y[0], C, m1)), ex2(fmaf(y[1], C, m1)))};
    const uint32_t p1 = pack_bf16(ex2(fmaf(y[2], C, m1)), ex2(fmaf(y[3], C, m1)));
    float o[4][4], l[4] = {0.f, 0.f, 0.f, 0.f};
#pragma unroll
    for (int n = 0; n < 4; n++) { o[n][0] = o[n][1] = o[n][2] = o[n][3] = 0.f; }
    mma16816(l, p0, 0x3F803F80u, 0x3F803F80u);
#pragma unroll
    for (int n = 0; n < 4; n++) mma16816(o[n], p0, v[2 * n], v[2 * n + 1]);
    mma1688(l, 0u, p1, 0x3F803F80u);
#pragma unroll
    for (int n = 0; n < 4; n++) mma1688(o[n], 0u, p1, v2[n]);
    if (lane == 0) mbar_arrive(ebar);
    const float i0f = rcp_fast(l[0]), i1f = rcp_fast(l[2]);
    uint4* dst = (uint4*)(g_bo + (uint32_t)((2 * (i0 + 16 * mt + gq) + par) * DM + head * 32 + t * 8));
    dst[0] = make_uint4(pack_bf16(o[0][0] * i0f, o[0][1] * i0f), pack_bf16(o[1][0] * i0f, o[1][1] * i0f),
                        pack_bf16(o[2][0] * i0f, o[2][1] * i0f), pack_bf16(o[3][0] * i0f, o[3][1] * i0f));
    dst[16 * DM / 8] = make_uint4(pack_bf16(o[0][2] * i1f, o[0][3] * i1f), pack_bf16(o[1][2] * i1f, o[1][3] * i1f),
                                  pack_bf16(o[2][2] * i1f, o[2][3] * i1f), pack_bf16(o[3][2] * i1f, o[3][3] * i1f));
}

constexpr float SCALE_LOG2E = 0.08838834764831845f * 1.4426950408889634f;

constexpr int P_UNITS = 12, P_STAGES = 6;
constexpr int PS_STG = P_UNITS * 16384;
constexpr int P_SMEM = 232448;
constexpr int PS_BAR = P_SMEM - 256;
static_assert(PS_STG + 32768 <= PS_BAR, "smem");
enum { K_Q, K_B1, K_B3, K_A4, K_QH, K_A3, K_SK, K_B2, K_SN, K_END };
struct PList { int n, nworker, late; int4 run[16]; };
struct PTask { int kind, a, b, c, id; };
DEVI PTask p_decode(const PList& pl, int id) {
    int i = pl.n - 1;
    if (id >= pl.run[i].w) return {K_END, 0, 0, 0, id};
    while (id < pl.run[i].z) i--;
    const int4 r = pl.run[i];
    const int j = id - r.z;
    if (r.x == K_Q || r.x == K_QH) return {r.x, j & 31, r.y + (j >> 5), 0, id};
    if (r.x == K_B1) return {r.x, j % 24, r.y + j / 24, 0, id};
    if (r.x == K_B2) return {r.x, 0, r.y + j, 0, id};
    if (r.x == K_SK || r.x == K_SN) return {r.x, (j / P_SPLIT) & 7, r.y + j / (8 * P_SPLIT), j % P_SPLIT, id};
    return {r.x, j & 7, r.y + (j >> 3), 0, id};
}
DEVI void wait_count_warp(const unsigned* p, unsigned target) {
    int n = 0;
    while (true) {
        unsigned v; asm volatile("ld.acquire.gpu.global.u32 %0, [%1];" : "=r"(v) : "l"(p) : "memory");
        if (__all_sync(0xffffffffu, (int)(v - target) >= 0)) break;
        __nanosleep(100);
        if (++n > SPIN_LIMIT) __trap();
    }
}
DEVI void signal_count(unsigned* p) { __threadfence(); atomicAdd(p, 1u); }

struct PMaps { CUtensorMap wq, bw, bwo, wo, x, bx, bo, ox, ox64, cb, cout, cq, b40; PList list; };
constexpr int PB_F = PS_BAR, PB_E = PB_F + 48, PB_TF = PB_F + 96, PB_TE = PB_F + 112, PB_S = PB_F + 128;
constexpr int PS_T = PB_F + 160, PS_SIG = PS_T + 32, PS_SK = PS_SIG + 16;

struct PRing {
    int st, ph, u;
    DEVI void next(int n) { u += n; if (u >= P_UNITS) u -= P_UNITS; if (++st == P_STAGES) { st = 0; ph ^= 1; } }
    DEVI uint32_t w(bool wide) const { return wide && u == P_UNITS - 2 ? 0u : u * 16384u; }
    DEVI uint32_t x(bool wide) const { return wide && u == P_UNITS - 2 ? u * 16384u : (u == P_UNITS - 1 ? 0u : (u + 1) * 16384u); }
};
struct POut { const CUtensorMap* map; int col, tok, cnt; bool blocked; };
DEVI void p_store(const uint32_t* pk, const POut& o, int c, uint32_t stg, int warp, int lane_, int barid, bool elected) {
    const int lane = (int)opaque((uint32_t)lane_);
    const int mi = lane >> 3, r = lane & 7;
    const uint32_t buf = stg + (c & 1) * 8192;
    if (elected) asm volatile("cp.async.bulk.wait_group.read 1;" ::: "memory");
    nbar_sync(barid, 128);
    if (o.blocked) {
#pragma unroll
        for (int j = 0; j < 8; j += 2)
            stsm4(buf + (j + (mi >> 1)) * 1024 + (warp * 16 + (mi & 1) * 8 + r) * 16, pk[2 * j], pk[2 * j + 1], pk[2 * j + 2], pk[2 * j + 3]);
    } else {
#pragma unroll
        for (int j = 0; j < 8; j += 2)
            stsm4t(buf + (8 * (j + (mi >> 1)) + r) * 128 + ((2 * warp + (mi & 1)) ^ r) * 16, pk[2 * j], pk[2 * j + 1], pk[2 * j + 2], pk[2 * j + 3]);
    }
    fence_proxy_async();
    nbar_sync(barid, 128);
    if (elected) {
        if (o.blocked)
            asm volatile("cp.async.bulk.tensor.4d.global.shared::cta.bulk_group [%0, {%2, %3, %4, %5}], [%1];"
                         :: "l"(o.map), "r"(buf), "r"(0), "r"((o.col >> 5) & 2), "r"((o.col >> 7) * 4), "r"((o.tok >> 5) + 2 * c) : "memory");
        else tma_store_2d(o.map, buf, o.col, o.tok + c * 64);
        bulk_commit();
    }
}
DEVI void p_signal(uint32_t sb, int g, int cnt, int& nsig) {
    sts32(sb + PS_SIG + g * 8 + (nsig & 1) * 4, (uint32_t)cnt);
    mbar_arrive(sb + PB_S + g * 16 + (nsig & 1) * 8);
    nsig++;
}
DEVI void p_release(uint32_t sb, const PRing& r) {
    if (elect_one()) mbar_arrive(sb + PB_E + (r.st ? r.st - 1 : P_STAGES - 1) * 8);
}
template <int BN, bool FIRST>
DEVI void p_kblock(float* d, uint32_t sb, int g, PRing& r) {
    mbar_wait(sb + PB_F + r.st * 8, r.ph);
    const uint64_t da = mk_desc(sb + r.w(BN == 256) + g * 8192, 16, 1024, 1), db = mk_desc(sb + r.x(BN == 256), 16, 1024, 1);
    wg_fence();
#pragma unroll
    for (int kk = 0; kk < 4; kk++) {
        if (BN == 256) { if (FIRST && kk == 0) wgmma_n256_ss<true>(d, da, db); else wgmma_n256_ss<false>(d, da + (uint64_t)(kk * 128), db + (uint64_t)(kk * 2)); }
        if (BN == 128) { if (FIRST && kk == 0) wgmma_n128_ss<true>(d, da, db); else wgmma_n128_ss<false>(d, da + (uint64_t)(kk * 128), db + (uint64_t)(kk * 2)); }
        if (BN == 64)  { if (FIRST && kk == 0) wgmma_n64_ss<true>(d, da, db); else wgmma_n64_ss<false>(d, da + (uint64_t)(kk * 128), db + (uint64_t)(kk * 2)); }
    }
    wg_commit();
    if (!FIRST) {
        wg_wait<1>();
        p_release(sb, r);
    }
    r.next(BN == 256 ? 3 : 2);
}

DEVI PTask post_claim(const PMaps& mp, unsigned E) {
    unsigned v = 0;
    if ((threadIdx.x & 31) == 0) v = atomicAdd(&g_qctr, 1u);
    return p_decode(mp.list, (int)(__shfl_sync(0xffffffffu, v, 0) - (E - 1) * (unsigned)(mp.list.run[mp.list.n - 1].w + mp.list.nworker)));
}
DEVI void post_producer(const PMaps& mp, uint32_t sb, unsigned E, bool early) {
    PRing r = {0, 0, 0};
    int ts = 0, tp = 0, used = 0;
    uint32_t big = 0;
    auto reserve = [&](int n) {
        while (used + n > P_UNITS) {
            mbar_wait(sb + PB_E + ts * 8, tp);
            used -= 2 + ((big >> ts) & 1);
            if (++ts == P_STAGES) { ts = 0; tp ^= 1; }
        }
        used += n;
        big = (big & ~(1u << r.st)) | ((uint32_t)(n & 1) << r.st);
    };
    for (int i = 0;; i++) {
        if (i > 0) mbar_wait(sb + PB_TE + (i & 1) * 8, ((i >> 1) & 1) ^ 1);
        else if (!early) nbar_sync(0, 384);
        const PTask tk = post_claim(mp, E);
        if (i == 0) { if (early) nbar_sync(0, 384); fence_proxy_async(); }
        const bool sn = tk.kind == K_SN, split = tk.kind == K_SK || sn, wide = tk.kind <= K_A4;
        const bool qk = tk.kind == K_Q || tk.kind == K_QH, ak = tk.kind == K_A4 || tk.kind == K_A3 || split;
        const int nk = split ? HD / 64 / P_SPLIT : (ak ? HD / 64 : DM / 64), kb0 = tk.c * (HD / 64 / P_SPLIT);
        const int tok0 = tk.b * (wide ? 256 : (sn ? 64 : 128)), grp = (tok0 >> 6) + (wide ? 3 : (sn ? 0 : 1));
        const uint32_t bytes = wide ? 49152 : (sn ? 24576 : 32768);
        const CUtensorMap* tx = tk.kind == K_B1 ? &mp.bx : (qk ? &mp.x : (sn ? &mp.ox64 : (ak ? &mp.ox : &mp.bo)));
        const int npre = split && (i == 0 || __any_sync(0xffffffffu, (int)(*(volatile unsigned*)&g_prog[grp] - 64 * E) < 0)) ? P_STAGES : 0;
        PRing rp = r;
        for (int kb = kb0; kb < kb0 + npre; kb++) {
            reserve(2);
            const uint32_t bar = sb + PB_F + r.st * 8;
            if (elect_one()) {
                mbar_expect_tx(bar, bytes);
                tma_load_wo(sb + r.w(false), &mp.wo, tk.a * 128, kb * 2, bar);
                tma_load_wo(sb + r.w(false) + 8192, &mp.wo, tk.a * 128 + 64, kb * 2, bar);
            }
            r.next(2);
        }
        if (tk.kind == K_B2) {
            wait_count_warp(&g_cnt[C_B1 + (tk.b >> 2)], 48 * E);
            if ((tk.b & 3) == 0 && tk.b > 0) wait_count_warp(&g_cnt[C_B1 + (tk.b >> 2) - 1], 48 * E);
        } else if (tk.kind == K_B3) wait_count_warp(&g_cnt[C_B2 + tk.b], 8 * E);
        else if (ak) wait_count_warp(&g_prog[grp], 64 * E);
        fence_proxy_global();
        for (int kb = kb0; kb < kb0 + npre; kb++) {
            if (elect_one()) tma_load_2d(sb + rp.x(false), tx, kb * 64, tok0, sb + PB_F + rp.st * 8);
            rp.next(2);
        }
        if (elect_one()) {
            sts128(sb + PS_T + (i & 1) * 16, make_uint4((uint32_t)tk.kind | ((uint32_t)tk.id << 8), (uint32_t)tk.a, (uint32_t)tk.b, (uint32_t)tk.c));
            mbar_arrive(sb + PB_TF + (i & 1) * 8);
        }
        if (tk.kind == K_END) break;
        if (tk.kind == K_B2) {
            for (int j = 0; j < 16; j++) {
                reserve(2);
                const uint32_t bar = sb + PB_F + r.st * 8;
                if (elect_one()) {
                    mbar_expect_tx(bar, 2 * 15360);
#pragma unroll
                    for (int u = 0; u < 2; u++) asm volatile("cp.async.bulk.tensor.4d.shared::cluster.global.mbarrier::complete_tx::bytes [%0], [%1, {%3, %4, %5, %6}], [%2];"
                                 :: "r"(sb + (u ? r.x(false) : r.w(false))), "l"(&mp.b40), "r"(bar), "r"(j * 64), "r"(0), "r"(u), "r"(tk.b * 32 - 8) : "memory");
                }
                r.next(2);
            }
            continue;
        }
        const CUtensorMap* tw = tk.kind == K_B1 ? &mp.bw : (qk ? &mp.wq : (ak ? &mp.wo : &mp.bwo));
        for (int kb = kb0 + npre; kb < kb0 + nk; kb++) {
            reserve(wide ? 3 : 2);
            const uint32_t aw = sb + r.w(wide), ax = sb + r.x(wide), bar = sb + PB_F + r.st * 8;
            if (elect_one()) {
                mbar_expect_tx(bar, bytes);
                if (ak || tk.kind == K_B3) {
                    tma_load_wo(aw, tw, tk.a * 128, kb * 2, bar);
                    tma_load_wo(aw + 8192, tw, tk.a * 128 + 64, kb * 2, bar);
                } else {
                    tma_load_2d(aw, tw, tk.a * 128, kb * 64, bar);
                    tma_load_2d(aw + 8192, tw, tk.a * 128 + 64, kb * 64, bar);
                }
                tma_load_2d(ax, tx, kb * 64, tok0, bar);
                if (wide) tma_load_2d(ax + 16384, tx, kb * 64, tok0 + 128, bar);
            }
            r.next(wide ? 3 : 2);
        }
        if (tk.id >= mp.list.late) { reserve(P_UNITS - 3); used -= P_UNITS - 3; }
    }
    if (elect_one()) {
        __threadfence();
        if (atomicAdd(&g_done, 1u) == E * mp.list.nworker - 1) { __threadfence(); *(volatile unsigned*)&g_epoch = E; }
    }
}
DEVI void post_helper(uint32_t sb, int g) {
    for (int n = 0;; n++) {
        mbar_wait_sleepy(sb + PB_S + g * 16 + (n & 1) * 8, (n >> 1) & 1);
        const int cnt = (int)lds32(sb + PS_SIG + g * 8 + (n & 1) * 4);
        if (cnt < 0) break;
        signal_count(&g_cnt[cnt]);
    }
}
template <int BN>
DEVI void p_narrow(const PMaps& mp, const PTask& tk, uint32_t sb, int g, int warp, PRing& r, int& nsig) {
    const int barid = 1 + g, tid = threadIdx.x;
    const bool elected = (tid & 127) == 0, split = BN == 64 || tk.kind == K_SK;
    constexpr int NV = BN / 16;
    float d[BN / 2];
    const int nk = split ? HD / 64 / P_SPLIT : (tk.kind == K_A3 ? HD / 64 : DM / 64);
    p_kblock<BN, true>(d, sb, g, r);
#pragma unroll 1
    for (int kb = 1; kb < nk; kb++) p_kblock<BN, false>(d, sb, g, r);
    wg_wait<0>();
    reg_fence<BN / 2>(d);
    p_release(sb, r);
    if (split) {
        const int tile = (tk.b * (BN / 64) - 2 * (16 - P_NSK)) * 8 + tk.a * (BN / 64);
        uint4* const base = g_skp + (uint32_t)(tile * P_SPLIT * 1024 + g * NV * 128 + (tid & 127));
#pragma unroll
        for (int j = 0; j < NV; j++)
            base[tk.c * NV * 256 + j * 128] = make_uint4(pack_bf16(d[8 * j], d[8 * j + 1]), pack_bf16(d[8 * j + 2], d[8 * j + 3]),
                                                         pack_bf16(d[8 * j + 4], d[8 * j + 5]), pack_bf16(d[8 * j + 6], d[8 * j + 7]));
        nbar_sync(barid, 128);
        if (elected) {
            unsigned old;
            asm volatile("atom.acq_rel.gpu.global.add.u32 %0, [%1], 1;" : "=r"(old) : "l"(&g_cnt_sk[tile * 2 + g]) : "memory");
            sts32(sb + PS_SK + g * 4, old % P_SPLIT);
        }
        nbar_sync(barid, 128);
        const bool last = lds32(sb + PS_SK + g * 4) == P_SPLIT - 1;
        nbar_sync(barid, 128);
        if (!last) return;
        uint4 v[(P_SPLIT - 1) * NV];
#pragma unroll
        for (int j = 0; j < (P_SPLIT - 1) * NV; j++) v[j] = __ldcg(base + ((tk.c + 1 + j / NV) % P_SPLIT) * NV * 256 + (j % NV) * 128);
#pragma unroll
        for (int j = 0; j < (P_SPLIT - 1) * NV; j++) {
            float* e = d + 8 * (j % NV);
            e[0] += __uint_as_float(v[j].x << 16); e[1] += __uint_as_float(v[j].x & 0xFFFF0000u);
            e[2] += __uint_as_float(v[j].y << 16); e[3] += __uint_as_float(v[j].y & 0xFFFF0000u);
            e[4] += __uint_as_float(v[j].z << 16); e[5] += __uint_as_float(v[j].z & 0xFFFF0000u);
            e[6] += __uint_as_float(v[j].w << 16); e[7] += __uint_as_float(v[j].w & 0xFFFF0000u);
        }
    }
    const bool qh = BN == 128 && tk.kind == K_QH;
    const POut o = {qh ? &mp.cq : &mp.cout, tk.a * 128 + g * 64, tk.b * BN, 0, qh};
    uint32_t q[BN / 4];
#pragma unroll
    for (int j = 0; j < BN / 4; j++) q[j] = pack_bf16(d[2 * j], d[2 * j + 1]);
    if (BN == 64 && elected) bulk_wait_read();
#pragma unroll
    for (int c = 0; c < BN / 64; c++) p_store(q + 16 * c, o, c, sb + PS_STG + g * 16384, warp, tid & 31, barid, elected);
    if (BN == 64 && elected) bulk_wait_read();
    if (elected && qh) { bulk_wait_all(); p_signal(sb, g, tk.b == 0 ? C_QH : C_Q, nsig); }
}
DEVI void post_consumer(const PMaps& mp, uint32_t sb, int g, int warp) {
    const int barid = 1 + g, tid = threadIdx.x, lane = tid & 31;
    const bool elected = (tid & 127) == 0;
    const uint32_t stg = sb + PS_STG + g * 16384;
    int nsig = 0;
    PRing r = {0, 0, 0};
    uint32_t pk[64];
    POut out;
    bool pend = false;
#pragma unroll
    for (int i = 0; i < 64; i++) pk[i] = 0u;
    for (int i = 0;; i++) {
        const uint32_t bTF = sb + PB_TF + (i & 1) * 8;
        if (pend) {
            uint32_t now;
            asm volatile("{.reg .pred p, q; mbarrier.test_wait.parity.shared::cta.b64 p, [%1], %2; bar.red.and.pred q, %3, 128, p; selp.u32 %0, 1, 0, q;}"
                         : "=r"(now) : "r"(bTF), "r"((i >> 1) & 1), "r"(barid) : "memory");
            if (!now || (lds32(sb + PS_T + (i & 1) * 16) & 255u) > K_A4) {
#pragma unroll
                for (int c = 0; c < 4; c++) p_store(pk + 16 * c, out, c, stg, warp, lane, barid, elected);
                if (elected && out.cnt != C_NONE) { bulk_wait_all(); p_signal(sb, g, out.cnt, nsig); }
                pend = false;
            }
        }
        mbar_wait(bTF, (i >> 1) & 1);
        const uint4 tw = lds128(sb + PS_T + (i & 1) * 16);
        mbar_arrive(sb + PB_TE + (i & 1) * 8);
        const PTask tk = {(int)(tw.x & 255u), (int)tw.y, (int)tw.z, (int)tw.w, 0};
        if (tk.kind == K_END) break;
        if (tk.kind <= K_A4) {
            float d[128];
            const int nk = tk.kind == K_A4 ? HD / 64 : DM / 64;
            p_kblock<256, true>(d, sb, g, r);
            if (pend) p_store(pk, out, 0, stg, warp, lane, barid, elected);
#pragma unroll
            for (int c = 1; c < 4; c++) {
                p_kblock<256, false>(d, sb, g, r);
                if (pend) p_store(pk + 16 * c, out, c, stg, warp, lane, barid, elected);
            }
#pragma unroll 1
            for (int kb = 4; kb < nk; kb++) {
                p_kblock<256, false>(d, sb, g, r);
                if (kb == 6 && pend && elected && out.cnt != C_NONE) { bulk_wait_all(); p_signal(sb, g, out.cnt, nsig); }
            }
            wg_wait<0>();
            reg_fence<128>(d);
            p_release(sb, r);
#pragma unroll
            for (int j = 0; j < 64; j++) pk[j] = pack_bf16(d[2 * j], d[2 * j + 1]);
            out.map = tk.kind == K_Q ? &mp.cq : (tk.kind == K_B1 ? &mp.cb : &mp.cout);
            out.col = tk.a * 128 + g * 64 + (tk.kind == K_B3 ? DM : 0);
            out.tok = tk.b * 256;
            out.cnt = tk.kind == K_Q ? C_Q + tk.b : (tk.kind == K_B1 ? C_B1 + tk.b : C_NONE);
            out.blocked = tk.kind == K_Q;
            pend = true;
        } else if (tk.kind == K_B2) {
#pragma unroll 2
            for (int j = 0; j < 16; j++) {
                mbar_wait(sb + PB_F + r.st * 8, r.ph);
                const uint32_t a = sb + (g ? r.x(false) : r.w(false));
                battn_warp(a, sb + PB_E + r.st * 8, tk.b * 32, g, j * 2 + (warp >> 1), warp >> 1, warp & 1, lane);
                r.next(2);
            }
            nbar_sync(barid, 128);
            if (elected) p_signal(sb, g, C_B2 + (tk.b >> 2), nsig);
#pragma unroll
            for (int j = 0; j < 64; j++) pk[j] = 0u;
        } else {
            if (tk.kind == K_SN) p_narrow<64>(mp, tk, sb, g, warp, r, nsig); else p_narrow<128>(mp, tk, sb, g, warp, r, nsig);
#pragma unroll
            for (int j = 0; j < 64; j++) pk[j] = 0u;
        }
    }
    if (elected) { bulk_wait_all(); p_signal(sb, g, -1, nsig); }
}
DEVI void post_init(uint32_t sb) {
    for (int i = 0; i < P_STAGES; i++) { mbar_init(sb + PB_F + i * 8, 1); mbar_init(sb + PB_E + i * 8, 8); }
    for (int i = 0; i < 2; i++) { mbar_init(sb + PB_TF + i * 8, 1); mbar_init(sb + PB_TE + i * 8, 256); }
    for (int i = 0; i < 4; i++) mbar_init(sb + PB_S + i * 8, 1);
    fence_mbar_init();
}

constexpr unsigned long long R_TORD_PACK = 0xfae93542dc187b60ull;
__host__ __device__ constexpr int r_tord(int pos) { return (int)((R_TORD_PACK >> (4 * pos)) & 15ull); }
__host__ __device__ constexpr int r_tinv(int T) { for (int p = 0; p < 16; p++) if (r_tord(p) == T) return p; return 0; }
__host__ __device__ constexpr bool r_pos_ss(int pos) { return pos % 3 == 2; }
__host__ __device__ constexpr int r_ss(int pos) { return pos / 3; }
__host__ __device__ constexpr int r_rs(int pos) { return pos - pos / 3; }
constexpr int R_NRS = 11, R_NSS = 5;
constexpr int R_G1 = 3, R_G2 = 9, R_G3 = 12;
#define REG_KB 232
constexpr int X_SLOTS = 4;
constexpr int X_NST = 8;

constexpr int RS_WSS  = 0;
constexpr int RS_WO   = RS_WSS + R_NSS * 16384;
constexpr int RS_MEM  = RS_WO + 5 * 16384;
constexpr int RS_O    = RS_MEM + 16384;
constexpr int RS_SX   = RS_O + 2048;
constexpr int RS_BAR  = RS_SX + 2048;
constexpr int RS_TAIL = RS_BAR + 1024;
constexpr int RS_WO5  = RS_TAIL;
constexpr int RS_K    = RS_WO5 + 16384;
constexpr int RS_V    = RS_K + 10240;
constexpr int RS_Q    = RS_V + 10240;
constexpr int RS_QX   = RS_Q + 2048;
constexpr int RS_QEND = RS_QX + 8192;
constexpr int RS_X    = RS_TAIL;
constexpr int X_PITCH = X_SLOTS * 4096;
constexpr int RS_XD   = RS_X + 2 * X_PITCH;
constexpr int RS_WX   = RS_XD + 8192;
constexpr int RS_XE   = RS_WX + 4096;
constexpr int RS_KEND = RS_XE + 2048;
constexpr int RS_EV   = RS_BAR + 256;
constexpr int R_SMEM  = RS_KEND > RS_QEND ? RS_KEND : RS_QEND;
static_assert(R_SMEM <= 232448 && P_SMEM <= R_SMEM, "smem");
static_assert(RS_TAIL % 1024 == 0 && RS_MEM % 1024 == 0, "alignment");

constexpr int RB_G = RS_BAR, RB_K = RS_BAR + 24, RB_V = RS_BAR + 32, RB_KV = RS_BAR + 40, RB_QX = RS_BAR + 48, RB_O = RS_BAR + 56;
constexpr int RB_ATT = RS_BAR + 64, RB_W = RS_BAR + 72, RB_SF = RS_BAR + 80, RB_SE = RB_SF + 40, RB_XF = RB_SE + 40;
constexpr int RB_VX = RB_XF + 48, RB_WO = RB_XF + 56, RB_T = RB_XF + 64, RB_G3 = RB_XF + 72, RS_INV = RB_XF + 16;
static_assert(RB_G3 + 8 <= RS_EV, "barriers");
constexpr uint32_t SB0 = 1024;
__host__ __device__ constexpr uint32_t cdesc(uint32_t off, uint32_t lbo) { return ((SB0 + off) >> 4) | ((lbo >> 4) << 16); }
#define SCHED_FENCE() __syncwarp()
constexpr int NB_BIG = 1, NB_Q = 2, NB_AUX = 3, NB_WO = 4, NB_XS = 5, NB_WG = 6, NB_PAIR = 8, NB_PRO = 12;

DEVI int tid_now() { int t; asm volatile("mov.u32 %0, %%tid.x;" : "=r"(t)); return t; }
DEVI uint32_t a_frag_off(int lane, int warp) { return (uint32_t)((((lane >> 4) * 8 + (lane & 7)) * 128) + (((2 * warp + ((lane >> 3) & 1)) ^ (lane & 7)) * 16)); }
DEVI uint32_t b_frag_off(int lane) { return (uint32_t)((lane & 3) * 64 + (((lane >> 2) * 8) ^ ((lane & 2) * 16))); }
DEVI void lds_b(uint32_t* b, uint32_t a) {
    asm volatile("ld.shared.v2.u32 {%0,%1}, [%2];" : "=r"(b[0]), "=r"(b[1]) : "r"(a) : "memory");
    asm volatile("ld.shared.v2.u32 {%0,%1}, [%2];" : "=r"(b[2]), "=r"(b[3]) : "r"(a + 256) : "memory");
}
DEVI uint32_t clk32() { unsigned long long c; asm volatile("mov.u64 %0, %%clock64;" : "=l"(c)); return (uint32_t)c; }

__host__ __device__ constexpr int x_pair(int j) { return j < 2 || j > 5 ? j : (j == 2 ? 5 : j - 1); }
DEVI void x_load(uint32_t sb, int seg, int j, int g, const CUtensorMap* tmX) {
    const uint32_t bar = sb + RB_XF + g * 8;
    mbar_expect_tx(bar, 4096);
    tma_load_3d(sb + RS_X + g * X_PITCH + (j % X_SLOTS) * 4096, tmX + (j == 3), g * 32, seg * 32, x_pair(j) * 2, bar);
    if (j == 3) tma_load_3d(sb + RS_SX + g * (RS_XE - RS_SX), tmX + 1, g * 32, seg * 32, x_pair(3) * 2 + 1, bar);
}
DEVI void x_refill(uint32_t sb, int seg, int j, int g, int warp, const CUtensorMap* tmX) {
    const int sn = j + X_SLOTS < X_NST ? seg : seg + 1;
    if (warp == (j & 3) && sn < NSEG) {
        if (elect_one()) x_load(sb, sn, (j + X_SLOTS) % X_NST, g, tmX);
    }
}
template <int J, int Q0, int Q1, int DQ>
DEVI void x_steps(float* xa, const uint32_t* w, int g0) {
    const int g = (int)opaque((uint32_t)g0);
    const uint32_t dW0 = cdesc(RS_WSS, 16) + g * 768, dW1 = cdesc(RS_WSS + 8192, 16) - g * 256;
#pragma unroll
    for (int q = Q0; q < Q1; q += DQ) {
        const int pos = r_tinv(2 * x_pair(J) + (q >> 2)), kk = (q >> 1) & 1, mt = q & 1;
        const uint32_t db = (J == 3 && q >= 4 ? cdesc(RS_SX, 16) + g * ((RS_XE - RS_SX) >> 4)
                                                    : cdesc(RS_X + (J % X_SLOTS) * 4096, 16) + g * (X_PITCH >> 4) + (q >> 2) * 128) + kk * 2;
        if (J == 0 && q < 2)   wgmma_n32_rs_first(xa + 16 * mt, &w[((r_rs(pos) * 2 + kk) * 2 + mt) * 4], db);
        else if (J == 0 && q == 3) wgmma_n32_ss(xa + 16, cdesc(RS_WX, 16) + g * 128, db);
        else if (r_pos_ss(pos)) wgmma_n32_ss(xa + 16 * mt, (mt ? dW1 : dW0) + r_ss(pos) * 1024 + kk * 128, db);
        else                   wgmma_n32_rs(xa + 16 * mt, &w[((r_rs(pos) * 2 + kk) * 2 + mt) * 4], db);
    }
}
DEVI void x_first(float* xa, const uint32_t* w, uint32_t sb, int seg, int g0, int warp, const CUtensorMap* tmX) {
    wg_fence();
    x_steps<0, 0, 8, 1>(xa, w, g0); wg_commit();
    x_steps<1, 0, 8, 1>(xa, w, g0); wg_commit();
    x_steps<2, 0, 8, 1>(xa, w, g0); wg_commit();
    x_steps<3, 0, 4, 1>(xa, w, g0); wg_commit();
    const int g = (int)opaque((uint32_t)g0);
    wg_wait<3>(); x_refill(sb, seg, 0, g, warp, tmX);
    wg_wait<2>(); x_refill(sb, seg, 1, g, warp, tmX);
    wg_wait<1>(); x_refill(sb, seg, 2, g, warp, tmX);
    wg_wait<0>(); x_refill(sb, seg, 3, g, warp, tmX);
    reg_fence<32>(xa);
    mbar_wait(sb + RB_XF + g * 8, 1);
}
DEVI void x_second(float* xa, uint32_t* a, uint32_t aA0, const uint32_t* w, uint32_t sb, int seg, int g0, int warp, const CUtensorMap* tmX) {
    wg_fence();
    x_steps<4, 0, 8, 1>(xa, w, g0); wg_commit();
    x_steps<3, 5, 8, 2>(xa, w, g0); x_steps<5, 1, 8, 2>(xa, w, g0); x_steps<6, 1, 8, 2>(xa, w, g0); x_steps<7, 1, 8, 2>(xa, w, g0); wg_commit();
    x_steps<3, 4, 8, 2>(xa, w, g0); x_steps<5, 0, 8, 2>(xa, w, g0); x_steps<6, 0, 8, 2>(xa, w, g0); x_steps<7, 0, 8, 2>(xa, w, g0); wg_commit();
    const int g = (int)opaque((uint32_t)g0);
    wg_wait<2>(); x_refill(sb, seg, 4, g, warp, tmX);
    SCHED_FENCE();
#pragma unroll
    for (int q = 0; q < 4; q++) ldsm4t(a + 4 * q, aA0 + (q & 1) * (8192 - g * 16384) + (q >> 1) * 2048);
    SCHED_FENCE();
    wg_wait<1>();
    reg_fence<16>(xa + 16);
}
DEVI void x_finish(float* xa, uint32_t sb, int g, int warp, int lane) {
    const uint32_t d = sb + RS_XD + (lane >> 4) * 2048 + warp * 256 + (lane & 15) * 16;
#pragma unroll
    for (int i = 0; i < 2; i++) {
        const float* x = xa + 16 + 8 * i;
        sts128(d + (g ^ 1) * 1024 + i * 4096, make_uint4(pack_bf16(x[0], x[1]), pack_bf16(x[2], x[3]), pack_bf16(x[4], x[5]), pack_bf16(x[6], x[7])));
    }
    nbar_sync(NB_PAIR + warp, 64);
    float y[16];
#pragma unroll
    for (int i = 0; i < 2; i++) {
        const uint4 v = lds128(d + g * 1024 + i * 4096);
        const uint32_t u[4] = {v.x, v.y, v.z, v.w};
#pragma unroll
        for (int j = 0; j < 4; j++) { y[8 * i + 2 * j] = __uint_as_float(u[j] << 16); y[8 * i + 2 * j + 1] = __uint_as_float(u[j] & 0xFFFF0000u); }
    }
    reg_fence<16>(y);
    wg_wait<0>();
    reg_fence<16>(xa);
    uint32_t p[8];
#pragma unroll
    for (int j = 0; j < 8; j++) p[j] = pack_bf16(xa[2 * j] + y[2 * j], xa[2 * j + 1] + y[2 * j + 1]);
    __syncwarp();
    stsm4(d + g * 1024, p[0], p[1], p[2], p[3]);
    stsm4(d + g * 1024 + 4096, p[4], p[5], p[6], p[7]);
    nbar_arrive(NB_XS, 256 + 32);
}
DEVI void x_send(uint32_t sb, int seg, uint32_t rank, const CUtensorMap* tmX) {
    auto refill = [&]() {
        if (seg + 1 < NSEG && elect_one()) {
#pragma unroll
            for (int j = 1; j < 4; j++) { x_load(sb, seg + 1, j, 0, tmX); x_load(sb, seg + 1, j, 1, tmX); }
        }
        __syncwarp();
    };
    mbar_wait(sb + RB_ATT, (seg - 1) & 1);
    nbar_sync(NB_XS, 256 + 32);
    if (rank == 2) { refill(); mbar_wait(sb + RB_G3, (seg - 1) & 1); }
    if (elect_one()) {
        fence_proxy_async();
        bulk_copy_s2c(mapa(sb + (rank == 1 ? RS_K : RS_V) + 2048, 0), sb + RS_XD, 8192, mapa(sb + (rank == 1 ? RB_KV : RB_VX), 0));
    }
    __syncwarp();
    if (rank == 1) refill();
}

template <bool XP>
DEVI void mem_pass(float* c0, float* c1, uint32_t* a, const uint32_t* w, uint32_t sb, uint32_t aA0, uint32_t aB, int g, int warp, int s) {
    const uint32_t aA1 = aA0 + 8192 - g * 16384, par = (s - 1) & 1;
    uint32_t b[2][4], e[4];
    float d0[4], d1[4];
    if (XP) ldsm4t(e, aA0 + opaque((RS_WX - RS_WSS) - g * (8192 + 2048)));
#pragma unroll
    for (int q = XP ? 4 : 0; q < 4; q++) ldsm4t(a + 4 * q, ((q & 1) ? aA1 : aA0) + (q >> 1) * 2048);
#pragma unroll
    for (int i = 0; i < 4; i++) { c0[i] = 0.f; c1[i] = 0.f; d0[i] = 0.f; d1[i] = 0.f; }
    EV(EV_BIG0, s, 0);
    mbar_wait(sb + RB_G, par);
    EV(EV_BIG0, s, 1);
    lds_b(b[0], aB + r_tord(0) * 1024);
    bool in = false;
#pragma unroll
    for (int pos = 0; pos < 16; pos++) {
        if (pos + 1 < 16) {
            if (pos + 1 == R_G1 && !in) mbar_wait(sb + RB_G + 8, par);
            if (pos + 1 == R_G2 && !in) mbar_wait(sb + RB_G + 16, par);
            if (pos + 1 == R_G3) { if (!in) mbar_wait(sb + RB_G3, par); EV(EV_BIG0, s, 2); }
            lds_b(b[(pos + 1) & 1], aB + r_tord(pos + 1) * 1024);
        }
        if (pos + 2 == R_G1) in = mbar_try(sb + RB_G + 8, par);
        if (pos + 2 == R_G2) in = mbar_try(sb + RB_G + 16, par);
        if (pos + 2 == R_G3) in = mbar_try(sb + RB_G3, par);
        if (XP && pos == 14) in = mbar_try(sb + RB_ATT, par);
        const uint32_t* bb = b[pos & 1];
        const uint32_t* aa = r_pos_ss(pos) ? a : &w[r_rs(pos) * 16];
        mma16816(c1, aa + 4, bb[0], bb[1]);
        mma16816(d1, XP && pos == 0 ? e : aa + 12, bb[2], bb[3]);
        mma16816(c0, aa, bb[0], bb[1]);
        mma16816(d0, aa + 8, bb[2], bb[3]);
        if (r_pos_ss(pos) && pos + 3 < 16) {
#pragma unroll
            for (int q = 0; q < 4; q++) ldsm4t(a + 4 * q, ((q & 1) ? aA1 : aA0) + (r_ss(pos) + 1) * 16384 + (q >> 1) * 2048);
        }
        SCHED_FENCE();
    }
    if (XP && !in) mbar_wait(sb + RB_ATT, par);
#pragma unroll
    for (int i = 0; i < 4; i++) { c1[i] += d1[i]; c0[i] += d0[i]; }
}

DEVI uint32_t k_frag_off(int lane) { return (uint32_t)((((lane >> 3) & 1) * 16 + (lane >> 4) * 8 + (lane & 7)) * 16); }
DEVI uint32_t v_frag_off(int lane) { return (uint32_t)(((lane >> 3) & 1) * 2048 + ((lane >> 4) * 8 + (lane & 7)) * 16); }
DEVI void pv_pair(float (*o)[4], const uint32_t* p, const uint32_t* v) {
#pragma unroll
    for (int n = 0; n < 4; n++) mma16816(o[n], p, v[2 * n], v[2 * n + 1]);
}
DEVI void pv_single(float (*o)[4], const uint32_t* p, const uint32_t* v) {
#pragma unroll
    for (int n = 0; n < 4; n++) mma1688(o[n], p[0], p[1], v[n]);
}
DEVI void s_tile(const uint32_t* qa, const uint32_t* k, float& s0, float& s1) {
    float c[4][4];
#pragma unroll
    for (int q = 0; q < 4; q++) { c[q][0] = c[q][1] = c[q][2] = c[q][3] = 0.f; }
#pragma unroll
    for (int q = 0; q < 4; q++) {
        mma16816(c[2 * (q & 1)], qa + 4 * q, k[4 * q], k[4 * q + 1]);
        mma16816(c[2 * (q & 1) + 1], qa + 4 * q, k[4 * q + 2], k[4 * q + 3]);
    }
    s0 = (c[0][0] + c[1][2]) + (c[2][0] + c[3][2]);
    s1 = (c[0][1] + c[1][3]) + (c[2][1] + c[3][3]);
}
DEVI void mem_scores(uint32_t sb, int s, int lane) {
    const uint32_t ka = sb + RS_K + k_frag_off(lane), sa = sb + RS_SX + 1024 + lane * 8;
    uint32_t qa[16], km[16];
    nbar_sync(NB_Q, 256);
#pragma unroll
    for (int q = 0; q < 4; q++) ldsm4t(qa + 4 * q, sb + RS_Q + q * 512 + lane * 16);
    mbar_wait(sb + RB_K, s & 1);
#pragma unroll
    for (int q = 0; q < 4; q++) ldsm4t(km + 4 * q, ka + q * 512);
    SCHED_FENCE();
    float s0, s1;
    s_tile(qa, km, s0, s1);
    asm volatile("st.shared.v2.f32 [%0], {%1,%2};" :: "r"(sa), "f"(s0 * SCALE_LOG2E), "f"(s1 * SCALE_LOG2E) : "memory");
    nbar_arrive(NB_XS, 128 + 32);
}
DEVI float quad_max(float m) {
    return fmaxf(fmaxf(m, __shfl_xor_sync(0xffffffffu, m, 1)), fmaxf(__shfl_xor_sync(0xffffffffu, m, 2), __shfl_xor_sync(0xffffffffu, m, 3)));
}
DEVI void mem_attn(uint32_t sb, int s, int warp, int lane) {
    const uint32_t va = sb + RS_V + warp * 512, sa = sb + RS_SX + lane * 8;
    [[maybe_unused]] constexpr int g = 0;
    float o[4][4], mx, l = 0.f;
    {
        const uint32_t ka = sb + RS_K + k_frag_off(lane) + (1 + warp) * 2048;
        uint32_t qa[16], kx[16];
        const bool in = mbar_try(sb + RB_KV, s & 1);
        nbar_sync(NB_Q, 256);
        EV(EV_BIG0 && lds32(sb + RS_Q) != 0x12345678u, s, 8);
#pragma unroll
        for (int q = 0; q < 4; q++) ldsm4t(qa + 4 * q, sb + RS_Q + q * 512 + lane * 16);
        if (!in) mbar_wait(sb + RB_KV, s & 1);
#pragma unroll
        for (int q = 0; q < 4; q++) ldsm4t(kx + 4 * q, ka + q * 512);
        const bool vin = mbar_try(sb + RB_VX, s & 1);
        SCHED_FENCE();
        float s0, s1;
        s_tile(qa, kx, s0, s1);
        asm volatile("st.shared.v2.f32 [%0], {%1,%2};" :: "r"(sa + warp * 256), "f"(s0), "f"(s1) : "memory");
        nbar_sync(NB_WG, 128);
        float sc[8];
#pragma unroll
        for (int n = 0; n < 4; n++) { const float2 v = lds64f(sa + n * 256); sc[2 * n] = v.x; sc[2 * n + 1] = v.y; }
        if (!vin) mbar_wait(sb + RB_VX, s & 1);
        mx = quad_max(fmaxf(fmaxf(fmaxf(sc[0], sc[1]), fmaxf(sc[2], sc[3])), fmaxf(fmaxf(sc[4], sc[5]), fmaxf(sc[6], sc[7])))) * SCALE_LOG2E;
        uint32_t vx[16], p[8];
#pragma unroll
        for (int q = 0; q < 4; q++) ldsm4(vx + 4 * q, va + 2048 + (q >> 1) * 4096 + (q & 1) * 256 + v_frag_off(lane));
#pragma unroll
        for (int n = 0; n < 4; n++) {
            const float e0 = ex2(fmaf(sc[2 * n], SCALE_LOG2E, -mx)), e1 = ex2(fmaf(sc[2 * n + 1], SCALE_LOG2E, -mx));
            l += e0 + e1;
            p[2 * n] = pack_bf16(e0, e1); p[2 * n + 1] = __float_as_uint(e0);
        }
#pragma unroll
        for (int n = 0; n < 4; n++) { o[n][0] = o[n][1] = o[n][2] = o[n][3] = 0.f; }
        pv_pair(o, p, vx);
        pv_pair(o, p + 4, vx + 8);
    }
    const uint32_t dst = sb + RS_O + warp * 512 + (lane & 3) * 128 + (lane >> 2) * 16, dl = sb + RS_INV + (lane & 28);
    EV(EV_BIG0, s, 5);
    mbar_wait(sb + RB_V, s & 1);
    uint32_t vm[4], p[2];
    ldsm4(vm, va + lane * 16);
    nbar_sync(NB_XS, 128 + 32);
    EV(EV_BIG0 && lds32(sb + RS_Q) != 0x12345678u, s, 9);
    const float2 sm = lds64f(sa + 1024);
    const float s0 = sm.x, s1 = sm.y;
    const float m = quad_max(fmaxf(mx, fmaxf(s0, s1)));
    const float e0 = ex2(s0 - m), e1 = ex2(s1 - m), f = ex2(mx - m);
    p[0] = pack_bf16(e0, e1); p[1] = __float_as_uint(e0);
#pragma unroll
    for (int n = 0; n < 4; n++) { o[n][0] *= f; o[n][1] *= f; }
    pv_single(o, p, vm);
    l = fmaf(l, f, e0 + e1);
    l = (l + __shfl_xor_sync(0xffffffffu, l, 1)) + (__shfl_xor_sync(0xffffffffu, l, 2) + __shfl_xor_sync(0xffffffffu, l, 3));
    const uint4 u = make_uint4(pack_bf16(o[0][0], o[0][1]), pack_bf16(o[1][0], o[1][1]), pack_bf16(o[2][0], o[2][1]), pack_bf16(o[3][0], o[3][1]));
    st_async128(mapa(dst, 1), u.x, u.y, u.z, u.w, mapa(sb + RB_O, 1));
    st_async128(mapa(dst, 2), u.x, u.y, u.z, u.w, mapa(sb + RB_O, 2));
    st_async32(mapa(dl, 1 + (warp & 1)), __float_as_uint(l), mapa(sb + RB_O, 1 + (warp & 1)));
    sts128(dst, u);
    sts32(dl, __float_as_uint(l));
    __syncwarp();
    if (elect_one()) mbar_arrive(sb + RB_O);
    EV(EV_BIG0, s, 15);
}

DEVI void ta_mask(float* c, int cw, int lane) {
    const int mt = cw >= 3, over = 8 * (cw - 3 * mt - 1) + 2 * (lane & 3) - 16 * mt - (lane >> 2);
    if (over > 0) c[0] = -INFINITY;
    if (over >= 0) c[1] = -INFINITY;
    if (over > 8) c[2] = -INFINITY;
    if (over >= 8) c[3] = -INFINITY;
}
DEVI void ta_scores(uint32_t sb, int seg, int warp, int lane) {
    const int tx = warp == 3 ? 0 : (warp == 2 ? 1 : 4 + 2 * warp), ty = warp == 3 ? 3 : tx + 1;
    const uint32_t qa = sb + RS_QX + ((warp < 2 ? 2 : 0) + ((lane >> 3) & 1)) * 2048 + ((lane >> 4) * 8 + (lane & 7)) * 16;
    const uint32_t ka = sb + RS_K + (warp < 2 ? tx - 3 : tx) * 2048 + lane * 16;
    float x[4] = {0.f, 0.f, 0.f, 0.f}, y[4] = {0.f, 0.f, 0.f, 0.f};
    mbar_wait(sb + RB_QX, seg & 1);
    if (warp < 3) {
#pragma unroll
        for (int j = 0; j < 4; j++) {
            uint32_t a0[4], a1[4], bx[4], by[4];
            ldsm4t(a0, qa + j * 512); ldsm4t(bx, ka + j * 512); ldsm4t(by, ka + 2048 + j * 512); ldsm4t(a1, qa + j * 512 + 256);
            mma16816(x, a0, bx[0], bx[1]); mma16816(y, a0, by[0], by[1]);
            mma16816(x, a1, bx[2], bx[3]); mma16816(y, a1, by[2], by[3]);
        }
        ta_mask(x, tx, lane); ta_mask(y, ty, lane);
    } else {
        mbar_wait(sb + RB_K, seg & 1);
#pragma unroll
        for (int j = 0; j < 4; j++) {
            uint32_t a0[4], a1[4], a2[4], a3[4], b[4];
            ldsm4t(a0, qa + j * 512); ldsm4t(b, ka + j * 512); ldsm4t(a2, qa + 4096 + j * 512);
            ldsm4t(a1, qa + j * 512 + 256); ldsm4t(a3, qa + 4096 + j * 512 + 256);
            mma16816(x, a0, b[0], b[1]); mma16816(y, a2, b[0], b[1]);
            mma16816(x, a1, b[2], b[3]); mma16816(y, a3, b[2], b[3]);
        }
    }
    nbar_sync(NB_WG + 1, 128);
    asm volatile("st.shared.v2.f32 [%0], {%1,%2};" :: "r"(sb + RS_QX + 4096 + tx * 256 + lane * 8), "f"(fmaxf(x[0], x[1])), "f"(fmaxf(x[2], x[3])) : "memory");
    asm volatile("st.shared.v2.f32 [%0], {%1,%2};" :: "r"(sb + RS_QX + 4096 + ty * 256 + lane * 8), "f"(fmaxf(y[0], y[1])), "f"(fmaxf(y[2], y[3])) : "memory");
    nbar_sync(NB_WG + 1, 128);
    float m[4] = {-INFINITY, -INFINITY, -INFINITY, -INFINITY};
#pragma unroll
    for (int n = 0; n < 8; n++) {
        if (n < 3 ? warp >= 2 : warp != 2) {
            const float2 v = lds64f(sb + RS_QX + 4096 + n * 256 + lane * 8);
            m[n < 3 ? 0 : 2] = fmaxf(m[n < 3 ? 0 : 2], v.x); m[n < 3 ? 1 : 3] = fmaxf(m[n < 3 ? 1 : 3], v.y);
        }
    }
#pragma unroll
    for (int o = 1; o < 4; o <<= 1) {
#pragma unroll
        for (int i = 0; i < 4; i++) m[i] = fmaxf(m[i], __shfl_xor_sync(0xffffffffu, m[i], o));
    }
    const float x0 = (warp < 2 ? m[2] : m[0]) * -SCALE_LOG2E, x1 = (warp < 2 ? m[3] : m[1]) * -SCALE_LOG2E;
    const float y0 = (warp == 2 ? m[0] : m[2]) * -SCALE_LOG2E, y1 = (warp == 2 ? m[1] : m[3]) * -SCALE_LOG2E;
    sts64(sb + RS_QX + tx * 256 + lane * 8, pack_bf16(ex2(fmaf(x[0], SCALE_LOG2E, x0)), ex2(fmaf(x[1], SCALE_LOG2E, x0))),
                                            pack_bf16(ex2(fmaf(x[2], SCALE_LOG2E, x1)), ex2(fmaf(x[3], SCALE_LOG2E, x1))));
    sts64(sb + RS_QX + ty * 256 + lane * 8, pack_bf16(ex2(fmaf(y[0], SCALE_LOG2E, y0)), ex2(fmaf(y[1], SCALE_LOG2E, y0))),
                                            pack_bf16(ex2(fmaf(y[2], SCALE_LOG2E, y1)), ex2(fmaf(y[3], SCALE_LOG2E, y1))));
}
template <int MT>
DEVI void ta_output(uint32_t sb, int seg, int head, int j, int lane) {
    const uint32_t pa = sb + RS_QX + MT * 768 + lane * 8, vb = sb + RS_V + j * 512;
    uint32_t p[6 + 4 * MT], v[12 + 8 * MT];
#pragma unroll
    for (int n = 0; n < 3 + 2 * MT; n++)
        asm volatile("ld.shared.v2.u32 {%0,%1}, [%2];" : "=r"(p[2 * n]), "=r"(p[2 * n + 1]) : "r"(pa + n * 256) : "memory");
#pragma unroll
    for (int q = 0; q < 2 + 2 * MT; q++) ldsm4(v + 4 * q, vb + (q >> 1) * 4096 + (q & 1) * 256 + v_frag_off(lane));
    ldsm4(v + 8 + 8 * MT, vb + 4096 + MT * 4096 + lane * 16);
    float o[4][4], l[4] = {0.f, 0.f, 0.f, 0.f};
#pragma unroll
    for (int n = 0; n < 4; n++) { o[n][0] = o[n][1] = o[n][2] = o[n][3] = 0.f; }
    mma16816(l, p, 0x3F803F80u, 0x3F803F80u);
    pv_pair(o, p, v);
    if (MT) { mma16816(l, p + 4, 0x3F803F80u, 0x3F803F80u); pv_pair(o, p + 4, v + 8); }
    mma1688(l, p[4 + 4 * MT], p[5 + 4 * MT], 0x3F803F80u);
    pv_single(o, p + 4 + 4 * MT, v + 8 + 8 * MT);
    const float i0 = rcp_fast(l[0]), i1 = rcp_fast(l[2]);
    bf16* dst = g_ox + (uint32_t)((seg * 32 + MT * 16 + (lane >> 2)) * HD + head * DH + j * 32 + (lane & 3) * 8);
    asm volatile("st.global.v4.u32 [%0], {%1,%2,%3,%4};" :: "l"(dst), "r"(pack_bf16(o[0][0] * i0, o[0][1] * i0)), "r"(pack_bf16(o[1][0] * i0, o[1][1] * i0)),
                 "r"(pack_bf16(o[2][0] * i0, o[2][1] * i0)), "r"(pack_bf16(o[3][0] * i0, o[3][1] * i0)) : "memory");
    asm volatile("st.global.v4.u32 [%0], {%1,%2,%3,%4};" :: "l"(dst + 8 * HD), "r"(pack_bf16(o[0][2] * i1, o[0][3] * i1)), "r"(pack_bf16(o[1][2] * i1, o[1][3] * i1)),
                 "r"(pack_bf16(o[2][2] * i1, o[2][3] * i1)), "r"(pack_bf16(o[3][2] * i1, o[3][3] * i1)) : "memory");
}

template <bool XP>
DEVI void big_main(const uint32_t* w, const uint32_t sb, const int g, const int warp, const uint32_t rank, const int head,
                   const CUtensorMap* tmX, const bf16* xg, const unsigned E) {
    float xa[32];
    uint32_t a[16];
    const uint32_t aB = __shfl_sync(0xffffffffu, sb + RS_MEM + (g * 32 + (tid_now() & 31)) * 16, tid_now() & 31);
#define lane0 ((int)(opaque(aB) >> 4) & 31)
    const uint32_t aA0 = sb + RS_WSS + g * (8192 + 4096) + a_frag_off(lane0, warp);
    const uint32_t aBf = sb + RS_MEM + g * 512 + b_frag_off(lane0);
    if constexpr (XP) {
        mbar_wait(sb + RB_XF + g * 8, 0);
        x_first(xa, w, sb, 0, g, warp, tmX);
        x_second(xa, a, aA0, w, sb, 0, g, warp, tmX);
        x_finish(xa, sb, g, warp, lane0);
    }
    nbar_sync(NB_BIG, 256);
    for (int s = 0; s < NSEG; s++) {
        float c0[4], c1[4];
        mem_pass<XP>(c0, c1, a, w, sb, aA0, aBf, g, warp, s);
        EV(EV_BIG0 && c0[0] != 1.2345e30f, s, 3);
        bool xin = true;
        const uint32_t xs = sb + RS_O + warp * 256 + lane0 * 8;
        sts64(xs + g * 1024, pack_bf16(c1[0], c1[1]), pack_bf16(c1[2], c1[3]));
        {
            const uint32_t d = sb + (XP ? (rank == 1 ? RS_K : RS_V) : RS_Q) + (g * 4 + warp) * 256 + lane0 * 4;
            const uint32_t rbar = XP ? mapa(sb + (rank == 1 ? RB_K : RB_V), 0) : 0u;
            nbar_sync(NB_PAIR + warp, 64);
            const float2 v = lds64f(xs + (g ^ 1) * 1024);
            if (XP) xin = mbar_test(sb + RB_XF + g * 8, 0);
            const uint32_t v0 = __float_as_uint(v.x), v1 = __float_as_uint(v.y);
            const uint32_t p0 = pack_bf16(c0[0] + __uint_as_float(v0 << 16), c0[1] + __uint_as_float(v0 & 0xFFFF0000u));
            const uint32_t p1 = pack_bf16(c0[2] + __uint_as_float(v1 << 16), c0[3] + __uint_as_float(v1 & 0xFFFF0000u));
            if constexpr (XP) { st_async32(mapa(d, 0), p0, rbar); st_async32(mapa(d + 128, 0), p1, rbar); }
            else { sts32(d, p0); sts32(d + 128, p1); }
            EV(EV_BIG0, s, 4);
        }
        if constexpr (XP) {
            if (s == NSEG - 1) break;
            if (!xin) mbar_wait(sb + RB_XF + g * 8, 0);
            x_first(xa, w, sb, s + 1, g, warp, tmX);
            EV(EV_BIG0, s, 5);
            EVCAL(s);
            nbar_sync(NB_WO, 384);
            EV(EV_BIG0 && lds32(sb + RS_O) != 0x12345678u, s, 6);
            x_second(xa, a, aA0, w, sb, s + 1, g, warp, tmX);
            EV(EV_BIG0, s, 7);
            x_finish(xa, sb, g, warp, lane0);
        } else {
            if (g == 0) {
                if (s < NSEG - 1) mem_attn(sb, s, warp, lane0);
            } else {
                if (s < NSEG - 1) { if (warp == 3) mem_scores(sb, s, lane0); else nbar_arrive(NB_Q, 256); }
                mbar_wait(sb + RB_KV, s & 1);
                if (s == 0 && warp == 0) {
                    wait_count_warp(&g_cnt[C_QH], 64 * E);
                    if (elect_one()) {
                        fence_proxy_global();
                        mbar_expect_tx(sb + RB_QX, 8192);
                        bulk_load(sb + RS_QX, g_qx + (uint32_t)(head * 4096), 8192, sb + RB_QX);
                    }
                    __syncwarp();
                }
                ta_scores(sb, s, warp, lane0);
            }
            EVCAL(s);
            mbar_wait(sb + RB_V, s & 1);
            mbar_wait(sb + RB_VX, s & 1);
            if (s < NSEG - 1) nbar_sync(NB_WO, 384); else nbar_sync(NB_BIG, 256);
            EV(EV_BIG0 && lds32(sb + RS_O) != 0x12345678u, s, 6);
            if (g == 0) ta_output<0>(sb, s, head, warp, lane0); else ta_output<1>(sb, s, head, warp, lane0);
            nbar_sync(NB_BIG, 256);
            EV(EV_BIG0 && lds32(sb + RS_O) != 0x12345678u, s, 7);
            if (g == 0 && warp == 0 && s + 1 < NSEG) {
                if (elect_one()) {
                    mbar_arrive_remote(mapa(sb + RB_ATT, 1));
                    mbar_arrive_remote(mapa(sb + RB_ATT, 2));
                    mbar_expect_tx(sb + RB_KV, 8192);
                    mbar_expect_tx(sb + RB_K, 2048);
                    mbar_expect_tx(sb + RB_V, 2048); mbar_expect_tx(sb + RB_VX, 8192);
                    mbar_arrive(sb + RB_T);
                }
                __syncwarp();
            }
        }
    }
    if constexpr (!XP) { if (tid_now() == 0) signal_count(&g_prog[(NSEG - 1) >> 1]); }
#undef lane0
}

template <int T, int K0, int K1>
DEVI void wo_part(float* acc) {
    constexpr uint32_t dWo = cdesc(T < 5 ? RS_WO + T * 16384 : RS_WO5, 16), dO = cdesc(RS_O, 128);
#pragma unroll
    for (int kk = K0; kk < K1; kk++) {
        if (kk == 0) { if (T < 3) wgmma_n8_ss_first<0>(acc, dWo, dO); else wgmma_n8_ss<0, 0>(acc, dWo, dO); }
        else wgmma_n8_ss<0, 1>(acc, dWo + kk * 128, dO + kk * 16);
    }
    wg_commit();
}
DEVI void red3(uint8_t* p, uint32_t a, uint32_t b, uint32_t c, uint32_t one) {
    asm volatile("red.relaxed.gpu.global.add.noftz.v4.bf16x2 [%0], {%1,%2,%3,%4};" :: "l"(p), "r"(a), "r"(b), "r"(c), "r"(one) : "memory");
}
constexpr int ACC_CH = 3 * 16 * 1024;
template <bool Q>
DEVI void wo_phase(uint32_t sb, int s, int warp, uint8_t* p, uint32_t ainv, int gap) {
    float a0[4], a1[4], a2[4];
    fence_proxy_async();
    const float2 iv = lds64f(ainv);
    SCHED_FENCE();
    const float i0 = rcp_fast(iv.x), i1 = rcp_fast(iv.y);
#define WORD(a, h) pack_bf16(a[2 * h] * i0, a[2 * h + 1] * i1)
    wg_fence();
    wo_part<0, 0, 8>(a0); wo_part<1, 0, 8>(a1); wo_part<2, 0, 8>(a2);
    wg_wait<1>(); reg_fence<4>(a0); reg_fence<4>(a1);
    red3(p, WORD(a0, 0), WORD(a0, 1), WORD(a1, 0), 0x3F80u);
    SCHED_FENCE();
    EV(warp == 0 && elect_one(), s, 11);
    wg_wait<0>(); reg_fence<4>(a2);
    red3(p + ACC_CH, WORD(a2, 0), WORD(a2, 1), WORD(a1, 1), 0x3F80u);
    SCHED_FENCE();
    { const uint32_t t = clk32() + gap; while ((int)(clk32() - t) < 0) { } }
    wg_fence();
    wo_part<3, 0, 8>(a0); wo_part<4, 0, 8>(a1);
    if (Q) {
        wo_part<5, 0, 8>(a2);
        wg_wait<1>(); reg_fence<4>(a0); reg_fence<4>(a1);
        red3(p + 2 * ACC_CH, WORD(a0, 0), WORD(a0, 1), WORD(a1, 0), 0x3F80u);
        SCHED_FENCE();
        wg_wait<0>(); reg_fence<4>(a2);
        red3(p + 3 * ACC_CH, WORD(a2, 0), WORD(a2, 1), WORD(a1, 1), 0x3F80u);
        nbar_arrive(NB_WO, 384);
    } else {
        wg_wait<1>();
        nbar_arrive(NB_WO, 384);
        wg_wait<0>(); reg_fence<4>(a0); reg_fence<4>(a1);
        red3(p + 2 * ACC_CH, WORD(a0, 0), WORD(a0, 1), WORD(a1, 0), 0x3F80u);
        red3(p + 3 * ACC_CH, 0u, 0u, WORD(a1, 1), 0x3F80u);
    }
#undef WORD
}
DEVI void unit_pack(uint32_t* u, uint32_t x0, uint32_t x1, uint32_t x2, uint32_t x3) {
    u[0] = __byte_perm(x0, x1, 0x5410); u[1] = __byte_perm(x2, x3, 0x5410); u[2] = __byte_perm(x0, x1, 0x7632); u[3] = __byte_perm(x2, x3, 0x7632);
}
DEVI void unit_send(uint32_t d, const uint32_t* u, uint32_t bar, uint32_t r1, uint32_t r2) {
    st_async128(mapa(d, r1), u[0], u[1], u[2], u[3], mapa(bar, r1));
    st_async128(mapa(d, r2), u[0], u[1], u[2], u[3], mapa(bar, r2));
}
template <bool Q>
DEVI void stage_sums(uint32_t sb, int s, uint32_t rank, int warp, const uint8_t* src, uint32_t l, uint32_t gate) {
    uint4 v[4];
    while ((int)(clk32() - gate) < 0) { }
    EV(elect_one(), s, 16 + warp);
#pragma unroll
    for (int j = 0; j < 4; j++) v[j] = ld_rlx4(src + j * 1024);
    const uint32_t col = sb + RS_MEM + ((Q ? 0 : (rank == 1 ? 6 : 11)) + 3 * (warp >> 1)) * 1024 + ((l >> 2) & 0x300) + (l & 0x70);
    const uint32_t d0 = col + (warp & 1) * 2048, d1 = d0 ^ 160, d2 = (col ^ ((warp & 1) * 160)) + 1024;
    const uint32_t r1 = Q ? 1 : 0, r2 = Q ? 2 : 3 - rank, bar = sb + (warp < 2 ? RB_G + 8 * warp : (Q ? RB_G + 16 : RB_G3));
    int n = 0;
    while (!__all_sync(0xffffffffu, v[0].w == 0x4200u && v[1].w == 0x4200u && v[2].w == 0x4200u && v[3].w == 0x4200u)) {
#pragma unroll
        for (int j = 0; j < 4; j++) v[j] = ld_rlx4(src + j * 1024);
        if (++n > SPIN_LIMIT) __trap();
    }
    EV(elect_one(), s, 24 + warp);
    uint32_t u[12];
    unit_pack(u + 8, v[0].z, v[1].z, v[2].z, v[3].z);
    unit_send(d2, u + 8, bar, r1, r2);
    if (Q || warp < 3) {
        unit_pack(u, v[0].x, v[1].x, v[2].x, v[3].x);
        unit_pack(u + 4, v[0].y, v[1].y, v[2].y, v[3].y);
        unit_send(d0, u, bar, r1, r2);
        unit_send(d1, u + 4, bar, r1, r2);
        sts128(d0, make_uint4(u[0], u[1], u[2], u[3]));
        sts128(d1, make_uint4(u[4], u[5], u[6], u[7]));
    }
    sts128(d2, make_uint4(u[8], u[9], u[10], u[11]));
    __syncwarp();
    if (elect_one()) {
        mbar_expect_tx(bar, warp < 2 ? 3072u : (Q ? 0u : 1024u));
        if (warp == 0) mbar_expect_tx(sb + (Q ? RB_G3 : RB_G + 16), Q ? 4096u : 3072u);
    }
    EV(elect_one(), s, 20 + warp);
}
DEVI void wo_permute(uint32_t tile, int t) {
    const uint32_t a = tile + t * 32 + ((t >> 2) & 1) * 16;
#pragma unroll
    for (int h = 0; h < 2; h++) {
        uint4 v[3], u[3];
#pragma unroll
        for (int i = 0; i < 3; i++) if (3 * h + i < 5 || t < 32) { v[i] = lds128(a + (3 * h + i) * 3072); u[i] = lds128((a ^ 16) + (3 * h + i) * 3072); }
#pragma unroll
        for (int i = 0; i < 3; i++) if (3 * h + i < 5 || t < 32) {
            sts128(a + (3 * h + i) * 3072, make_uint4(__byte_perm(v[i].x, v[i].y, 0x5410), __byte_perm(v[i].x, v[i].y, 0x7632),
                                                      __byte_perm(u[i].x, u[i].y, 0x5410), __byte_perm(u[i].x, u[i].y, 0x7632)));
            sts128((a ^ 16) + (3 * h + i) * 3072, make_uint4(__byte_perm(v[i].z, v[i].w, 0x5410), __byte_perm(v[i].z, v[i].w, 0x7632),
                                                             __byte_perm(u[i].z, u[i].w, 0x5410), __byte_perm(u[i].z, u[i].w, 0x7632)));
        }
    }
}
DEVI uint32_t acc_clear(int slot, int idx, uint32_t lo) {
    uint8_t* p = g_acc + (uint32_t)(slot * 128 + idx * 3072 + (lo < 3072 ? lo : lo - 1024));
    st_rlx4(p, 0u, 0u, 0u, 0u);
    uint32_t z; asm volatile("ld.relaxed.gpu.global.u32 %0, [%1];" : "=r"(z) : "l"(p) : "memory");
    return z;
}

template <bool Q>
DEVI void aux_main(uint32_t sb, int warp, uint32_t rank, int head, const CUtensorMap* tmX, const bf16* xg, unsigned E, const int delay, const int gap) {
    const uint32_t lo = __shfl_sync(0xffffffffu, ((tid_now() >> 3) & 3) * 1024 + (tid_now() & 7) * 16, tid_now() & 31);
    for (int s = 0; s < NSEG - 1; s++) {
        if (!Q && warp == 0 && elect_one()) mbar_expect_tx(sb + RB_O, 2048 + 256);
        __syncwarp();
        const uint32_t slot = (s & 3) * 128;
        mbar_wait(sb + RB_O, s & 1);
        EV(warp == 0 && elect_one(), s, 10);
        wo_phase<Q>(sb, s, warp, g_acc + (uint32_t)(slot + (rank * 4 + warp) * 4096 + opaque(lo)), sb + RS_INV + ((opaque(lo) >> 1) & 24), gap);
        SCHED_FENCE();
        const uint32_t t_o = clk32();
        EV(warp == 0 && elect_one(), s, 12);
        {
            const uint32_t l = opaque(lo);
            stage_sums<Q>(sb, s, rank, warp, g_acc + (uint32_t)(slot + rank * 16384 + warp * ACC_CH + (l & 0xC00) * 4 + (l & 0x70)), l, t_o + delay);
        }
        EV(warp == 2 && elect_one(), s, 14);
        if (warp == (Q ? 3 : 1)) {
            if (Q) {
                mbar_wait(sb + RB_T, s & 1);
                if (s == 3) wait_count_warp(&g_cnt[C_Q], 64 * E);
                if (elect_one()) {
                    if (s == 3) fence_proxy_global();
                    fence_proxy_async();
                    mbar_expect_tx(sb + RB_QX, 8192);
                    bulk_load(sb + RS_QX, g_qx + (uint32_t)(((s + 1) * NH + head) * 4096), 8192, sb + RB_QX);
                    if (head == 0) { TLOG(1400 + s, 0, gtime()); TLOG(1400 + s, 1, clock64()); }
                }
                __syncwarp();
                const bool fresh = (s & 7) == 6 && s + 2 < NSEG;
                if (fresh) wait_count_warp(&g_cnt[C_Q + ((s + 2) >> 3)], 64 * E);
                if (elect_one()) {
                    if (fresh) fence_proxy_global();
                    if (s + 2 < NSEG && s != 2) l2_prefetch(g_qx + (uint32_t)(((s + 2) * NH + head) * 4096), 8192);
                    if (s + 4 < NSEG) l2_prefetch(xg + (uint32_t)(((s + 4) * 32 + head) * DM), 2048);
                    signal_count(&g_prog[s >> 1]);
                }
                __syncwarp();
            } else {
                const uint32_t zero = acc_clear((s + 2) & 3, 2 * head + (int)rank - 1, opaque(lo));
                x_send(sb, s + 1, rank, tmX);
                if (__any_sync(0xffffffffu, zero != 0u)) __trap();
            }
        }
    }
}

DEVI void load_weights(uint32_t sb, const CUtensorMap* tmW, const CUtensorMap* tmWo, int head, uint32_t rank, int2 t0) {
    const uint32_t c0 = clk32();
    if (rank == 0) while ((int)(clk32() - c0) < t0.x) { }
    const uint32_t bW = sb + RB_W, bSF = sb + RB_SF, bSE = sb + RB_SE;
    const int tile0 = rank == 0 ? 0 : (rank == 1 ? 6 : 11);
    mbar_expect_tx(bW, R_NSS * 16384);
    for (int pass = 0; pass < 2; pass++) {
        for (int pos = 0; pos < 16; pos++) {
            const int k = (int)((R_TORD_PACK >> (4 * pos)) & 15ull) * 64, rd = pos - pos / 3, slot = rd % 5;
            if (r_pos_ss(pos)) {
                if (pass) continue;
                const uint32_t dst = sb + RS_WSS + (pos / 3) * 16384;
                tma_load_2d(dst, tmW, head * DH, k, bW);
                tma_load_2d(dst + 8192, tmW, head * DH + 64, k, bW);
            } else if (pass == (rd >= 5)) {
                if (rd >= 5) mbar_wait(bSE + 8 * slot, ((rd / 5) - 1) & 1);
                mbar_expect_tx(bSF + 8 * slot, 16384);
                const uint32_t dst = sb + RS_WO + slot * 16384;
                tma_load_2d(dst, tmW, head * DH, k, bSF + 8 * slot);
                tma_load_2d(dst + 8192, tmW, head * DH + 64, k, bSF + 8 * slot);
            }
        }
    }
    while ((int)(clk32() - c0) < t0.y) { }
    if (rank == 0) { mbar_expect_tx(sb + RB_WO, 16384); tma_load_wo(sb + RS_WO5, tmWo, 5 * 64, head * 4, sb + RB_WO); }
    for (int i = 1; i <= 5; i++) {
        const int slot = i % 5, last = slot + 10 < R_NRS ? slot + 10 : slot + 5;
        mbar_wait(bSE + 8 * slot, (last / 5) & 1);
        mbar_expect_tx(bSF + 8 * slot, 16384);
        tma_load_wo(sb + RS_WO + slot * 16384, tmWo, (tile0 + slot) * 64, head * 4, bSF + 8 * slot);
    }
}
template <bool XP>
DEVI void big_prologue(uint32_t* w, uint32_t sb, int g, int warp, const bf16* __restrict__ mem0) {
    const int tid = tid_now(), lane = tid & 31;
    {
        const uint32_t* m = (const uint32_t*)(mem0 + (lane >> 2) * DM + (tid >> 5) * 16) + (lane & 3);
        uint32_t u[16];
#pragma unroll
        for (int j = 0; j < 8; j++) { u[2 * j] = m[j * 64]; u[2 * j + 1] = m[j * 64 + 4]; }
#pragma unroll
        for (int j = 0; j < 8; j++) sts64(sb + RS_MEM + ((tid >> 5) + j * 8) * 256 + b_frag_off(lane), u[2 * j], u[2 * j + 1]);
    }
    const uint32_t a0 = sb + RS_WO + g * (8192 + 4096) + a_frag_off(lane, warp), a1 = a0 + 8192 - g * 16384;
#pragma unroll
    for (int rd = 0; rd < R_NRS; rd++) {
        const int slot = rd % 5;
        mbar_wait(sb + RB_SF + 8 * slot, (rd / 5) & 1);
#pragma unroll
        for (int q = 0; q < 4; q++) {
            if (XP && rd == 0 && q == 3) {
                sts128(sb + RS_WX + g * 2048 + (tid & 127) * 16, lds128(sb + RS_WO + 8192 - g * 4096 + 2048 + (tid & 127) * 16));
                fence_proxy_async();
                nbar_sync(NB_WG + g, 128);
            } else ldsm4t(&w[rd * 16 + q * 4], ((q & 1) ? a1 : a0) + slot * 16384 + (q >> 1) * 2048);
        }
        mbar_arrive(sb + RB_SE + 8 * slot);
    }
    mbar_wait(sb + RB_W, 0);
    if (tid == 0) TLOG(1500 + blockIdx.x, 2, gtime());
}

#define REC_END() do { if (tid_now() == 0) TLOG(1024 + blockIdx.x, 1, gtime()); } while (0)
struct XMaps { CUtensorMap m[2]; };
__global__ void __launch_bounds__(384, 1)
k_rec(const __grid_constant__ PMaps mp, const __grid_constant__ CUtensorMap tmWk, const __grid_constant__ CUtensorMap tmWv,
      const __grid_constant__ CUtensorMap tmWo, const __grid_constant__ XMaps xm, const bf16* __restrict__ mem0, const bf16* __restrict__ xg,
      int4 tq, int4 tk, int2 t0, int rec) {
    extern __shared__ __align__(1024) uint8_t smem_raw[];
    const uint32_t sb = smem_u32(smem_raw);
    if ((sb & 0x3FFFFu) != SB0) __trap();
    const int tid = threadIdx.x;
    const int wg = __shfl_sync(0xffffffffu, tid >> 7, 0), warp = __shfl_sync(0xffffffffu, (tid >> 5) & 3, 0);
    uint32_t rank; asm("mov.u32 %0, %%cluster_ctarank;" : "=r"(rank));
    int head; asm("mov.u32 %0, %%clusterid.x;" : "=r"(head));
    asm volatile("griddepcontrol.launch_dependents;");
    if (tid == 0 && rec) {
        mbar_init(sb + RB_G, 1);
        mbar_init(sb + RB_G + 8, 1);
        mbar_init(sb + RB_G + 16, rank == 0 ? 2 : 1);
        mbar_init(sb + RB_G3, rank == 0 ? 1 : 2);
        mbar_init(sb + RB_T, 1); mbar_init(sb + RB_VX, 1); mbar_init(sb + RB_WO, 1);
        mbar_init(sb + RB_K, 1); mbar_init(sb + RB_V, 1); mbar_init(sb + RB_KV, 1); mbar_init(sb + RB_QX, 1);
        mbar_init(sb + RB_O, rank == 0 ? 4 : 1); mbar_init(sb + RB_ATT, 1); mbar_init(sb + RB_W, 1);
        for (int i = 0; i < 5; i++) { mbar_init(sb + RB_SF + 8 * i, 1); mbar_init(sb + RB_SE + 8 * i, 256); }
        for (int i = 0; i < 2; i++) mbar_init(sb + RB_XF + 8 * i, X_SLOTS);
        fence_mbar_init();
        if (rank == 0) { mbar_expect_tx(sb + RB_KV, 8192); mbar_expect_tx(sb + RB_K, 2048); mbar_expect_tx(sb + RB_V, 2048); mbar_expect_tx(sb + RB_VX, 8192); }
    }
    __syncthreads();
    asm volatile("barrier.cluster.arrive.release.aligned;" ::: "memory");

    if (wg < 2) {
        reg_inc<REG_KB>();
        if (rank != 0) {
            uint32_t w[R_NRS * 16];
            if ((tid & 127) == 0) for (int j = 0; j < X_SLOTS; j++) x_load(sb, 0, j, wg, xm.m);
            __syncwarp();
            cluster_wait();
            big_prologue<true>(w, sb, wg, warp, mem0);
            big_main<true>(w, sb, wg, warp, rank, head, xm.m, xg, 0u);
            REC_END();
        } else if (rec) {
            uint32_t w[R_NRS * 16];
            cluster_wait();
            big_prologue<false>(w, sb, wg, warp, mem0);
            big_main<false>(w, sb, wg, warp, rank, head, xm.m, xg, *(volatile unsigned*)&g_epoch + 1);
            REC_END();
        } else cluster_wait();
        if (rank == 0 && rec) nbar_arrive(NB_PRO, 256 + 32);
        nbar_sync(0, 384);
        post_consumer(mp, sb, wg, warp);
    } else {
        reg_dec<504 - 2 * REG_KB>();
        if (rec) {
            if (tid == 256) {
                if (rank == 0) l2_prefetch(xg + (uint32_t)(head * 8 * DM), 16384);
                load_weights(sb, rank == 0 ? &mp.wq : (rank == 1 ? &tmWk : &tmWv), &tmWo, head, rank, t0);
            }
            if (warp == 3 && rank != 0) {
                const uint32_t lo = ((tid >> 3) & 3) * 1024 + (tid & 7) * 16;
                acc_clear(0, 2 * head + (int)rank - 1, lo); acc_clear(1, 2 * head + (int)rank - 1, lo);
                __threadfence();
                __syncwarp();
                if (tid == 256 + 96) atomicAdd(&g_zero, 1u);
            }
            __syncwarp();
        }
        cluster_wait();
        const unsigned E = __shfl_sync(0xffffffffu, *(volatile unsigned*)&g_epoch + 1, 0);
        if (rec) {
            if (warp == 1) wait_count_warp(&g_zero, E * 64u);
            if (warp == 3) { if (rank != 0) x_send(sb, 0, rank, xm.m); }
            else {
                nbar_sync(NB_PRO, 96);
#pragma unroll 1
                for (int i = rank == 0 ? 0 : 1; i <= 5; i++) {
                    mbar_wait(sb + (i == 0 ? RB_WO : RB_SF + 8 * (i % 5)), i == 5);
                    if (i == 5 && tid == 288) TLOG(1500 + blockIdx.x, 0, gtime());
                    wo_permute(sb + (i == 0 ? RS_WO5 : RS_WO + (i % 5) * 16384), tid & 127);
                }
            }
            fence_proxy_async();
            nbar_sync(NB_AUX, 128);
            if (tid == 288) { TLOG(1500 + blockIdx.x, 1, gtime()); }
            if (rank == 0) aux_main<true>(sb, warp, rank, head, xm.m, xg, E, warp == 0 ? tq.x : (warp == 1 ? tq.y : tq.z), tq.w);
            else           aux_main<false>(sb, warp, rank, head, xm.m, xg, E, warp == 0 ? tk.x : (warp == 1 ? tk.y : tk.z), tk.w);
        }
        const int t = tid_now();
        if (t >= 320 && t < 320 + 13) asm volatile("prefetch.tensormap [%0];" :: "l"(&mp.wq + (t - 320)) : "memory");
        __syncwarp();
        if (warp == 0) post_producer(mp, sb, E, rank != 0 || !rec);
        else {
            if (warp == 1) {
                if (rank == 0 && rec) nbar_sync(NB_PRO, 256 + 32);
                if (elect_one()) post_init(sb);
                __syncwarp();
            }
            nbar_sync(0, 384);
            if (t == 288 || t == 320) post_helper(sb, warp - 1);
        }
    }
    __syncthreads();
    asm volatile("griddepcontrol.wait;" ::: "memory");
}

typedef CUresult (*EncodeFn)(CUtensorMap*, CUtensorMapDataType, cuuint32_t, void*, const cuuint64_t*, const cuuint64_t*,
                             const cuuint32_t*, const cuuint32_t*, CUtensorMapInterleave, CUtensorMapSwizzle,
                             CUtensorMapL2promotion, CUtensorMapFloatOOBfill);

static CUtensorMap make_map(EncodeFn fn, const void* ptr, uint64_t inner, uint64_t outer, uint32_t box_inner, uint32_t box_outer) {
    CUtensorMap m;
    cuuint64_t dims[2] = {inner, outer};
    cuuint64_t strides[1] = {inner * 2};
    cuuint32_t box[2] = {box_inner, box_outer};
    cuuint32_t es[2] = {1, 1};
    fn(&m, CU_TENSOR_MAP_DATA_TYPE_BFLOAT16, 2, const_cast<void*>(ptr), dims, strides, box, es,
       CU_TENSOR_MAP_INTERLEAVE_NONE, CU_TENSOR_MAP_SWIZZLE_128B, CU_TENSOR_MAP_L2_PROMOTION_L2_256B, CU_TENSOR_MAP_FLOAT_OOB_FILL_NONE);
    return m;
}

static CUtensorMap make_wo_map(EncodeFn fn, const void* ptr, uint64_t rows, uint32_t ngrp) {
    CUtensorMap m;
    cuuint64_t dims[5] = {DM, 2, 4, 4, rows / 32};
    cuuint64_t strides[4] = {DM * 2, 8 * DM * 2, 2 * DM * 2, 32 * DM * 2};
    cuuint32_t box[5] = {64, 2, 4, 4, ngrp};
    cuuint32_t es[5] = {1, 1, 1, 1, 1};
    fn(&m, CU_TENSOR_MAP_DATA_TYPE_BFLOAT16, 5, const_cast<void*>(ptr), dims, strides, box, es,
       CU_TENSOR_MAP_INTERLEAVE_NONE, CU_TENSOR_MAP_SWIZZLE_128B, CU_TENSOR_MAP_L2_PROMOTION_L2_256B, CU_TENSOR_MAP_FLOAT_OOB_FILL_NONE);
    return m;
}

struct Maps {
    PMaps post;
    CUtensorMap wk16, wv16, wo128;
    XMaps x32;
};

extern "C" void kernel_launch(void* const* d_in, const int* in_sizes, int n_in, void* d_out, int out_size) {
    const bf16* A_x   = (const bf16*)d_in[0];
    const bf16* A_mem = (const bf16*)d_in[1];
    const bf16* A_Wq  = (const bf16*)d_in[2];
    const bf16* A_Wk  = (const bf16*)d_in[3];
    const bf16* A_Wv  = (const bf16*)d_in[4];
    const bf16* A_Wo  = (const bf16*)d_in[5];
    const bf16* B_x   = (const bf16*)d_in[7];
    const bf16* B_w   = (const bf16*)d_in[8];
    const bf16* B_wo  = (const bf16*)d_in[9];

    static EncodeFn fn = nullptr;
    static Maps mp;
    static const void* cached[10];
    const void* cur[10] = {A_x, A_mem, A_Wq, A_Wk, A_Wv, A_Wo, B_x, B_w, B_wo, d_out};
    bool same = fn != nullptr;
    for (int i = 0; i < 10 && same; i++) same = cached[i] == cur[i];
    if (!same) {
        if (!fn) {
            void* p = nullptr; cudaDriverEntryPointQueryResult qr;
            cudaGetDriverEntryPoint("cuTensorMapEncodeTiled", &p, cudaEnableDefault, &qr);
            fn = (EncodeFn)p;
            cudaFuncSetAttribute(k_rec, cudaFuncAttributeMaxDynamicSharedMemorySize, R_SMEM);
        }
        void *p_ox, *p_bqkv, *p_bo, *p_qx;
        cudaGetSymbolAddress(&p_qx, g_qx);
        cudaGetSymbolAddress(&p_ox, g_ox); cudaGetSymbolAddress(&p_bqkv, g_bqkv); cudaGetSymbolAddress(&p_bo, g_bo);
        mp.post.wq   = make_map(fn, A_Wq, HD, DM, 64, 64);
        mp.post.wo   = make_wo_map(fn, A_Wo, HD, 2);
        mp.post.bw   = make_map(fn, B_w, 3 * DM, DM, 64, 64);
        mp.post.bwo  = make_wo_map(fn, B_wo, DM, 2);
        mp.post.x    = make_map(fn, A_x, DM, S_TOK, 64, 128);
        mp.post.bx   = make_map(fn, B_x, DM, S_TOK, 64, 128);
        mp.post.bo   = make_map(fn, p_bo, DM, S_TOK, 64, 128);
        mp.post.ox   = make_map(fn, p_ox, HD, S_TOK, 64, 128);
        mp.post.ox64 = make_map(fn, p_ox, HD, S_TOK, 64, 64);
        mp.post.cb   = make_map(fn, p_bqkv, 3 * DM, S_TOK, 64, 64);
        mp.post.cout = make_map(fn, d_out, 2 * DM, S_TOK, 64, 64);
        {
            cuuint64_t dims[4] = {256, 4, NH * 4, NSEG};
            cuuint64_t strides[3] = {512, 2048, NH * 8192};
            cuuint32_t box[4] = {256, 2, 4, 2};
            cuuint32_t es[4] = {1, 1, 1, 1};
            fn(&mp.post.cq, CU_TENSOR_MAP_DATA_TYPE_BFLOAT16, 4, p_qx, dims, strides, box, es,
               CU_TENSOR_MAP_INTERLEAVE_NONE, CU_TENSOR_MAP_SWIZZLE_NONE, CU_TENSOR_MAP_L2_PROMOTION_NONE, CU_TENSOR_MAP_FLOAT_OOB_FILL_NONE);
        }
        {
            int runs[48] = {K_QH, 0, 2, K_Q, 1, 7, K_B1, 0, 8, K_A4, 0, 4, K_B2, 0, 32, K_A4, 4, 2, K_B3, 0, 4, K_A3, 12, 2, K_B3, 4, 4,
                            K_SK, 14, 1, K_SN, 30, 2, -1};
            int nlate = 9;
            const int per[9] = {32, 24, 8, 8, 32, 8, 8 * P_SPLIT, 1, 8 * P_SPLIT};
            int n = 0, id = 0;
            for (; runs[3 * n] >= 0; n++) {
                mp.post.list.run[n] = make_int4(runs[3 * n], runs[3 * n + 1], id, id + runs[3 * n + 2] * per[runs[3 * n]]);
                id = mp.post.list.run[n].w;
            }
            mp.post.list.n = n;
            mp.post.list.late = mp.post.list.run[nlate].z;
            int dev = 0, nsm = 132;
            cudaGetDevice(&dev);
            cudaDeviceGetAttribute(&nsm, cudaDevAttrMultiProcessorCount, dev);
            mp.post.list.nworker = nsm > 96 ? nsm : 97;
        }
        {
            cuuint64_t dims[4] = {DM, 3, 2, S_TOK / 2};
            cuuint64_t strides[3] = {DM * 2, 3 * DM * 2, 3 * DM * 4};
            cuuint32_t box[4] = {64, 3, 1, 40};
            cuuint32_t es[4] = {1, 1, 1, 1};
            fn(&mp.post.b40, CU_TENSOR_MAP_DATA_TYPE_BFLOAT16, 4, p_bqkv, dims, strides, box, es,
               CU_TENSOR_MAP_INTERLEAVE_NONE, CU_TENSOR_MAP_SWIZZLE_128B, CU_TENSOR_MAP_L2_PROMOTION_L2_256B, CU_TENSOR_MAP_FLOAT_OOB_FILL_NONE);
        }
        mp.wk16 = make_map(fn, A_Wk, HD, DM, 64, 64);
        mp.wv16 = make_map(fn, A_Wv, HD, DM, 64, 64);
        mp.wo128 = make_wo_map(fn, A_Wo, HD, 4);
        for (int i = 0; i < 2; i++) {
            cuuint64_t dims[3] = {64, S_TOK, DM / 64};
            cuuint64_t strides[2] = {DM * 2, 128};
            cuuint32_t box[3] = {32, 32, 2u - i};
            cuuint32_t es[3] = {1, 1, 1};
            fn(&mp.x32.m[i], CU_TENSOR_MAP_DATA_TYPE_BFLOAT16, 3, const_cast<bf16*>(A_x), dims, strides, box, es,
               CU_TENSOR_MAP_INTERLEAVE_NONE, CU_TENSOR_MAP_SWIZZLE_64B, CU_TENSOR_MAP_L2_PROMOTION_L2_128B, CU_TENSOR_MAP_FLOAT_OOB_FILL_NONE);
        }
        for (int i = 0; i < 10; i++) cached[i] = cur[i];
    }

    cudaStream_t st = cudaStreamPerThread;
    int4 tq = make_int4(100, 200, 700, 60), tk = make_int4(50, 300, 800, 40);
    int2 t0 = make_int2(13000, 16000);
    cudaLaunchConfig_t cfg = {};
    cfg.gridDim = dim3(96); cfg.blockDim = dim3(384); cfg.dynamicSmemBytes = R_SMEM; cfg.stream = st;
    cudaLaunchAttribute at[1];
    at[0].id = cudaLaunchAttributeClusterDimension;
    at[0].val.clusterDim.x = 3; at[0].val.clusterDim.y = 1; at[0].val.clusterDim.z = 1;
    cfg.attrs = at; cfg.numAttrs = 1;
    cudaLaunchKernelEx(&cfg, k_rec, mp.post, mp.wk16, mp.wv16, mp.wo128, mp.x32, A_mem, A_x, tq, tk, t0, 1);
    cfg.gridDim = dim3(mp.post.list.nworker - 96);
    at[0].id = cudaLaunchAttributeProgrammaticStreamSerialization;
    at[0].val.programmaticStreamSerializationAllowed = 1;
    cudaLaunchKernelEx(&cfg, k_rec, mp.post, mp.wk16, mp.wv16, mp.wo128, mp.x32, A_mem, A_x, tq, tk, t0, 0);
}
```

```cpp
#include <cuda_runtime.h>
#include <cuda_bf16.h>
#include <cuda.h>
#include <stdint.h>

typedef __nv_bfloat16 bf16;

constexpr int S_TOK = 2048;
constexpr int DM    = 1024;
constexpr int NH    = 32;
constexpr int DH    = 128;
constexpr int NSEG  = 64;
constexpr int HD    = NH * DH;

__device__ __align__(1024) bf16 g_qx[NSEG * NH * 4 * DH * 8];
__device__ __align__(1024) bf16 g_ox[S_TOK * HD];
__device__ __align__(1024) bf16 g_bqkv[S_TOK * 3 * DM];
__device__ __align__(1024) bf16 g_bo[S_TOK * DM];
__device__ __align__(1024) uint8_t g_acc[192 * 1024];

#define EV(cond, s, k) do {} while (0)
#define EVCAL(s) do {} while (0)

constexpr int P_NSK = 4;
__device__ unsigned g_epoch, g_qctr, g_done, g_zero;
enum { C_B1 = 0, C_B2 = 8, C_Q = 16, C_QH = 24, C_NONE = 31 };
__device__ unsigned g_cnt[32], g_prog[32], g_cnt_sk[P_NSK * 32];
constexpr int P_SPLIT = 4;
__device__ __align__(1024) uint4 g_skp[P_NSK * 8 * P_SPLIT * 2 * 8 * 128];
#define TLOG(i, k, v) do {} while (0)

#define DEVI __device__ __forceinline__

DEVI uint32_t opaque(uint32_t v) { uint32_t r; asm volatile("mov.u32 %0, %1;" : "=r"(r) : "r"(v)); return r; }
DEVI uint32_t smem_u32(const void* p) { return (uint32_t)__cvta_generic_to_shared(p); }

constexpr int SPIN_LIMIT = 1 << 22;
#define MBAR_HINT_NS 20000u
constexpr int SPIN_LIMIT_MBAR = 1 << 17;

DEVI void mbar_init(uint32_t bar, uint32_t cnt) { asm volatile("mbarrier.init.shared::cta.b64 [%0], %1;" :: "r"(bar), "r"(cnt)); }
DEVI void mbar_expect_tx(uint32_t bar, uint32_t bytes) {
    asm volatile("mbarrier.arrive.expect_tx.shared::cta.b64 _, [%0], %1;" :: "r"(bar), "r"(bytes) : "memory");
}
DEVI void mbar_arrive(uint32_t bar) { asm volatile("mbarrier.arrive.shared::cta.b64 _, [%0];" :: "r"(bar) : "memory"); }
DEVI bool mbar_try(uint32_t bar, uint32_t parity) {
    uint32_t ok;
    asm volatile("{.reg .pred p; mbarrier.try_wait.parity.shared::cta.b64 p, [%1], %2; selp.u32 %0, 1, 0, p;}"
                 : "=r"(ok) : "r"(bar), "r"(parity) : "memory");
    return ok;
}
DEVI bool mbar_try_hint(uint32_t bar, uint32_t parity) {
    uint32_t ok;
    asm volatile("{.reg .pred p; mbarrier.try_wait.parity.shared::cta.b64 p, [%1], %2, %3; selp.u32 %0, 1, 0, p;}"
                 : "=r"(ok) : "r"(bar), "r"(parity), "r"(MBAR_HINT_NS) : "memory");
    return ok;
}
DEVI bool mbar_test(uint32_t bar, uint32_t parity) {
    uint32_t ok;
    asm volatile("{.reg .pred p; mbarrier.test_wait.parity.shared::cta.b64 p, [%1], %2; selp.u32 %0, 1, 0, p;}"
                 : "=r"(ok) : "r"(bar), "r"(parity) : "memory");
    return ok;
}
DEVI void mbar_wait(uint32_t bar, uint32_t parity) {
    int n = 0;
    while (!mbar_try(bar, parity)) { if (++n > SPIN_LIMIT) __trap(); }
}
DEVI void mbar_wait_sleepy(uint32_t bar, uint32_t parity) {
    int n = 0;
    while (!mbar_try_hint(bar, parity)) { if (++n > SPIN_LIMIT_MBAR) __trap(); }
}
DEVI void fence_mbar_init() { asm volatile("fence.mbarrier_init.release.cluster;" ::: "memory"); }
DEVI void fence_proxy_async() { asm volatile("fence.proxy.async.shared::cta;" ::: "memory"); }
DEVI bool elect_one() {
    uint32_t e; asm volatile("{.reg .pred p; elect.sync _|p, 0xffffffff; selp.u32 %0, 1, 0, p;}" : "=r"(e)); return e;
}
DEVI void fence_proxy_global() { asm volatile("fence.proxy.async.global;" ::: "memory"); }
DEVI void cluster_wait() { asm volatile("barrier.cluster.wait.acquire.aligned;" ::: "memory"); }
DEVI void nbar_sync(int id, int n) { asm volatile("bar.sync %0, %1;" :: "r"(id), "r"(n) : "memory"); }
DEVI void nbar_arrive(int id, int n) { asm volatile("bar.arrive %0, %1;" :: "r"(id), "r"(n) : "memory"); }

DEVI void tma_load_2d(uint32_t dst, const CUtensorMap* map, int x, int y, uint32_t bar) {
    asm volatile("cp.async.bulk.tensor.2d.shared::cluster.global.mbarrier::complete_tx::bytes [%0], [%1, {%3, %4}], [%2];"
                 :: "r"(dst), "l"(map), "r"(bar), "r"(x), "r"(y) : "memory");
}
DEVI void tma_load_3d(uint32_t dst, const CUtensorMap* map, int x, int y, int z, uint32_t bar) {
    asm volatile("cp.async.bulk.tensor.3d.shared::cluster.global.mbarrier::complete_tx::bytes [%0], [%1, {%3, %4, %5}], [%2];"
                 :: "r"(dst), "l"(map), "r"(bar), "r"(x), "r"(y), "r"(z) : "memory");
}
DEVI void tma_load_wo(uint32_t dst, const CUtensorMap* map, int col, int k32, uint32_t bar) {
    asm volatile("cp.async.bulk.tensor.5d.shared::cluster.global.mbarrier::complete_tx::bytes [%0], [%1, {%3, %5, %5, %5, %4}], [%2];"
                 :: "r"(dst), "l"(map), "r"(bar), "r"(col), "r"(k32), "r"(0) : "memory");
}
DEVI void tma_store_2d(const CUtensorMap* map, uint32_t src, int x, int y) {
    asm volatile("cp.async.bulk.tensor.2d.global.shared::cta.bulk_group [%0, {%2, %3}], [%1];"
                 :: "l"(map), "r"(src), "r"(x), "r"(y) : "memory");
}
DEVI void bulk_load(uint32_t dst, const void* src, uint32_t bytes, uint32_t bar) {
    asm volatile("cp.async.bulk.shared::cluster.global.mbarrier::complete_tx::bytes [%0], [%1], %2, [%3];"
                 :: "r"(dst), "l"(src), "r"(bytes), "r"(bar) : "memory");
}
DEVI void bulk_copy_s2c(uint32_t dst_cluster, uint32_t src, uint32_t bytes, uint32_t bar_cluster) {
    asm volatile("cp.async.bulk.shared::cluster.shared::cta.mbarrier::complete_tx::bytes [%0], [%1], %2, [%3];"
                 :: "r"(dst_cluster), "r"(src), "r"(bytes), "r"(bar_cluster) : "memory");
}
DEVI void bulk_wait_read() { asm volatile("cp.async.bulk.wait_group.read 0;" ::: "memory"); }
DEVI void mbar_arrive_remote(uint32_t bar_cluster) {
    asm volatile("mbarrier.arrive.shared::cluster.b64 _, [%0];" :: "r"(bar_cluster) : "memory");
}
DEVI void l2_prefetch(const void* p, uint32_t bytes) {
    asm volatile("cp.async.bulk.prefetch.L2.global [%0], %1;" :: "l"(p), "r"(bytes) : "memory");
}
DEVI void bulk_commit() { asm volatile("cp.async.bulk.commit_group;" ::: "memory"); }
DEVI void bulk_wait_all() { asm volatile("cp.async.bulk.wait_group 0;" ::: "memory"); }

DEVI void wg_fence() { asm volatile("wgmma.fence.sync.aligned;" ::: "memory"); }
DEVI void wg_commit() { asm volatile("wgmma.commit_group.sync.aligned;" ::: "memory"); }
template <int N> DEVI void wg_wait() { asm volatile("wgmma.wait_group.sync.aligned %0;" :: "n"(N) : "memory"); }

template <int R> DEVI void reg_dec() { asm volatile("setmaxnreg.dec.sync.aligned.u32 %0;" :: "n"(R)); }
template <int R> DEVI void reg_inc() { asm volatile("setmaxnreg.inc.sync.aligned.u32 %0;" :: "n"(R)); }

DEVI uint64_t mk_desc(uint32_t addr, uint32_t lbo, uint32_t sbo, uint32_t sw) {
    return (uint64_t)((addr & 0x3FFFF) >> 4) | ((uint64_t)(lbo >> 4) << 16) | ((uint64_t)(sbo >> 4) << 32) | ((uint64_t)sw << 62);
}

constexpr uint32_t DHI_SW128 = (1024u >> 4) | (1u << 30);
constexpr uint32_t DHI_SW64  = (512u >> 4) | (2u << 30);
constexpr uint32_t DHI_NONE  = (128u >> 4);

template <int TB, int SCALE_D>
DEVI void wgmma_n8_ss(float* d, uint32_t alo, uint32_t blo) {
    asm volatile("{.reg .b64 da, db; mov.b64 da, {%4, %6}; mov.b64 db, {%5, %7};\n"
                 "wgmma.mma_async.sync.aligned.m64n8k16.f32.bf16.bf16 {%0,%1,%2,%3}, da, db, %8, 1, 1, 1, %9;}"
                 : "+f"(d[0]), "+f"(d[1]), "+f"(d[2]), "+f"(d[3])
                 : "r"(alo), "r"(blo), "n"(DHI_SW128), "n"(DHI_NONE), "n"(SCALE_D), "n"(TB));
}

template <int TB>
DEVI void wgmma_n8_ss_first(float* d, uint32_t alo, uint32_t blo) {
    asm volatile("{.reg .b64 da, db; mov.b64 da, {%4, %6}; mov.b64 db, {%5, %7};\n"
                 "wgmma.mma_async.sync.aligned.m64n8k16.f32.bf16.bf16 {%0,%1,%2,%3}, da, db, 0, 1, 1, 1, %8;}"
                 : "=f"(d[0]), "=f"(d[1]), "=f"(d[2]), "=f"(d[3])
                 : "r"(alo), "r"(blo), "n"(DHI_SW128), "n"(DHI_NONE), "n"(TB));
}
DEVI void wgmma_n32_rs_first(float* d, const uint32_t* a, uint32_t blo) {
    asm volatile("{.reg .b64 db; mov.b64 db, {%20, %21};\n"
                 "wgmma.mma_async.sync.aligned.m64n32k16.f32.bf16.bf16 {%0,%1,%2,%3,%4,%5,%6,%7,%8,%9,%10,%11,%12,%13,%14,%15}, "
                 "{%16,%17,%18,%19}, db, 0, 1, 1, 0;}"
                 : "=f"(d[0]), "=f"(d[1]), "=f"(d[2]), "=f"(d[3]), "=f"(d[4]), "=f"(d[5]), "=f"(d[6]), "=f"(d[7]),
                   "=f"(d[8]), "=f"(d[9]), "=f"(d[10]), "=f"(d[11]), "=f"(d[12]), "=f"(d[13]), "=f"(d[14]), "=f"(d[15])
                 : "r"(a[0]), "r"(a[1]), "r"(a[2]), "r"(a[3]), "r"(blo), "n"(DHI_SW64));
}
template <int N> DEVI void reg_fence(float* d) {
#pragma unroll
    for (int i = 0; i < N; i++) asm volatile("" : "+f"(d[i]) :: "memory");
}
DEVI void wgmma_n32_rs(float* d, const uint32_t* a, uint32_t blo) {
    asm volatile("{.reg .b64 db; mov.b64 db, {%20, %21};\n"
                 "wgmma.mma_async.sync.aligned.m64n32k16.f32.bf16.bf16 {%0,%1,%2,%3,%4,%5,%6,%7,%8,%9,%10,%11,%12,%13,%14,%15}, "
                 "{%16,%17,%18,%19}, db, 1, 1, 1, 0;}"
                 : "+f"(d[0]), "+f"(d[1]), "+f"(d[2]), "+f"(d[3]), "+f"(d[4]), "+f"(d[5]), "+f"(d[6]), "+f"(d[7]),
                   "+f"(d[8]), "+f"(d[9]), "+f"(d[10]), "+f"(d[11]), "+f"(d[12]), "+f"(d[13]), "+f"(d[14]), "+f"(d[15])
                 : "r"(a[0]), "r"(a[1]), "r"(a[2]), "r"(a[3]), "r"(blo), "n"(DHI_SW64));
}
DEVI void wgmma_n32_ss(float* d, uint32_t alo, uint32_t blo) {
    asm volatile("{.reg .b64 da, db; mov.b64 da, {%16, %18}; mov.b64 db, {%17, %19};\n"
                 "wgmma.mma_async.sync.aligned.m64n32k16.f32.bf16.bf16 {%0,%1,%2,%3,%4,%5,%6,%7,%8,%9,%10,%11,%12,%13,%14,%15}, "
                 "da, db, 1, 1, 1, 1, 0;}"
                 : "+f"(d[0]), "+f"(d[1]), "+f"(d[2]), "+f"(d[3]), "+f"(d[4]), "+f"(d[5]), "+f"(d[6]), "+f"(d[7]),
                   "+f"(d[8]), "+f"(d[9]), "+f"(d[10]), "+f"(d[11]), "+f"(d[12]), "+f"(d[13]), "+f"(d[14]), "+f"(d[15])
                 : "r"(alo), "r"(blo), "n"(DHI_SW128), "n"(DHI_SW64));
}

template <bool FIRST>
DEVI void wgmma_n256_ss(float* d, uint64_t a, uint64_t b) {
    if (FIRST)
        asm volatile("wgmma.mma_async.sync.aligned.m64n256k16.f32.bf16.bf16 {%0,%1,%2,%3,%4,%5,%6,%7,%8,%9,%10,%11,%12,%13,%14,%15,%16,%17,%18,%19,%20,%21,%22,%23,%24,%25,%26,%27,%28,%29,%30,%31,%32,%33,%34,%35,%36,%37,%38,%39,%40,%41,%42,%43,%44,%45,%46,%47,%48,%49,%50,%51,%52,%53,%54,%55,%56,%57,%58,%59,%60,%61,%62,%63,%64,%65,%66,%67,%68,%69,%70,%71,%72,%73,%74,%75,%76,%77,%78,%79,%80,%81,%82,%83,%84,%85,%86,%87,%88,%89,%90,%91,%92,%93,%94,%95,%96,%97,%98,%99,%100,%101,%102,%103,%104,%105,%106,%107,%108,%109,%110,%111,%112,%113,%114,%115,%116,%117,%118,%119,%120,%121,%122,%123,%124,%125,%126,%127}, %128, %129, 0, 1, 1, 1, 0;"
            : "=f"(d[0]), "=f"(d[1]), "=f"(d[2]), "=f"(d[3]), "=f"(d[4]), "=f"(d[5]), "=f"(d[6]), "=f"(d[7]), "=f"(d[8]), "=f"(d[9]), "=f"(d[10]), "=f"(d[11]), "=f"(d[12]), "=f"(d[13]), "=f"(d[14]), "=f"(d[15]), "=f"(d[16]), "=f"(d[17]), "=f"(d[18]), "=f"(d[19]), "=f"(d[20]), "=f"(d[21]), "=f"(d[22]), "=f"(d[23]), "=f"(d[24]), "=f"(d[25]), "=f"(d[26]), "=f"(d[27]), "=f"(d[28]), "=f"(d[29]), "=f"(d[30]), "=f"(d[31]), "=f"(d[32]), "=f"(d[33]), "=f"(d[34]), "=f"(d[35]), "=f"(d[36]), "=f"(d[37]), "=f"(d[38]), "=f"(d[39]), "=f"(d[40]), "=f"(d[41]), "=f"(d[42]), "=f"(d[43]), "=f"(d[44]), "=f"(d[45]), "=f"(d[46]), "=f"(d[47]), "=f"(d[48]), "=f"(d[49]), "=f"(d[50]), "=f"(d[51]), "=f"(d[52]), "=f"(d[53]), "=f"(d[54]), "=f"(d[55]), "=f"(d[56]), "=f"(d[57]), "=f"(d[58]), "=f"(d[59]), "=f"(d[60]), "=f"(d[61]), "=f"(d[62]), "=f"(d[63]), "=f"(d[64]), "=f"(d[65]), "=f"(d[66]), "=f"(d[67]), "=f"(d[68]), "=f"(d[69]), "=f"(d[70]), "=f"(d[71]), "=f"(d[72]), "=f"(d[73]), "=f"(d[74]), "=f"(d[75]), "=f"(d[76]), "=f"(d[77]), "=f"(d[78]), "=f"(d[79]), "=f"(d[80]), "=f"(d[81]), "=f"(d[82]), "=f"(d[83]), "=f"(d[84]), "=f"(d[85]), "=f"(d[86]), "=f"(d[87]), "=f"(d[88]), "=f"(d[89]), "=f"(d[90]), "=f"(d[91]), "=f"(d[92]), "=f"(d[93]), "=f"(d[94]), "=f"(d[95]), "=f"(d[96]), "=f"(d[97]), "=f"(d[98]), "=f"(d[99]), "=f"(d[100]), "=f"(d[101]), "=f"(d[102]), "=f"(d[103]), "=f"(d[104]), "=f"(d[105]), "=f"(d[106]), "=f"(d[107]), "=f"(d[108]), "=f"(d[109]), "=f"(d[110]), "=f"(d[111]), "=f"(d[112]), "=f"(d[113]), "=f"(d[114]), "=f"(d[115]), "=f"(d[116]), "=f"(d[117]), "=f"(d[118]), "=f"(d[119]), "=f"(d[120]), "=f"(d[121]), "=f"(d[122]), "=f"(d[123]), "=f"(d[124]), "=f"(d[125]), "=f"(d[126]), "=f"(d[127]) : "l"(a), "l"(b));
    else
        asm volatile("wgmma.mma_async.sync.aligned.m64n256k16.f32.bf16.bf16 {%0,%1,%2,%3,%4,%5,%6,%7,%8,%9,%10,%11,%12,%13,%14,%15,%16,%17,%18,%19,%20,%21,%22,%23,%24,%25,%26,%27,%28,%29,%30,%31,%32,%33,%34,%35,%36,%37,%38,%39,%40,%41,%42,%43,%44,%45,%46,%47,%48,%49,%50,%51,%52,%53,%54,%55,%56,%57,%58,%59,%60,%61,%62,%63,%64,%65,%66,%67,%68,%69,%70,%71,%72,%73,%74,%75,%76,%77,%78,%79,%80,%81,%82,%83,%84,%85,%86,%87,%88,%89,%90,%91,%92,%93,%94,%95,%96,%97,%98,%99,%100,%101,%102,%103,%104,%105,%106,%107,%108,%109,%110,%111,%112,%113,%114,%115,%116,%117,%118,%119,%120,%121,%122,%123,%124,%125,%126,%127}, %128, %129, 1, 1, 1, 1, 0;"
            : "+f"(d[0]), "+f"(d[1]), "+f"(d[2]), "+f"(d[3]), "+f"(d[4]), "+f"(d[5]), "+f"(d[6]), "+f"(d[7]), "+f"(d[8]), "+f"(d[9]), "+f"(d[10]), "+f"(d[11]), "+f"(d[12]), "+f"(d[13]), "+f"(d[14]), "+f"(d[15]), "+f"(d[16]), "+f"(d[17]), "+f"(d[18]), "+f"(d[19]), "+f"(d[20]), "+f"(d[21]), "+f"(d[22]), "+f"(d[23]), "+f"(d[24]), "+f"(d[25]), "+f"(d[26]), "+f"(d[27]), "+f"(d[28]), "+f"(d[29]), "+f"(d[30]), "+f"(d[31]), "+f"(d[32]), "+f"(d[33]), "+f"(d[34]), "+f"(d[35]), "+f"(d[36]), "+f"(d[37]), "+f"(d[38]), "+f"(d[39]), "+f"(d[40]), "+f"(d[41]), "+f"(d[42]), "+f"(d[43]), "+f"(d[44]), "+f"(d[45]), "+f"(d[46]), "+f"(d[47]), "+f"(d[48]), "+f"(d[49]), "+f"(d[50]), "+f"(d[51]), "+f"(d[52]), "+f"(d[53]), "+f"(d[54]), "+f"(d[55]), "+f"(d[56]), "+f"(d[57]), "+f"(d[58]), "+f"(d[59]), "+f"(d[60]), "+f"(d[61]), "+f"(d[62]), "+f"(d[63]), "+f"(d[64]), "+f"(d[65]), "+f"(d[66]), "+f"(d[67]), "+f"(d[68]), "+f"(d[69]), "+f"(d[70]), "+f"(d[71]), "+f"(d[72]), "+f"(d[73]), "+f"(d[74]), "+f"(d[75]), "+f"(d[76]), "+f"(d[77]), "+f"(d[78]), "+f"(d[79]), "+f"(d[80]), "+f"(d[81]), "+f"(d[82]), "+f"(d[83]), "+f"(d[84]), "+f"(d[85]), "+f"(d[86]), "+f"(d[87]), "+f"(d[88]), "+f"(d[89]), "+f"(d[90]), "+f"(d[91]), "+f"(d[92]), "+f"(d[93]), "+f"(d[94]), "+f"(d[95]), "+f"(d[96]), "+f"(d[97]), "+f"(d[98]), "+f"(d[99]), "+f"(d[100]), "+f"(d[101]), "+f"(d[102]), "+f"(d[103]), "+f"(d[104]), "+f"(d[105]), "+f"(d[106]), "+f"(d[107]), "+f"(d[108]), "+f"(d[109]), "+f"(d[110]), "+f"(d[111]), "+f"(d[112]), "+f"(d[113]), "+f"(d[114]), "+f"(d[115]), "+f"(d[116]), "+f"(d[117]), "+f"(d[118]), "+f"(d[119]), "+f"(d[120]), "+f"(d[121]), "+f"(d[122]), "+f"(d[123]), "+f"(d[124]), "+f"(d[125]), "+f"(d[126]), "+f"(d[127]) : "l"(a), "l"(b));
}
template <bool FIRST>
DEVI void wgmma_n128_ss(float* d, uint64_t a, uint64_t b) {
    if (FIRST)
        asm volatile("wgmma.mma_async.sync.aligned.m64n128k16.f32.bf16.bf16 {%0,%1,%2,%3,%4,%5,%6,%7,%8,%9,%10,%11,%12,%13,%14,%15,%16,%17,%18,%19,%20,%21,%22,%23,%24,%25,%26,%27,%28,%29,%30,%31,%32,%33,%34,%35,%36,%37,%38,%39,%40,%41,%42,%43,%44,%45,%46,%47,%48,%49,%50,%51,%52,%53,%54,%55,%56,%57,%58,%59,%60,%61,%62,%63}, %64, %65, 0, 1, 1, 1, 0;"
            : "=f"(d[0]), "=f"(d[1]), "=f"(d[2]), "=f"(d[3]), "=f"(d[4]), "=f"(d[5]), "=f"(d[6]), "=f"(d[7]), "=f"(d[8]), "=f"(d[9]), "=f"(d[10]), "=f"(d[11]), "=f"(d[12]), "=f"(d[13]), "=f"(d[14]), "=f"(d[15]), "=f"(d[16]), "=f"(d[17]), "=f"(d[18]), "=f"(d[19]), "=f"(d[20]), "=f"(d[21]), "=f"(d[22]), "=f"(d[23]), "=f"(d[24]), "=f"(d[25]), "=f"(d[26]), "=f"(d[27]), "=f"(d[28]), "=f"(d[29]), "=f"(d[30]), "=f"(d[31]), "=f"(d[32]), "=f"(d[33]), "=f"(d[34]), "=f"(d[35]), "=f"(d[36]), "=f"(d[37]), "=f"(d[38]), "=f"(d[39]), "=f"(d[40]), "=f"(d[41]), "=f"(d[42]), "=f"(d[43]), "=f"(d[44]), "=f"(d[45]), "=f"(d[46]), "=f"(d[47]), "=f"(d[48]), "=f"(d[49]), "=f"(d[50]), "=f"(d[51]), "=f"(d[52]), "=f"(d[53]), "=f"(d[54]), "=f"(d[55]), "=f"(d[56]), "=f"(d[57]), "=f"(d[58]), "=f"(d[59]), "=f"(d[60]), "=f"(d[61]), "=f"(d[62]), "=f"(d[63]) : "l"(a), "l"(b));
    else
        asm volatile("wgmma.mma_async.sync.aligned.m64n128k16.f32.bf16.bf16 {%0,%1,%2,%3,%4,%5,%6,%7,%8,%9,%10,%11,%12,%13,%14,%15,%16,%17,%18,%19,%20,%21,%22,%23,%24,%25,%26,%27,%28,%29,%30,%31,%32,%33,%34,%35,%36,%37,%38,%39,%40,%41,%42,%43,%44,%45,%46,%47,%48,%49,%50,%51,%52,%53,%54,%55,%56,%57,%58,%59,%60,%61,%62,%63}, %64, %65, 1, 1, 1, 1, 0;"
            : "+f"(d[0]), "+f"(d[1]), "+f"(d[2]), "+f"(d[3]), "+f"(d[4]), "+f"(d[5]), "+f"(d[6]), "+f"(d[7]), "+f"(d[8]), "+f"(d[9]), "+f"(d[10]), "+f"(d[11]), "+f"(d[12]), "+f"(d[13]), "+f"(d[14]), "+f"(d[15]), "+f"(d[16]), "+f"(d[17]), "+f"(d[18]), "+f"(d[19]), "+f"(d[20]), "+f"(d[21]), "+f"(d[22]), "+f"(d[23]), "+f"(d[24]), "+f"(d[25]), "+f"(d[26]), "+f"(d[27]), "+f"(d[28]), "+f"(d[29]), "+f"(d[30]), "+f"(d[31]), "+f"(d[32]), "+f"(d[33]), "+f"(d[34]), "+f"(d[35]), "+f"(d[36]), "+f"(d[37]), "+f"(d[38]), "+f"(d[39]), "+f"(d[40]), "+f"(d[41]), "+f"(d[42]), "+f"(d[43]), "+f"(d[44]), "+f"(d[45]), "+f"(d[46]), "+f"(d[47]), "+f"(d[48]), "+f"(d[49]), "+f"(d[50]), "+f"(d[51]), "+f"(d[52]), "+f"(d[53]), "+f"(d[54]), "+f"(d[55]), "+f"(d[56]), "+f"(d[57]), "+f"(d[58]), "+f"(d[59]), "+f"(d[60]), "+f"(d[61]), "+f"(d[62]), "+f"(d[63]) : "l"(a), "l"(b));
}

template <bool FIRST>
DEVI void wgmma_n64_ss(float* d, uint64_t a, uint64_t b) {
    if (FIRST)
        asm volatile("wgmma.mma_async.sync.aligned.m64n64k16.f32.bf16.bf16 {%0,%1,%2,%3,%4,%5,%6,%7,%8,%9,%10,%11,%12,%13,%14,%15,%16,%17,%18,%19,%20,%21,%22,%23,%24,%25,%26,%27,%28,%29,%30,%31}, %32, %33, 0, 1, 1, 1, 0;"
            : "=f"(d[0]), "=f"(d[1]), "=f"(d[2]), "=f"(d[3]), "=f"(d[4]), "=f"(d[5]), "=f"(d[6]), "=f"(d[7]), "=f"(d[8]), "=f"(d[9]), "=f"(d[10]), "=f"(d[11]), "=f"(d[12]), "=f"(d[13]), "=f"(d[14]), "=f"(d[15]), "=f"(d[16]), "=f"(d[17]), "=f"(d[18]), "=f"(d[19]), "=f"(d[20]), "=f"(d[21]), "=f"(d[22]), "=f"(d[23]), "=f"(d[24]), "=f"(d[25]), "=f"(d[26]), "=f"(d[27]), "=f"(d[28]), "=f"(d[29]), "=f"(d[30]), "=f"(d[31]) : "l"(a), "l"(b));
    else
        asm volatile("wgmma.mma_async.sync.aligned.m64n64k16.f32.bf16.bf16 {%0,%1,%2,%3,%4,%5,%6,%7,%8,%9,%10,%11,%12,%13,%14,%15,%16,%17,%18,%19,%20,%21,%22,%23,%24,%25,%26,%27,%28,%29,%30,%31}, %32, %33, 1, 1, 1, 1, 0;"
            : "+f"(d[0]), "+f"(d[1]), "+f"(d[2]), "+f"(d[3]), "+f"(d[4]), "+f"(d[5]), "+f"(d[6]), "+f"(d[7]), "+f"(d[8]), "+f"(d[9]), "+f"(d[10]), "+f"(d[11]), "+f"(d[12]), "+f"(d[13]), "+f"(d[14]), "+f"(d[15]), "+f"(d[16]), "+f"(d[17]), "+f"(d[18]), "+f"(d[19]), "+f"(d[20]), "+f"(d[21]), "+f"(d[22]), "+f"(d[23]), "+f"(d[24]), "+f"(d[25]), "+f"(d[26]), "+f"(d[27]), "+f"(d[28]), "+f"(d[29]), "+f"(d[30]), "+f"(d[31]) : "l"(a), "l"(b));
}

DEVI void mma16816(float* d, const uint32_t* a, uint32_t b0, uint32_t b1) {
    asm volatile("mma.sync.aligned.m16n8k16.row.col.f32.bf16.bf16.f32 {%0,%1,%2,%3}, {%4,%5,%6,%7}, {%8,%9}, {%0,%1,%2,%3};"
                 : "+f"(d[0]), "+f"(d[1]), "+f"(d[2]), "+f"(d[3])
                 : "r"(a[0]), "r"(a[1]), "r"(a[2]), "r"(a[3]), "r"(b0), "r"(b1));
}
DEVI void mma1688(float* d, uint32_t a0, uint32_t a1, uint32_t b0) {
    asm volatile("mma.sync.aligned.m16n8k8.row.col.f32.bf16.bf16.f32 {%0,%1,%2,%3}, {%4,%5}, {%6}, {%0,%1,%2,%3};"
                 : "+f"(d[0]), "+f"(d[1]), "+f"(d[2]), "+f"(d[3]) : "r"(a0), "r"(a1), "r"(b0));
}
DEVI void ldsm4(uint32_t* r, uint32_t addr) {
    asm volatile("ldmatrix.sync.aligned.m8n8.x4.shared.b16 {%0,%1,%2,%3}, [%4];"
                 : "=r"(r[0]), "=r"(r[1]), "=r"(r[2]), "=r"(r[3]) : "r"(addr) : "memory");
}
DEVI void ldsm4t(uint32_t* r, uint32_t addr) {
    asm volatile("ldmatrix.sync.aligned.m8n8.x4.trans.shared.b16 {%0,%1,%2,%3}, [%4];"
                 : "=r"(r[0]), "=r"(r[1]), "=r"(r[2]), "=r"(r[3]) : "r"(addr) : "memory");
}
DEVI void stsm4(uint32_t addr, uint32_t r0, uint32_t r1, uint32_t r2, uint32_t r3) {
    asm volatile("stmatrix.sync.aligned.m8n8.x4.shared.b16 [%0], {%1,%2,%3,%4};" :: "r"(addr), "r"(r0), "r"(r1), "r"(r2), "r"(r3) : "memory");
}
DEVI void stsm4t(uint32_t addr, uint32_t r0, uint32_t r1, uint32_t r2, uint32_t r3) {
    asm volatile("stmatrix.sync.aligned.m8n8.x4.trans.shared.b16 [%0], {%1,%2,%3,%4};" :: "r"(addr), "r"(r0), "r"(r1), "r"(r2), "r"(r3) : "memory");
}
DEVI uint32_t pack_bf16(float lo, float hi) {
    uint32_t r; asm("cvt.rn.bf16x2.f32 %0, %1, %2;" : "=r"(r) : "f"(hi), "f"(lo)); return r;
}
DEVI float ex2(float x) { float y; asm("ex2.approx.ftz.f32 %0, %1;" : "=f"(y) : "f"(x)); return y; }

DEVI uint4 ld_rlx4(const void* p) {
    uint4 v;
    asm volatile("ld.relaxed.gpu.global.v4.u32 {%0,%1,%2,%3}, [%4];" : "=r"(v.x), "=r"(v.y), "=r"(v.z), "=r"(v.w) : "l"(p) : "memory");
    return v;
}
DEVI void st_rlx4(void* p, uint32_t a, uint32_t b, uint32_t c, uint32_t d) {
    asm volatile("st.relaxed.gpu.global.v4.u32 [%0], {%1,%2,%3,%4};" :: "l"(p), "r"(a), "r"(b), "r"(c), "r"(d) : "memory");
}
DEVI void sts128(uint32_t addr, uint4 v) {
    asm volatile("st.shared.v4.u32 [%0], {%1,%2,%3,%4};" :: "r"(addr), "r"(v.x), "r"(v.y), "r"(v.z), "r"(v.w) : "memory");
}
DEVI void sts64(uint32_t addr, uint32_t a, uint32_t b) { asm volatile("st.shared.v2.u32 [%0], {%1,%2};" :: "r"(addr), "r"(a), "r"(b) : "memory"); }
DEVI void sts32(uint32_t addr, uint32_t v) { asm volatile("st.shared.u32 [%0], %1;" :: "r"(addr), "r"(v) : "memory"); }
DEVI uint4 lds128(uint32_t addr) {
    uint4 v; asm volatile("ld.shared.v4.u32 {%0,%1,%2,%3}, [%4];" : "=r"(v.x), "=r"(v.y), "=r"(v.z), "=r"(v.w) : "r"(addr) : "memory"); return v;
}
DEVI float2 lds64f(uint32_t addr) {
    float2 v; asm volatile("ld.shared.v2.f32 {%0,%1}, [%2];" : "=f"(v.x), "=f"(v.y) : "r"(addr) : "memory"); return v;
}
DEVI uint32_t lds32(uint32_t addr) { uint32_t v; asm volatile("ld.shared.u32 %0, [%1];" : "=r"(v) : "r"(addr) : "memory"); return v; }
DEVI float rcp_fast(float x) { float y; asm("rcp.approx.ftz.f32 %0, %1;" : "=f"(y) : "f"(x)); return y; }
DEVI uint32_t mapa(uint32_t addr, uint32_t rank) {
    uint32_t r; asm("mapa.shared::cluster.u32 %0, %1, %2;" : "=r"(r) : "r"(addr), "r"(rank)); return r;
}
DEVI void st_async32(uint32_t dst, uint32_t a, uint32_t bar) {
    asm volatile("st.async.weak.shared::cluster.mbarrier::complete_tx::bytes.b32 [%0], %1, [%2];" :: "r"(dst), "r"(a), "r"(bar) : "memory");
}

DEVI void st_async128(uint32_t dst, uint32_t a, uint32_t b, uint32_t c, uint32_t d, uint32_t bar) {
    asm volatile("st.async.weak.shared::cluster.mbarrier::complete_tx::bytes.v4.b32 [%0], {%1,%2,%3,%4}, [%5];"
                 :: "r"(dst), "r"(a), "r"(b), "r"(c), "r"(d), "r"(bar) : "memory");
}

DEVI uint32_t b_addr(uint32_t sb, int row, int which, int chunk) { const int l = 3 * row + which; return sb + l * 128 + ((chunk ^ (l & 7)) * 16); }
DEVI void battn_warp(uint32_t st, uint32_t ebar, int i0, int par, int head, int hh, int mt, int lane) {
    const int gq = lane >> 2, t = lane & 3, r = 16 * mt + (lane & 7), b3 = (lane >> 3) & 1, b4 = lane >> 4;
    uint32_t a[8], k[8], k2[4], v[8], v2[4];
#pragma unroll
    for (int ks = 0; ks < 2; ks++) {
        ldsm4(a + 4 * ks, b_addr(st, 8 + r + b3 * 8, 0, hh * 4 + ks * 2 + b4));
        ldsm4(k + 4 * ks, b_addr(st, r + b4 * 8, 1, hh * 4 + ks * 2 + b3));
    }
    ldsm4(k2, b_addr(st, r + 16, 1, hh * 4 + (lane >> 3)));
#pragma unroll
    for (int n = 0; n < 2; n++) ldsm4t(v + 4 * n, b_addr(st, r + b3 * 8, 2, hh * 4 + 2 * n + b4));
    ldsm4t(v2, b_addr(st, r + 16, 2, hh * 4 + (lane >> 3)));
    float s[3][4];
#pragma unroll
    for (int n = 0; n < 3; n++) { s[n][0] = s[n][1] = s[n][2] = s[n][3] = 0.f; }
#pragma unroll
    for (int ks = 0; ks < 2; ks++) {
        mma16816(s[0], a + 4 * ks, k[4 * ks], k[4 * ks + 1]);
        mma16816(s[1], a + 4 * ks, k[4 * ks + 2], k[4 * ks + 3]);
        mma16816(s[2], a + 4 * ks, k2[2 * ks], k2[2 * ks + 1]);
    }
    const bool ex = i0 + 16 * mt > 0;
    float x[4], y[4];
#pragma unroll
    for (int c = 0; c < 2; c++) {
        const bool low = 2 * t + c <= gq;
        x[c] = !low && ex ? s[0][c] : -INFINITY; x[2 + c] = low ? s[1][c] : -INFINITY;
        y[c] = !low ? s[1][2 + c] : -INFINITY;   y[2 + c] = low ? s[2][2 + c] : -INFINITY;
    }
    float m0 = fmaxf(fmaxf(x[0], x[1]), fmaxf(x[2], x[3])), m1 = fmaxf(fmaxf(y[0], y[1]), fmaxf(y[2], y[3]));
    m0 = fmaxf(fmaxf(m0, __shfl_xor_sync(0xffffffffu, m0, 1)), fmaxf(__shfl_xor_sync(0xffffffffu, m0, 2), __shfl_xor_sync(0xffffffffu, m0, 3)));
    m1 = fmaxf(fmaxf(m1, __shfl_xor_sync(0xffffffffu, m1, 1)), fmaxf(__shfl_xor_sync(0xffffffffu, m1, 2), __shfl_xor_sync(0xffffffffu, m1, 3)));
    constexpr float C = 0.17677669529663687f * 1.4426950408889634f;
    m0 *= -C; m1 *= -C;
    const uint32_t p0[4] = {pack_bf16(ex2(fmaf(x[0], C, m0)), ex2(fmaf(x[1], C, m0))), 0u,
                            pack_bf16(ex2(fmaf(x[2], C, m0)), ex2(fmaf(x[3], C, m0))), pack_bf16(ex2(fmaf(y[0], C, m1)), ex2(fmaf(y[1], C, m1)))};
    const uint32_t p1 = pack_bf16(ex2(fmaf(y[2], C, m1)), ex2(fmaf(y[3], C, m1)));
    float o[4][4], l[4] = {0.f, 0.f, 0.f, 0.f};
#pragma unroll
    for (int n = 0; n < 4; n++) { o[n][0] = o[n][1] = o[n][2] = o[n][3] = 0.f; }
    mma16816(l, p0, 0x3F803F80u, 0x3F803F80u);
#pragma unroll
    for (int n = 0; n < 4; n++) mma16816(o[n], p0, v[2 * n], v[2 * n + 1]);
    mma1688(l, 0u, p1, 0x3F803F80u);
#pragma unroll
    for (int n = 0; n < 4; n++) mma1688(o[n], 0u, p1, v2[n]);
    if (lane == 0) mbar_arrive(ebar);
    const float i0f = rcp_fast(l[0]), i1f = rcp_fast(l[2]);
    uint4* dst = (uint4*)(g_bo + (uint32_t)((2 * (i0 + 16 * mt + gq) + par) * DM + head * 32 + t * 8));
    dst[0] = make_uint4(pack_bf16(o[0][0] * i0f, o[0][1] * i0f), pack_bf16(o[1][0] * i0f, o[1][1] * i0f),
                        pack_bf16(o[2][0] * i0f, o[2][1] * i0f), pack_bf16(o[3][0] * i0f, o[3][1] * i0f));
    dst[16 * DM / 8] = make_uint4(pack_bf16(o[0][2] * i1f, o[0][3] * i1f), pack_bf16(o[1][2] * i1f, o[1][3] * i1f),
                                  pack_bf16(o[2][2] * i1f, o[2][3] * i1f), pack_bf16(o[3][2] * i1f, o[3][3] * i1f));
}

constexpr float SCALE_LOG2E = 0.08838834764831845f * 1.4426950408889634f;

constexpr int P_UNITS = 12, P_STAGES = 6;
constexpr int PS_STG = P_UNITS * 16384;
constexpr int P_SMEM = 232448;
constexpr int PS_BAR = P_SMEM - 256;
static_assert(PS_STG + 32768 <= PS_BAR, "smem");
enum { K_Q, K_B1, K_B3, K_A4, K_QH, K_A3, K_SK, K_B2, K_SN, K_END };
struct PList { int n, nworker, late; int4 run[16]; };
struct PTask { int kind, a, b, c, id; };
DEVI PTask p_decode(const PList& pl, int id) {
    int i = pl.n - 1;
    if (id >= pl.run[i].w) return {K_END, 0, 0, 0, id};
    while (id < pl.run[i].z) i--;
    const int4 r = pl.run[i];
    const int j = id - r.z;
    if (r.x == K_Q || r.x == K_QH) return {r.x, j & 31, r.y + (j >> 5), 0, id};
    if (r.x == K_B1) return {r.x, j % 24, r.y + j / 24, 0, id};
    if (r.x == K_B2) return {r.x, 0, r.y + j, 0, id};
    if (r.x == K_SK || r.x == K_SN) return {r.x, (j / P_SPLIT) & 7, r.y + j / (8 * P_SPLIT), j % P_SPLIT, id};
    return {r.x, j & 7, r.y + (j >> 3), 0, id};
}
DEVI void wait_count_warp(const unsigned* p, unsigned target) {
    int n = 0;
    while (true) {
        unsigned v; asm volatile("ld.acquire.gpu.global.u32 %0, [%1];" : "=r"(v) : "l"(p) : "memory");
        if (__all_sync(0xffffffffu, (int)(v - target) >= 0)) break;
        __nanosleep(100);
        if (++n > SPIN_LIMIT) __trap();
    }
}
DEVI void signal_count(unsigned* p) { __threadfence(); atomicAdd(p, 1u); }

struct PMaps { CUtensorMap wq, bw, bwo, wo, x, bx, bo, ox, ox64, cb, cout, cq, b40; PList list; };
constexpr int PB_F = PS_BAR, PB_E = PB_F + 48, PB_TF = PB_F + 96, PB_TE = PB_F + 112, PB_S = PB_F + 128;
constexpr int PS_T = PB_F + 160, PS_SIG = PS_T + 32, PS_SK = PS_SIG + 16;

struct PRing {
    int st, ph, u;
    DEVI void next(int n) { u += n; if (u >= P_UNITS) u -= P_UNITS; if (++st == P_STAGES) { st = 0; ph ^= 1; } }
    DEVI uint32_t w(bool wide) const { return wide && u == P_UNITS - 2 ? 0u : u * 16384u; }
    DEVI uint32_t x(bool wide) const { return wide && u == P_UNITS - 2 ? u * 16384u : (u == P_UNITS - 1 ? 0u : (u + 1) * 16384u); }
};
struct POut { const CUtensorMap* map; int col, tok, cnt; bool blocked; };
DEVI void p_store(const uint32_t* pk, const POut& o, int c, uint32_t stg, int warp, int lane_, int barid) {
    const int lane = (int)opaque((uint32_t)lane_);
    const int mi = lane >> 3, r = lane & 7;
    const uint32_t buf = stg + (c & 1) * 8192;
    if (warp == 0) asm volatile("cp.async.bulk.wait_group.read 1;" ::: "memory");
    nbar_sync(barid, 128);
    if (o.blocked) {
#pragma unroll
        for (int j = 0; j < 8; j += 2)
            stsm4(buf + (j + (mi >> 1)) * 1024 + (warp * 16 + (mi & 1) * 8 + r) * 16, pk[2 * j], pk[2 * j + 1], pk[2 * j + 2], pk[2 * j + 3]);
    } else {
#pragma unroll
        for (int j = 0; j < 8; j += 2)
            stsm4t(buf + (8 * (j + (mi >> 1)) + r) * 128 + ((2 * warp + (mi & 1)) ^ r) * 16, pk[2 * j], pk[2 * j + 1], pk[2 * j + 2], pk[2 * j + 3]);
    }
    fence_proxy_async();
    nbar_sync(barid, 128);
    if (warp == 0 && elect_one()) {
        if (o.blocked)
            asm volatile("cp.async.bulk.tensor.4d.global.shared::cta.bulk_group [%0, {%2, %3, %4, %5}], [%1];"
                         :: "l"(o.map), "r"(buf), "r"(0), "r"((o.col >> 5) & 2), "r"((o.col >> 7) * 4), "r"((o.tok >> 5) + 2 * c) : "memory");
        else tma_store_2d(o.map, buf, o.col, o.tok + c * 64);
        bulk_commit();
    }
}
DEVI void p_signal(uint32_t sb, int g, int cnt, int& nsig) {
    if (elect_one()) {
        sts32(sb + PS_SIG + g * 8 + (nsig & 1) * 4, (uint32_t)cnt);
        mbar_arrive(sb + PB_S + g * 16 + (nsig & 1) * 8);
    }
    nsig++;
}
DEVI void p_release(uint32_t sb, const PRing& r) {
    if (elect_one()) mbar_arrive(sb + PB_E + (r.st ? r.st - 1 : P_STAGES - 1) * 8);
}
template <int BN, bool FIRST>
DEVI void p_kblock(float* d, uint32_t sb, int g, PRing& r) {
    mbar_wait(sb + PB_F + r.st * 8, r.ph);
    const uint64_t da = mk_desc(sb + r.w(BN == 256) + g * 8192, 16, 1024, 1), db = mk_desc(sb + r.x(BN == 256), 16, 1024, 1);
    wg_fence();
#pragma unroll
    for (int kk = 0; kk < 4; kk++) {
        if (BN == 256) { if (FIRST && kk == 0) wgmma_n256_ss<true>(d, da, db); else wgmma_n256_ss<false>(d, da + (uint64_t)(kk * 128), db + (uint64_t)(kk * 2)); }
        if (BN == 128) { if (FIRST && kk == 0) wgmma_n128_ss<true>(d, da, db); else wgmma_n128_ss<false>(d, da + (uint64_t)(kk * 128), db + (uint64_t)(kk * 2)); }
        if (BN == 64)  { if (FIRST && kk == 0) wgmma_n64_ss<true>(d, da, db); else wgmma_n64_ss<false>(d, da + (uint64_t)(kk * 128), db + (uint64_t)(kk * 2)); }
    }
    wg_commit();
    if (!FIRST) {
        wg_wait<1>();
        p_release(sb, r);
    }
    r.next(BN == 256 ? 3 : 2);
}

DEVI PTask post_claim(const PMaps& mp, unsigned E) {
    unsigned v = 0;
    if ((threadIdx.x & 31) == 0) v = atomicAdd(&g_qctr, 1u);
    return p_decode(mp.list, (int)(__shfl_sync(0xffffffffu, v, 0) - (E - 1) * (unsigned)(mp.list.run[mp.list.n - 1].w + mp.list.nworker)));
}
DEVI void post_producer(const PMaps& mp, uint32_t sb, unsigned E, bool early) {
    PRing r = {0, 0, 0};
    int ts = 0, tp = 0, used = 0;
    uint32_t big = 0;
    auto reserve = [&](int n) {
        while (used + n > P_UNITS) {
            mbar_wait(sb + PB_E + ts * 8, tp);
            used -= 2 + ((big >> ts) & 1);
            if (++ts == P_STAGES) { ts = 0; tp ^= 1; }
        }
        used += n;
        big = (big & ~(1u << r.st)) | ((uint32_t)(n & 1) << r.st);
    };
    for (int i = 0;; i++) {
        if (i > 0) mbar_wait(sb + PB_TE + (i & 1) * 8, ((i >> 1) & 1) ^ 1);
        else if (!early) nbar_sync(0, 384);
        const PTask tk = post_claim(mp, E);
        if (i == 0) { if (early) nbar_sync(0, 384); fence_proxy_async(); }
        const bool sn = tk.kind == K_SN, split = tk.kind == K_SK || sn, wide = tk.kind <= K_A4;
        const bool qk = tk.kind == K_Q || tk.kind == K_QH, ak = tk.kind == K_A4 || tk.kind == K_A3 || split;
        const int nk = split ? HD / 64 / P_SPLIT : (ak ? HD / 64 : DM / 64), kb0 = tk.c * (HD / 64 / P_SPLIT);
        const int tok0 = tk.b * (wide ? 256 : (sn ? 64 : 128)), grp = (tok0 >> 6) + (wide ? 3 : (sn ? 0 : 1));
        const uint32_t bytes = wide ? 49152 : (sn ? 24576 : 32768);
        const CUtensorMap* tx = tk.kind == K_B1 ? &mp.bx : (qk ? &mp.x : (sn ? &mp.ox64 : (ak ? &mp.ox : &mp.bo)));
        const int npre = split && (i == 0 || __any_sync(0xffffffffu, (int)(*(volatile unsigned*)&g_prog[grp] - 64 * E) < 0)) ? P_STAGES : 0;
        PRing rp = r;
        for (int kb = kb0; kb < kb0 + npre; kb++) {
            reserve(2);
            const uint32_t bar = sb + PB_F + r.st * 8;
            if (elect_one()) {
                mbar_expect_tx(bar, bytes);
                tma_load_wo(sb + r.w(false), &mp.wo, tk.a * 128, kb * 2, bar);
                tma_load_wo(sb + r.w(false) + 8192, &mp.wo, tk.a * 128 + 64, kb * 2, bar);
            }
            r.next(2);
        }
        if (tk.kind == K_B2) {
            wait_count_warp(&g_cnt[C_B1 + (tk.b >> 2)], 48 * E);
            if ((tk.b & 3) == 0 && tk.b > 0) wait_count_warp(&g_cnt[C_B1 + (tk.b >> 2) - 1], 48 * E);
        } else if (tk.kind == K_B3) wait_count_warp(&g_cnt[C_B2 + tk.b], 8 * E);
        else if (ak) wait_count_warp(&g_prog[grp], 64 * E);
        fence_proxy_global();
        for (int kb = kb0; kb < kb0 + npre; kb++) {
            if (elect_one()) tma_load_2d(sb + rp.x(false), tx, kb * 64, tok0, sb + PB_F + rp.st * 8);
            rp.next(2);
        }
        if (elect_one()) {
            sts128(sb + PS_T + (i & 1) * 16, make_uint4((uint32_t)tk.kind | ((uint32_t)tk.id << 8), (uint32_t)tk.a, (uint32_t)tk.b, (uint32_t)tk.c));
            mbar_arrive(sb + PB_TF + (i & 1) * 8);
        }
        if (tk.kind == K_END) break;
        if (tk.kind == K_B2) {
            for (int j = 0; j < 16; j++) {
                reserve(2);
                const uint32_t bar = sb + PB_F + r.st * 8;
                if (elect_one()) {
                    mbar_expect_tx(bar, 2 * 15360);
#pragma unroll
                    for (int u = 0; u < 2; u++) asm volatile("cp.async.bulk.tensor.4d.shared::cluster.global.mbarrier::complete_tx::bytes [%0], [%1, {%3, %4, %5, %6}], [%2];"
                                 :: "r"(sb + (u ? r.x(false) : r.w(false))), "l"(&mp.b40), "r"(bar), "r"(j * 64), "r"(0), "r"(u), "r"(tk.b * 32 - 8) : "memory");
                }
                r.next(2);
            }
            continue;
        }
        const CUtensorMap* tw = tk.kind == K_B1 ? &mp.bw : (qk ? &mp.wq : (ak ? &mp.wo : &mp.bwo));
        for (int kb = kb0 + npre; kb < kb0 + nk; kb++) {
            reserve(wide ? 3 : 2);
            const uint32_t aw = sb + r.w(wide), ax = sb + r.x(wide), bar = sb + PB_F + r.st * 8;
            if (elect_one()) {
                mbar_expect_tx(bar, bytes);
                if (ak || tk.kind == K_B3) {
                    tma_load_wo(aw, tw, tk.a * 128, kb * 2, bar);
                    tma_load_wo(aw + 8192, tw, tk.a * 128 + 64, kb * 2, bar);
                } else {
                    tma_load_2d(aw, tw, tk.a * 128, kb * 64, bar);
                    tma_load_2d(aw + 8192, tw, tk.a * 128 + 64, kb * 64, bar);
                }
                tma_load_2d(ax, tx, kb * 64, tok0, bar);
                if (wide) tma_load_2d(ax + 16384, tx, kb * 64, tok0 + 128, bar);
            }
            r.next(wide ? 3 : 2);
        }
        if (tk.id >= mp.list.late) { reserve(P_UNITS - 3); used -= P_UNITS - 3; }
    }
    if (elect_one()) {
        __threadfence();
        if (atomicAdd(&g_done, 1u) == E * mp.list.nworker - 1) { __threadfence(); *(volatile unsigned*)&g_epoch = E; }
    }
}
DEVI void post_helper(uint32_t sb, int g) {
    for (int n = 0;; n++) {
        mbar_wait_sleepy(sb + PB_S + g * 16 + (n & 1) * 8, (n >> 1) & 1);
        const int cnt = (int)lds32(sb + PS_SIG + g * 8 + (n & 1) * 4);
        if (cnt < 0) break;
        signal_count(&g_cnt[cnt]);
    }
}
template <int BN>
DEVI void p_narrow(const PMaps& mp, const PTask& tk, uint32_t sb, int g, int warp, PRing& r, int& nsig) {
    const int barid = 1 + g, tid = threadIdx.x;
    const bool split = BN == 64 || tk.kind == K_SK;
    constexpr int NV = BN / 16;
    float d[BN / 2];
    const int nk = split ? HD / 64 / P_SPLIT : (tk.kind == K_A3 ? HD / 64 : DM / 64);
    p_kblock<BN, true>(d, sb, g, r);
#pragma unroll 1
    for (int kb = 1; kb < nk; kb++) p_kblock<BN, false>(d, sb, g, r);
    wg_wait<0>();
    reg_fence<BN / 2>(d);
    p_release(sb, r);
    if (split) {
        const int tile = (tk.b * (BN / 64) - 2 * (16 - P_NSK)) * 8 + tk.a * (BN / 64);
        uint4* const base = g_skp + (uint32_t)(tile * P_SPLIT * 1024 + g * NV * 128 + (tid & 127));
#pragma unroll
        for (int j = 0; j < NV; j++)
            base[tk.c * NV * 256 + j * 128] = make_uint4(pack_bf16(d[8 * j], d[8 * j + 1]), pack_bf16(d[8 * j + 2], d[8 * j + 3]),
                                                         pack_bf16(d[8 * j + 4], d[8 * j + 5]), pack_bf16(d[8 * j + 6], d[8 * j + 7]));
        nbar_sync(barid, 128);
        if (warp == 0 && elect_one()) {
            unsigned old;
            asm volatile("atom.acq_rel.gpu.global.add.u32 %0, [%1], 1;" : "=r"(old) : "l"(&g_cnt_sk[tile * 2 + g]) : "memory");
            sts32(sb + PS_SK + g * 4, old % P_SPLIT);
        }
        nbar_sync(barid, 128);
        const bool last = __any_sync(0xffffffffu, lds32(sb + PS_SK + g * 4) == P_SPLIT - 1);
        nbar_sync(barid, 128);
        if (!last) return;
        uint4 v[(P_SPLIT - 1) * NV];
#pragma unroll
        for (int j = 0; j < (P_SPLIT - 1) * NV; j++) v[j] = __ldcg(base + ((tk.c + 1 + j / NV) % P_SPLIT) * NV * 256 + (j % NV) * 128);
#pragma unroll
        for (int j = 0; j < (P_SPLIT - 1) * NV; j++) {
            float* e = d + 8 * (j % NV);
            e[0] += __uint_as_float(v[j].x << 16); e[1] += __uint_as_float(v[j].x & 0xFFFF0000u);
            e[2] += __uint_as_float(v[j].y << 16); e[3] += __uint_as_float(v[j].y & 0xFFFF0000u);
            e[4] += __uint_as_float(v[j].z << 16); e[5] += __uint_as_float(v[j].z & 0xFFFF0000u);
            e[6] += __uint_as_float(v[j].w << 16); e[7] += __uint_as_float(v[j].w & 0xFFFF0000u);
        }
    }
    const bool qh = BN == 128 && tk.kind == K_QH;
    const POut o = {qh ? &mp.cq : &mp.cout, tk.a * 128 + g * 64, tk.b * BN, 0, qh};
    uint32_t q[BN / 4];
#pragma unroll
    for (int j = 0; j < BN / 4; j++) q[j] = pack_bf16(d[2 * j], d[2 * j + 1]);
    if (BN == 64 && warp == 0) bulk_wait_read();
#pragma unroll
    for (int c = 0; c < BN / 64; c++) p_store(q + 16 * c, o, c, sb + PS_STG + g * 16384, warp, tid & 31, barid);
    if (BN == 64 && warp == 0) bulk_wait_read();
    if (warp == 0 && qh) { bulk_wait_all(); p_signal(sb, g, tk.b == 0 ? C_QH : C_Q, nsig); }
}
DEVI void post_consumer(const PMaps& mp, uint32_t sb, int g, int warp) {
    const int barid = 1 + g, tid = threadIdx.x, lane = tid & 31;
    const uint32_t stg = sb + PS_STG + g * 16384;
    int nsig = 0;
    PRing r = {0, 0, 0};
    uint32_t pk[64];
    POut out;
    bool pend = false;
#pragma unroll
    for (int i = 0; i < 64; i++) pk[i] = 0u;
    for (int i = 0;; i++) {
        const uint32_t bTF = sb + PB_TF + (i & 1) * 8;
        if (pend) {
            uint32_t now;
            asm volatile("{.reg .pred p, q; mbarrier.test_wait.parity.shared::cta.b64 p, [%1], %2; bar.red.and.pred q, %3, 128, p; selp.u32 %0, 1, 0, q;}"
                         : "=r"(now) : "r"(bTF), "r"((i >> 1) & 1), "r"(barid) : "memory");
            if (__any_sync(0xffffffffu, !now || (lds32(sb + PS_T + (i & 1) * 16) & 255u) > K_A4)) {
#pragma unroll
                for (int c = 0; c < 4; c++) p_store(pk + 16 * c, out, c, stg, warp, lane, barid);
                if (warp == 0 && out.cnt != C_NONE) { bulk_wait_all(); p_signal(sb, g, out.cnt, nsig); }
                pend = false;
            }
        }
        mbar_wait(bTF, (i >> 1) & 1);
        uint4 tw = lds128(sb + PS_T + (i & 1) * 16);
        tw = make_uint4(__shfl_sync(0xffffffffu, tw.x, 0), __shfl_sync(0xffffffffu, tw.y, 0), __shfl_sync(0xffffffffu, tw.z, 0), __shfl_sync(0xffffffffu, tw.w, 0));
        mbar_arrive(sb + PB_TE + (i & 1) * 8);
        const PTask tk = {(int)(tw.x & 255u), (int)tw.y, (int)tw.z, (int)tw.w, 0};
        if (tk.kind == K_END) break;
        if (tk.kind <= K_A4) {
            float d[128];
            const int nk = tk.kind == K_A4 ? HD / 64 : DM / 64;
            p_kblock<256, true>(d, sb, g, r);
            if (pend) p_store(pk, out, 0, stg, warp, lane, barid);
#pragma unroll
            for (int c = 1; c < 4; c++) {
                p_kblock<256, false>(d, sb, g, r);
                if (pend) p_store(pk + 16 * c, out, c, stg, warp, lane, barid);
            }
#pragma unroll 1
            for (int kb = 4; kb < nk; kb++) {
                p_kblock<256, false>(d, sb, g, r);
                if (kb == 6 && pend && warp == 0 && out.cnt != C_NONE) { bulk_wait_all(); p_signal(sb, g, out.cnt, nsig); }
            }
            wg_wait<0>();
            reg_fence<128>(d);
            p_release(sb, r);
#pragma unroll
            for (int j = 0; j < 64; j++) pk[j] = pack_bf16(d[2 * j], d[2 * j + 1]);
            out.map = tk.kind == K_Q ? &mp.cq : (tk.kind == K_B1 ? &mp.cb : &mp.cout);
            out.col = tk.a * 128 + g * 64 + (tk.kind == K_B3 ? DM : 0);
            out.tok = tk.b * 256;
            out.cnt = tk.kind == K_Q ? C_Q + tk.b : (tk.kind == K_B1 ? C_B1 + tk.b : C_NONE);
            out.blocked = tk.kind == K_Q;
            pend = true;
        } else if (tk.kind == K_B2) {
#pragma unroll 2
            for (int j = 0; j < 16; j++) {
                mbar_wait(sb + PB_F + r.st * 8, r.ph);
                const uint32_t a = sb + (g ? r.x(false) : r.w(false));
                battn_warp(a, sb + PB_E + r.st * 8, tk.b * 32, g, j * 2 + (warp >> 1), warp >> 1, warp & 1, lane);
                r.next(2);
            }
            nbar_sync(barid, 128);
            if (warp == 0) p_signal(sb, g, C_B2 + (tk.b >> 2), nsig);
#pragma unroll
            for (int j = 0; j < 64; j++) pk[j] = 0u;
        } else {
            if (tk.kind == K_SN) p_narrow<64>(mp, tk, sb, g, warp, r, nsig); else p_narrow<128>(mp, tk, sb, g, warp, r, nsig);
#pragma unroll
            for (int j = 0; j < 64; j++) pk[j] = 0u;
        }
    }
    if (warp == 0) { bulk_wait_all(); p_signal(sb, g, -1, nsig); }
}
DEVI void post_init(uint32_t sb) {
    for (int i = 0; i < P_STAGES; i++) { mbar_init(sb + PB_F + i * 8, 1); mbar_init(sb + PB_E + i * 8, 8); }
    for (int i = 0; i < 2; i++) { mbar_init(sb + PB_TF + i * 8, 1); mbar_init(sb + PB_TE + i * 8, 256); }
    for (int i = 0; i < 4; i++) mbar_init(sb + PB_S + i * 8, 1);
    fence_mbar_init();
}

constexpr unsigned long long R_TORD_PACK = 0xfae93542dc187b60ull;
__host__ __device__ constexpr int r_tord(int pos) { return (int)((R_TORD_PACK >> (4 * pos)) & 15ull); }
__host__ __device__ constexpr int r_tinv(int T) { for (int p = 0; p < 16; p++) if (r_tord(p) == T) return p; return 0; }
__host__ __device__ constexpr bool r_pos_ss(int pos) { return pos % 3 == 2; }
__host__ __device__ constexpr int r_ss(int pos) { return pos / 3; }
__host__ __device__ constexpr int r_rs(int pos) { return pos - pos / 3; }
constexpr int R_NRS = 11, R_NSS = 5;
constexpr int R_G1 = 3, R_G2 = 9, R_G3 = 12;
#define REG_KB 232
constexpr int X_SLOTS = 4;
constexpr int X_NST = 8;

constexpr int RS_WSS  = 0;
constexpr int RS_WO   = RS_WSS + R_NSS * 16384;
constexpr int RS_MEM  = RS_WO + 5 * 16384;
constexpr int RS_O    = RS_MEM + 16384;
constexpr int RS_SX   = RS_O + 2048;
constexpr int RS_BAR  = RS_SX + 2048;
constexpr int RS_TAIL = RS_BAR + 1024;
constexpr int RS_WO5  = RS_TAIL;
constexpr int RS_K    = RS_WO5 + 16384;
constexpr int RS_V    = RS_K + 10240;
constexpr int RS_Q    = RS_V + 10240;
constexpr int RS_QX   = RS_Q + 2048;
constexpr int RS_QEND = RS_QX + 8192;
constexpr int RS_X    = RS_TAIL;
constexpr int X_PITCH = X_SLOTS * 4096;
constexpr int RS_XD   = RS_X + 2 * X_PITCH;
constexpr int RS_WX   = RS_XD + 8192;
constexpr int RS_XE   = RS_WX + 4096;
constexpr int RS_KEND = RS_XE + 2048;
constexpr int RS_EV   = RS_BAR + 256;
constexpr int R_SMEM  = RS_KEND > RS_QEND ? RS_KEND : RS_QEND;
static_assert(R_SMEM <= 232448 && P_SMEM <= R_SMEM, "smem");
static_assert(RS_TAIL % 1024 == 0 && RS_MEM % 1024 == 0, "alignment");

constexpr int RB_G = RS_BAR, RB_K = RS_BAR + 24, RB_V = RS_BAR + 32, RB_KV = RS_BAR + 40, RB_QX = RS_BAR + 48, RB_O = RS_BAR + 56;
constexpr int RB_ATT = RS_BAR + 64, RB_W = RS_BAR + 72, RB_SF = RS_BAR + 80, RB_SE = RB_SF + 40, RB_XF = RB_SE + 40;
constexpr int RB_VX = RB_XF + 48, RB_WO = RB_XF + 56, RB_T = RB_XF + 64, RB_G3 = RB_XF + 72, RS_INV = RB_XF + 16;
static_assert(RB_G3 + 8 <= RS_EV, "barriers");
constexpr uint32_t SB0 = 1024;
__host__ __device__ constexpr uint32_t cdesc(uint32_t off, uint32_t lbo) { return ((SB0 + off) >> 4) | ((lbo >> 4) << 16); }
#define SCHED_FENCE() __syncwarp()
constexpr int NB_BIG = 1, NB_Q = 2, NB_AUX = 3, NB_WO = 4, NB_XS = 5, NB_WG = 6, NB_PAIR = 8, NB_PRO = 12;

DEVI int tid_now() { int t; asm volatile("mov.u32 %0, %%tid.x;" : "=r"(t)); return t; }
DEVI uint32_t a_frag_off(int lane, int warp) { return (uint32_t)((((lane >> 4) * 8 + (lane & 7)) * 128) + (((2 * warp + ((lane >> 3) & 1)) ^ (lane & 7)) * 16)); }
DEVI uint32_t b_frag_off(int lane) { return (uint32_t)((lane & 3) * 64 + (((lane >> 2) * 8) ^ ((lane & 2) * 16))); }
DEVI void lds_b(uint32_t* b, uint32_t a) {
    asm volatile("ld.shared.v2.u32 {%0,%1}, [%2];" : "=r"(b[0]), "=r"(b[1]) : "r"(a) : "memory");
    asm volatile("ld.shared.v2.u32 {%0,%1}, [%2];" : "=r"(b[2]), "=r"(b[3]) : "r"(a + 256) : "memory");
}
DEVI uint32_t clk32() { unsigned long long c; asm volatile("mov.u64 %0, %%clock64;" : "=l"(c)); return (uint32_t)c; }

__host__ __device__ constexpr int x_pair(int j) { return j < 2 || j > 5 ? j : (j == 2 ? 5 : j - 1); }
DEVI void x_load(uint32_t sb, int seg, int j, int g, const CUtensorMap* tmX) {
    const uint32_t bar = sb + RB_XF + g * 8;
    mbar_expect_tx(bar, 4096);
    tma_load_3d(sb + RS_X + g * X_PITCH + (j % X_SLOTS) * 4096, tmX + (j == 3), g * 32, seg * 32, x_pair(j) * 2, bar);
    if (j == 3) tma_load_3d(sb + RS_SX + g * (RS_XE - RS_SX), tmX + 1, g * 32, seg * 32, x_pair(3) * 2 + 1, bar);
}
DEVI void x_refill(uint32_t sb, int seg, int j, int g, int warp, const CUtensorMap* tmX) {
    const int sn = j + X_SLOTS < X_NST ? seg : seg + 1;
    if (warp == (j & 3) && sn < NSEG) {
        if (elect_one()) x_load(sb, sn, (j + X_SLOTS) % X_NST, g, tmX);
    }
}
template <int J, int Q0, int Q1, int DQ>
DEVI void x_steps(float* xa, const uint32_t* w, int g0) {
    const int g = (int)opaque((uint32_t)g0);
    const uint32_t dW0 = cdesc(RS_WSS, 16) + g * 768, dW1 = cdesc(RS_WSS + 8192, 16) - g * 256;
#pragma unroll
    for (int q = Q0; q < Q1; q += DQ) {
        const int pos = r_tinv(2 * x_pair(J) + (q >> 2)), kk = (q >> 1) & 1, mt = q & 1;
        const uint32_t db = (J == 3 && q >= 4 ? cdesc(RS_SX, 16) + g * ((RS_XE - RS_SX) >> 4)
                                                    : cdesc(RS_X + (J % X_SLOTS) * 4096, 16) + g * (X_PITCH >> 4) + (q >> 2) * 128) + kk * 2;
        if (J == 0 && q < 2)   wgmma_n32_rs_first(xa + 16 * mt, &w[((r_rs(pos) * 2 + kk) * 2 + mt) * 4], db);
        else if (J == 0 && q == 3) wgmma_n32_ss(xa + 16, cdesc(RS_WX, 16) + g * 128, db);
        else if (r_pos_ss(pos)) wgmma_n32_ss(xa + 16 * mt, (mt ? dW1 : dW0) + r_ss(pos) * 1024 + kk * 128, db);
        else                   wgmma_n32_rs(xa + 16 * mt, &w[((r_rs(pos) * 2 + kk) * 2 + mt) * 4], db);
    }
}
DEVI void x_first(float* xa, const uint32_t* w, uint32_t sb, int seg, int g0, int warp, const CUtensorMap* tmX) {
    wg_fence();
    x_steps<0, 0, 8, 1>(xa, w, g0); wg_commit();
    x_steps<1, 0, 8, 1>(xa, w, g0); wg_commit();
    x_steps<2, 0, 8, 1>(xa, w, g0); wg_commit();
    x_steps<3, 0, 4, 1>(xa, w, g0); wg_commit();
    const int g = (int)opaque((uint32_t)g0);
    wg_wait<3>(); x_refill(sb, seg, 0, g, warp, tmX);
    wg_wait<2>(); x_refill(sb, seg, 1, g, warp, tmX);
    wg_wait<1>(); x_refill(sb, seg, 2, g, warp, tmX);
    wg_wait<0>(); x_refill(sb, seg, 3, g, warp, tmX);
    reg_fence<32>(xa);
    mbar_wait(sb + RB_XF + g * 8, 1);
}
DEVI void x_second(float* xa, uint32_t* a, uint32_t aA0, const uint32_t* w, uint32_t sb, int seg, int g0, int warp, const CUtensorMap* tmX) {
    wg_fence();
    x_steps<4, 0, 8, 1>(xa, w, g0); wg_commit();
    x_steps<3, 5, 8, 2>(xa, w, g0); x_steps<5, 1, 8, 2>(xa, w, g0); x_steps<6, 1, 8, 2>(xa, w, g0); x_steps<7, 1, 8, 2>(xa, w, g0); wg_commit();
    x_steps<3, 4, 8, 2>(xa, w, g0); x_steps<5, 0, 8, 2>(xa, w, g0); x_steps<6, 0, 8, 2>(xa, w, g0); x_steps<7, 0, 8, 2>(xa, w, g0); wg_commit();
    const int g = (int)opaque((uint32_t)g0);
    wg_wait<2>(); x_refill(sb, seg, 4, g, warp, tmX);
    SCHED_FENCE();
#pragma unroll
    for (int q = 0; q < 4; q++) ldsm4t(a + 4 * q, aA0 + (q & 1) * (8192 - g * 16384) + (q >> 1) * 2048);
    SCHED_FENCE();
    wg_wait<1>();
    reg_fence<16>(xa + 16);
}
DEVI void x_finish(float* xa, uint32_t sb, int g, int warp, int lane) {
    const uint32_t d = sb + RS_XD + (lane >> 4) * 2048 + warp * 256 + (lane & 15) * 16;
#pragma unroll
    for (int i = 0; i < 2; i++) {
        const float* x = xa + 16 + 8 * i;
        sts128(d + (g ^ 1) * 1024 + i * 4096, make_uint4(pack_bf16(x[0], x[1]), pack_bf16(x[2], x[3]), pack_bf16(x[4], x[5]), pack_bf16(x[6], x[7])));
    }
    nbar_sync(NB_PAIR + warp, 64);
    float y[16];
#pragma unroll
    for (int i = 0; i < 2; i++) {
        const uint4 v = lds128(d + g * 1024 + i * 4096);
        const uint32_t u[4] = {v.x, v.y, v.z, v.w};
#pragma unroll
        for (int j = 0; j < 4; j++) { y[8 * i + 2 * j] = __uint_as_float(u[j] << 16); y[8 * i + 2 * j + 1] = __uint_as_float(u[j] & 0xFFFF0000u); }
    }
    reg_fence<16>(y);
    wg_wait<0>();
    reg_fence<16>(xa);
    uint32_t p[8];
#pragma unroll
    for (int j = 0; j < 8; j++) p[j] = pack_bf16(xa[2 * j] + y[2 * j], xa[2 * j + 1] + y[2 * j + 1]);
    __syncwarp();
    stsm4(d + g * 1024, p[0], p[1], p[2], p[3]);
    stsm4(d + g * 1024 + 4096, p[4], p[5], p[6], p[7]);
    nbar_arrive(NB_XS, 256 + 32);
}
DEVI void x_send(uint32_t sb, int seg, uint32_t rank, const CUtensorMap* tmX) {
    auto refill = [&]() {
        if (seg + 1 < NSEG && elect_one()) {
#pragma unroll
            for (int j = 1; j < 4; j++) { x_load(sb, seg + 1, j, 0, tmX); x_load(sb, seg + 1, j, 1, tmX); }
        }
        __syncwarp();
    };
    mbar_wait(sb + RB_ATT, (seg - 1) & 1);
    nbar_sync(NB_XS, 256 + 32);
    if (rank == 2) { refill(); mbar_wait(sb + RB_G3, (seg - 1) & 1); }
    if (elect_one()) {
        fence_proxy_async();
        bulk_copy_s2c(mapa(sb + (rank == 1 ? RS_K : RS_V) + 2048, 0), sb + RS_XD, 8192, mapa(sb + (rank == 1 ? RB_KV : RB_VX), 0));
    }
    __syncwarp();
    if (rank == 1) refill();
}

template <bool XP>
DEVI void mem_pass(float* c0, float* c1, uint32_t* a, const uint32_t* w, uint32_t sb, uint32_t aA0, uint32_t aB, int g, int warp, int s) {
    const uint32_t aA1 = aA0 + 8192 - g * 16384, par = (s - 1) & 1;
    uint32_t b[2][4], e[4];
    float d0[4], d1[4];
    if (XP) ldsm4t(e, aA0 + opaque((RS_WX - RS_WSS) - g * (8192 + 2048)));
#pragma unroll
    for (int q = XP ? 4 : 0; q < 4; q++) ldsm4t(a + 4 * q, ((q & 1) ? aA1 : aA0) + (q >> 1) * 2048);
#pragma unroll
    for (int i = 0; i < 4; i++) { c0[i] = 0.f; c1[i] = 0.f; d0[i] = 0.f; d1[i] = 0.f; }
    EV(EV_BIG0, s, 0);
    mbar_wait(sb + RB_G, par);
    EV(EV_BIG0, s, 1);
    lds_b(b[0], aB + r_tord(0) * 1024);
    bool in = false;
#pragma unroll
    for (int pos = 0; pos < 16; pos++) {
        if (pos + 1 < 16) {
            if (pos + 1 == R_G1 && !in) mbar_wait(sb + RB_G + 8, par);
            if (pos + 1 == R_G2 && !in) mbar_wait(sb + RB_G + 16, par);
            if (pos + 1 == R_G3) { if (!in) mbar_wait(sb + RB_G3, par); EV(EV_BIG0, s, 2); }
            lds_b(b[(pos + 1) & 1], aB + r_tord(pos + 1) * 1024);
        }
        if (pos + 2 == R_G1) in = mbar_try(sb + RB_G + 8, par);
        if (pos + 2 == R_G2) in = mbar_try(sb + RB_G + 16, par);
        if (pos + 2 == R_G3) in = mbar_try(sb + RB_G3, par);
        if (XP && pos == 14) in = mbar_try(sb + RB_ATT, par);
        const uint32_t* bb = b[pos & 1];
        const uint32_t* aa = r_pos_ss(pos) ? a : &w[r_rs(pos) * 16];
        mma16816(c1, aa + 4, bb[0], bb[1]);
        mma16816(d1, XP && pos == 0 ? e : aa + 12, bb[2], bb[3]);
        mma16816(c0, aa, bb[0], bb[1]);
        mma16816(d0, aa + 8, bb[2], bb[3]);
        if (r_pos_ss(pos) && pos + 3 < 16) {
#pragma unroll
            for (int q = 0; q < 4; q++) ldsm4t(a + 4 * q, ((q & 1) ? aA1 : aA0) + (r_ss(pos) + 1) * 16384 + (q >> 1) * 2048);
        }
        SCHED_FENCE();
    }
    if (XP && !in) mbar_wait(sb + RB_ATT, par);
#pragma unroll
    for (int i = 0; i < 4; i++) { c1[i] += d1[i]; c0[i] += d0[i]; }
}

DEVI uint32_t k_frag_off(int lane) { return (uint32_t)((((lane >> 3) & 1) * 16 + (lane >> 4) * 8 + (lane & 7)) * 16); }
DEVI uint32_t v_frag_off(int lane) { return (uint32_t)(((lane >> 3) & 1) * 2048 + ((lane >> 4) * 8 + (lane & 7)) * 16); }
DEVI void pv_pair(float (*o)[4], const uint32_t* p, const uint32_t* v) {
#pragma unroll
    for (int n = 0; n < 4; n++) mma16816(o[n], p, v[2 * n], v[2 * n + 1]);
}
DEVI void pv_single(float (*o)[4], const uint32_t* p, const uint32_t* v) {
#pragma unroll
    for (int n = 0; n < 4; n++) mma1688(o[n], p[0], p[1], v[n]);
}
DEVI void s_tile(const uint32_t* qa, const uint32_t* k, float& s0, float& s1) {
    float c[4][4];
#pragma unroll
    for (int q = 0; q < 4; q++) { c[q][0] = c[q][1] = c[q][2] = c[q][3] = 0.f; }
#pragma unroll
    for (int q = 0; q < 4; q++) {
        mma16816(c[2 * (q & 1)], qa + 4 * q, k[4 * q], k[4 * q + 1]);
        mma16816(c[2 * (q & 1) + 1], qa + 4 * q, k[4 * q + 2], k[4 * q + 3]);
    }
    s0 = (c[0][0] + c[1][2]) + (c[2][0] + c[3][2]);
    s1 = (c[0][1] + c[1][3]) + (c[2][1] + c[3][3]);
}
DEVI void mem_scores(uint32_t sb, int s, int lane) {
    const uint32_t ka = sb + RS_K + k_frag_off(lane), sa = sb + RS_SX + 1024 + lane * 8;
    uint32_t qa[16], km[16];
    nbar_sync(NB_Q, 256);
#pragma unroll
    for (int q = 0; q < 4; q++) ldsm4t(qa + 4 * q, sb + RS_Q + q * 512 + lane * 16);
    mbar_wait(sb + RB_K, s & 1);
#pragma unroll
    for (int q = 0; q < 4; q++) ldsm4t(km + 4 * q, ka + q * 512);
    SCHED_FENCE();
    float s0, s1;
    s_tile(qa, km, s0, s1);
    asm volatile("st.shared.v2.f32 [%0], {%1,%2};" :: "r"(sa), "f"(s0 * SCALE_LOG2E), "f"(s1 * SCALE_LOG2E) : "memory");
    nbar_arrive(NB_XS, 128 + 32);
}
DEVI float quad_max(float m) {
    return fmaxf(fmaxf(m, __shfl_xor_sync(0xffffffffu, m, 1)), fmaxf(__shfl_xor_sync(0xffffffffu, m, 2), __shfl_xor_sync(0xffffffffu, m, 3)));
}
DEVI void mem_attn(uint32_t sb, int s, int warp, int lane) {
    const uint32_t va = sb + RS_V + warp * 512, sa = sb + RS_SX + lane * 8;
    [[maybe_unused]] constexpr int g = 0;
    float o[4][4], mx, l = 0.f;
    {
        const uint32_t ka = sb + RS_K + k_frag_off(lane) + (1 + warp) * 2048;
        uint32_t qa[16], kx[16];
        const bool in = mbar_try(sb + RB_KV, s & 1);
        nbar_sync(NB_Q, 256);
        EV(EV_BIG0 && lds32(sb + RS_Q) != 0x12345678u, s, 8);
#pragma unroll
        for (int q = 0; q < 4; q++) ldsm4t(qa + 4 * q, sb + RS_Q + q * 512 + lane * 16);
        if (!in) mbar_wait(sb + RB_KV, s & 1);
#pragma unroll
        for (int q = 0; q < 4; q++) ldsm4t(kx + 4 * q, ka + q * 512);
        const bool vin = mbar_try(sb + RB_VX, s & 1);
        SCHED_FENCE();
        float s0, s1;
        s_tile(qa, kx, s0, s1);
        asm volatile("st.shared.v2.f32 [%0], {%1,%2};" :: "r"(sa + warp * 256), "f"(s0), "f"(s1) : "memory");
        nbar_sync(NB_WG, 128);
        float sc[8];
#pragma unroll
        for (int n = 0; n < 4; n++) { const float2 v = lds64f(sa + n * 256); sc[2 * n] = v.x; sc[2 * n + 1] = v.y; }
        if (!vin) mbar_wait(sb + RB_VX, s & 1);
        mx = quad_max(fmaxf(fmaxf(fmaxf(sc[0], sc[1]), fmaxf(sc[2], sc[3])), fmaxf(fmaxf(sc[4], sc[5]), fmaxf(sc[6], sc[7])))) * SCALE_LOG2E;
        uint32_t vx[16], p[8];
#pragma unroll
        for (int q = 0; q < 4; q++) ldsm4(vx + 4 * q, va + 2048 + (q >> 1) * 4096 + (q & 1) * 256 + v_frag_off(lane));
#pragma unroll
        for (int n = 0; n < 4; n++) {
            const float e0 = ex2(fmaf(sc[2 * n], SCALE_LOG2E, -mx)), e1 = ex2(fmaf(sc[2 * n + 1], SCALE_LOG2E, -mx));
            l += e0 + e1;
            p[2 * n] = pack_bf16(e0, e1); p[2 * n + 1] = __float_as_uint(e0);
        }
#pragma unroll
        for (int n = 0; n < 4; n++) { o[n][0] = o[n][1] = o[n][2] = o[n][3] = 0.f; }
        pv_pair(o, p, vx);
        pv_pair(o, p + 4, vx + 8);
    }
    const uint32_t dst = sb + RS_O + warp * 512 + (lane & 3) * 128 + (lane >> 2) * 16, dl = sb + RS_INV + (lane & 28);
    EV(EV_BIG0, s, 5);
    mbar_wait(sb + RB_V, s & 1);
    uint32_t vm[4], p[2];
    ldsm4(vm, va + lane * 16);
    nbar_sync(NB_XS, 128 + 32);
    EV(EV_BIG0 && lds32(sb + RS_Q) != 0x12345678u, s, 9);
    const float2 sm = lds64f(sa + 1024);
    const float s0 = sm.x, s1 = sm.y;
    const float m = quad_max(fmaxf(mx, fmaxf(s0, s1)));
    const float e0 = ex2(s0 - m), e1 = ex2(s1 - m), f = ex2(mx - m);
    p[0] = pack_bf16(e0, e1); p[1] = __float_as_uint(e0);
#pragma unroll
    for (int n = 0; n < 4; n++) { o[n][0] *= f; o[n][1] *= f; }
    pv_single(o, p, vm);
    l = fmaf(l, f, e0 + e1);
    l = (l + __shfl_xor_sync(0xffffffffu, l, 1)) + (__shfl_xor_sync(0xffffffffu, l, 2) + __shfl_xor_sync(0xffffffffu, l, 3));
    const uint4 u = make_uint4(pack_bf16(o[0][0], o[0][1]), pack_bf16(o[1][0], o[1][1]), pack_bf16(o[2][0], o[2][1]), pack_bf16(o[3][0], o[3][1]));
    st_async128(mapa(dst, 1), u.x, u.y, u.z, u.w, mapa(sb + RB_O, 1));
    st_async128(mapa(dst, 2), u.x, u.y, u.z, u.w, mapa(sb + RB_O, 2));
    st_async32(mapa(dl, 1 + (warp & 1)), __float_as_uint(l), mapa(sb + RB_O, 1 + (warp & 1)));
    sts128(dst, u);
    sts32(dl, __float_as_uint(l));
    __syncwarp();
    if (elect_one()) mbar_arrive(sb + RB_O);
    EV(EV_BIG0, s, 15);
}

DEVI void ta_mask(float* c, int cw, int lane) {
    const int mt = cw >= 3, over = 8 * (cw - 3 * mt - 1) + 2 * (lane & 3) - 16 * mt - (lane >> 2);
    if (over > 0) c[0] = -INFINITY;
    if (over >= 0) c[1] = -INFINITY;
    if (over > 8) c[2] = -INFINITY;
    if (over >= 8) c[3] = -INFINITY;
}
DEVI void ta_scores(uint32_t sb, int seg, int warp, int lane) {
    const int tx = warp == 3 ? 0 : (warp == 2 ? 1 : 4 + 2 * warp), ty = warp == 3 ? 3 : tx + 1;
    const uint32_t qa = sb + RS_QX + ((warp < 2 ? 2 : 0) + ((lane >> 3) & 1)) * 2048 + ((lane >> 4) * 8 + (lane & 7)) * 16;
    const uint32_t ka = sb + RS_K + (warp < 2 ? tx - 3 : tx) * 2048 + lane * 16;
    float x[4] = {0.f, 0.f, 0.f, 0.f}, y[4] = {0.f, 0.f, 0.f, 0.f};
    mbar_wait(sb + RB_QX, seg & 1);
    if (warp < 3) {
#pragma unroll
        for (int j = 0; j < 4; j++) {
            uint32_t a0[4], a1[4], bx[4], by[4];
            ldsm4t(a0, qa + j * 512); ldsm4t(bx, ka + j * 512); ldsm4t(by, ka + 2048 + j * 512); ldsm4t(a1, qa + j * 512 + 256);
            mma16816(x, a0, bx[0], bx[1]); mma16816(y, a0, by[0], by[1]);
            mma16816(x, a1, bx[2], bx[3]); mma16816(y, a1, by[2], by[3]);
        }
        ta_mask(x, tx, lane); ta_mask(y, ty, lane);
    } else {
        mbar_wait(sb + RB_K, seg & 1);
#pragma unroll
        for (int j = 0; j < 4; j++) {
            uint32_t a0[4], a1[4], a2[4], a3[4], b[4];
            ldsm4t(a0, qa + j * 512); ldsm4t(b, ka + j * 512); ldsm4t(a2, qa + 4096 + j * 512);
            ldsm4t(a1, qa + j * 512 + 256); ldsm4t(a3, qa + 4096 + j * 512 + 256);
            mma16816(x, a0, b[0], b[1]); mma16816(y, a2, b[0], b[1]);
            mma16816(x, a1, b[2], b[3]); mma16816(y, a3, b[2], b[3]);
        }
    }
    nbar_sync(NB_WG + 1, 128);
    asm volatile("st.shared.v2.f32 [%0], {%1,%2};" :: "r"(sb + RS_QX + 4096 + tx * 256 + lane * 8), "f"(fmaxf(x[0], x[1])), "f"(fmaxf(x[2], x[3])) : "memory");
    asm volatile("st.shared.v2.f32 [%0], {%1,%2};" :: "r"(sb + RS_QX + 4096 + ty * 256 + lane * 8), "f"(fmaxf(y[0], y[1])), "f"(fmaxf(y[2], y[3])) : "memory");
    nbar_sync(NB_WG + 1, 128);
    float m[4] = {-INFINITY, -INFINITY, -INFINITY, -INFINITY};
#pragma unroll
    for (int n = 0; n < 8; n++) {
        if (n < 3 ? warp >= 2 : warp != 2) {
            const float2 v = lds64f(sb + RS_QX + 4096 + n * 256 + lane * 8);
            m[n < 3 ? 0 : 2] = fmaxf(m[n < 3 ? 0 : 2], v.x); m[n < 3 ? 1 : 3] = fmaxf(m[n < 3 ? 1 : 3], v.y);
        }
    }
#pragma unroll
    for (int o = 1; o < 4; o <<= 1) {
#pragma unroll
        for (int i = 0; i < 4; i++) m[i] = fmaxf(m[i], __shfl_xor_sync(0xffffffffu, m[i], o));
    }
    const float x0 = (warp < 2 ? m[2] : m[0]) * -SCALE_LOG2E, x1 = (warp < 2 ? m[3] : m[1]) * -SCALE_LOG2E;
    const float y0 = (warp == 2 ? m[0] : m[2]) * -SCALE_LOG2E, y1 = (warp == 2 ? m[1] : m[3]) * -SCALE_LOG2E;
    sts64(sb + RS_QX + tx * 256 + lane * 8, pack_bf16(ex2(fmaf(x[0], SCALE_LOG2E, x0)), ex2(fmaf(x[1], SCALE_LOG2E, x0))),
                                            pack_bf16(ex2(fmaf(x[2], SCALE_LOG2E, x1)), ex2(fmaf(x[3], SCALE_LOG2E, x1))));
    sts64(sb + RS_QX + ty * 256 + lane * 8, pack_bf16(ex2(fmaf(y[0], SCALE_LOG2E, y0)), ex2(fmaf(y[1], SCALE_LOG2E, y0))),
                                            pack_bf16(ex2(fmaf(y[2], SCALE_LOG2E, y1)), ex2(fmaf(y[3], SCALE_LOG2E, y1))));
}
template <int MT>
DEVI void ta_output(uint32_t sb, int seg, int head, int j, int lane) {
    const uint32_t pa = sb + RS_QX + MT * 768 + lane * 8, vb = sb + RS_V + j * 512;
    uint32_t p[6 + 4 * MT], v[12 + 8 * MT];
#pragma unroll
    for (int n = 0; n < 3 + 2 * MT; n++)
        asm volatile("ld.shared.v2.u32 {%0,%1}, [%2];" : "=r"(p[2 * n]), "=r"(p[2 * n + 1]) : "r"(pa + n * 256) : "memory");
#pragma unroll
    for (int q = 0; q < 2 + 2 * MT; q++) ldsm4(v + 4 * q, vb + (q >> 1) * 4096 + (q & 1) * 256 + v_frag_off(lane));
    ldsm4(v + 8 + 8 * MT, vb + 4096 + MT * 4096 + lane * 16);
    float o[4][4], l[4] = {0.f, 0.f, 0.f, 0.f};
#pragma unroll
    for (int n = 0; n < 4; n++) { o[n][0] = o[n][1] = o[n][2] = o[n][3] = 0.f; }
    mma16816(l, p, 0x3F803F80u, 0x3F803F80u);
    pv_pair(o, p, v);
    if (MT) { mma16816(l, p + 4, 0x3F803F80u, 0x3F803F80u); pv_pair(o, p + 4, v + 8); }
    mma1688(l, p[4 + 4 * MT], p[5 + 4 * MT], 0x3F803F80u);
    pv_single(o, p + 4 + 4 * MT, v + 8 + 8 * MT);
    const float i0 = rcp_fast(l[0]), i1 = rcp_fast(l[2]);
    bf16* dst = g_ox + (uint32_t)((seg * 32 + MT * 16 + (lane >> 2)) * HD + head * DH + j * 32 + (lane & 3) * 8);
    asm volatile("st.global.v4.u32 [%0], {%1,%2,%3,%4};" :: "l"(dst), "r"(pack_bf16(o[0][0] * i0, o[0][1] * i0)), "r"(pack_bf16(o[1][0] * i0, o[1][1] * i0)),
                 "r"(pack_bf16(o[2][0] * i0, o[2][1] * i0)), "r"(pack_bf16(o[3][0] * i0, o[3][1] * i0)) : "memory");
    asm volatile("st.global.v4.u32 [%0], {%1,%2,%3,%4};" :: "l"(dst + 8 * HD), "r"(pack_bf16(o[0][2] * i1, o[0][3] * i1)), "r"(pack_bf16(o[1][2] * i1, o[1][3] * i1)),
                 "r"(pack_bf16(o[2][2] * i1, o[2][3] * i1)), "r"(pack_bf16(o[3][2] * i1, o[3][3] * i1)) : "memory");
}

template <bool XP>
DEVI void big_main(const uint32_t* w, const uint32_t sb, const int g, const int warp, const uint32_t rank, const int head,
                   const CUtensorMap* tmX, const bf16* xg, const unsigned E) {
    float xa[32];
    uint32_t a[16];
    const uint32_t aB = __shfl_sync(0xffffffffu, sb + RS_MEM + (g * 32 + (tid_now() & 31)) * 16, tid_now() & 31);
#define lane0 ((int)(opaque(aB) >> 4) & 31)
    const uint32_t aA0 = sb + RS_WSS + g * (8192 + 4096) + a_frag_off(lane0, warp);
    const uint32_t aBf = sb + RS_MEM + g * 512 + b_frag_off(lane0);
    if constexpr (XP) {
        mbar_wait(sb + RB_XF + g * 8, 0);
        x_first(xa, w, sb, 0, g, warp, tmX);
        x_second(xa, a, aA0, w, sb, 0, g, warp, tmX);
        x_finish(xa, sb, g, warp, lane0);
    }
    nbar_sync(NB_BIG, 256);
    for (int s = 0; s < NSEG; s++) {
        float c0[4], c1[4];
        mem_pass<XP>(c0, c1, a, w, sb, aA0, aBf, g, warp, s);
        EV(EV_BIG0 && c0[0] != 1.2345e30f, s, 3);
        bool xin = true;
        const uint32_t xs = sb + RS_O + warp * 256 + lane0 * 8;
        sts64(xs + g * 1024, pack_bf16(c1[0], c1[1]), pack_bf16(c1[2], c1[3]));
        {
            const uint32_t d = sb + (XP ? (rank == 1 ? RS_K : RS_V) : RS_Q) + (g * 4 + warp) * 256 + lane0 * 4;
            const uint32_t rbar = XP ? mapa(sb + (rank == 1 ? RB_K : RB_V), 0) : 0u;
            nbar_sync(NB_PAIR + warp, 64);
            const float2 v = lds64f(xs + (g ^ 1) * 1024);
            if (XP) xin = mbar_test(sb + RB_XF + g * 8, 0);
            const uint32_t v0 = __float_as_uint(v.x), v1 = __float_as_uint(v.y);
            const uint32_t p0 = pack_bf16(c0[0] + __uint_as_float(v0 << 16), c0[1] + __uint_as_float(v0 & 0xFFFF0000u));
            const uint32_t p1 = pack_bf16(c0[2] + __uint_as_float(v1 << 16), c0[3] + __uint_as_float(v1 & 0xFFFF0000u));
            if constexpr (XP) { st_async32(mapa(d, 0), p0, rbar); st_async32(mapa(d + 128, 0), p1, rbar); }
            else { sts32(d, p0); sts32(d + 128, p1); }
            EV(EV_BIG0, s, 4);
        }
        if constexpr (XP) {
            if (s == NSEG - 1) break;
            if (!xin) mbar_wait(sb + RB_XF + g * 8, 0);
            x_first(xa, w, sb, s + 1, g, warp, tmX);
            EV(EV_BIG0, s, 5);
            EVCAL(s);
            nbar_sync(NB_WO, 384);
            EV(EV_BIG0 && lds32(sb + RS_O) != 0x12345678u, s, 6);
            x_second(xa, a, aA0, w, sb, s + 1, g, warp, tmX);
            EV(EV_BIG0, s, 7);
            x_finish(xa, sb, g, warp, lane0);
        } else {
            if (g == 0) {
                if (s < NSEG - 1) mem_attn(sb, s, warp, lane0);
            } else {
                if (s < NSEG - 1) { if (warp == 3) mem_scores(sb, s, lane0); else nbar_arrive(NB_Q, 256); }
                mbar_wait(sb + RB_KV, s & 1);
                if (s == 0 && warp == 0) {
                    wait_count_warp(&g_cnt[C_QH], 64 * E);
                    if (elect_one()) {
                        fence_proxy_global();
                        mbar_expect_tx(sb + RB_QX, 8192);
                        bulk_load(sb + RS_QX, g_qx + (uint32_t)(head * 4096), 8192, sb + RB_QX);
                    }
                    __syncwarp();
                }
                ta_scores(sb, s, warp, lane0);
            }
            EVCAL(s);
            mbar_wait(sb + RB_V, s & 1);
            mbar_wait(sb + RB_VX, s & 1);
            if (s < NSEG - 1) nbar_sync(NB_WO, 384); else nbar_sync(NB_BIG, 256);
            EV(EV_BIG0 && lds32(sb + RS_O) != 0x12345678u, s, 6);
            if (g == 0) ta_output<0>(sb, s, head, warp, lane0); else ta_output<1>(sb, s, head, warp, lane0);
            nbar_sync(NB_BIG, 256);
            EV(EV_BIG0 && lds32(sb + RS_O) != 0x12345678u, s, 7);
            if (g == 0 && warp == 0 && s + 1 < NSEG) {
                if (elect_one()) {
                    mbar_arrive_remote(mapa(sb + RB_ATT, 1));
                    mbar_arrive_remote(mapa(sb + RB_ATT, 2));
                    mbar_expect_tx(sb + RB_KV, 8192);
                    mbar_expect_tx(sb + RB_K, 2048);
                    mbar_expect_tx(sb + RB_V, 2048); mbar_expect_tx(sb + RB_VX, 8192);
                    mbar_arrive(sb + RB_T);
                }
                __syncwarp();
            }
        }
    }
    if constexpr (!XP) { if (tid_now() == 0) signal_count(&g_prog[(NSEG - 1) >> 1]); }
#undef lane0
}

template <int T, int K0, int K1>
DEVI void wo_part(float* acc) {
    constexpr uint32_t dWo = cdesc(T < 5 ? RS_WO + T * 16384 : RS_WO5, 16), dO = cdesc(RS_O, 128);
#pragma unroll
    for (int kk = K0; kk < K1; kk++) {
        if (kk == 0) { if (T < 3) wgmma_n8_ss_first<0>(acc, dWo, dO); else wgmma_n8_ss<0, 0>(acc, dWo, dO); }
        else wgmma_n8_ss<0, 1>(acc, dWo + kk * 128, dO + kk * 16);
    }
    wg_commit();
}
DEVI void red3(uint8_t* p, uint32_t a, uint32_t b, uint32_t c, uint32_t one) {
    asm volatile("red.relaxed.gpu.global.add.noftz.v4.bf16x2 [%0], {%1,%2,%3,%4};" :: "l"(p), "r"(a), "r"(b), "r"(c), "r"(one) : "memory");
}
constexpr int ACC_CH = 3 * 16 * 1024;
template <bool Q>
DEVI void wo_phase(uint32_t sb, int s, int warp, uint8_t* p, uint32_t ainv, int gap) {
    float a0[4], a1[4], a2[4];
    fence_proxy_async();
    const float2 iv = lds64f(ainv);
    SCHED_FENCE();
    const float i0 = rcp_fast(iv.x), i1 = rcp_fast(iv.y);
#define WORD(a, h) pack_bf16(a[2 * h] * i0, a[2 * h + 1] * i1)
    wg_fence();
    wo_part<0, 0, 8>(a0); wo_part<1, 0, 8>(a1); wo_part<2, 0, 8>(a2);
    wg_wait<1>(); reg_fence<4>(a0); reg_fence<4>(a1);
    red3(p, WORD(a0, 0), WORD(a0, 1), WORD(a1, 0), 0x3F80u);
    SCHED_FENCE();
    EV(warp == 0 && elect_one(), s, 11);
    wg_wait<0>(); reg_fence<4>(a2);
    red3(p + ACC_CH, WORD(a2, 0), WORD(a2, 1), WORD(a1, 1), 0x3F80u);
    SCHED_FENCE();
    { const uint32_t t = clk32() + gap; while ((int)(clk32() - t) < 0) { } }
    wg_fence();
    wo_part<3, 0, 8>(a0); wo_part<4, 0, 8>(a1);
    if (Q) {
        wo_part<5, 0, 8>(a2);
        wg_wait<1>(); reg_fence<4>(a0); reg_fence<4>(a1);
        red3(p + 2 * ACC_CH, WORD(a0, 0), WORD(a0, 1), WORD(a1, 0), 0x3F80u);
        SCHED_FENCE();
        wg_wait<0>(); reg_fence<4>(a2);
        red3(p + 3 * ACC_CH, WORD(a2, 0), WORD(a2, 1), WORD(a1, 1), 0x3F80u);
        nbar_arrive(NB_WO, 384);
    } else {
        wg_wait<1>();
        nbar_arrive(NB_WO, 384);
        wg_wait<0>(); reg_fence<4>(a0); reg_fence<4>(a1);
        red3(p + 2 * ACC_CH, WORD(a0, 0), WORD(a0, 1), WORD(a1, 0), 0x3F80u);
        red3(p + 3 * ACC_CH, 0u, 0u, WORD(a1, 1), 0x3F80u);
    }
#undef WORD
}
DEVI void unit_pack(uint32_t* u, uint32_t x0, uint32_t x1, uint32_t x2, uint32_t x3) {
    u[0] = __byte_perm(x0, x1, 0x5410); u[1] = __byte_perm(x2, x3, 0x5410); u[2] = __byte_perm(x0, x1, 0x7632); u[3] = __byte_perm(x2, x3, 0x7632);
}
DEVI void unit_send(uint32_t d, const uint32_t* u, uint32_t bar, uint32_t r1, uint32_t r2) {
    st_async128(mapa(d, r1), u[0], u[1], u[2], u[3], mapa(bar, r1));
    st_async128(mapa(d, r2), u[0], u[1], u[2], u[3], mapa(bar, r2));
}
template <bool Q>
DEVI void stage_sums(uint32_t sb, int s, uint32_t rank, int warp, const uint8_t* src, uint32_t l, uint32_t gate) {
    uint4 v[4];
    while ((int)(clk32() - gate) < 0) { }
    EV(elect_one(), s, 16 + warp);
#pragma unroll
    for (int j = 0; j < 4; j++) v[j] = ld_rlx4(src + j * 1024);
    const uint32_t col = sb + RS_MEM + ((Q ? 0 : (rank == 1 ? 6 : 11)) + 3 * (warp >> 1)) * 1024 + ((l >> 2) & 0x300) + (l & 0x70);
    const uint32_t d0 = col + (warp & 1) * 2048, d1 = d0 ^ 160, d2 = (col ^ ((warp & 1) * 160)) + 1024;
    const uint32_t r1 = Q ? 1 : 0, r2 = Q ? 2 : 3 - rank, bar = sb + (warp < 2 ? RB_G + 8 * warp : (Q ? RB_G + 16 : RB_G3));
    int n = 0;
    while (!__all_sync(0xffffffffu, v[0].w == 0x4200u && v[1].w == 0x4200u && v[2].w == 0x4200u && v[3].w == 0x4200u)) {
#pragma unroll
        for (int j = 0; j < 4; j++) v[j] = ld_rlx4(src + j * 1024);
        if (++n > SPIN_LIMIT) __trap();
    }
    EV(elect_one(), s, 24 + warp);
    uint32_t u[12];
    unit_pack(u + 8, v[0].z, v[1].z, v[2].z, v[3].z);
    unit_send(d2, u + 8, bar, r1, r2);
    if (Q || warp < 3) {
        unit_pack(u, v[0].x, v[1].x, v[2].x, v[3].x);
        unit_pack(u + 4, v[0].y, v[1].y, v[2].y, v[3].y);
        unit_send(d0, u, bar, r1, r2);
        unit_send(d1, u + 4, bar, r1, r2);
        sts128(d0, make_uint4(u[0], u[1], u[2], u[3]));
        sts128(d1, make_uint4(u[4], u[5], u[6], u[7]));
    }
    sts128(d2, make_uint4(u[8], u[9], u[10], u[11]));
    __syncwarp();
    if (elect_one()) {
        mbar_expect_tx(bar, warp < 2 ? 3072u : (Q ? 0u : 1024u));
        if (warp == 0) mbar_expect_tx(sb + (Q ? RB_G3 : RB_G + 16), Q ? 4096u : 3072u);
    }
    EV(elect_one(), s, 20 + warp);
}
DEVI void wo_permute(uint32_t tile, int t) {
    const uint32_t a = tile + t * 32 + ((t >> 2) & 1) * 16;
#pragma unroll
    for (int h = 0; h < 2; h++) {
        uint4 v[3], u[3];
#pragma unroll
        for (int i = 0; i < 3; i++) if (3 * h + i < 5 || t < 32) { v[i] = lds128(a + (3 * h + i) * 3072); u[i] = lds128((a ^ 16) + (3 * h + i) * 3072); }
#pragma unroll
        for (int i = 0; i < 3; i++) if (3 * h + i < 5 || t < 32) {
            sts128(a + (3 * h + i) * 3072, make_uint4(__byte_perm(v[i].x, v[i].y, 0x5410), __byte_perm(v[i].x, v[i].y, 0x7632),
                                                      __byte_perm(u[i].x, u[i].y, 0x5410), __byte_perm(u[i].x, u[i].y, 0x7632)));
            sts128((a ^ 16) + (3 * h + i) * 3072, make_uint4(__byte_perm(v[i].z, v[i].w, 0x5410), __byte_perm(v[i].z, v[i].w, 0x7632),
                                                             __byte_perm(u[i].z, u[i].w, 0x5410), __byte_perm(u[i].z, u[i].w, 0x7632)));
        }
    }
}
DEVI uint32_t acc_clear(int slot, int idx, uint32_t lo) {
    uint8_t* p = g_acc + (uint32_t)(slot * 128 + idx * 3072 + (lo < 3072 ? lo : lo - 1024));
    st_rlx4(p, 0u, 0u, 0u, 0u);
    uint32_t z; asm volatile("ld.relaxed.gpu.global.u32 %0, [%1];" : "=r"(z) : "l"(p) : "memory");
    return z;
}

template <bool Q>
DEVI void aux_main(uint32_t sb, int warp, uint32_t rank, int head, const CUtensorMap* tmX, const bf16* xg, unsigned E, const int delay, const int gap) {
    const uint32_t lo = __shfl_sync(0xffffffffu, ((tid_now() >> 3) & 3) * 1024 + (tid_now() & 7) * 16, tid_now() & 31);
    for (int s = 0; s < NSEG - 1; s++) {
        if (!Q && warp == 0 && elect_one()) mbar_expect_tx(sb + RB_O, 2048 + 256);
        __syncwarp();
        const uint32_t slot = (s & 3) * 128;
        mbar_wait(sb + RB_O, s & 1);
        EV(warp == 0 && elect_one(), s, 10);
        wo_phase<Q>(sb, s, warp, g_acc + (uint32_t)(slot + (rank * 4 + warp) * 4096 + opaque(lo)), sb + RS_INV + ((opaque(lo) >> 1) & 24), gap);
        SCHED_FENCE();
        const uint32_t t_o = clk32();
        EV(warp == 0 && elect_one(), s, 12);
        {
            const uint32_t l = opaque(lo);
            stage_sums<Q>(sb, s, rank, warp, g_acc + (uint32_t)(slot + rank * 16384 + warp * ACC_CH + (l & 0xC00) * 4 + (l & 0x70)), l, t_o + delay);
        }
        EV(warp == 2 && elect_one(), s, 14);
        if (warp == (Q ? 3 : 1)) {
            if (Q) {
                mbar_wait(sb + RB_T, s & 1);
                if (s == 3) wait_count_warp(&g_cnt[C_Q], 64 * E);
                if (elect_one()) {
                    if (s == 3) fence_proxy_global();
                    fence_proxy_async();
                    mbar_expect_tx(sb + RB_QX, 8192);
                    bulk_load(sb + RS_QX, g_qx + (uint32_t)(((s + 1) * NH + head) * 4096), 8192, sb + RB_QX);
                    if (head == 0) { TLOG(1400 + s, 0, gtime()); TLOG(1400 + s, 1, clock64()); }
                }
                __syncwarp();
                const bool fresh = (s & 7) == 6 && s + 2 < NSEG;
                if (fresh) wait_count_warp(&g_cnt[C_Q + ((s + 2) >> 3)], 64 * E);
                if (elect_one()) {
                    if (fresh) fence_proxy_global();
                    if (s + 2 < NSEG && s != 2) l2_prefetch(g_qx + (uint32_t)(((s + 2) * NH + head) * 4096), 8192);
                    if (s + 4 < NSEG) l2_prefetch(xg + (uint32_t)(((s + 4) * 32 + head) * DM), 2048);
                    signal_count(&g_prog[s >> 1]);
                }
                __syncwarp();
            } else {
                const uint32_t zero = acc_clear((s + 2) & 3, 2 * head + (int)rank - 1, opaque(lo));
                x_send(sb, s + 1, rank, tmX);
                if (__any_sync(0xffffffffu, zero != 0u)) __trap();
            }
        }
    }
}

DEVI void load_weights(uint32_t sb, const CUtensorMap* tmW, const CUtensorMap* tmWo, int head, uint32_t rank, int2 t0) {
    const uint32_t c0 = clk32();
    if (rank == 0) while ((int)(clk32() - c0) < t0.x) { }
    const uint32_t bW = sb + RB_W, bSF = sb + RB_SF, bSE = sb + RB_SE;
    const int tile0 = rank == 0 ? 0 : (rank == 1 ? 6 : 11);
    mbar_expect_tx(bW, R_NSS * 16384);
    for (int pass = 0; pass < 2; pass++) {
        for (int pos = 0; pos < 16; pos++) {
            const int k = (int)((R_TORD_PACK >> (4 * pos)) & 15ull) * 64, rd = pos - pos / 3, slot = rd % 5;
            if (r_pos_ss(pos)) {
                if (pass) continue;
                const uint32_t dst = sb + RS_WSS + (pos / 3) * 16384;
                tma_load_2d(dst, tmW, head * DH, k, bW);
                tma_load_2d(dst + 8192, tmW, head * DH + 64, k, bW);
            } else if (pass == (rd >= 5)) {
                if (rd >= 5) mbar_wait(bSE + 8 * slot, ((rd / 5) - 1) & 1);
                mbar_expect_tx(bSF + 8 * slot, 16384);
                const uint32_t dst = sb + RS_WO + slot * 16384;
                tma_load_2d(dst, tmW, head * DH, k, bSF + 8 * slot);
                tma_load_2d(dst + 8192, tmW, head * DH + 64, k, bSF + 8 * slot);
            }
        }
    }
    while ((int)(clk32() - c0) < t0.y) { }
    if (rank == 0) { mbar_expect_tx(sb + RB_WO, 16384); tma_load_wo(sb + RS_WO5, tmWo, 5 * 64, head * 4, sb + RB_WO); }
    for (int i = 1; i <= 5; i++) {
        const int slot = i % 5, last = slot + 10 < R_NRS ? slot + 10 : slot + 5;
        mbar_wait(bSE + 8 * slot, (last / 5) & 1);
        mbar_expect_tx(bSF + 8 * slot, 16384);
        tma_load_wo(sb + RS_WO + slot * 16384, tmWo, (tile0 + slot) * 64, head * 4, bSF + 8 * slot);
    }
}
template <bool XP>
DEVI void big_prologue(uint32_t* w, uint32_t sb, int g, int warp, const bf16* __restrict__ mem0) {
    const int tid = tid_now(), lane = tid & 31;
    {
        const uint32_t* m = (const uint32_t*)(mem0 + (lane >> 2) * DM + (tid >> 5) * 16) + (lane & 3);
        uint32_t u[16];
#pragma unroll
        for (int j = 0; j < 8; j++) { u[2 * j] = m[j * 64]; u[2 * j + 1] = m[j * 64 + 4]; }
#pragma unroll
        for (int j = 0; j < 8; j++) sts64(sb + RS_MEM + ((tid >> 5) + j * 8) * 256 + b_frag_off(lane), u[2 * j], u[2 * j + 1]);
    }
    const uint32_t a0 = sb + RS_WO + g * (8192 + 4096) + a_frag_off(lane, warp), a1 = a0 + 8192 - g * 16384;
#pragma unroll
    for (int rd = 0; rd < R_NRS; rd++) {
        const int slot = rd % 5;
        mbar_wait(sb + RB_SF + 8 * slot, (rd / 5) & 1);
#pragma unroll
        for (int q = 0; q < 4; q++) {
            if (XP && rd == 0 && q == 3) {
                sts128(sb + RS_WX + g * 2048 + (tid & 127) * 16, lds128(sb + RS_WO + 8192 - g * 4096 + 2048 + (tid & 127) * 16));
                fence_proxy_async();
                nbar_sync(NB_WG + g, 128);
            } else ldsm4t(&w[rd * 16 + q * 4], ((q & 1) ? a1 : a0) + slot * 16384 + (q >> 1) * 2048);
        }
        mbar_arrive(sb + RB_SE + 8 * slot);
    }
    mbar_wait(sb + RB_W, 0);
    if (tid == 0) TLOG(1500 + blockIdx.x, 2, gtime());
}

#define REC_END() do { if (tid_now() == 0) TLOG(1024 + blockIdx.x, 1, gtime()); } while (0)
struct XMaps { CUtensorMap m[2]; };
__global__ void __launch_bounds__(384, 1)
k_rec(const __grid_constant__ PMaps mp, const __grid_constant__ CUtensorMap tmWk, const __grid_constant__ CUtensorMap tmWv,
      const __grid_constant__ CUtensorMap tmWo, const __grid_constant__ XMaps xm, const bf16* __restrict__ mem0, const bf16* __restrict__ xg,
      int4 tq, int4 tk, int2 t0, int rec) {
    extern __shared__ __align__(1024) uint8_t smem_raw[];
    const uint32_t sb = smem_u32(smem_raw);
    if ((sb & 0x3FFFFu) != SB0) __trap();
    const int tid = threadIdx.x;
    const int wg = __shfl_sync(0xffffffffu, tid >> 7, 0), warp = __shfl_sync(0xffffffffu, (tid >> 5) & 3, 0);
    uint32_t rank; asm("mov.u32 %0, %%cluster_ctarank;" : "=r"(rank));
    int head; asm("mov.u32 %0, %%clusterid.x;" : "=r"(head));
    asm volatile("griddepcontrol.launch_dependents;");
    if (tid == 0 && rec) {
        mbar_init(sb + RB_G, 1);
        mbar_init(sb + RB_G + 8, 1);
        mbar_init(sb + RB_G + 16, rank == 0 ? 2 : 1);
        mbar_init(sb + RB_G3, rank == 0 ? 1 : 2);
        mbar_init(sb + RB_T, 1); mbar_init(sb + RB_VX, 1); mbar_init(sb + RB_WO, 1);
        mbar_init(sb + RB_K, 1); mbar_init(sb + RB_V, 1); mbar_init(sb + RB_KV, 1); mbar_init(sb + RB_QX, 1);
        mbar_init(sb + RB_O, rank == 0 ? 4 : 1); mbar_init(sb + RB_ATT, 1); mbar_init(sb + RB_W, 1);
        for (int i = 0; i < 5; i++) { mbar_init(sb + RB_SF + 8 * i, 1); mbar_init(sb + RB_SE + 8 * i, 256); }
        for (int i = 0; i < 2; i++) mbar_init(sb + RB_XF + 8 * i, X_SLOTS);
        fence_mbar_init();
        if (rank == 0) { mbar_expect_tx(sb + RB_KV, 8192); mbar_expect_tx(sb + RB_K, 2048); mbar_expect_tx(sb + RB_V, 2048); mbar_expect_tx(sb + RB_VX, 8192); }
    }
    __syncthreads();
    asm volatile("barrier.cluster.arrive.release.aligned;" ::: "memory");

    if (wg < 2) {
        reg_inc<REG_KB>();
        if (rank != 0) {
            uint32_t w[R_NRS * 16];
            if ((tid & 127) == 0) for (int j = 0; j < X_SLOTS; j++) x_load(sb, 0, j, wg, xm.m);
            __syncwarp();
            cluster_wait();
            big_prologue<true>(w, sb, wg, warp, mem0);
            big_main<true>(w, sb, wg, warp, rank, head, xm.m, xg, 0u);
            REC_END();
        } else if (rec) {
            uint32_t w[R_NRS * 16];
            cluster_wait();
            big_prologue<false>(w, sb, wg, warp, mem0);
            big_main<false>(w, sb, wg, warp, rank, head, xm.m, xg, *(volatile unsigned*)&g_epoch + 1);
            REC_END();
        } else cluster_wait();
        if (rank == 0 && rec) nbar_arrive(NB_PRO, 256 + 32);
        nbar_sync(0, 384);
        post_consumer(mp, sb, wg, warp);
    } else {
        reg_dec<504 - 2 * REG_KB>();
        if (rec) {
            if (tid == 256) {
                if (rank == 0) l2_prefetch(xg + (uint32_t)(head * 8 * DM), 16384);
                load_weights(sb, rank == 0 ? &mp.wq : (rank == 1 ? &tmWk : &tmWv), &tmWo, head, rank, t0);
            }
            if (warp == 3 && rank != 0) {
                const uint32_t lo = ((tid >> 3) & 3) * 1024 + (tid & 7) * 16;
                acc_clear(0, 2 * head + (int)rank - 1, lo); acc_clear(1, 2 * head + (int)rank - 1, lo);
                __threadfence();
                __syncwarp();
                if (tid == 256 + 96) atomicAdd(&g_zero, 1u);
            }
            __syncwarp();
        }
        cluster_wait();
        const unsigned E = __shfl_sync(0xffffffffu, *(volatile unsigned*)&g_epoch + 1, 0);
        if (rec) {
            if (warp == 1) wait_count_warp(&g_zero, E * 64u);
            if (warp == 3) { if (rank != 0) x_send(sb, 0, rank, xm.m); }
            else {
                nbar_sync(NB_PRO, 96);
#pragma unroll 1
                for (int i = rank == 0 ? 0 : 1; i <= 5; i++) {
                    mbar_wait(sb + (i == 0 ? RB_WO : RB_SF + 8 * (i % 5)), i == 5);
                    if (i == 5 && tid == 288) TLOG(1500 + blockIdx.x, 0, gtime());
                    wo_permute(sb + (i == 0 ? RS_WO5 : RS_WO + (i % 5) * 16384), tid & 127);
                }
            }
            fence_proxy_async();
            nbar_sync(NB_AUX, 128);
            if (tid == 288) { TLOG(1500 + blockIdx.x, 1, gtime()); }
            if (rank == 0) aux_main<true>(sb, warp, rank, head, xm.m, xg, E, warp == 0 ? tq.x : (warp == 1 ? tq.y : tq.z), tq.w);
            else           aux_main<false>(sb, warp, rank, head, xm.m, xg, E, warp == 0 ? tk.x : (warp == 1 ? tk.y : tk.z), tk.w);
        }
        const int t = tid_now();
        if (t >= 320 && t < 320 + 13) asm volatile("prefetch.tensormap [%0];" :: "l"(&mp.wq + (t - 320)) : "memory");
        __syncwarp();
        if (warp == 0) post_producer(mp, sb, E, rank != 0 || !rec);
        else {
            if (warp == 1) {
                if (rank == 0 && rec) nbar_sync(NB_PRO, 256 + 32);
                if (elect_one()) post_init(sb);
                __syncwarp();
            }
            nbar_sync(0, 384);
            if (t == 288 || t == 320) post_helper(sb, warp - 1);
        }
    }
    __syncthreads();
    asm volatile("griddepcontrol.wait;" ::: "memory");
}

typedef CUresult (*EncodeFn)(CUtensorMap*, CUtensorMapDataType, cuuint32_t, void*, const cuuint64_t*, const cuuint64_t*,
                             const cuuint32_t*, const cuuint32_t*, CUtensorMapInterleave, CUtensorMapSwizzle,
                             CUtensorMapL2promotion, CUtensorMapFloatOOBfill);

static CUtensorMap make_map(EncodeFn fn, const void* ptr, uint64_t inner, uint64_t outer, uint32_t box_inner, uint32_t box_outer) {
    CUtensorMap m;
    cuuint64_t dims[2] = {inner, outer};
    cuuint64_t strides[1] = {inner * 2};
    cuuint32_t box[2] = {box_inner, box_outer};
    cuuint32_t es[2] = {1, 1};
    fn(&m, CU_TENSOR_MAP_DATA_TYPE_BFLOAT16, 2, const_cast<void*>(ptr), dims, strides, box, es,
       CU_TENSOR_MAP_INTERLEAVE_NONE, CU_TENSOR_MAP_SWIZZLE_128B, CU_TENSOR_MAP_L2_PROMOTION_L2_256B, CU_TENSOR_MAP_FLOAT_OOB_FILL_NONE);
    return m;
}

static CUtensorMap make_wo_map(EncodeFn fn, const void* ptr, uint64_t rows, uint32_t ngrp) {
    CUtensorMap m;
    cuuint64_t dims[5] = {DM, 2, 4, 4, rows / 32};
    cuuint64_t strides[4] = {DM * 2, 8 * DM * 2, 2 * DM * 2, 32 * DM * 2};
    cuuint32_t box[5] = {64, 2, 4, 4, ngrp};
    cuuint32_t es[5] = {1, 1, 1, 1, 1};
    fn(&m, CU_TENSOR_MAP_DATA_TYPE_BFLOAT16, 5, const_cast<void*>(ptr), dims, strides, box, es,
       CU_TENSOR_MAP_INTERLEAVE_NONE, CU_TENSOR_MAP_SWIZZLE_128B, CU_TENSOR_MAP_L2_PROMOTION_L2_256B, CU_TENSOR_MAP_FLOAT_OOB_FILL_NONE);
    return m;
}

struct Maps {
    PMaps post;
    CUtensorMap wk16, wv16, wo128;
    XMaps x32;
};

extern "C" void kernel_launch(void* const* d_in, const int* in_sizes, int n_in, void* d_out, int out_size) {
    const bf16* A_x   = (const bf16*)d_in[0];
    const bf16* A_mem = (const bf16*)d_in[1];
    const bf16* A_Wq  = (const bf16*)d_in[2];
    const bf16* A_Wk  = (const bf16*)d_in[3];
    const bf16* A_Wv  = (const bf16*)d_in[4];
    const bf16* A_Wo  = (const bf16*)d_in[5];
    const bf16* B_x   = (const bf16*)d_in[7];
    const bf16* B_w   = (const bf16*)d_in[8];
    const bf16* B_wo  = (const bf16*)d_in[9];

    static EncodeFn fn = nullptr;
    static Maps mp;
    static const void* cached[10];
    const void* cur[10] = {A_x, A_mem, A_Wq, A_Wk, A_Wv, A_Wo, B_x, B_w, B_wo, d_out};
    bool same = fn != nullptr;
    for (int i = 0; i < 10 && same; i++) same = cached[i] == cur[i];
    if (!same) {
        if (!fn) {
            void* p = nullptr; cudaDriverEntryPointQueryResult qr;
            cudaGetDriverEntryPoint("cuTensorMapEncodeTiled", &p, cudaEnableDefault, &qr);
            fn = (EncodeFn)p;
            cudaFuncSetAttribute(k_rec, cudaFuncAttributeMaxDynamicSharedMemorySize, R_SMEM);
        }
        void *p_ox, *p_bqkv, *p_bo, *p_qx;
        cudaGetSymbolAddress(&p_qx, g_qx);
        cudaGetSymbolAddress(&p_ox, g_ox); cudaGetSymbolAddress(&p_bqkv, g_bqkv); cudaGetSymbolAddress(&p_bo, g_bo);
        mp.post.wq   = make_map(fn, A_Wq, HD, DM, 64, 64);
        mp.post.wo   = make_wo_map(fn, A_Wo, HD, 2);
        mp.post.bw   = make_map(fn, B_w, 3 * DM, DM, 64, 64);
        mp.post.bwo  = make_wo_map(fn, B_wo, DM, 2);
        mp.post.x    = make_map(fn, A_x, DM, S_TOK, 64, 128);
        mp.post.bx   = make_map(fn, B_x, DM, S_TOK, 64, 128);
        mp.post.bo   = make_map(fn, p_bo, DM, S_TOK, 64, 128);
        mp.post.ox   = make_map(fn, p_ox, HD, S_TOK, 64, 128);
        mp.post.ox64 = make_map(fn, p_ox, HD, S_TOK, 64, 64);
        mp.post.cb   = make_map(fn, p_bqkv, 3 * DM, S_TOK, 64, 64);
        mp.post.cout = make_map(fn, d_out, 2 * DM, S_TOK, 64, 64);
        {
            cuuint64_t dims[4] = {256, 4, NH * 4, NSEG};
            cuuint64_t strides[3] = {512, 2048, NH * 8192};
            cuuint32_t box[4] = {256, 2, 4, 2};
            cuuint32_t es[4] = {1, 1, 1, 1};
            fn(&mp.post.cq, CU_TENSOR_MAP_DATA_TYPE_BFLOAT16, 4, p_qx, dims, strides, box, es,
               CU_TENSOR_MAP_INTERLEAVE_NONE, CU_TENSOR_MAP_SWIZZLE_NONE, CU_TENSOR_MAP_L2_PROMOTION_NONE, CU_TENSOR_MAP_FLOAT_OOB_FILL_NONE);
        }
        {
            int runs[48] = {K_QH, 0, 2, K_Q, 1, 7, K_B1, 0, 8, K_A4, 0, 4, K_B2, 0, 32, K_A4, 4, 2, K_B3, 0, 4, K_A3, 12, 2, K_B3, 4, 4,
                            K_SK, 14, 1, K_SN, 30, 2, -1};
            int nlate = 9;
            const int per[9] = {32, 24, 8, 8, 32, 8, 8 * P_SPLIT, 1, 8 * P_SPLIT};
            int n = 0, id = 0;
            for (; runs[3 * n] >= 0; n++) {
                mp.post.list.run[n] = make_int4(runs[3 * n], runs[3 * n + 1], id, id + runs[3 * n + 2] * per[runs[3 * n]]);
                id = mp.post.list.run[n].w;
            }
            mp.post.list.n = n;
            mp.post.list.late = mp.post.list.run[nlate].z;
            int dev = 0, nsm = 132;
            cudaGetDevice(&dev);
            cudaDeviceGetAttribute(&nsm, cudaDevAttrMultiProcessorCount, dev);
            mp.post.list.nworker = nsm > 96 ? nsm : 97;
        }
        {
            cuuint64_t dims[4] = {DM, 3, 2, S_TOK / 2};
            cuuint64_t strides[3] = {DM * 2, 3 * DM * 2, 3 * DM * 4};
            cuuint32_t box[4] = {64, 3, 1, 40};
            cuuint32_t es[4] = {1, 1, 1, 1};
            fn(&mp.post.b40, CU_TENSOR_MAP_DATA_TYPE_BFLOAT16, 4, p_bqkv, dims, strides, box, es,
               CU_TENSOR_MAP_INTERLEAVE_NONE, CU_TENSOR_MAP_SWIZZLE_128B, CU_TENSOR_MAP_L2_PROMOTION_L2_256B, CU_TENSOR_MAP_FLOAT_OOB_FILL_NONE);
        }
        mp.wk16 = make_map(fn, A_Wk, HD, DM, 64, 64);
        mp.wv16 = make_map(fn, A_Wv, HD, DM, 64, 64);
        mp.wo128 = make_wo_map(fn, A_Wo, HD, 4);
        for (int i = 0; i < 2; i++) {
            cuuint64_t dims[3] = {64, S_TOK, DM / 64};
            cuuint64_t strides[2] = {DM * 2, 128};
            cuuint32_t box[3] = {32, 32, 2u - i};
            cuuint32_t es[3] = {1, 1, 1};
            fn(&mp.x32.m[i], CU_TENSOR_MAP_DATA_TYPE_BFLOAT16, 3, const_cast<bf16*>(A_x), dims, strides, box, es,
               CU_TENSOR_MAP_INTERLEAVE_NONE, CU_TENSOR_MAP_SWIZZLE_64B, CU_TENSOR_MAP_L2_PROMOTION_L2_128B, CU_TENSOR_MAP_FLOAT_OOB_FILL_NONE);
        }
        for (int i = 0; i < 10; i++) cached[i] = cur[i];
    }

    cudaStream_t st = cudaStreamPerThread;
    int4 tq = make_int4(100, 200, 700, 60), tk = make_int4(50, 300, 800, 40);
    int2 t0 = make_int2(13000, 16000);
    cudaLaunchConfig_t cfg = {};
    cfg.gridDim = dim3(96); cfg.blockDim = dim3(384); cfg.dynamicSmemBytes = R_SMEM; cfg.stream = st;
    cudaLaunchAttribute at[1];
    at[0].id = cudaLaunchAttributeClusterDimension;
    at[0].val.clusterDim.x = 3; at[0].val.clusterDim.y = 1; at[0].val.clusterDim.z = 1;
    cfg.attrs = at; cfg.numAttrs = 1;
    cudaLaunchKernelEx(&cfg, k_rec, mp.post, mp.wk16, mp.wv16, mp.wo128, mp.x32, A_mem, A_x, tq, tk, t0, 1);
    cfg.gridDim = dim3(mp.post.list.nworker - 96);
    at[0].id = cudaLaunchAttributeProgrammaticStreamSerialization;
    at[0].val.programmaticStreamSerializationAllowed = 1;
    cudaLaunchKernelEx(&cfg, k_rec, mp.post, mp.wk16, mp.wv16, mp.wo128, mp.x32, A_mem, A_x, tq, tk, t0, 0);
}
```

```cpp
#include <cuda_runtime.h>
#include <cuda_bf16.h>
#include <cuda.h>
#include <stdint.h>

typedef __nv_bfloat16 bf16;

constexpr int S_TOK = 2048;
constexpr int DM    = 1024;
constexpr int NH    = 32;
constexpr int DH    = 128;
constexpr int NSEG  = 64;
constexpr int HD    = NH * DH;

__device__ __align__(1024) bf16 g_qx[NSEG * NH * 4 * DH * 8];
__device__ __align__(1024) bf16 g_ox[S_TOK * HD];
__device__ __align__(1024) bf16 g_bqkv[S_TOK * 3 * DM];
__device__ __align__(1024) bf16 g_bo[S_TOK * DM];
__device__ __align__(1024) uint8_t g_acc[192 * 1024];

#define EV(cond, s, k) do {} while (0)
#define EVCAL(s) do {} while (0)

constexpr int P_NSK = 4;
__device__ unsigned g_epoch, g_qctr, g_done, g_zero;
enum { C_B1 = 0, C_B2 = 8, C_Q = 16, C_QH = 24, C_NONE = 31 };
__device__ unsigned g_cnt[32], g_prog[32], g_cnt_sk[P_NSK * 32];
constexpr int P_SPLIT = 4;
__device__ __align__(1024) uint4 g_skp[P_NSK * 8 * P_SPLIT * 2 * 8 * 128];
#define TLOG(i, k, v) do {} while (0)

#define DEVI __device__ __forceinline__

DEVI uint32_t opaque(uint32_t v) { uint32_t r; asm volatile("mov.u32 %0, %1;" : "=r"(r) : "r"(v)); return r; }
DEVI uint32_t smem_u32(const void* p) { return (uint32_t)__cvta_generic_to_shared(p); }

constexpr int SPIN_LIMIT = 1 << 22;
#define MBAR_HINT_NS 20000u
constexpr int SPIN_LIMIT_MBAR = 1 << 17;

DEVI void mbar_init(uint32_t bar, uint32_t cnt) { asm volatile("mbarrier.init.shared::cta.b64 [%0], %1;" :: "r"(bar), "r"(cnt)); }
DEVI void mbar_expect_tx(uint32_t bar, uint32_t bytes) {
    asm volatile("mbarrier.arrive.expect_tx.shared::cta.b64 _, [%0], %1;" :: "r"(bar), "r"(bytes) : "memory");
}
DEVI void mbar_arrive(uint32_t bar) { asm volatile("mbarrier.arrive.shared::cta.b64 _, [%0];" :: "r"(bar) : "memory"); }
DEVI bool mbar_try(uint32_t bar, uint32_t parity) {
    uint32_t ok;
    asm volatile("{.reg .pred p; mbarrier.try_wait.parity.shared::cta.b64 p, [%1], %2; selp.u32 %0, 1, 0, p;}"
                 : "=r"(ok) : "r"(bar), "r"(parity) : "memory");
    return ok;
}
DEVI bool mbar_try_hint(uint32_t bar, uint32_t parity) {
    uint32_t ok;
    asm volatile("{.reg .pred p; mbarrier.try_wait.parity.shared::cta.b64 p, [%1], %2, %3; selp.u32 %0, 1, 0, p;}"
                 : "=r"(ok) : "r"(bar), "r"(parity), "r"(MBAR_HINT_NS) : "memory");
    return ok;
}
DEVI bool mbar_test(uint32_t bar, uint32_t parity) {
    uint32_t ok;
    asm volatile("{.reg .pred p; mbarrier.test_wait.parity.shared::cta.b64 p, [%1], %2; selp.u32 %0, 1, 0, p;}"
                 : "=r"(ok) : "r"(bar), "r"(parity) : "memory");
    return ok;
}
DEVI void mbar_wait(uint32_t bar, uint32_t parity) {
    int n = 0;
    while (!mbar_try(bar, parity)) { if (++n > SPIN_LIMIT) __trap(); }
}
DEVI void mbar_wait_sleepy(uint32_t bar, uint32_t parity) {
    int n = 0;
    while (!mbar_try_hint(bar, parity)) { if (++n > SPIN_LIMIT_MBAR) __trap(); }
}
DEVI void fence_mbar_init() { asm volatile("fence.mbarrier_init.release.cluster;" ::: "memory"); }
DEVI void fence_proxy_async() { asm volatile("fence.proxy.async.shared::cta;" ::: "memory"); }
DEVI bool elect_one() {
    uint32_t e; asm volatile("{.reg .pred p; elect.sync _|p, 0xffffffff; selp.u32 %0, 1, 0, p;}" : "=r"(e)); return e;
}
DEVI void fence_proxy_global() { asm volatile("fence.proxy.async.global;" ::: "memory"); }
DEVI void cluster_wait() { asm volatile("barrier.cluster.wait.acquire.aligned;" ::: "memory"); }
DEVI void nbar_sync(int id, int n) { asm volatile("bar.sync %0, %1;" :: "r"(id), "r"(n) : "memory"); }
DEVI void nbar_arrive(int id, int n) { asm volatile("bar.arrive %0, %1;" :: "r"(id), "r"(n) : "memory"); }

DEVI void tma_load_2d(uint32_t dst, const CUtensorMap* map, int x, int y, uint32_t bar) {
    asm volatile("cp.async.bulk.tensor.2d.shared::cluster.global.mbarrier::complete_tx::bytes [%0], [%1, {%3, %4}], [%2];"
                 :: "r"(dst), "l"(map), "r"(bar), "r"(x), "r"(y) : "memory");
}
DEVI void tma_load_3d(uint32_t dst, const CUtensorMap* map, int x, int y, int z, uint32_t bar) {
    asm volatile("cp.async.bulk.tensor.3d.shared::cluster.global.mbarrier::complete_tx::bytes [%0], [%1, {%3, %4, %5}], [%2];"
                 :: "r"(dst), "l"(map), "r"(bar), "r"(x), "r"(y), "r"(z) : "memory");
}
DEVI void tma_load_wo(uint32_t dst, const CUtensorMap* map, int col, int k32, uint32_t bar) {
    asm volatile("cp.async.bulk.tensor.5d.shared::cluster.global.mbarrier::complete_tx::bytes [%0], [%1, {%3, %5, %5, %5, %4}], [%2];"
                 :: "r"(dst), "l"(map), "r"(bar), "r"(col), "r"(k32), "r"(0) : "memory");
}
DEVI void tma_store_2d(const CUtensorMap* map, uint32_t src, int x, int y) {
    asm volatile("cp.async.bulk.tensor.2d.global.shared::cta.bulk_group [%0, {%2, %3}], [%1];"
                 :: "l"(map), "r"(src), "r"(x), "r"(y) : "memory");
}
DEVI void bulk_load(uint32_t dst, const void* src, uint32_t bytes, uint32_t bar) {
    asm volatile("cp.async.bulk.shared::cluster.global.mbarrier::complete_tx::bytes [%0], [%1], %2, [%3];"
                 :: "r"(dst), "l"(src), "r"(bytes), "r"(bar) : "memory");
}
DEVI void bulk_copy_s2c(uint32_t dst_cluster, uint32_t src, uint32_t bytes, uint32_t bar_cluster) {
    asm volatile("cp.async.bulk.shared::cluster.shared::cta.mbarrier::complete_tx::bytes [%0], [%1], %2, [%3];"
                 :: "r"(dst_cluster), "r"(src), "r"(bytes), "r"(bar_cluster) : "memory");
}
DEVI void bulk_wait_read() { asm volatile("cp.async.bulk.wait_group.read 0;" ::: "memory"); }
DEVI void mbar_arrive_remote(uint32_t bar_cluster) {
    asm volatile("mbarrier.arrive.shared::cluster.b64 _, [%0];" :: "r"(bar_cluster) : "memory");
}
DEVI void l2_prefetch(const void* p, uint32_t bytes) {
    asm volatile("cp.async.bulk.prefetch.L2.global [%0], %1;" :: "l"(p), "r"(bytes) : "memory");
}
DEVI void bulk_commit() { asm volatile("cp.async.bulk.commit_group;" ::: "memory"); }
DEVI void bulk_wait_all() { asm volatile("cp.async.bulk.wait_group 0;" ::: "memory"); }

DEVI void wg_fence() { asm volatile("wgmma.fence.sync.aligned;" ::: "memory"); }
DEVI void wg_commit() { asm volatile("wgmma.commit_group.sync.aligned;" ::: "memory"); }
template <int N> DEVI void wg_wait() { asm volatile("wgmma.wait_group.sync.aligned %0;" :: "n"(N) : "memory"); }

template <int R> DEVI void reg_dec() { asm volatile("setmaxnreg.dec.sync.aligned.u32 %0;" :: "n"(R)); }
template <int R> DEVI void reg_inc() { asm volatile("setmaxnreg.inc.sync.aligned.u32 %0;" :: "n"(R)); }

DEVI uint64_t mk_desc(uint32_t addr, uint32_t lbo, uint32_t sbo, uint32_t sw) {
    return (uint64_t)((addr & 0x3FFFF) >> 4) | ((uint64_t)(lbo >> 4) << 16) | ((uint64_t)(sbo >> 4) << 32) | ((uint64_t)sw << 62);
}

constexpr uint32_t DHI_SW128 = (1024u >> 4) | (1u << 30);
constexpr uint32_t DHI_SW64  = (512u >> 4) | (2u << 30);
constexpr uint32_t DHI_NONE  = (128u >> 4);

template <int TB, int SCALE_D>
DEVI void wgmma_n8_ss(float* d, uint32_t alo, uint32_t blo) {
    asm volatile("{.reg .b64 da, db; mov.b64 da, {%4, %6}; mov.b64 db, {%5, %7};\n"
                 "wgmma.mma_async.sync.aligned.m64n8k16.f32.bf16.bf16 {%0,%1,%2,%3}, da, db, %8, 1, 1, 1, %9;}"
                 : "+f"(d[0]), "+f"(d[1]), "+f"(d[2]), "+f"(d[3])
                 : "r"(alo), "r"(blo), "n"(DHI_SW128), "n"(DHI_NONE), "n"(SCALE_D), "n"(TB));
}

template <int TB>
DEVI void wgmma_n8_ss_first(float* d, uint32_t alo, uint32_t blo) {
    asm volatile("{.reg .b64 da, db; mov.b64 da, {%4, %6}; mov.b64 db, {%5, %7};\n"
                 "wgmma.mma_async.sync.aligned.m64n8k16.f32.bf16.bf16 {%0,%1,%2,%3}, da, db, 0, 1, 1, 1, %8;}"
                 : "=f"(d[0]), "=f"(d[1]), "=f"(d[2]), "=f"(d[3])
                 : "r"(alo), "r"(blo), "n"(DHI_SW128), "n"(DHI_NONE), "n"(TB));
}
DEVI void wgmma_n32_rs_first(float* d, const uint32_t* a, uint32_t blo) {
    asm volatile("{.reg .b64 db; mov.b64 db, {%20, %21};\n"
                 "wgmma.mma_async.sync.aligned.m64n32k16.f32.bf16.bf16 {%0,%1,%2,%3,%4,%5,%6,%7,%8,%9,%10,%11,%12,%13,%14,%15}, "
                 "{%16,%17,%18,%19}, db, 0, 1, 1, 0;}"
                 : "=f"(d[0]), "=f"(d[1]), "=f"(d[2]), "=f"(d[3]), "=f"(d[4]), "=f"(d[5]), "=f"(d[6]), "=f"(d[7]),
                   "=f"(d[8]), "=f"(d[9]), "=f"(d[10]), "=f"(d[11]), "=f"(d[12]), "=f"(d[13]), "=f"(d[14]), "=f"(d[15])
                 : "r"(a[0]), "r"(a[1]), "r"(a[2]), "r"(a[3]), "r"(blo), "n"(DHI_SW64));
}
template <int N> DEVI void reg_fence(float* d) {
#pragma unroll
    for (int i = 0; i < N; i++) asm volatile("" : "+f"(d[i]) :: "memory");
}
DEVI void wgmma_n32_rs(float* d, const uint32_t* a, uint32_t blo) {
    asm volatile("{.reg .b64 db; mov.b64 db, {%20, %21};\n"
                 "wgmma.mma_async.sync.aligned.m64n32k16.f32.bf16.bf16 {%0,%1,%2,%3,%4,%5,%6,%7,%8,%9,%10,%11,%12,%13,%14,%15}, "
                 "{%16,%17,%18,%19}, db, 1, 1, 1, 0;}"
                 : "+f"(d[0]), "+f"(d[1]), "+f"(d[2]), "+f"(d[3]), "+f"(d[4]), "+f"(d[5]), "+f"(d[6]), "+f"(d[7]),
                   "+f"(d[8]), "+f"(d[9]), "+f"(d[10]), "+f"(d[11]), "+f"(d[12]), "+f"(d[13]), "+f"(d[14]), "+f"(d[15])
                 : "r"(a[0]), "r"(a[1]), "r"(a[2]), "r"(a[3]), "r"(blo), "n"(DHI_SW64));
}
DEVI void wgmma_n32_ss(float* d, uint32_t alo, uint32_t blo) {
    asm volatile("{.reg .b64 da, db; mov.b64 da, {%16, %18}; mov.b64 db, {%17, %19};\n"
                 "wgmma.mma_async.sync.aligned.m64n32k16.f32.bf16.bf16 {%0,%1,%2,%3,%4,%5,%6,%7,%8,%9,%10,%11,%12,%13,%14,%15}, "
                 "da, db, 1, 1, 1, 1, 0;}"
                 : "+f"(d[0]), "+f"(d[1]), "+f"(d[2]), "+f"(d[3]), "+f"(d[4]), "+f"(d[5]), "+f"(d[6]), "+f"(d[7]),
                   "+f"(d[8]), "+f"(d[9]), "+f"(d[10]), "+f"(d[11]), "+f"(d[12]), "+f"(d[13]), "+f"(d[14]), "+f"(d[15])
                 : "r"(alo), "r"(blo), "n"(DHI_SW128), "n"(DHI_SW64));
}

template <bool FIRST>
DEVI void wgmma_n256_ss(float* d, uint64_t a, uint64_t b) {
    if (FIRST)
        asm volatile("wgmma.mma_async.sync.aligned.m64n256k16.f32.bf16.bf16 {%0,%1,%2,%3,%4,%5,%6,%7,%8,%9,%10,%11,%12,%13,%14,%15,%16,%17,%18,%19,%20,%21,%22,%23,%24,%25,%26,%27,%28,%29,%30,%31,%32,%33,%34,%35,%36,%37,%38,%39,%40,%41,%42,%43,%44,%45,%46,%47,%48,%49,%50,%51,%52,%53,%54,%55,%56,%57,%58,%59,%60,%61,%62,%63,%64,%65,%66,%67,%68,%69,%70,%71,%72,%73,%74,%75,%76,%77,%78,%79,%80,%81,%82,%83,%84,%85,%86,%87,%88,%89,%90,%91,%92,%93,%94,%95,%96,%97,%98,%99,%100,%101,%102,%103,%104,%105,%106,%107,%108,%109,%110,%111,%112,%113,%114,%115,%116,%117,%118,%119,%120,%121,%122,%123,%124,%125,%126,%127}, %128, %129, 0, 1, 1, 1, 0;"
            : "=f"(d[0]), "=f"(d[1]), "=f"(d[2]), "=f"(d[3]), "=f"(d[4]), "=f"(d[5]), "=f"(d[6]), "=f"(d[7]), "=f"(d[8]), "=f"(d[9]), "=f"(d[10]), "=f"(d[11]), "=f"(d[12]), "=f"(d[13]), "=f"(d[14]), "=f"(d[15]), "=f"(d[16]), "=f"(d[17]), "=f"(d[18]), "=f"(d[19]), "=f"(d[20]), "=f"(d[21]), "=f"(d[22]), "=f"(d[23]), "=f"(d[24]), "=f"(d[25]), "=f"(d[26]), "=f"(d[27]), "=f"(d[28]), "=f"(d[29]), "=f"(d[30]), "=f"(d[31]), "=f"(d[32]), "=f"(d[33]), "=f"(d[34]), "=f"(d[35]), "=f"(d[36]), "=f"(d[37]), "=f"(d[38]), "=f"(d[39]), "=f"(d[40]), "=f"(d[41]), "=f"(d[42]), "=f"(d[43]), "=f"(d[44]), "=f"(d[45]), "=f"(d[46]), "=f"(d[47]), "=f"(d[48]), "=f"(d[49]), "=f"(d[50]), "=f"(d[51]), "=f"(d[52]), "=f"(d[53]), "=f"(d[54]), "=f"(d[55]), "=f"(d[56]), "=f"(d[57]), "=f"(d[58]), "=f"(d[59]), "=f"(d[60]), "=f"(d[61]), "=f"(d[62]), "=f"(d[63]), "=f"(d[64]), "=f"(d[65]), "=f"(d[66]), "=f"(d[67]), "=f"(d[68]), "=f"(d[69]), "=f"(d[70]), "=f"(d[71]), "=f"(d[72]), "=f"(d[73]), "=f"(d[74]), "=f"(d[75]), "=f"(d[76]), "=f"(d[77]), "=f"(d[78]), "=f"(d[79]), "=f"(d[80]), "=f"(d[81]), "=f"(d[82]), "=f"(d[83]), "=f"(d[84]), "=f"(d[85]), "=f"(d[86]), "=f"(d[87]), "=f"(d[88]), "=f"(d[89]), "=f"(d[90]), "=f"(d[91]), "=f"(d[92]), "=f"(d[93]), "=f"(d[94]), "=f"(d[95]), "=f"(d[96]), "=f"(d[97]), "=f"(d[98]), "=f"(d[99]), "=f"(d[100]), "=f"(d[101]), "=f"(d[102]), "=f"(d[103]), "=f"(d[104]), "=f"(d[105]), "=f"(d[106]), "=f"(d[107]), "=f"(d[108]), "=f"(d[109]), "=f"(d[110]), "=f"(d[111]), "=f"(d[112]), "=f"(d[113]), "=f"(d[114]), "=f"(d[115]), "=f"(d[116]), "=f"(d[117]), "=f"(d[118]), "=f"(d[119]), "=f"(d[120]), "=f"(d[121]), "=f"(d[122]), "=f"(d[123]), "=f"(d[124]), "=f"(d[125]), "=f"(d[126]), "=f"(d[127]) : "l"(a), "l"(b));
    else
        asm volatile("wgmma.mma_async.sync.aligned.m64n256k16.f32.bf16.bf16 {%0,%1,%2,%3,%4,%5,%6,%7,%8,%9,%10,%11,%12,%13,%14,%15,%16,%17,%18,%19,%20,%21,%22,%23,%24,%25,%26,%27,%28,%29,%30,%31,%32,%33,%34,%35,%36,%37,%38,%39,%40,%41,%42,%43,%44,%45,%46,%47,%48,%49,%50,%51,%52,%53,%54,%55,%56,%57,%58,%59,%60,%61,%62,%63,%64,%65,%66,%67,%68,%69,%70,%71,%72,%73,%74,%75,%76,%77,%78,%79,%80,%81,%82,%83,%84,%85,%86,%87,%88,%89,%90,%91,%92,%93,%94,%95,%96,%97,%98,%99,%100,%101,%102,%103,%104,%105,%106,%107,%108,%109,%110,%111,%112,%113,%114,%115,%116,%117,%118,%119,%120,%121,%122,%123,%124,%125,%126,%127}, %128, %129, 1, 1, 1, 1, 0;"
            : "+f"(d[0]), "+f"(d[1]), "+f"(d[2]), "+f"(d[3]), "+f"(d[4]), "+f"(d[5]), "+f"(d[6]), "+f"(d[7]), "+f"(d[8]), "+f"(d[9]), "+f"(d[10]), "+f"(d[11]), "+f"(d[12]), "+f"(d[13]), "+f"(d[14]), "+f"(d[15]), "+f"(d[16]), "+f"(d[17]), "+f"(d[18]), "+f"(d[19]), "+f"(d[20]), "+f"(d[21]), "+f"(d[22]), "+f"(d[23]), "+f"(d[24]), "+f"(d[25]), "+f"(d[26]), "+f"(d[27]), "+f"(d[28]), "+f"(d[29]), "+f"(d[30]), "+f"(d[31]), "+f"(d[32]), "+f"(d[33]), "+f"(d[34]), "+f"(d[35]), "+f"(d[36]), "+f"(d[37]), "+f"(d[38]), "+f"(d[39]), "+f"(d[40]), "+f"(d[41]), "+f"(d[42]), "+f"(d[43]), "+f"(d[44]), "+f"(d[45]), "+f"(d[46]), "+f"(d[47]), "+f"(d[48]), "+f"(d[49]), "+f"(d[50]), "+f"(d[51]), "+f"(d[52]), "+f"(d[53]), "+f"(d[54]), "+f"(d[55]), "+f"(d[56]), "+f"(d[57]), "+f"(d[58]), "+f"(d[59]), "+f"(d[60]), "+f"(d[61]), "+f"(d[62]), "+f"(d[63]), "+f"(d[64]), "+f"(d[65]), "+f"(d[66]), "+f"(d[67]), "+f"(d[68]), "+f"(d[69]), "+f"(d[70]), "+f"(d[71]), "+f"(d[72]), "+f"(d[73]), "+f"(d[74]), "+f"(d[75]), "+f"(d[76]), "+f"(d[77]), "+f"(d[78]), "+f"(d[79]), "+f"(d[80]), "+f"(d[81]), "+f"(d[82]), "+f"(d[83]), "+f"(d[84]), "+f"(d[85]), "+f"(d[86]), "+f"(d[87]), "+f"(d[88]), "+f"(d[89]), "+f"(d[90]), "+f"(d[91]), "+f"(d[92]), "+f"(d[93]), "+f"(d[94]), "+f"(d[95]), "+f"(d[96]), "+f"(d[97]), "+f"(d[98]), "+f"(d[99]), "+f"(d[100]), "+f"(d[101]), "+f"(d[102]), "+f"(d[103]), "+f"(d[104]), "+f"(d[105]), "+f"(d[106]), "+f"(d[107]), "+f"(d[108]), "+f"(d[109]), "+f"(d[110]), "+f"(d[111]), "+f"(d[112]), "+f"(d[113]), "+f"(d[114]), "+f"(d[115]), "+f"(d[116]), "+f"(d[117]), "+f"(d[118]), "+f"(d[119]), "+f"(d[120]), "+f"(d[121]), "+f"(d[122]), "+f"(d[123]), "+f"(d[124]), "+f"(d[125]), "+f"(d[126]), "+f"(d[127]) : "l"(a), "l"(b));
}
template <bool FIRST>
DEVI void wgmma_n128_ss(float* d, uint64_t a, uint64_t b) {
    if (FIRST)
        asm volatile("wgmma.mma_async.sync.aligned.m64n128k16.f32.bf16.bf16 {%0,%1,%2,%3,%4,%5,%6,%7,%8,%9,%10,%11,%12,%13,%14,%15,%16,%17,%18,%19,%20,%21,%22,%23,%24,%25,%26,%27,%28,%29,%30,%31,%32,%33,%34,%35,%36,%37,%38,%39,%40,%41,%42,%43,%44,%45,%46,%47,%48,%49,%50,%51,%52,%53,%54,%55,%56,%57,%58,%59,%60,%61,%62,%63}, %64, %65, 0, 1, 1, 1, 0;"
            : "=f"(d[0]), "=f"(d[1]), "=f"(d[2]), "=f"(d[3]), "=f"(d[4]), "=f"(d[5]), "=f"(d[6]), "=f"(d[7]), "=f"(d[8]), "=f"(d[9]), "=f"(d[10]), "=f"(d[11]), "=f"(d[12]), "=f"(d[13]), "=f"(d[14]), "=f"(d[15]), "=f"(d[16]), "=f"(d[17]), "=f"(d[18]), "=f"(d[19]), "=f"(d[20]), "=f"(d[21]), "=f"(d[22]), "=f"(d[23]), "=f"(d[24]), "=f"(d[25]), "=f"(d[26]), "=f"(d[27]), "=f"(d[28]), "=f"(d[29]), "=f"(d[30]), "=f"(d[31]), "=f"(d[32]), "=f"(d[33]), "=f"(d[34]), "=f"(d[35]), "=f"(d[36]), "=f"(d[37]), "=f"(d[38]), "=f"(d[39]), "=f"(d[40]), "=f"(d[41]), "=f"(d[42]), "=f"(d[43]), "=f"(d[44]), "=f"(d[45]), "=f"(d[46]), "=f"(d[47]), "=f"(d[48]), "=f"(d[49]), "=f"(d[50]), "=f"(d[51]), "=f"(d[52]), "=f"(d[53]), "=f"(d[54]), "=f"(d[55]), "=f"(d[56]), "=f"(d[57]), "=f"(d[58]), "=f"(d[59]), "=f"(d[60]), "=f"(d[61]), "=f"(d[62]), "=f"(d[63]) : "l"(a), "l"(b));
    else
        asm volatile("wgmma.mma_async.sync.aligned.m64n128k16.f32.bf16.bf16 {%0,%1,%2,%3,%4,%5,%6,%7,%8,%9,%10,%11,%12,%13,%14,%15,%16,%17,%18,%19,%20,%21,%22,%23,%24,%25,%26,%27,%28,%29,%30,%31,%32,%33,%34,%35,%36,%37,%38,%39,%40,%41,%42,%43,%44,%45,%46,%47,%48,%49,%50,%51,%52,%53,%54,%55,%56,%57,%58,%59,%60,%61,%62,%63}, %64, %65, 1, 1, 1, 1, 0;"
            : "+f"(d[0]), "+f"(d[1]), "+f"(d[2]), "+f"(d[3]), "+f"(d[4]), "+f"(d[5]), "+f"(d[6]), "+f"(d[7]), "+f"(d[8]), "+f"(d[9]), "+f"(d[10]), "+f"(d[11]), "+f"(d[12]), "+f"(d[13]), "+f"(d[14]), "+f"(d[15]), "+f"(d[16]), "+f"(d[17]), "+f"(d[18]), "+f"(d[19]), "+f"(d[20]), "+f"(d[21]), "+f"(d[22]), "+f"(d[23]), "+f"(d[24]), "+f"(d[25]), "+f"(d[26]), "+f"(d[27]), "+f"(d[28]), "+f"(d[29]), "+f"(d[30]), "+f"(d[31]), "+f"(d[32]), "+f"(d[33]), "+f"(d[34]), "+f"(d[35]), "+f"(d[36]), "+f"(d[37]), "+f"(d[38]), "+f"(d[39]), "+f"(d[40]), "+f"(d[41]), "+f"(d[42]), "+f"(d[43]), "+f"(d[44]), "+f"(d[45]), "+f"(d[46]), "+f"(d[47]), "+f"(d[48]), "+f"(d[49]), "+f"(d[50]), "+f"(d[51]), "+f"(d[52]), "+f"(d[53]), "+f"(d[54]), "+f"(d[55]), "+f"(d[56]), "+f"(d[57]), "+f"(d[58]), "+f"(d[59]), "+f"(d[60]), "+f"(d[61]), "+f"(d[62]), "+f"(d[63]) : "l"(a), "l"(b));
}

template <bool FIRST>
DEVI void wgmma_n64_ss(float* d, uint64_t a, uint64_t b) {
    if (FIRST)
        asm volatile("wgmma.mma_async.sync.aligned.m64n64k16.f32.bf16.bf16 {%0,%1,%2,%3,%4,%5,%6,%7,%8,%9,%10,%11,%12,%13,%14,%15,%16,%17,%18,%19,%20,%21,%22,%23,%24,%25,%26,%27,%28,%29,%30,%31}, %32, %33, 0, 1, 1, 1, 0;"
            : "=f"(d[0]), "=f"(d[1]), "=f"(d[2]), "=f"(d[3]), "=f"(d[4]), "=f"(d[5]), "=f"(d[6]), "=f"(d[7]), "=f"(d[8]), "=f"(d[9]), "=f"(d[10]), "=f"(d[11]), "=f"(d[12]), "=f"(d[13]), "=f"(d[14]), "=f"(d[15]), "=f"(d[16]), "=f"(d[17]), "=f"(d[18]), "=f"(d[19]), "=f"(d[20]), "=f"(d[21]), "=f"(d[22]), "=f"(d[23]), "=f"(d[24]), "=f"(d[25]), "=f"(d[26]), "=f"(d[27]), "=f"(d[28]), "=f"(d[29]), "=f"(d[30]), "=f"(d[31]) : "l"(a), "l"(b));
    else
        asm volatile("wgmma.mma_async.sync.aligned.m64n64k16.f32.bf16.bf16 {%0,%1,%2,%3,%4,%5,%6,%7,%8,%9,%10,%11,%12,%13,%14,%15,%16,%17,%18,%19,%20,%21,%22,%23,%24,%25,%26,%27,%28,%29,%30,%31}, %32, %33, 1, 1, 1, 1, 0;"
            : "+f"(d[0]), "+f"(d[1]), "+f"(d[2]), "+f"(d[3]), "+f"(d[4]), "+f"(d[5]), "+f"(d[6]), "+f"(d[7]), "+f"(d[8]), "+f"(d[9]), "+f"(d[10]), "+f"(d[11]), "+f"(d[12]), "+f"(d[13]), "+f"(d[14]), "+f"(d[15]), "+f"(d[16]), "+f"(d[17]), "+f"(d[18]), "+f"(d[19]), "+f"(d[20]), "+f"(d[21]), "+f"(d[22]), "+f"(d[23]), "+f"(d[24]), "+f"(d[25]), "+f"(d[26]), "+f"(d[27]), "+f"(d[28]), "+f"(d[29]), "+f"(d[30]), "+f"(d[31]) : "l"(a), "l"(b));
}

DEVI void mma16816(float* d, const uint32_t* a, uint32_t b0, uint32_t b1) {
    asm volatile("mma.sync.aligned.m16n8k16.row.col.f32.bf16.bf16.f32 {%0,%1,%2,%3}, {%4,%5,%6,%7}, {%8,%9}, {%0,%1,%2,%3};"
                 : "+f"(d[0]), "+f"(d[1]), "+f"(d[2]), "+f"(d[3])
                 : "r"(a[0]), "r"(a[1]), "r"(a[2]), "r"(a[3]), "r"(b0), "r"(b1));
}
DEVI void mma1688(float* d, uint32_t a0, uint32_t a1, uint32_t b0) {
    asm volatile("mma.sync.aligned.m16n8k8.row.col.f32.bf16.bf16.f32 {%0,%1,%2,%3}, {%4,%5}, {%6}, {%0,%1,%2,%3};"
                 : "+f"(d[0]), "+f"(d[1]), "+f"(d[2]), "+f"(d[3]) : "r"(a0), "r"(a1), "r"(b0));
}
DEVI void ldsm4(uint32_t* r, uint32_t addr) {
    asm volatile("ldmatrix.sync.aligned.m8n8.x4.shared.b16 {%0,%1,%2,%3}, [%4];"
                 : "=r"(r[0]), "=r"(r[1]), "=r"(r[2]), "=r"(r[3]) : "r"(addr) : "memory");
}
DEVI void ldsm4t(uint32_t* r, uint32_t addr) {
    asm volatile("ldmatrix.sync.aligned.m8n8.x4.trans.shared.b16 {%0,%1,%2,%3}, [%4];"
                 : "=r"(r[0]), "=r"(r[1]), "=r"(r[2]), "=r"(r[3]) : "r"(addr) : "memory");
}
DEVI void stsm4(uint32_t addr, uint32_t r0, uint32_t r1, uint32_t r2, uint32_t r3) {
    asm volatile("stmatrix.sync.aligned.m8n8.x4.shared.b16 [%0], {%1,%2,%3,%4};" :: "r"(addr), "r"(r0), "r"(r1), "r"(r2), "r"(r3) : "memory");
}
DEVI void stsm4t(uint32_t addr, uint32_t r0, uint32_t r1, uint32_t r2, uint32_t r3) {
    asm volatile("stmatrix.sync.aligned.m8n8.x4.trans.shared.b16 [%0], {%1,%2,%3,%4};" :: "r"(addr), "r"(r0), "r"(r1), "r"(r2), "r"(r3) : "memory");
}
DEVI uint32_t pack_bf16(float lo, float hi) {
    uint32_t r; asm("cvt.rn.bf16x2.f32 %0, %1, %2;" : "=r"(r) : "f"(hi), "f"(lo)); return r;
}
DEVI float ex2(float x) { float y; asm("ex2.approx.ftz.f32 %0, %1;" : "=f"(y) : "f"(x)); return y; }

DEVI uint4 ld_rlx4(const void* p) {
    uint4 v;
    asm volatile("ld.relaxed.gpu.global.v4.u32 {%0,%1,%2,%3}, [%4];" : "=r"(v.x), "=r"(v.y), "=r"(v.z), "=r"(v.w) : "l"(p) : "memory");
    return v;
}
DEVI void st_rlx4(void* p, uint32_t a, uint32_t b, uint32_t c, uint32_t d) {
    asm volatile("st.relaxed.gpu.global.v4.u32 [%0], {%1,%2,%3,%4};" :: "l"(p), "r"(a), "r"(b), "r"(c), "r"(d) : "memory");
}
DEVI void sts128(uint32_t addr, uint4 v) {
    asm volatile("st.shared.v4.u32 [%0], {%1,%2,%3,%4};" :: "r"(addr), "r"(v.x), "r"(v.y), "r"(v.z), "r"(v.w) : "memory");
}
DEVI void sts64(uint32_t addr, uint32_t a, uint32_t b) { asm volatile("st.shared.v2.u32 [%0], {%1,%2};" :: "r"(addr), "r"(a), "r"(b) : "memory"); }
DEVI void sts32(uint32_t addr, uint32_t v) { asm volatile("st.shared.u32 [%0], %1;" :: "r"(addr), "r"(v) : "memory"); }
DEVI uint4 lds128(uint32_t addr) {
    uint4 v; asm volatile("ld.shared.v4.u32 {%0,%1,%2,%3}, [%4];" : "=r"(v.x), "=r"(v.y), "=r"(v.z), "=r"(v.w) : "r"(addr) : "memory"); return v;
}
DEVI float2 lds64f(uint32_t addr) {
    float2 v; asm volatile("ld.shared.v2.f32 {%0,%1}, [%2];" : "=f"(v.x), "=f"(v.y) : "r"(addr) : "memory"); return v;
}
DEVI uint32_t lds32(uint32_t addr) { uint32_t v; asm volatile("ld.shared.u32 %0, [%1];" : "=r"(v) : "r"(addr) : "memory"); return v; }
DEVI float rcp_fast(float x) { float y; asm("rcp.approx.ftz.f32 %0, %1;" : "=f"(y) : "f"(x)); return y; }
DEVI uint32_t mapa(uint32_t addr, uint32_t rank) {
    uint32_t r; asm("mapa.shared::cluster.u32 %0, %1, %2;" : "=r"(r) : "r"(addr), "r"(rank)); return r;
}
DEVI void st_async32(uint32_t dst, uint32_t a, uint32_t bar) {
    asm volatile("st.async.weak.shared::cluster.mbarrier::complete_tx::bytes.b32 [%0], %1, [%2];" :: "r"(dst), "r"(a), "r"(bar) : "memory");
}

DEVI void st_async128(uint32_t dst, uint32_t a, uint32_t b, uint32_t c, uint32_t d, uint32_t bar) {
    asm volatile("st.async.weak.shared::cluster.mbarrier::complete_tx::bytes.v4.b32 [%0], {%1,%2,%3,%4}, [%5];"
                 :: "r"(dst), "r"(a), "r"(b), "r"(c), "r"(d), "r"(bar) : "memory");
}

DEVI uint32_t b_addr(uint32_t sb, int row, int which, int chunk) { const int l = 3 * row + which; return sb + l * 128 + ((chunk ^ (l & 7)) * 16); }
DEVI void battn_warp(uint32_t st, uint32_t ebar, int i0, int par, int head, int hh, int mt, int lane) {
    const int gq = lane >> 2, t = lane & 3, r = 16 * mt + (lane & 7), b3 = (lane >> 3) & 1, b4 = lane >> 4;
    uint32_t a[8], k[8], k2[4], v[8], v2[4];
#pragma unroll
    for (int ks = 0; ks < 2; ks++) {
        ldsm4(a + 4 * ks, b_addr(st, 8 + r + b3 * 8, 0, hh * 4 + ks * 2 + b4));
        ldsm4(k + 4 * ks, b_addr(st, r + b4 * 8, 1, hh * 4 + ks * 2 + b3));
    }
    ldsm4(k2, b_addr(st, r + 16, 1, hh * 4 + (lane >> 3)));
#pragma unroll
    for (int n = 0; n < 2; n++) ldsm4t(v + 4 * n, b_addr(st, r + b3 * 8, 2, hh * 4 + 2 * n + b4));
    ldsm4t(v2, b_addr(st, r + 16, 2, hh * 4 + (lane >> 3)));
    float s[3][4];
#pragma unroll
    for (int n = 0; n < 3; n++) { s[n][0] = s[n][1] = s[n][2] = s[n][3] = 0.f; }
#pragma unroll
    for (int ks = 0; ks < 2; ks++) {
        mma16816(s[0], a + 4 * ks, k[4 * ks], k[4 * ks + 1]);
        mma16816(s[1], a + 4 * ks, k[4 * ks + 2], k[4 * ks + 3]);
        mma16816(s[2], a + 4 * ks, k2[2 * ks], k2[2 * ks + 1]);
    }
    const bool ex = i0 + 16 * mt > 0;
    float x[4], y[4];
#pragma unroll
    for (int c = 0; c < 2; c++) {
        const bool low = 2 * t + c <= gq;
        x[c] = !low && ex ? s[0][c] : -INFINITY; x[2 + c] = low ? s[1][c] : -INFINITY;
        y[c] = !low ? s[1][2 + c] : -INFINITY;   y[2 + c] = low ? s[2][2 + c] : -INFINITY;
    }
    float m0 = fmaxf(fmaxf(x[0], x[1]), fmaxf(x[2], x[3])), m1 = fmaxf(fmaxf(y[0], y[1]), fmaxf(y[2], y[3]));
    m0 = fmaxf(fmaxf(m0, __shfl_xor_sync(0xffffffffu, m0, 1)), fmaxf(__shfl_xor_sync(0xffffffffu, m0, 2), __shfl_xor_sync(0xffffffffu, m0, 3)));
    m1 = fmaxf(fmaxf(m1, __shfl_xor_sync(0xffffffffu, m1, 1)), fmaxf(__shfl_xor_sync(0xffffffffu, m1, 2), __shfl_xor_sync(0xffffffffu, m1, 3)));
    constexpr float C = 0.17677669529663687f * 1.4426950408889634f;
    m0 *= -C; m1 *= -C;
    const uint32_t p0[4] = {pack_bf16(ex2(fmaf(x[0], C, m0)), ex2(fmaf(x[1], C, m0))), 0u,
                            pack_bf16(ex2(fmaf(x[2], C, m0)), ex2(fmaf(x[3], C, m0))), pack_bf16(ex2(fmaf(y[0], C, m1)), ex2(fmaf(y[1], C, m1)))};
    const uint32_t p1 = pack_bf16(ex2(fmaf(y[2], C, m1)), ex2(fmaf(y[3], C, m1)));
    float o[4][4], l[4] = {0.f, 0.f, 0.f, 0.f};
#pragma unroll
    for (int n = 0; n < 4; n++) { o[n][0] = o[n][1] = o[n][2] = o[n][3] = 0.f; }
    mma16816(l, p0, 0x3F803F80u, 0x3F803F80u);
#pragma unroll
    for (int n = 0; n < 4; n++) mma16816(o[n], p0, v[2 * n], v[2 * n + 1]);
    mma1688(l, 0u, p1, 0x3F803F80u);
#pragma unroll
    for (int n = 0; n < 4; n++) mma1688(o[n], 0u, p1, v2[n]);
    if (lane == 0) mbar_arrive(ebar);
    const float i0f = rcp_fast(l[0]), i1f = rcp_fast(l[2]);
    uint4* dst = (uint4*)(g_bo + (uint32_t)((2 * (i0 + 16 * mt + gq) + par) * DM + head * 32 + t * 8));
    dst[0] = make_uint4(pack_bf16(o[0][0] * i0f, o[0][1] * i0f), pack_bf16(o[1][0] * i0f, o[1][1] * i0f),
                        pack_bf16(o[2][0] * i0f, o[2][1] * i0f), pack_bf16(o[3][0] * i0f, o[3][1] * i0f));
    dst[16 * DM / 8] = make_uint4(pack_bf16(o[0][2] * i1f, o[0][3] * i1f), pack_bf16(o[1][2] * i1f, o[1][3] * i1f),
                                  pack_bf16(o[2][2] * i1f, o[2][3] * i1f), pack_bf16(o[3][2] * i1f, o[3][3] * i1f));
}

constexpr float SCALE_LOG2E = 0.08838834764831845f * 1.4426950408889634f;

constexpr int P_UNITS = 12, P_STAGES = 6;
constexpr int PS_STG = P_UNITS * 16384;
constexpr int P_SMEM = 232448;
constexpr int PS_BAR = P_SMEM - 256;
static_assert(PS_STG + 32768 <= PS_BAR, "smem");
enum { K_Q, K_B1, K_B3, K_A4, K_QH, K_A3, K_SK, K_B2, K_SN, K_END };
struct PList { int n, nworker, late; int4 run[16]; };
struct PTask { int kind, a, b, c, id; };
DEVI PTask p_decode(const PList& pl, int id) {
    int i = pl.n - 1;
    if (id >= pl.run[i].w) return {K_END, 0, 0, 0, id};
    while (id < pl.run[i].z) i--;
    const int4 r = pl.run[i];
    const int j = id - r.z;
    if (r.x == K_Q || r.x == K_QH) return {r.x, j & 31, r.y + (j >> 5), 0, id};
    if (r.x == K_B1) return {r.x, j % 24, r.y + j / 24, 0, id};
    if (r.x == K_B2) return {r.x, 0, r.y + j, 0, id};
    if (r.x == K_SK || r.x == K_SN) return {r.x, (j / P_SPLIT) & 7, r.y + j / (8 * P_SPLIT), j % P_SPLIT, id};
    return {r.x, j & 7, r.y + (j >> 3), 0, id};
}
DEVI void wait_count_warp(const unsigned* p, unsigned target) {
    int n = 0;
    while (true) {
        unsigned v; asm volatile("ld.acquire.gpu.global.u32 %0, [%1];" : "=r"(v) : "l"(p) : "memory");
        if (__all_sync(0xffffffffu, (int)(v - target) >= 0)) break;
        __nanosleep(100);
        if (++n > SPIN_LIMIT) __trap();
    }
}
DEVI void signal_count(unsigned* p) { __threadfence(); atomicAdd(p, 1u); }

struct PMaps { CUtensorMap wq, bw, bwo, wo, x, bx, bo, ox, ox64, cb, cout, cq, b40; PList list; };
constexpr int PB_F = PS_BAR, PB_E = PB_F + 48, PB_TF = PB_F + 96, PB_TE = PB_F + 112, PB_S = PB_F + 128;
constexpr int PS_T = PB_F + 160, PS_SIG = PS_T + 32, PS_SK = PS_SIG + 16;

struct PRing {
    int st, ph, u;
    DEVI void next(int n) { u += n; if (u >= P_UNITS) u -= P_UNITS; if (++st == P_STAGES) { st = 0; ph ^= 1; } }
    DEVI uint32_t w(bool wide) const { return wide && u == P_UNITS - 2 ? 0u : u * 16384u; }
    DEVI uint32_t x(bool wide) const { return wide && u == P_UNITS - 2 ? u * 16384u : (u == P_UNITS - 1 ? 0u : (u + 1) * 16384u); }
};
struct POut { const CUtensorMap* map; int col, tok, cnt; bool blocked; };
DEVI void p_store(const uint32_t* pk, const POut& o, int c, uint32_t stg, int warp, int lane_, int barid) {
    const int lane = (int)opaque((uint32_t)lane_);
    const int mi = lane >> 3, r = lane & 7;
    const uint32_t buf = stg + (c & 1) * 8192;
    if (warp == 0) asm volatile("cp.async.bulk.wait_group.read 1;" ::: "memory");
    nbar_sync(barid, 128);
    if (o.blocked) {
#pragma unroll
        for (int j = 0; j < 8; j += 2)
            stsm4(buf + (j + (mi >> 1)) * 1024 + (warp * 16 + (mi & 1) * 8 + r) * 16, pk[2 * j], pk[2 * j + 1], pk[2 * j + 2], pk[2 * j + 3]);
    } else {
#pragma unroll
        for (int j = 0; j < 8; j += 2)
            stsm4t(buf + (8 * (j + (mi >> 1)) + r) * 128 + ((2 * warp + (mi & 1)) ^ r) * 16, pk[2 * j], pk[2 * j + 1], pk[2 * j + 2], pk[2 * j + 3]);
    }
    fence_proxy_async();
    nbar_sync(barid, 128);
    if (warp == 0 && elect_one()) {
        if (o.blocked)
            asm volatile("cp.async.bulk.tensor.4d.global.shared::cta.bulk_group [%0, {%2, %3, %4, %5}], [%1];"
                         :: "l"(o.map), "r"(buf), "r"(0), "r"((o.col >> 5) & 2), "r"((o.col >> 7) * 4), "r"((o.tok >> 5) + 2 * c) : "memory");
        else tma_store_2d(o.map, buf, o.col, o.tok + c * 64);
        bulk_commit();
    }
}
DEVI void p_signal(uint32_t sb, int g, int cnt, int& nsig) {
    if (elect_one()) {
        sts32(sb + PS_SIG + g * 8 + (nsig & 1) * 4, (uint32_t)cnt);
        mbar_arrive(sb + PB_S + g * 16 + (nsig & 1) * 8);
    }
    nsig++;
}
DEVI void p_release(uint32_t sb, const PRing& r) {
    if (elect_one()) mbar_arrive(sb + PB_E + (r.st ? r.st - 1 : P_STAGES - 1) * 8);
}
template <int BN, bool FIRST>
DEVI void p_kblock(float* d, uint32_t sb, int g, PRing& r) {
    mbar_wait(sb + PB_F + r.st * 8, r.ph);
    const uint64_t da = mk_desc(sb + r.w(BN == 256) + g * 8192, 16, 1024, 1), db = mk_desc(sb + r.x(BN == 256), 16, 1024, 1);
    wg_fence();
#pragma unroll
    for (int kk = 0; kk < 4; kk++) {
        if (BN == 256) { if (FIRST && kk == 0) wgmma_n256_ss<true>(d, da, db); else wgmma_n256_ss<false>(d, da + (uint64_t)(kk * 128), db + (uint64_t)(kk * 2)); }
        if (BN == 128) { if (FIRST && kk == 0) wgmma_n128_ss<true>(d, da, db); else wgmma_n128_ss<false>(d, da + (uint64_t)(kk * 128), db + (uint64_t)(kk * 2)); }
        if (BN == 64)  { if (FIRST && kk == 0) wgmma_n64_ss<true>(d, da, db); else wgmma_n64_ss<false>(d, da + (uint64_t)(kk * 128), db + (uint64_t)(kk * 2)); }
    }
    wg_commit();
    if (!FIRST) {
        wg_wait<1>();
        p_release(sb, r);
    }
    r.next(BN == 256 ? 3 : 2);
}

DEVI PTask post_claim(const PMaps& mp, unsigned E) {
    unsigned v = 0;
    if ((threadIdx.x & 31) == 0) v = atomicAdd(&g_qctr, 1u);
    return p_decode(mp.list, (int)(__shfl_sync(0xffffffffu, v, 0) - (E - 1) * (unsigned)(mp.list.run[mp.list.n - 1].w + mp.list.nworker)));
}
DEVI void post_producer(const PMaps& mp, uint32_t sb, unsigned E, bool early) {
    PRing r = {0, 0, 0};
    int ts = 0, tp = 0, used = 0;
    uint32_t big = 0;
    auto reserve = [&](int n) {
        while (used + n > P_UNITS) {
            mbar_wait(sb + PB_E + ts * 8, tp);
            used -= 2 + ((big >> ts) & 1);
            if (++ts == P_STAGES) { ts = 0; tp ^= 1; }
        }
        used += n;
        big = (big & ~(1u << r.st)) | ((uint32_t)(n & 1) << r.st);
    };
    for (int i = 0;; i++) {
        if (i > 0) mbar_wait(sb + PB_TE + (i & 1) * 8, ((i >> 1) & 1) ^ 1);
        else if (!early) nbar_sync(0, 384);
        const PTask tk = post_claim(mp, E);
        if (i == 0) { if (early) nbar_sync(0, 384); fence_proxy_async(); }
        const bool sn = tk.kind == K_SN, split = tk.kind == K_SK || sn, wide = tk.kind <= K_A4;
        const bool qk = tk.kind == K_Q || tk.kind == K_QH, ak = tk.kind == K_A4 || tk.kind == K_A3 || split;
        const int nk = split ? HD / 64 / P_SPLIT : (ak ? HD / 64 : DM / 64), kb0 = tk.c * (HD / 64 / P_SPLIT);
        const int tok0 = tk.b * (wide ? 256 : (sn ? 64 : 128)), grp = (tok0 >> 6) + (wide ? 3 : (sn ? 0 : 1));
        const uint32_t bytes = wide ? 49152 : (sn ? 24576 : 32768);
        const CUtensorMap* tx = tk.kind == K_B1 ? &mp.bx : (qk ? &mp.x : (sn ? &mp.ox64 : (ak ? &mp.ox : &mp.bo)));
        const int npre = split && (i == 0 || __any_sync(0xffffffffu, (int)(*(volatile unsigned*)&g_prog[grp] - 64 * E) < 0)) ? P_STAGES : 0;
        PRing rp = r;
        for (int kb = kb0; kb < kb0 + npre; kb++) {
            reserve(2);
            const uint32_t bar = sb + PB_F + r.st * 8;
            if (elect_one()) {
                mbar_expect_tx(bar, bytes);
                tma_load_wo(sb + r.w(false), &mp.wo, tk.a * 128, kb * 2, bar);
                tma_load_wo(sb + r.w(false) + 8192, &mp.wo, tk.a * 128 + 64, kb * 2, bar);
            }
            r.next(2);
        }
        if (tk.kind == K_B2) {
            wait_count_warp(&g_cnt[C_B1 + (tk.b >> 2)], 48 * E);
            if ((tk.b & 3) == 0 && tk.b > 0) wait_count_warp(&g_cnt[C_B1 + (tk.b >> 2) - 1], 48 * E);
        } else if (tk.kind == K_B3) wait_count_warp(&g_cnt[C_B2 + tk.b], 8 * E);
        else if (ak) wait_count_warp(&g_prog[grp], 64 * E);
        fence_proxy_global();
        for (int kb = kb0; kb < kb0 + npre; kb++) {
            if (elect_one()) tma_load_2d(sb + rp.x(false), tx, kb * 64, tok0, sb + PB_F + rp.st * 8);
            rp.next(2);
        }
        if (elect_one()) {
            sts128(sb + PS_T + (i & 1) * 16, make_uint4((uint32_t)tk.kind | ((uint32_t)tk.id << 8), (uint32_t)tk.a, (uint32_t)tk.b, (uint32_t)tk.c));
            mbar_arrive(sb + PB_TF + (i & 1) * 8);
        }
        if (tk.kind == K_END) break;
        if (tk.kind == K_B2) {
            for (int j = 0; j < 16; j++) {
                reserve(2);
                const uint32_t bar = sb + PB_F + r.st * 8;
                if (elect_one()) {
                    mbar_expect_tx(bar, 2 * 15360);
#pragma unroll
                    for (int u = 0; u < 2; u++) asm volatile("cp.async.bulk.tensor.4d.shared::cluster.global.mbarrier::complete_tx::bytes [%0], [%1, {%3, %4, %5, %6}], [%2];"
                                 :: "r"(sb + (u ? r.x(false) : r.w(false))), "l"(&mp.b40), "r"(bar), "r"(j * 64), "r"(0), "r"(u), "r"(tk.b * 32 - 8) : "memory");
                }
                r.next(2);
            }
            continue;
        }
        const CUtensorMap* tw = tk.kind == K_B1 ? &mp.bw : (qk ? &mp.wq : (ak ? &mp.wo : &mp.bwo));
        for (int kb = kb0 + npre; kb < kb0 + nk; kb++) {
            reserve(wide ? 3 : 2);
            const uint32_t aw = sb + r.w(wide), ax = sb + r.x(wide), bar = sb + PB_F + r.st * 8;
            if (elect_one()) {
                mbar_expect_tx(bar, bytes);
                if (ak || tk.kind == K_B3) {
                    tma_load_wo(aw, tw, tk.a * 128, kb * 2, bar);
                    tma_load_wo(aw + 8192, tw, tk.a * 128 + 64, kb * 2, bar);
                } else {
                    tma_load_2d(aw, tw, tk.a * 128, kb * 64, bar);
                    tma_load_2d(aw + 8192, tw, tk.a * 128 + 64, kb * 64, bar);
                }
                tma_load_2d(ax, tx, kb * 64, tok0, bar);
                if (wide) tma_load_2d(ax + 16384, tx, kb * 64, tok0 + 128, bar);
            }
            r.next(wide ? 3 : 2);
        }
        if (tk.id >= mp.list.late) { reserve(P_UNITS - 3); used -= P_UNITS - 3; }
    }
    if (elect_one()) {
        __threadfence();
        if (atomicAdd(&g_done, 1u) == E * mp.list.nworker - 1) { __threadfence(); *(volatile unsigned*)&g_epoch = E; }
    }
}
DEVI void post_helper(uint32_t sb, int g) {
    for (int n = 0;; n++) {
        mbar_wait_sleepy(sb + PB_S + g * 16 + (n & 1) * 8, (n >> 1) & 1);
        const int cnt = (int)lds32(sb + PS_SIG + g * 8 + (n & 1) * 4);
        if (cnt < 0) break;
        signal_count(&g_cnt[cnt]);
    }
}
template <int BN>
DEVI void p_narrow(const PMaps& mp, const PTask& tk, uint32_t sb, int g, int warp, PRing& r, int& nsig) {
    const int barid = 1 + g, tid = threadIdx.x;
    const bool split = BN == 64 || tk.kind == K_SK;
    constexpr int NV = BN / 16;
    float d[BN / 2];
    const int nk = split ? HD / 64 / P_SPLIT : (tk.kind == K_A3 ? HD / 64 : DM / 64);
    p_kblock<BN, true>(d, sb, g, r);
#pragma unroll 1
    for (int kb = 1; kb < nk; kb++) p_kblock<BN, false>(d, sb, g, r);
    wg_wait<0>();
    reg_fence<BN / 2>(d);
    p_release(sb, r);
    if (split) {
        const int tile = (tk.b * (BN / 64) - 2 * (16 - P_NSK)) * 8 + tk.a * (BN / 64);
        uint4* const base = g_skp + (uint32_t)(tile * P_SPLIT * 1024 + g * NV * 128 + (tid & 127));
#pragma unroll
        for (int j = 0; j < NV; j++)
            base[tk.c * NV * 256 + j * 128] = make_uint4(pack_bf16(d[8 * j], d[8 * j + 1]), pack_bf16(d[8 * j + 2], d[8 * j + 3]),
                                                         pack_bf16(d[8 * j + 4], d[8 * j + 5]), pack_bf16(d[8 * j + 6], d[8 * j + 7]));
        nbar_sync(barid, 128);
        if (warp == 0 && elect_one()) {
            unsigned old;
            asm volatile("atom.acq_rel.gpu.global.add.u32 %0, [%1], 1;" : "=r"(old) : "l"(&g_cnt_sk[tile * 2 + g]) : "memory");
            sts32(sb + PS_SK + g * 4, old % P_SPLIT);
        }
        nbar_sync(barid, 128);
        const bool last = __any_sync(0xffffffffu, lds32(sb + PS_SK + g * 4) == P_SPLIT - 1);
        nbar_sync(barid, 128);
        if (!last) return;
        uint4 v[(P_SPLIT - 1) * NV];
#pragma unroll
        for (int j = 0; j < (P_SPLIT - 1) * NV; j++) v[j] = __ldcg(base + ((tk.c + 1 + j / NV) % P_SPLIT) * NV * 256 + (j % NV) * 128);
#pragma unroll
        for (int j = 0; j < (P_SPLIT - 1) * NV; j++) {
            float* e = d + 8 * (j % NV);
            e[0] += __uint_as_float(v[j].x << 16); e[1] += __uint_as_float(v[j].x & 0xFFFF0000u);
            e[2] += __uint_as_float(v[j].y << 16); e[3] += __uint_as_float(v[j].y & 0xFFFF0000u);
            e[4] += __uint_as_float(v[j].z << 16); e[5] += __uint_as_float(v[j].z & 0xFFFF0000u);
            e[6] += __uint_as_float(v[j].w << 16); e[7] += __uint_as_float(v[j].w & 0xFFFF0000u);
        }
    }
    const bool qh = BN == 128 && tk.kind == K_QH;
    const POut o = {qh ? &mp.cq : &mp.cout, tk.a * 128 + g * 64, tk.b * BN, 0, qh};
    uint32_t q[BN / 4];
#pragma unroll
    for (int j = 0; j < BN / 4; j++) q[j] = pack_bf16(d[2 * j], d[2 * j + 1]);
    if (BN == 64 && warp == 0) bulk_wait_read();
#pragma unroll
    for (int c = 0; c < BN / 64; c++) p_store(q + 16 * c, o, c, sb + PS_STG + g * 16384, warp, tid & 31, barid);
    if (BN == 64 && warp == 0) bulk_wait_read();
    if (warp == 0 && qh) { bulk_wait_all(); p_signal(sb, g, tk.b == 0 ? C_QH : C_Q, nsig); }
}
DEVI void post_consumer(const PMaps& mp, uint32_t sb, int g, int warp) {
    const int barid = 1 + g, tid = threadIdx.x, lane = tid & 31;
    const uint32_t stg = sb + PS_STG + g * 16384;
    int nsig = 0;
    PRing r = {0, 0, 0};
    uint32_t pk[64];
    POut out;
    bool pend = false;
#pragma unroll
    for (int i = 0; i < 64; i++) pk[i] = 0u;
    for (int i = 0;; i++) {
        const uint32_t bTF = sb + PB_TF + (i & 1) * 8;
        if (pend) {
            uint32_t now;
            asm volatile("{.reg .pred p, q; mbarrier.test_wait.parity.shared::cta.b64 p, [%1], %2; bar.red.and.pred q, %3, 128, p; selp.u32 %0, 1, 0, q;}"
                         : "=r"(now) : "r"(bTF), "r"((i >> 1) & 1), "r"(barid) : "memory");
            if (__any_sync(0xffffffffu, !now || (lds32(sb + PS_T + (i & 1) * 16) & 255u) > K_A4)) {
#pragma unroll
                for (int c = 0; c < 4; c++) p_store(pk + 16 * c, out, c, stg, warp, lane, barid);
                if (warp == 0 && out.cnt != C_NONE) { bulk_wait_all(); p_signal(sb, g, out.cnt, nsig); }
                pend = false;
            }
        }
        mbar_wait(bTF, (i >> 1) & 1);
        uint4 tw = lds128(sb + PS_T + (i & 1) * 16);
        tw = make_uint4(__shfl_sync(0xffffffffu, tw.x, 0), __shfl_sync(0xffffffffu, tw.y, 0), __shfl_sync(0xffffffffu, tw.z, 0), __shfl_sync(0xffffffffu, tw.w, 0));
        mbar_arrive(sb + PB_TE + (i & 1) * 8);
        const PTask tk = {(int)(tw.x & 255u), (int)tw.y, (int)tw.z, (int)tw.w, 0};
        if (tk.kind == K_END) break;
        if (tk.kind <= K_A4) {
            float d[128];
            const int nk = tk.kind == K_A4 ? HD / 64 : DM / 64;
            p_kblock<256, true>(d, sb, g, r);
            if (pend) p_store(pk, out, 0, stg, warp, lane, barid);
#pragma unroll
            for (int c = 1; c < 4; c++) {
                p_kblock<256, false>(d, sb, g, r);
                if (pend) p_store(pk + 16 * c, out, c, stg, warp, lane, barid);
            }
#pragma unroll 1
            for (int kb = 4; kb < nk; kb++) {
                p_kblock<256, false>(d, sb, g, r);
                if (kb == 6 && pend && warp == 0 && out.cnt != C_NONE) { bulk_wait_all(); p_signal(sb, g, out.cnt, nsig); }
            }
            wg_wait<0>();
            reg_fence<128>(d);
            p_release(sb, r);
#pragma unroll
            for (int j = 0; j < 64; j++) pk[j] = pack_bf16(d[2 * j], d[2 * j + 1]);
            out.map = tk.kind == K_Q ? &mp.cq : (tk.kind == K_B1 ? &mp.cb : &mp.cout);
            out.col = tk.a * 128 + g * 64 + (tk.kind == K_B3 ? DM : 0);
            out.tok = tk.b * 256;
            out.cnt = tk.kind == K_Q ? C_Q + tk.b : (tk.kind == K_B1 ? C_B1 + tk.b : C_NONE);
            out.blocked = tk.kind == K_Q;
            pend = true;
        } else if (tk.kind == K_B2) {
#pragma unroll 2
            for (int j = 0; j < 16; j++) {
                mbar_wait(sb + PB_F + r.st * 8, r.ph);
                const uint32_t a = sb + (g ? r.x(false) : r.w(false));
                battn_warp(a, sb + PB_E + r.st * 8, tk.b * 32, g, j * 2 + (warp >> 1), warp >> 1, warp & 1, lane);
                r.next(2);
            }
            nbar_sync(barid, 128);
            if (warp == 0) p_signal(sb, g, C_B2 + (tk.b >> 2), nsig);
#pragma unroll
            for (int j = 0; j < 64; j++) pk[j] = 0u;
        } else {
            if (tk.kind == K_SN) p_narrow<64>(mp, tk, sb, g, warp, r, nsig); else p_narrow<128>(mp, tk, sb, g, warp, r, nsig);
#pragma unroll
            for (int j = 0; j < 64; j++) pk[j] = 0u;
        }
    }
    if (warp == 0) { bulk_wait_all(); p_signal(sb, g, -1, nsig); }
}
DEVI void post_init(uint32_t sb) {
    for (int i = 0; i < P_STAGES; i++) { mbar_init(sb + PB_F + i * 8, 1); mbar_init(sb + PB_E + i * 8, 8); }
    for (int i = 0; i < 2; i++) { mbar_init(sb + PB_TF + i * 8, 1); mbar_init(sb + PB_TE + i * 8, 256); }
    for (int i = 0; i < 4; i++) mbar_init(sb + PB_S + i * 8, 1);
    fence_mbar_init();
}

constexpr unsigned long long R_TORD_PACK = 0xfae93542dc187b60ull;
__host__ __device__ constexpr int r_tord(int pos) { return (int)((R_TORD_PACK >> (4 * pos)) & 15ull); }
__host__ __device__ constexpr int r_tinv(int T) { for (int p = 0; p < 16; p++) if (r_tord(p) == T) return p; return 0; }
__host__ __device__ constexpr bool r_pos_ss(int pos) { return pos % 3 == 2; }
__host__ __device__ constexpr int r_ss(int pos) { return pos / 3; }
__host__ __device__ constexpr int r_rs(int pos) { return pos - pos / 3; }
constexpr int R_NRS = 11, R_NSS = 5;
constexpr int R_G1 = 3, R_G2 = 9, R_G3 = 12;
#define REG_KB 232
constexpr int X_SLOTS = 4;
constexpr int X_NST = 8;

constexpr int RS_WSS  = 0;
constexpr int RS_WO   = RS_WSS + R_NSS * 16384;
constexpr int RS_MEM  = RS_WO + 5 * 16384;
constexpr int RS_O    = RS_MEM + 16384;
constexpr int RS_SX   = RS_O + 2048;
constexpr int RS_BAR  = RS_SX + 2048;
constexpr int RS_TAIL = RS_BAR + 1024;
constexpr int RS_WO5  = RS_TAIL;
constexpr int RS_K    = RS_WO5 + 16384;
constexpr int RS_V    = RS_K + 10240;
constexpr int RS_Q    = RS_V + 10240;
constexpr int RS_QX   = RS_Q + 2048;
constexpr int RS_QEND = RS_QX + 8192;
constexpr int RS_X    = RS_TAIL;
constexpr int X_PITCH = X_SLOTS * 4096;
constexpr int RS_XD   = RS_X + 2 * X_PITCH;
constexpr int RS_WX   = RS_XD + 8192;
constexpr int RS_XE   = RS_WX + 4096;
constexpr int RS_KEND = RS_XE + 2048;
constexpr int RS_EV   = RS_BAR + 256;
constexpr int R_SMEM  = RS_KEND > RS_QEND ? RS_KEND : RS_QEND;
static_assert(R_SMEM <= 232448 && P_SMEM <= R_SMEM, "smem");
static_assert(RS_TAIL % 1024 == 0 && RS_MEM % 1024 == 0, "alignment");

constexpr int RB_G = RS_BAR, RB_K = RS_BAR + 24, RB_V = RS_BAR + 32, RB_KV = RS_BAR + 40, RB_QX = RS_BAR + 48, RB_O = RS_BAR + 56;
constexpr int RB_ATT = RS_BAR + 64, RB_W = RS_BAR + 72, RB_SF = RS_BAR + 80, RB_SE = RB_SF + 40, RB_XF = RB_SE + 40;
constexpr int RB_VX = RB_XF + 48, RB_WO = RB_XF + 56, RB_T = RB_XF + 64, RB_G3 = RB_XF + 72, RS_INV = RB_XF + 16;
static_assert(RB_G3 + 8 <= RS_EV, "barriers");
constexpr uint32_t SB0 = 1024;
__host__ __device__ constexpr uint32_t cdesc(uint32_t off, uint32_t lbo) { return ((SB0 + off) >> 4) | ((lbo >> 4) << 16); }
#define SCHED_FENCE() __syncwarp()
constexpr int NB_BIG = 1, NB_Q = 2, NB_AUX = 3, NB_WO = 4, NB_XS = 5, NB_WG = 6, NB_PAIR = 8, NB_PRO = 12;

DEVI int tid_now() { int t; asm volatile("mov.u32 %0, %%tid.x;" : "=r"(t)); return t; }
DEVI uint32_t a_frag_off(int lane, int warp) { return (uint32_t)((((lane >> 4) * 8 + (lane & 7)) * 128) + (((2 * warp + ((lane >> 3) & 1)) ^ (lane & 7)) * 16)); }
DEVI uint32_t b_frag_off(int lane) { return (uint32_t)((lane & 3) * 64 + (((lane >> 2) * 8) ^ ((lane & 2) * 16))); }
DEVI void lds_b(uint32_t* b, uint32_t a) {
    asm volatile("ld.shared.v2.u32 {%0,%1}, [%2];" : "=r"(b[0]), "=r"(b[1]) : "r"(a) : "memory");
    asm volatile("ld.shared.v2.u32 {%0,%1}, [%2];" : "=r"(b[2]), "=r"(b[3]) : "r"(a + 256) : "memory");
}
DEVI uint32_t clk32() { unsigned long long c; asm volatile("mov.u64 %0, %%clock64;" : "=l"(c)); return (uint32_t)c; }

__host__ __device__ constexpr int x_pair(int j) { return j < 2 || j > 5 ? j : (j == 2 ? 5 : j - 1); }
DEVI void x_load(uint32_t sb, int seg, int j, int g, const CUtensorMap* tmX) {
    const uint32_t bar = sb + RB_XF + g * 8;
    mbar_expect_tx(bar, 4096);
    tma_load_3d(sb + RS_X + g * X_PITCH + (j % X_SLOTS) * 4096, tmX + (j == 3), g * 32, seg * 32, x_pair(j) * 2, bar);
    if (j == 3) tma_load_3d(sb + RS_SX + g * (RS_XE - RS_SX), tmX + 1, g * 32, seg * 32, x_pair(3) * 2 + 1, bar);
}
DEVI void x_refill(uint32_t sb, int seg, int j, int g, int warp, const CUtensorMap* tmX) {
    const int sn = j + X_SLOTS < X_NST ? seg : seg + 1;
    if (warp == (j & 3) && sn < NSEG) {
        if (elect_one()) x_load(sb, sn, (j + X_SLOTS) % X_NST, g, tmX);
    }
}
template <int J, int Q0, int Q1, int DQ>
DEVI void x_steps(float* xa, const uint32_t* w, int g0) {
    const int g = (int)opaque((uint32_t)g0);
    const uint32_t dW0 = cdesc(RS_WSS, 16) + g * 768, dW1 = cdesc(RS_WSS + 8192, 16) - g * 256;
#pragma unroll
    for (int q = Q0; q < Q1; q += DQ) {
        const int pos = r_tinv(2 * x_pair(J) + (q >> 2)), kk = (q >> 1) & 1, mt = q & 1;
        const uint32_t db = (J == 3 && q >= 4 ? cdesc(RS_SX, 16) + g * ((RS_XE - RS_SX) >> 4)
                                                    : cdesc(RS_X + (J % X_SLOTS) * 4096, 16) + g * (X_PITCH >> 4) + (q >> 2) * 128) + kk * 2;
        if (J == 0 && q < 2)   wgmma_n32_rs_first(xa + 16 * mt, &w[((r_rs(pos) * 2 + kk) * 2 + mt) * 4], db);
        else if (J == 0 && q == 3) wgmma_n32_ss(xa + 16, cdesc(RS_WX, 16) + g * 128, db);
        else if (r_pos_ss(pos)) wgmma_n32_ss(xa + 16 * mt, (mt ? dW1 : dW0) + r_ss(pos) * 1024 + kk * 128, db);
        else                   wgmma_n32_rs(xa + 16 * mt, &w[((r_rs(pos) * 2 + kk) * 2 + mt) * 4], db);
    }
}
DEVI void x_first(float* xa, const uint32_t* w, uint32_t sb, int seg, int g0, int warp, const CUtensorMap* tmX) {
    wg_fence();
    x_steps<0, 0, 8, 1>(xa, w, g0); wg_commit();
    x_steps<1, 0, 8, 1>(xa, w, g0); wg_commit();
    x_steps<2, 0, 8, 1>(xa, w, g0); wg_commit();
    x_steps<3, 0, 4, 1>(xa, w, g0); wg_commit();
    const int g = (int)opaque((uint32_t)g0);
    wg_wait<3>(); x_refill(sb, seg, 0, g, warp, tmX);
    wg_wait<2>(); x_refill(sb, seg, 1, g, warp, tmX);
    wg_wait<1>(); x_refill(sb, seg, 2, g, warp, tmX);
    wg_wait<0>(); x_refill(sb, seg, 3, g, warp, tmX);
    reg_fence<32>(xa);
    mbar_wait(sb + RB_XF + g * 8, 1);
}
DEVI void x_second(float* xa, uint32_t* a, uint32_t aA0, const uint32_t* w, uint32_t sb, int seg, int g0, int warp, const CUtensorMap* tmX) {
    wg_fence();
    x_steps<4, 0, 8, 1>(xa, w, g0); wg_commit();
    x_steps<3, 5, 8, 2>(xa, w, g0); x_steps<5, 1, 8, 2>(xa, w, g0); x_steps<6, 1, 8, 2>(xa, w, g0); x_steps<7, 1, 8, 2>(xa, w, g0); wg_commit();
    x_steps<3, 4, 8, 2>(xa, w, g0); x_steps<5, 0, 8, 2>(xa, w, g0); x_steps<6, 0, 8, 2>(xa, w, g0); x_steps<7, 0, 8, 2>(xa, w, g0); wg_commit();
    const int g = (int)opaque((uint32_t)g0);
    wg_wait<2>(); x_refill(sb, seg, 4, g, warp, tmX);
    SCHED_FENCE();
#pragma unroll
    for (int q = 0; q < 4; q++) ldsm4t(a + 4 * q, aA0 + (q & 1) * (8192 - g * 16384) + (q >> 1) * 2048);
    SCHED_FENCE();
    wg_wait<1>();
    reg_fence<16>(xa + 16);
}
DEVI void x_finish(float* xa, uint32_t sb, int g, int warp, int lane) {
    const uint32_t d = sb + RS_XD + (lane >> 4) * 2048 + warp * 256 + (lane & 15) * 16;
#pragma unroll
    for (int i = 0; i < 2; i++) {
        const float* x = xa + 16 + 8 * i;
        sts128(d + (g ^ 1) * 1024 + i * 4096, make_uint4(pack_bf16(x[0], x[1]), pack_bf16(x[2], x[3]), pack_bf16(x[4], x[5]), pack_bf16(x[6], x[7])));
    }
    nbar_sync(NB_PAIR + warp, 64);
    float y[16];
#pragma unroll
    for (int i = 0; i < 2; i++) {
        const uint4 v = lds128(d + g * 1024 + i * 4096);
        const uint32_t u[4] = {v.x, v.y, v.z, v.w};
#pragma unroll
        for (int j = 0; j < 4; j++) { y[8 * i + 2 * j] = __uint_as_float(u[j] << 16); y[8 * i + 2 * j + 1] = __uint_as_float(u[j] & 0xFFFF0000u); }
    }
    reg_fence<16>(y);
    wg_wait<0>();
    reg_fence<16>(xa);
    uint32_t p[8];
#pragma unroll
    for (int j = 0; j < 8; j++) p[j] = pack_bf16(xa[2 * j] + y[2 * j], xa[2 * j + 1] + y[2 * j + 1]);
    __syncwarp();
    stsm4(d + g * 1024, p[0], p[1], p[2], p[3]);
    stsm4(d + g * 1024 + 4096, p[4], p[5], p[6], p[7]);
    nbar_arrive(NB_XS, 256 + 32);
}
DEVI void x_send(uint32_t sb, int seg, uint32_t rank, const CUtensorMap* tmX) {
    auto refill = [&]() {
        if (seg + 1 < NSEG && elect_one()) {
#pragma unroll
            for (int j = 1; j < 4; j++) { x_load(sb, seg + 1, j, 0, tmX); x_load(sb, seg + 1, j, 1, tmX); }
        }
        __syncwarp();
    };
    mbar_wait(sb + RB_ATT, (seg - 1) & 1);
    nbar_sync(NB_XS, 256 + 32);
    if (rank == 2) { refill(); mbar_wait(sb + RB_G3, (seg - 1) & 1); }
    if (elect_one()) {
        fence_proxy_async();
        bulk_copy_s2c(mapa(sb + (rank == 1 ? RS_K : RS_V) + 2048, 0), sb + RS_XD, 8192, mapa(sb + (rank == 1 ? RB_KV : RB_VX), 0));
    }
    __syncwarp();
    if (rank == 1) refill();
}

template <bool XP>
DEVI void mem_pass(float* c0, float* c1, uint32_t* a, const uint32_t* w, uint32_t sb, uint32_t aA0, uint32_t aB, int g, int warp, int s) {
    const uint32_t aA1 = aA0 + 8192 - g * 16384, par = (s - 1) & 1;
    uint32_t b[3][4], e[4];
    float d0[4], d1[4];
    if (XP) ldsm4t(e, aA0 + opaque((RS_WX - RS_WSS) - g * (8192 + 2048)));
#pragma unroll
    for (int q = XP ? 4 : 0; q < 4; q++) ldsm4t(a + 4 * q, ((q & 1) ? aA1 : aA0) + (q >> 1) * 2048);
#pragma unroll
    for (int i = 0; i < 4; i++) { c0[i] = 0.f; c1[i] = 0.f; d0[i] = 0.f; d1[i] = 0.f; }
    EV(EV_BIG0, s, 0);
    mbar_wait(sb + RB_G, par);
    EV(EV_BIG0, s, 1);
    lds_b(b[0], aB + r_tord(0) * 1024);
    lds_b(b[1], aB + r_tord(1) * 1024);
    bool in = false;
#pragma unroll
    for (int pos = 0; pos < 16; pos++) {
        if (pos + 2 < 16) {
            if (pos + 2 == R_G1 && !in) mbar_wait(sb + RB_G + 8, par);
            if (pos + 2 == R_G2 && !in) mbar_wait(sb + RB_G + 16, par);
            if (pos + 2 == R_G3) { if (!in) mbar_wait(sb + RB_G3, par); EV(EV_BIG0, s, 2); }
            lds_b(b[(pos + 2) % 3], aB + r_tord(pos + 2) * 1024);
        }
        if (pos + 3 == R_G1) in = mbar_try(sb + RB_G + 8, par);
        if (pos + 3 == R_G2) in = mbar_try(sb + RB_G + 16, par);
        if (pos + 3 == R_G3) in = mbar_try(sb + RB_G3, par);
        if (XP && pos == 14) in = mbar_try(sb + RB_ATT, par);
        const uint32_t* bb = b[pos % 3];
        const uint32_t* aa = r_pos_ss(pos) ? a : &w[r_rs(pos) * 16];
        mma16816(c1, aa + 4, bb[0], bb[1]);
        mma16816(d1, XP && pos == 0 ? e : aa + 12, bb[2], bb[3]);
        mma16816(c0, aa, bb[0], bb[1]);
        mma16816(d0, aa + 8, bb[2], bb[3]);
        if (pos >= 2 && pos < 14) {
            const uint32_t nx = ((pos + 1) / 3) * 16384;
            if (r_pos_ss(pos)) { ldsm4t(a + 4, aA1 + nx); ldsm4t(a + 12, aA1 + nx + 2048); }
            else ldsm4t(a + 8 * (pos % 3), aA0 + nx + (pos % 3) * 2048);
        }
        SCHED_FENCE();
    }
    if (XP && !in) mbar_wait(sb + RB_ATT, par);
#pragma unroll
    for (int i = 0; i < 4; i++) { c1[i] += d1[i]; c0[i] += d0[i]; }
}

DEVI uint32_t k_frag_off(int lane) { return (uint32_t)((((lane >> 3) & 1) * 16 + (lane >> 4) * 8 + (lane & 7)) * 16); }
DEVI uint32_t v_frag_off(int lane) { return (uint32_t)(((lane >> 3) & 1) * 2048 + ((lane >> 4) * 8 + (lane & 7)) * 16); }
DEVI void pv_pair(float (*o)[4], const uint32_t* p, const uint32_t* v) {
#pragma unroll
    for (int n = 0; n < 4; n++) mma16816(o[n], p, v[2 * n], v[2 * n + 1]);
}
DEVI void pv_single(float (*o)[4], const uint32_t* p, const uint32_t* v) {
#pragma unroll
    for (int n = 0; n < 4; n++) mma1688(o[n], p[0], p[1], v[n]);
}
DEVI void s_tile(const uint32_t* qa, const uint32_t* k, float& s0, float& s1) {
    float c[4][4];
#pragma unroll
    for (int q = 0; q < 4; q++) { c[q][0] = c[q][1] = c[q][2] = c[q][3] = 0.f; }
#pragma unroll
    for (int q = 0; q < 4; q++) {
        mma16816(c[2 * (q & 1)], qa + 4 * q, k[4 * q], k[4 * q + 1]);
        mma16816(c[2 * (q & 1) + 1], qa + 4 * q, k[4 * q + 2], k[4 * q + 3]);
    }
    s0 = (c[0][0] + c[1][2]) + (c[2][0] + c[3][2]);
    s1 = (c[0][1] + c[1][3]) + (c[2][1] + c[3][3]);
}
DEVI void mem_scores(uint32_t sb, int s, int lane) {
    const uint32_t ka = sb + RS_K + k_frag_off(lane), sa = sb + RS_SX + 1024 + lane * 8;
    uint32_t qa[16], km[16];
    nbar_sync(NB_Q, 256);
#pragma unroll
    for (int q = 0; q < 4; q++) ldsm4t(qa + 4 * q, sb + RS_Q + q * 512 + lane * 16);
    mbar_wait(sb + RB_K, s & 1);
#pragma unroll
    for (int q = 0; q < 4; q++) ldsm4t(km + 4 * q, ka + q * 512);
    SCHED_FENCE();
    float s0, s1;
    s_tile(qa, km, s0, s1);
    asm volatile("st.shared.v2.f32 [%0], {%1,%2};" :: "r"(sa), "f"(s0 * SCALE_LOG2E), "f"(s1 * SCALE_LOG2E) : "memory");
    nbar_arrive(NB_XS, 128 + 32);
}
DEVI float quad_max(float m) {
    return fmaxf(fmaxf(m, __shfl_xor_sync(0xffffffffu, m, 1)), fmaxf(__shfl_xor_sync(0xffffffffu, m, 2), __shfl_xor_sync(0xffffffffu, m, 3)));
}
DEVI void mem_attn(uint32_t sb, int s, int warp, int lane) {
    const uint32_t va = sb + RS_V + warp * 512, sa = sb + RS_SX + lane * 8;
    [[maybe_unused]] constexpr int g = 0;
    float o[4][4], mx, l = 0.f;
    {
        const uint32_t ka = sb + RS_K + k_frag_off(lane) + (1 + warp) * 2048;
        uint32_t qa[16], kx[16];
        const bool in = mbar_try(sb + RB_KV, s & 1);
        nbar_sync(NB_Q, 256);
        EV(EV_BIG0 && lds32(sb + RS_Q) != 0x12345678u, s, 8);
#pragma unroll
        for (int q = 0; q < 4; q++) ldsm4t(qa + 4 * q, sb + RS_Q + q * 512 + lane * 16);
        if (!in) mbar_wait(sb + RB_KV, s & 1);
#pragma unroll
        for (int q = 0; q < 4; q++) ldsm4t(kx + 4 * q, ka + q * 512);
        const bool vin = mbar_try(sb + RB_VX, s & 1);
        SCHED_FENCE();
        float s0, s1;
        s_tile(qa, kx, s0, s1);
        asm volatile("st.shared.v2.f32 [%0], {%1,%2};" :: "r"(sa + warp * 256), "f"(s0), "f"(s1) : "memory");
        nbar_sync(NB_WG, 128);
        float sc[8];
#pragma unroll
        for (int n = 0; n < 4; n++) { const float2 v = lds64f(sa + n * 256); sc[2 * n] = v.x; sc[2 * n + 1] = v.y; }
        if (!vin) mbar_wait(sb + RB_VX, s & 1);
        mx = quad_max(fmaxf(fmaxf(fmaxf(sc[0], sc[1]), fmaxf(sc[2], sc[3])), fmaxf(fmaxf(sc[4], sc[5]), fmaxf(sc[6], sc[7])))) * SCALE_LOG2E;
        uint32_t vx[16], p[8];
#pragma unroll
        for (int q = 0; q < 4; q++) ldsm4(vx + 4 * q, va + 2048 + (q >> 1) * 4096 + (q & 1) * 256 + v_frag_off(lane));
#pragma unroll
        for (int n = 0; n < 4; n++) {
            const float e0 = ex2(fmaf(sc[2 * n], SCALE_LOG2E, -mx)), e1 = ex2(fmaf(sc[2 * n + 1], SCALE_LOG2E, -mx));
            l += e0 + e1;
            p[2 * n] = pack_bf16(e0, e1); p[2 * n + 1] = __float_as_uint(e0);
        }
#pragma unroll
        for (int n = 0; n < 4; n++) { o[n][0] = o[n][1] = o[n][2] = o[n][3] = 0.f; }
        pv_pair(o, p, vx);
        pv_pair(o, p + 4, vx + 8);
    }
    const uint32_t dst = sb + RS_O + warp * 512 + (lane & 3) * 128 + (lane >> 2) * 16, dl = sb + RS_INV + (lane & 28);
    EV(EV_BIG0, s, 5);
    mbar_wait(sb + RB_V, s & 1);
    uint32_t vm[4], p[2];
    ldsm4(vm, va + lane * 16);
    nbar_sync(NB_XS, 128 + 32);
    EV(EV_BIG0 && lds32(sb + RS_Q) != 0x12345678u, s, 9);
    const float2 sm = lds64f(sa + 1024);
    const float s0 = sm.x, s1 = sm.y;
    const float m = quad_max(fmaxf(mx, fmaxf(s0, s1)));
    const float e0 = ex2(s0 - m), e1 = ex2(s1 - m), f = ex2(mx - m);
    p[0] = pack_bf16(e0, e1); p[1] = __float_as_uint(e0);
#pragma unroll
    for (int n = 0; n < 4; n++) { o[n][0] *= f; o[n][1] *= f; }
    pv_single(o, p, vm);
    l = fmaf(l, f, e0 + e1);
    l = (l + __shfl_xor_sync(0xffffffffu, l, 1)) + (__shfl_xor_sync(0xffffffffu, l, 2) + __shfl_xor_sync(0xffffffffu, l, 3));
    const uint4 u = make_uint4(pack_bf16(o[0][0], o[0][1]), pack_bf16(o[1][0], o[1][1]), pack_bf16(o[2][0], o[2][1]), pack_bf16(o[3][0], o[3][1]));
    st_async128(mapa(dst, 1), u.x, u.y, u.z, u.w, mapa(sb + RB_O, 1));
    st_async128(mapa(dst, 2), u.x, u.y, u.z, u.w, mapa(sb + RB_O, 2));
    st_async32(mapa(dl, 1 + (warp & 1)), __float_as_uint(l), mapa(sb + RB_O, 1 + (warp & 1)));
    sts128(dst, u);
    sts32(dl, __float_as_uint(l));
    __syncwarp();
    if (elect_one()) mbar_arrive(sb + RB_O);
    EV(EV_BIG0, s, 15);
}

DEVI void ta_mask(float* c, int cw, int lane) {
    const int mt = cw >= 3, over = 8 * (cw - 3 * mt - 1) + 2 * (lane & 3) - 16 * mt - (lane >> 2);
    if (over > 0) c[0] = -INFINITY;
    if (over >= 0) c[1] = -INFINITY;
    if (over > 8) c[2] = -INFINITY;
    if (over >= 8) c[3] = -INFINITY;
}
DEVI void ta_scores(uint32_t sb, int seg, int warp, int lane) {
    const int tx = warp == 3 ? 0 : (warp == 2 ? 1 : 4 + 2 * warp), ty = warp == 3 ? 3 : tx + 1;
    const uint32_t qa = sb + RS_QX + ((warp < 2 ? 2 : 0) + ((lane >> 3) & 1)) * 2048 + ((lane >> 4) * 8 + (lane & 7)) * 16;
    const uint32_t ka = sb + RS_K + (warp < 2 ? tx - 3 : tx) * 2048 + lane * 16;
    float x[4] = {0.f, 0.f, 0.f, 0.f}, y[4] = {0.f, 0.f, 0.f, 0.f};
    mbar_wait(sb + RB_QX, seg & 1);
    if (warp < 3) {
#pragma unroll
        for (int j = 0; j < 4; j++) {
            uint32_t a0[4], a1[4], bx[4], by[4];
            ldsm4t(a0, qa + j * 512); ldsm4t(bx, ka + j * 512); ldsm4t(by, ka + 2048 + j * 512); ldsm4t(a1, qa + j * 512 + 256);
            mma16816(x, a0, bx[0], bx[1]); mma16816(y, a0, by[0], by[1]);
            mma16816(x, a1, bx[2], bx[3]); mma16816(y, a1, by[2], by[3]);
        }
        ta_mask(x, tx, lane); ta_mask(y, ty, lane);
    } else {
        mbar_wait(sb + RB_K, seg & 1);
#pragma unroll
        for (int j = 0; j < 4; j++) {
            uint32_t a0[4], a1[4], a2[4], a3[4], b[4];
            ldsm4t(a0, qa + j * 512); ldsm4t(b, ka + j * 512); ldsm4t(a2, qa + 4096 + j * 512);
            ldsm4t(a1, qa + j * 512 + 256); ldsm4t(a3, qa + 4096 + j * 512 + 256);
            mma16816(x, a0, b[0], b[1]); mma16816(y, a2, b[0], b[1]);
            mma16816(x, a1, b[2], b[3]); mma16816(y, a3, b[2], b[3]);
        }
    }
    nbar_sync(NB_WG + 1, 128);
    asm volatile("st.shared.v2.f32 [%0], {%1,%2};" :: "r"(sb + RS_QX + 4096 + tx * 256 + lane * 8), "f"(fmaxf(x[0], x[1])), "f"(fmaxf(x[2], x[3])) : "memory");
    asm volatile("st.shared.v2.f32 [%0], {%1,%2};" :: "r"(sb + RS_QX + 4096 + ty * 256 + lane * 8), "f"(fmaxf(y[0], y[1])), "f"(fmaxf(y[2], y[3])) : "memory");
    nbar_sync(NB_WG + 1, 128);
    float m[4] = {-INFINITY, -INFINITY, -INFINITY, -INFINITY};
#pragma unroll
    for (int n = 0; n < 8; n++) {
        if (n < 3 ? warp >= 2 : warp != 2) {
            const float2 v = lds64f(sb + RS_QX + 4096 + n * 256 + lane * 8);
            m[n < 3 ? 0 : 2] = fmaxf(m[n < 3 ? 0 : 2], v.x); m[n < 3 ? 1 : 3] = fmaxf(m[n < 3 ? 1 : 3], v.y);
        }
    }
#pragma unroll
    for (int o = 1; o < 4; o <<= 1) {
#pragma unroll
        for (int i = 0; i < 4; i++) m[i] = fmaxf(m[i], __shfl_xor_sync(0xffffffffu, m[i], o));
    }
    const float x0 = (warp < 2 ? m[2] : m[0]) * -SCALE_LOG2E, x1 = (warp < 2 ? m[3] : m[1]) * -SCALE_LOG2E;
    const float y0 = (warp == 2 ? m[0] : m[2]) * -SCALE_LOG2E, y1 = (warp == 2 ? m[1] : m[3]) * -SCALE_LOG2E;
    sts64(sb + RS_QX + tx * 256 + lane * 8, pack_bf16(ex2(fmaf(x[0], SCALE_LOG2E, x0)), ex2(fmaf(x[1], SCALE_LOG2E, x0))),
                                            pack_bf16(ex2(fmaf(x[2], SCALE_LOG2E, x1)), ex2(fmaf(x[3], SCALE_LOG2E, x1))));
    sts64(sb + RS_QX + ty * 256 + lane * 8, pack_bf16(ex2(fmaf(y[0], SCALE_LOG2E, y0)), ex2(fmaf(y[1], SCALE_LOG2E, y0))),
                                            pack_bf16(ex2(fmaf(y[2], SCALE_LOG2E, y1)), ex2(fmaf(y[3], SCALE_LOG2E, y1))));
}
template <int MT>
DEVI void ta_output(uint32_t sb, int seg, int head, int j, int lane) {
    const uint32_t pa = sb + RS_QX + MT * 768 + lane * 8, vb = sb + RS_V + j * 512;
    uint32_t p[6 + 4 * MT], v[12 + 8 * MT];
#pragma unroll
    for (int n = 0; n < 3 + 2 * MT; n++)
        asm volatile("ld.shared.v2.u32 {%0,%1}, [%2];" : "=r"(p[2 * n]), "=r"(p[2 * n + 1]) : "r"(pa + n * 256) : "memory");
#pragma unroll
    for (int q = 0; q < 2 + 2 * MT; q++) ldsm4(v + 4 * q, vb + (q >> 1) * 4096 + (q & 1) * 256 + v_frag_off(lane));
    ldsm4(v + 8 + 8 * MT, vb + 4096 + MT * 4096 + lane * 16);
    float o[4][4], l[4] = {0.f, 0.f, 0.f, 0.f};
#pragma unroll
    for (int n = 0; n < 4; n++) { o[n][0] = o[n][1] = o[n][2] = o[n][3] = 0.f; }
    mma16816(l, p, 0x3F803F80u, 0x3F803F80u);
    pv_pair(o, p, v);
    if (MT) { mma16816(l, p + 4, 0x3F803F80u, 0x3F803F80u); pv_pair(o, p + 4, v + 8); }
    mma1688(l, p[4 + 4 * MT], p[5 + 4 * MT], 0x3F803F80u);
    pv_single(o, p + 4 + 4 * MT, v + 8 + 8 * MT);
    const float i0 = rcp_fast(l[0]), i1 = rcp_fast(l[2]);
    bf16* dst = g_ox + (uint32_t)((seg * 32 + MT * 16 + (lane >> 2)) * HD + head * DH + j * 32 + (lane & 3) * 8);
    asm volatile("st.global.v4.u32 [%0], {%1,%2,%3,%4};" :: "l"(dst), "r"(pack_bf16(o[0][0] * i0, o[0][1] * i0)), "r"(pack_bf16(o[1][0] * i0, o[1][1] * i0)),
                 "r"(pack_bf16(o[2][0] * i0, o[2][1] * i0)), "r"(pack_bf16(o[3][0] * i0, o[3][1] * i0)) : "memory");
    asm volatile("st.global.v4.u32 [%0], {%1,%2,%3,%4};" :: "l"(dst + 8 * HD), "r"(pack_bf16(o[0][2] * i1, o[0][3] * i1)), "r"(pack_bf16(o[1][2] * i1, o[1][3] * i1)),
                 "r"(pack_bf16(o[2][2] * i1, o[2][3] * i1)), "r"(pack_bf16(o[3][2] * i1, o[3][3] * i1)) : "memory");
}

template <bool XP>
DEVI void big_main(const uint32_t* w, const uint32_t sb, const int g, const int warp, const uint32_t rank, const int head,
                   const CUtensorMap* tmX, const bf16* xg, const unsigned E) {
    float xa[32];
    uint32_t a[16];
    const uint32_t aB = __shfl_sync(0xffffffffu, sb + RS_MEM + (g * 32 + (tid_now() & 31)) * 16, tid_now() & 31);
#define lane0 ((int)(opaque(aB) >> 4) & 31)
    const uint32_t aA0 = sb + RS_WSS + g * (8192 + 4096) + a_frag_off(lane0, warp);
    const uint32_t aBf = sb + RS_MEM + g * 512 + b_frag_off(lane0);
    if constexpr (XP) {
        mbar_wait(sb + RB_XF + g * 8, 0);
        x_first(xa, w, sb, 0, g, warp, tmX);
        x_second(xa, a, aA0, w, sb, 0, g, warp, tmX);
        x_finish(xa, sb, g, warp, lane0);
    }
    nbar_sync(NB_BIG, 256);
    for (int s = 0; s < NSEG; s++) {
        float c0[4], c1[4];
        mem_pass<XP>(c0, c1, a, w, sb, aA0, aBf, g, warp, s);
        EV(EV_BIG0 && c0[0] != 1.2345e30f, s, 3);
        bool xin = true;
        const uint32_t xs = sb + RS_O + warp * 256 + lane0 * 8;
        sts64(xs + g * 1024, pack_bf16(c1[0], c1[1]), pack_bf16(c1[2], c1[3]));
        {
            const uint32_t d = sb + (XP ? (rank == 1 ? RS_K : RS_V) : RS_Q) + (g * 4 + warp) * 256 + lane0 * 4;
            const uint32_t rbar = XP ? mapa(sb + (rank == 1 ? RB_K : RB_V), 0) : 0u;
            nbar_sync(NB_PAIR + warp, 64);
            const float2 v = lds64f(xs + (g ^ 1) * 1024);
            if (XP) xin = mbar_test(sb + RB_XF + g * 8, 0);
            const uint32_t v0 = __float_as_uint(v.x), v1 = __float_as_uint(v.y);
            const uint32_t p0 = pack_bf16(c0[0] + __uint_as_float(v0 << 16), c0[1] + __uint_as_float(v0 & 0xFFFF0000u));
            const uint32_t p1 = pack_bf16(c0[2] + __uint_as_float(v1 << 16), c0[3] + __uint_as_float(v1 & 0xFFFF0000u));
            if constexpr (XP) { st_async32(mapa(d, 0), p0, rbar); st_async32(mapa(d + 128, 0), p1, rbar); }
            else { sts32(d, p0); sts32(d + 128, p1); }
            EV(EV_BIG0, s, 4);
        }
        if constexpr (XP) {
            if (s == NSEG - 1) break;
            if (!xin) mbar_wait(sb + RB_XF + g * 8, 0);
            x_first(xa, w, sb, s + 1, g, warp, tmX);
            EV(EV_BIG0, s, 5);
            EVCAL(s);
            nbar_sync(NB_WO, 384);
            EV(EV_BIG0 && lds32(sb + RS_O) != 0x12345678u, s, 6);
            x_second(xa, a, aA0, w, sb, s + 1, g, warp, tmX);
            EV(EV_BIG0, s, 7);
            x_finish(xa, sb, g, warp, lane0);
        } else {
            if (g == 0) {
                if (s < NSEG - 1) mem_attn(sb, s, warp, lane0);
            } else {
                if (s < NSEG - 1) { if (warp == 3) mem_scores(sb, s, lane0); else nbar_arrive(NB_Q, 256); }
                mbar_wait(sb + RB_KV, s & 1);
                if (s == 0 && warp == 0) {
                    wait_count_warp(&g_cnt[C_QH], 64 * E);
                    if (elect_one()) {
                        fence_proxy_global();
                        mbar_expect_tx(sb + RB_QX, 8192);
                        bulk_load(sb + RS_QX, g_qx + (uint32_t)(head * 4096), 8192, sb + RB_QX);
                    }
                    __syncwarp();
                }
                ta_scores(sb, s, warp, lane0);
            }
            EVCAL(s);
            mbar_wait(sb + RB_V, s & 1);
            mbar_wait(sb + RB_VX, s & 1);
            if (s < NSEG - 1) nbar_sync(NB_WO, 384); else nbar_sync(NB_BIG, 256);
            EV(EV_BIG0 && lds32(sb + RS_O) != 0x12345678u, s, 6);
            if (g == 0) ta_output<0>(sb, s, head, warp, lane0); else ta_output<1>(sb, s, head, warp, lane0);
            nbar_sync(NB_BIG, 256);
            EV(EV_BIG0 && lds32(sb + RS_O) != 0x12345678u, s, 7);
            if (g == 0 && warp == 0 && s + 1 < NSEG) {
                if (elect_one()) {
                    mbar_arrive_remote(mapa(sb + RB_ATT, 1));
                    mbar_arrive_remote(mapa(sb + RB_ATT, 2));
                    mbar_expect_tx(sb + RB_KV, 8192);
                    mbar_expect_tx(sb + RB_K, 2048);
                    mbar_expect_tx(sb + RB_V, 2048); mbar_expect_tx(sb + RB_VX, 8192);
                    mbar_arrive(sb + RB_T);
                }
                __syncwarp();
            }
        }
    }
    if constexpr (!XP) { if (tid_now() == 0) signal_count(&g_prog[(NSEG - 1) >> 1]); }
#undef lane0
}

template <int T, int K0, int K1>
DEVI void wo_part(float* acc) {
    constexpr uint32_t dWo = cdesc(T < 5 ? RS_WO + T * 16384 : RS_WO5, 16), dO = cdesc(RS_O, 128);
#pragma unroll
    for (int kk = K0; kk < K1; kk++) {
        if (kk == 0) { if (T < 3) wgmma_n8_ss_first<0>(acc, dWo, dO); else wgmma_n8_ss<0, 0>(acc, dWo, dO); }
        else wgmma_n8_ss<0, 1>(acc, dWo + kk * 128, dO + kk * 16);
    }
    wg_commit();
}
DEVI void red3(uint8_t* p, uint32_t a, uint32_t b, uint32_t c, uint32_t one) {
    asm volatile("red.relaxed.gpu.global.add.noftz.v4.bf16x2 [%0], {%1,%2,%3,%4};" :: "l"(p), "r"(a), "r"(b), "r"(c), "r"(one) : "memory");
}
constexpr int ACC_CH = 3 * 16 * 1024;
template <bool Q>
DEVI void wo_phase(uint32_t sb, int s, int warp, uint8_t* p, uint32_t ainv, int gap) {
    float a0[4], a1[4], a2[4];
    fence_proxy_async();
    const float2 iv = lds64f(ainv);
    SCHED_FENCE();
    const float i0 = rcp_fast(iv.x), i1 = rcp_fast(iv.y);
#define WORD(a, h) pack_bf16(a[2 * h] * i0, a[2 * h + 1] * i1)
    wg_fence();
    wo_part<0, 0, 8>(a0); wo_part<1, 0, 8>(a1); wo_part<2, 0, 8>(a2);
    wg_wait<1>(); reg_fence<4>(a0); reg_fence<4>(a1);
    red3(p, WORD(a0, 0), WORD(a0, 1), WORD(a1, 0), 0x3F80u);
    SCHED_FENCE();
    EV(warp == 0 && elect_one(), s, 11);
    wg_wait<0>(); reg_fence<4>(a2);
    red3(p + ACC_CH, WORD(a2, 0), WORD(a2, 1), WORD(a1, 1), 0x3F80u);
    SCHED_FENCE();
    { const uint32_t t = clk32() + gap; while ((int)(clk32() - t) < 0) { } }
    wg_fence();
    wo_part<3, 0, 8>(a0); wo_part<4, 0, 8>(a1);
    if (Q) {
        wo_part<5, 0, 8>(a2);
        wg_wait<1>(); reg_fence<4>(a0); reg_fence<4>(a1);
        red3(p + 2 * ACC_CH, WORD(a0, 0), WORD(a0, 1), WORD(a1, 0), 0x3F80u);
        SCHED_FENCE();
        wg_wait<0>(); reg_fence<4>(a2);
        red3(p + 3 * ACC_CH, WORD(a2, 0), WORD(a2, 1), WORD(a1, 1), 0x3F80u);
        nbar_arrive(NB_WO, 384);
    } else {
        wg_wait<1>();
        nbar_arrive(NB_WO, 384);
        wg_wait<0>(); reg_fence<4>(a0); reg_fence<4>(a1);
        red3(p + 2 * ACC_CH, WORD(a0, 0), WORD(a0, 1), WORD(a1, 0), 0x3F80u);
        red3(p + 3 * ACC_CH, 0u, 0u, WORD(a1, 1), 0x3F80u);
    }
#undef WORD
}
DEVI void unit_pack(uint32_t* u, uint32_t x0, uint32_t x1, uint32_t x2, uint32_t x3) {
    u[0] = __byte_perm(x0, x1, 0x5410); u[1] = __byte_perm(x2, x3, 0x5410); u[2] = __byte_perm(x0, x1, 0x7632); u[3] = __byte_perm(x2, x3, 0x7632);
}
DEVI void unit_send(uint32_t d, const uint32_t* u, uint32_t bar, uint32_t r1, uint32_t r2) {
    st_async128(mapa(d, r1), u[0], u[1], u[2], u[3], mapa(bar, r1));
    st_async128(mapa(d, r2), u[0], u[1], u[2], u[3], mapa(bar, r2));
}
template <bool Q>
DEVI void stage_sums(uint32_t sb, int s, uint32_t rank, int warp, const uint8_t* src, uint32_t l, uint32_t gate) {
    uint4 v[4];
    while ((int)(clk32() - gate) < 0) { }
    EV(elect_one(), s, 16 + warp);
#pragma unroll
    for (int j = 0; j < 4; j++) v[j] = ld_rlx4(src + j * 1024);
    const uint32_t col = sb + RS_MEM + ((Q ? 0 : (rank == 1 ? 6 : 11)) + 3 * (warp >> 1)) * 1024 + ((l >> 2) & 0x300) + (l & 0x70);
    const uint32_t d0 = col + (warp & 1) * 2048, d1 = d0 ^ 160, d2 = (col ^ ((warp & 1) * 160)) + 1024;
    const uint32_t r1 = Q ? 1 : 0, r2 = Q ? 2 : 3 - rank, bar = sb + (warp < 2 ? RB_G + 8 * warp : (Q ? RB_G + 16 : RB_G3));
    int n = 0;
    while (!__all_sync(0xffffffffu, v[0].w == 0x4200u && v[1].w == 0x4200u && v[2].w == 0x4200u && v[3].w == 0x4200u)) {
#pragma unroll
        for (int j = 0; j < 4; j++) v[j] = ld_rlx4(src + j * 1024);
        if (++n > SPIN_LIMIT) __trap();
    }
    EV(elect_one(), s, 24 + warp);
    uint32_t u[12];
    unit_pack(u + 8, v[0].z, v[1].z, v[2].z, v[3].z);
    unit_send(d2, u + 8, bar, r1, r2);
    if (Q || warp < 3) {
        unit_pack(u, v[0].x, v[1].x, v[2].x, v[3].x);
        unit_pack(u + 4, v[0].y, v[1].y, v[2].y, v[3].y);
        unit_send(d0, u, bar, r1, r2);
        unit_send(d1, u + 4, bar, r1, r2);
        sts128(d0, make_uint4(u[0], u[1], u[2], u[3]));
        sts128(d1, make_uint4(u[4], u[5], u[6], u[7]));
    }
    sts128(d2, make_uint4(u[8], u[9], u[10], u[11]));
    __syncwarp();
    if (elect_one()) {
        mbar_expect_tx(bar, warp < 2 ? 3072u : (Q ? 0u : 1024u));
        if (warp == 0) mbar_expect_tx(sb + (Q ? RB_G3 : RB_G + 16), Q ? 4096u : 3072u);
    }
    EV(elect_one(), s, 20 + warp);
}
DEVI void wo_permute(uint32_t tile, int t) {
    const uint32_t a = tile + t * 32 + ((t >> 2) & 1) * 16;
#pragma unroll
    for (int h = 0; h < 2; h++) {
        uint4 v[3], u[3];
#pragma unroll
        for (int i = 0; i < 3; i++) if (3 * h + i < 5 || t < 32) { v[i] = lds128(a + (3 * h + i) * 3072); u[i] = lds128((a ^ 16) + (3 * h + i) * 3072); }
#pragma unroll
        for (int i = 0; i < 3; i++) if (3 * h + i < 5 || t < 32) {
            sts128(a + (3 * h + i) * 3072, make_uint4(__byte_perm(v[i].x, v[i].y, 0x5410), __byte_perm(v[i].x, v[i].y, 0x7632),
                                                      __byte_perm(u[i].x, u[i].y, 0x5410), __byte_perm(u[i].x, u[i].y, 0x7632)));
            sts128((a ^ 16) + (3 * h + i) * 3072, make_uint4(__byte_perm(v[i].z, v[i].w, 0x5410), __byte_perm(v[i].z, v[i].w, 0x7632),
                                                             __byte_perm(u[i].z, u[i].w, 0x5410), __byte_perm(u[i].z, u[i].w, 0x7632)));
        }
    }
}
DEVI uint32_t acc_clear(int slot, int idx, uint32_t lo) {
    uint8_t* p = g_acc + (uint32_t)(slot * 128 + idx * 3072 + (lo < 3072 ? lo : lo - 1024));
    st_rlx4(p, 0u, 0u, 0u, 0u);
    uint32_t z; asm volatile("ld.relaxed.gpu.global.u32 %0, [%1];" : "=r"(z) : "l"(p) : "memory");
    return z;
}

template <bool Q>
DEVI void aux_main(uint32_t sb, int warp, uint32_t rank, int head, const CUtensorMap* tmX, const bf16* xg, unsigned E, const int delay, const int gap) {
    const uint32_t lo = __shfl_sync(0xffffffffu, ((tid_now() >> 3) & 3) * 1024 + (tid_now() & 7) * 16, tid_now() & 31);
    for (int s = 0; s < NSEG - 1; s++) {
        if (!Q && warp == 0 && elect_one()) mbar_expect_tx(sb + RB_O, 2048 + 256);
        __syncwarp();
        const uint32_t slot = (s & 3) * 128;
        mbar_wait(sb + RB_O, s & 1);
        EV(warp == 0 && elect_one(), s, 10);
        wo_phase<Q>(sb, s, warp, g_acc + (uint32_t)(slot + (rank * 4 + warp) * 4096 + opaque(lo)), sb + RS_INV + ((opaque(lo) >> 1) & 24), gap);
        SCHED_FENCE();
        const uint32_t t_o = clk32();
        EV(warp == 0 && elect_one(), s, 12);
        {
            const uint32_t l = opaque(lo);
            stage_sums<Q>(sb, s, rank, warp, g_acc + (uint32_t)(slot + rank * 16384 + warp * ACC_CH + (l & 0xC00) * 4 + (l & 0x70)), l, t_o + delay);
        }
        EV(warp == 2 && elect_one(), s, 14);
        if (warp == (Q ? 3 : 1)) {
            if (Q) {
                mbar_wait(sb + RB_T, s & 1);
                if (s == 3) wait_count_warp(&g_cnt[C_Q], 64 * E);
                if (elect_one()) {
                    if (s == 3) fence_proxy_global();
                    fence_proxy_async();
                    mbar_expect_tx(sb + RB_QX, 8192);
                    bulk_load(sb + RS_QX, g_qx + (uint32_t)(((s + 1) * NH + head) * 4096), 8192, sb + RB_QX);
                    if (head == 0) { TLOG(1400 + s, 0, gtime()); TLOG(1400 + s, 1, clock64()); }
                }
                __syncwarp();
                const bool fresh = (s & 7) == 6 && s + 2 < NSEG;
                if (fresh) wait_count_warp(&g_cnt[C_Q + ((s + 2) >> 3)], 64 * E);
                if (elect_one()) {
                    if (fresh) fence_proxy_global();
                    if (s + 2 < NSEG && s != 2) l2_prefetch(g_qx + (uint32_t)(((s + 2) * NH + head) * 4096), 8192);
                    if (s + 4 < NSEG) l2_prefetch(xg + (uint32_t)(((s + 4) * 32 + head) * DM), 2048);
                    signal_count(&g_prog[s >> 1]);
                }
                __syncwarp();
            } else {
                const uint32_t zero = acc_clear((s + 2) & 3, 2 * head + (int)rank - 1, opaque(lo));
                x_send(sb, s + 1, rank, tmX);
                if (__any_sync(0xffffffffu, zero != 0u)) __trap();
            }
        }
    }
}

DEVI void load_weights(uint32_t sb, const CUtensorMap* tmW, const CUtensorMap* tmWo, int head, uint32_t rank, int2 t0) {
    const uint32_t c0 = clk32();
    if (rank == 0) while ((int)(clk32() - c0) < t0.x) { }
    const uint32_t bW = sb + RB_W, bSF = sb + RB_SF, bSE = sb + RB_SE;
    const int tile0 = rank == 0 ? 0 : (rank == 1 ? 6 : 11);
    mbar_expect_tx(bW, R_NSS * 16384);
    for (int pass = 0; pass < 2; pass++) {
        for (int pos = 0; pos < 16; pos++) {
            const int k = (int)((R_TORD_PACK >> (4 * pos)) & 15ull) * 64, rd = pos - pos / 3, slot = rd % 5;
            if (r_pos_ss(pos)) {
                if (pass) continue;
                const uint32_t dst = sb + RS_WSS + (pos / 3) * 16384;
                tma_load_2d(dst, tmW, head * DH, k, bW);
                tma_load_2d(dst + 8192, tmW, head * DH + 64, k, bW);
            } else if (pass == (rd >= 5)) {
                if (rd >= 5) mbar_wait(bSE + 8 * slot, ((rd / 5) - 1) & 1);
                mbar_expect_tx(bSF + 8 * slot, 16384);
                const uint32_t dst = sb + RS_WO + slot * 16384;
                tma_load_2d(dst, tmW, head * DH, k, bSF + 8 * slot);
                tma_load_2d(dst + 8192, tmW, head * DH + 64, k, bSF + 8 * slot);
            }
        }
    }
    while ((int)(clk32() - c0) < t0.y) { }
    if (rank == 0) { mbar_expect_tx(sb + RB_WO, 16384); tma_load_wo(sb + RS_WO5, tmWo, 5 * 64, head * 4, sb + RB_WO); }
    for (int i = 1; i <= 5; i++) {
        const int slot = i % 5, last = slot + 10 < R_NRS ? slot + 10 : slot + 5;
        mbar_wait(bSE + 8 * slot, (last / 5) & 1);
        mbar_expect_tx(bSF + 8 * slot, 16384);
        tma_load_wo(sb + RS_WO + slot * 16384, tmWo, (tile0 + slot) * 64, head * 4, bSF + 8 * slot);
    }
}
template <bool XP>
DEVI void big_prologue(uint32_t* w, uint32_t sb, int g, int warp, const bf16* __restrict__ mem0) {
    const int tid = tid_now(), lane = tid & 31;
    {
        const uint32_t* m = (const uint32_t*)(mem0 + (lane >> 2) * DM + (tid >> 5) * 16) + (lane & 3);
        uint32_t u[16];
#pragma unroll
        for (int j = 0; j < 8; j++) { u[2 * j] = m[j * 64]; u[2 * j + 1] = m[j * 64 + 4]; }
#pragma unroll
        for (int j = 0; j < 8; j++) sts64(sb + RS_MEM + ((tid >> 5) + j * 8) * 256 + b_frag_off(lane), u[2 * j], u[2 * j + 1]);
    }
    const uint32_t a0 = sb + RS_WO + g * (8192 + 4096) + a_frag_off(lane, warp), a1 = a0 + 8192 - g * 16384;
#pragma unroll
    for (int rd = 0; rd < R_NRS; rd++) {
        const int slot = rd % 5;
        mbar_wait(sb + RB_SF + 8 * slot, (rd / 5) & 1);
#pragma unroll
        for (int q = 0; q < 4; q++) {
            if (XP && rd == 0 && q == 3) {
                sts128(sb + RS_WX + g * 2048 + (tid & 127) * 16, lds128(sb + RS_WO + 8192 - g * 4096 + 2048 + (tid & 127) * 16));
                fence_proxy_async();
                nbar_sync(NB_WG + g, 128);
            } else ldsm4t(&w[rd * 16 + q * 4], ((q & 1) ? a1 : a0) + slot * 16384 + (q >> 1) * 2048);
        }
        mbar_arrive(sb + RB_SE + 8 * slot);
    }
    mbar_wait(sb + RB_W, 0);
    if (tid == 0) TLOG(1500 + blockIdx.x, 2, gtime());
}

#define REC_END() do { if (tid_now() == 0) TLOG(1024 + blockIdx.x, 1, gtime()); } while (0)
struct XMaps { CUtensorMap m[2]; };
__global__ void __launch_bounds__(384, 1)
k_rec(const __grid_constant__ PMaps mp, const __grid_constant__ CUtensorMap tmWk, const __grid_constant__ CUtensorMap tmWv,
      const __grid_constant__ CUtensorMap tmWo, const __grid_constant__ XMaps xm, const bf16* __restrict__ mem0, const bf16* __restrict__ xg,
      int4 tq, int4 tk, int2 t0, int rec) {
    extern __shared__ __align__(1024) uint8_t smem_raw[];
    const uint32_t sb = smem_u32(smem_raw);
    if ((sb & 0x3FFFFu) != SB0) __trap();
    const int tid = threadIdx.x;
    const int wg = __shfl_sync(0xffffffffu, tid >> 7, 0), warp = __shfl_sync(0xffffffffu, (tid >> 5) & 3, 0);
    uint32_t rank; asm("mov.u32 %0, %%cluster_ctarank;" : "=r"(rank));
    int head; asm("mov.u32 %0, %%clusterid.x;" : "=r"(head));
    asm volatile("griddepcontrol.launch_dependents;");
    if (tid == 0 && rec) {
        mbar_init(sb + RB_G, 1);
        mbar_init(sb + RB_G + 8, 1);
        mbar_init(sb + RB_G + 16, rank == 0 ? 2 : 1);
        mbar_init(sb + RB_G3, rank == 0 ? 1 : 2);
        mbar_init(sb + RB_T, 1); mbar_init(sb + RB_VX, 1); mbar_init(sb + RB_WO, 1);
        mbar_init(sb + RB_K, 1); mbar_init(sb + RB_V, 1); mbar_init(sb + RB_KV, 1); mbar_init(sb + RB_QX, 1);
        mbar_init(sb + RB_O, rank == 0 ? 4 : 1); mbar_init(sb + RB_ATT, 1); mbar_init(sb + RB_W, 1);
        for (int i = 0; i < 5; i++) { mbar_init(sb + RB_SF + 8 * i, 1); mbar_init(sb + RB_SE + 8 * i, 256); }
        for (int i = 0; i < 2; i++) mbar_init(sb + RB_XF + 8 * i, X_SLOTS);
        fence_mbar_init();
        if (rank == 0) { mbar_expect_tx(sb + RB_KV, 8192); mbar_expect_tx(sb + RB_K, 2048); mbar_expect_tx(sb + RB_V, 2048); mbar_expect_tx(sb + RB_VX, 8192); }
    }
    __syncthreads();
    asm volatile("barrier.cluster.arrive.release.aligned;" ::: "memory");

    if (wg < 2) {
        reg_inc<REG_KB>();
        if (rank != 0) {
            uint32_t w[R_NRS * 16];
            if ((tid & 127) == 0) for (int j = 0; j < X_SLOTS; j++) x_load(sb, 0, j, wg, xm.m);
            __syncwarp();
            cluster_wait();
            big_prologue<true>(w, sb, wg, warp, mem0);
            big_main<true>(w, sb, wg, warp, rank, head, xm.m, xg, 0u);
            REC_END();
        } else if (rec) {
            uint32_t w[R_NRS * 16];
            cluster_wait();
            big_prologue<false>(w, sb, wg, warp, mem0);
            big_main<false>(w, sb, wg, warp, rank, head, xm.m, xg, *(volatile unsigned*)&g_epoch + 1);
            REC_END();
        } else cluster_wait();
        if (rank == 0 && rec) nbar_arrive(NB_PRO, 256 + 32);
        nbar_sync(0, 384);
        post_consumer(mp, sb, wg, warp);
    } else {
        reg_dec<504 - 2 * REG_KB>();
        if (rec) {
            if (tid == 256) {
                if (rank == 0) l2_prefetch(xg + (uint32_t)(head * 8 * DM), 16384);
                load_weights(sb, rank == 0 ? &mp.wq : (rank == 1 ? &tmWk : &tmWv), &tmWo, head, rank, t0);
            }
            if (warp == 3 && rank != 0) {
                const uint32_t lo = ((tid >> 3) & 3) * 1024 + (tid & 7) * 16;
                acc_clear(0, 2 * head + (int)rank - 1, lo); acc_clear(1, 2 * head + (int)rank - 1, lo);
                __threadfence();
                __syncwarp();
                if (tid == 256 + 96) atomicAdd(&g_zero, 1u);
            }
            __syncwarp();
        }
        cluster_wait();
        const unsigned E = __shfl_sync(0xffffffffu, *(volatile unsigned*)&g_epoch + 1, 0);
        if (rec) {
            if (warp == 1) wait_count_warp(&g_zero, E * 64u);
            if (warp == 3) { if (rank != 0) x_send(sb, 0, rank, xm.m); }
            else {
                nbar_sync(NB_PRO, 96);
#pragma unroll 1
                for (int i = rank == 0 ? 0 : 1; i <= 5; i++) {
                    mbar_wait(sb + (i == 0 ? RB_WO : RB_SF + 8 * (i % 5)), i == 5);
                    if (i == 5 && tid == 288) TLOG(1500 + blockIdx.x, 0, gtime());
                    wo_permute(sb + (i == 0 ? RS_WO5 : RS_WO + (i % 5) * 16384), tid & 127);
                }
            }
            fence_proxy_async();
            nbar_sync(NB_AUX, 128);
            if (tid == 288) { TLOG(1500 + blockIdx.x, 1, gtime()); }
            if (rank == 0) aux_main<true>(sb, warp, rank, head, xm.m, xg, E, warp == 0 ? tq.x : (warp == 1 ? tq.y : tq.z), tq.w);
            else           aux_main<false>(sb, warp, rank, head, xm.m, xg, E, warp == 0 ? tk.x : (warp == 1 ? tk.y : tk.z), tk.w);
        }
        const int t = tid_now();
        if (t >= 320 && t < 320 + 13) asm volatile("prefetch.tensormap [%0];" :: "l"(&mp.wq + (t - 320)) : "memory");
        __syncwarp();
        if (warp == 0) post_producer(mp, sb, E, rank != 0 || !rec);
        else {
            if (warp == 1) {
                if (rank == 0 && rec) nbar_sync(NB_PRO, 256 + 32);
                if (elect_one()) post_init(sb);
                __syncwarp();
            }
            nbar_sync(0, 384);
            if (t == 288 || t == 320) post_helper(sb, warp - 1);
        }
    }
    __syncthreads();
    asm volatile("griddepcontrol.wait;" ::: "memory");
}

typedef CUresult (*EncodeFn)(CUtensorMap*, CUtensorMapDataType, cuuint32_t, void*, const cuuint64_t*, const cuuint64_t*,
                             const cuuint32_t*, const cuuint32_t*, CUtensorMapInterleave, CUtensorMapSwizzle,
                             CUtensorMapL2promotion, CUtensorMapFloatOOBfill);

static CUtensorMap make_map(EncodeFn fn, const void* ptr, uint64_t inner, uint64_t outer, uint32_t box_inner, uint32_t box_outer) {
    CUtensorMap m;
    cuuint64_t dims[2] = {inner, outer};
    cuuint64_t strides[1] = {inner * 2};
    cuuint32_t box[2] = {box_inner, box_outer};
    cuuint32_t es[2] = {1, 1};
    fn(&m, CU_TENSOR_MAP_DATA_TYPE_BFLOAT16, 2, const_cast<void*>(ptr), dims, strides, box, es,
       CU_TENSOR_MAP_INTERLEAVE_NONE, CU_TENSOR_MAP_SWIZZLE_128B, CU_TENSOR_MAP_L2_PROMOTION_L2_256B, CU_TENSOR_MAP_FLOAT_OOB_FILL_NONE);
    return m;
}

static CUtensorMap make_wo_map(EncodeFn fn, const void* ptr, uint64_t rows, uint32_t ngrp) {
    CUtensorMap m;
    cuuint64_t dims[5] = {DM, 2, 4, 4, rows / 32};
    cuuint64_t strides[4] = {DM * 2, 8 * DM * 2, 2 * DM * 2, 32 * DM * 2};
    cuuint32_t box[5] = {64, 2, 4, 4, ngrp};
    cuuint32_t es[5] = {1, 1, 1, 1, 1};
    fn(&m, CU_TENSOR_MAP_DATA_TYPE_BFLOAT16, 5, const_cast<void*>(ptr), dims, strides, box, es,
       CU_TENSOR_MAP_INTERLEAVE_NONE, CU_TENSOR_MAP_SWIZZLE_128B, CU_TENSOR_MAP_L2_PROMOTION_L2_256B, CU_TENSOR_MAP_FLOAT_OOB_FILL_NONE);
    return m;
}

struct Maps {
    PMaps post;
    CUtensorMap wk16, wv16, wo128;
    XMaps x32;
};

extern "C" void kernel_launch(void* const* d_in, const int* in_sizes, int n_in, void* d_out, int out_size) {
    const bf16* A_x   = (const bf16*)d_in[0];
    const bf16* A_mem = (const bf16*)d_in[1];
    const bf16* A_Wq  = (const bf16*)d_in[2];
    const bf16* A_Wk  = (const bf16*)d_in[3];
    const bf16* A_Wv  = (const bf16*)d_in[4];
    const bf16* A_Wo  = (const bf16*)d_in[5];
    const bf16* B_x   = (const bf16*)d_in[7];
    const bf16* B_w   = (const bf16*)d_in[8];
    const bf16* B_wo  = (const bf16*)d_in[9];

    static EncodeFn fn = nullptr;
    static Maps mp;
    static const void* cached[10];
    const void* cur[10] = {A_x, A_mem, A_Wq, A_Wk, A_Wv, A_Wo, B_x, B_w, B_wo, d_out};
    bool same = fn != nullptr;
    for (int i = 0; i < 10 && same; i++) same = cached[i] == cur[i];
    if (!same) {
        if (!fn) {
            void* p = nullptr; cudaDriverEntryPointQueryResult qr;
            cudaGetDriverEntryPoint("cuTensorMapEncodeTiled", &p, cudaEnableDefault, &qr);
            fn = (EncodeFn)p;
            cudaFuncSetAttribute(k_rec, cudaFuncAttributeMaxDynamicSharedMemorySize, R_SMEM);
        }
        void *p_ox, *p_bqkv, *p_bo, *p_qx;
        cudaGetSymbolAddress(&p_qx, g_qx);
        cudaGetSymbolAddress(&p_ox, g_ox); cudaGetSymbolAddress(&p_bqkv, g_bqkv); cudaGetSymbolAddress(&p_bo, g_bo);
        mp.post.wq   = make_map(fn, A_Wq, HD, DM, 64, 64);
        mp.post.wo   = make_wo_map(fn, A_Wo, HD, 2);
        mp.post.bw   = make_map(fn, B_w, 3 * DM, DM, 64, 64);
        mp.post.bwo  = make_wo_map(fn, B_wo, DM, 2);
        mp.post.x    = make_map(fn, A_x, DM, S_TOK, 64, 128);
        mp.post.bx   = make_map(fn, B_x, DM, S_TOK, 64, 128);
        mp.post.bo   = make_map(fn, p_bo, DM, S_TOK, 64, 128);
        mp.post.ox   = make_map(fn, p_ox, HD, S_TOK, 64, 128);
        mp.post.ox64 = make_map(fn, p_ox, HD, S_TOK, 64, 64);
        mp.post.cb   = make_map(fn, p_bqkv, 3 * DM, S_TOK, 64, 64);
        mp.post.cout = make_map(fn, d_out, 2 * DM, S_TOK, 64, 64);
        {
            cuuint64_t dims[4] = {256, 4, NH * 4, NSEG};
            cuuint64_t strides[3] = {512, 2048, NH * 8192};
            cuuint32_t box[4] = {256, 2, 4, 2};
            cuuint32_t es[4] = {1, 1, 1, 1};
            fn(&mp.post.cq, CU_TENSOR_MAP_DATA_TYPE_BFLOAT16, 4, p_qx, dims, strides, box, es,
               CU_TENSOR_MAP_INTERLEAVE_NONE, CU_TENSOR_MAP_SWIZZLE_NONE, CU_TENSOR_MAP_L2_PROMOTION_NONE, CU_TENSOR_MAP_FLOAT_OOB_FILL_NONE);
        }
        {
            int runs[48] = {K_QH, 0, 2, K_Q, 1, 7, K_B1, 0, 8, K_A4, 0, 4, K_B2, 0, 32, K_A4, 4, 2, K_B3, 0, 4, K_A3, 12, 2, K_B3, 4, 4,
                            K_SK, 14, 1, K_SN, 30, 2, -1};
            int nlate = 9;
            const int per[9] = {32, 24, 8, 8, 32, 8, 8 * P_SPLIT, 1, 8 * P_SPLIT};
            int n = 0, id = 0;
            for (; runs[3 * n] >= 0; n++) {
                mp.post.list.run[n] = make_int4(runs[3 * n], runs[3 * n + 1], id, id + runs[3 * n + 2] * per[runs[3 * n]]);
                id = mp.post.list.run[n].w;
            }
            mp.post.list.n = n;
            mp.post.list.late = mp.post.list.run[nlate].z;
            int dev = 0, nsm = 132;
            cudaGetDevice(&dev);
            cudaDeviceGetAttribute(&nsm, cudaDevAttrMultiProcessorCount, dev);
            mp.post.list.nworker = nsm > 96 ? nsm : 97;
        }
        {
            cuuint64_t dims[4] = {DM, 3, 2, S_TOK / 2};
            cuuint64_t strides[3] = {DM * 2, 3 * DM * 2, 3 * DM * 4};
            cuuint32_t box[4] = {64, 3, 1, 40};
            cuuint32_t es[4] = {1, 1, 1, 1};
            fn(&mp.post.b40, CU_TENSOR_MAP_DATA_TYPE_BFLOAT16, 4, p_bqkv, dims, strides, box, es,
               CU_TENSOR_MAP_INTERLEAVE_NONE, CU_TENSOR_MAP_SWIZZLE_128B, CU_TENSOR_MAP_L2_PROMOTION_L2_256B, CU_TENSOR_MAP_FLOAT_OOB_FILL_NONE);
        }
        mp.wk16 = make_map(fn, A_Wk, HD, DM, 64, 64);
        mp.wv16 = make_map(fn, A_Wv, HD, DM, 64, 64);
        mp.wo128 = make_wo_map(fn, A_Wo, HD, 4);
        for (int i = 0; i < 2; i++) {
            cuuint64_t dims[3] = {64, S_TOK, DM / 64};
            cuuint64_t strides[2] = {DM * 2, 128};
            cuuint32_t box[3] = {32, 32, 2u - i};
            cuuint32_t es[3] = {1, 1, 1};
            fn(&mp.x32.m[i], CU_TENSOR_MAP_DATA_TYPE_BFLOAT16, 3, const_cast<bf16*>(A_x), dims, strides, box, es,
               CU_TENSOR_MAP_INTERLEAVE_NONE, CU_TENSOR_MAP_SWIZZLE_64B, CU_TENSOR_MAP_L2_PROMOTION_L2_128B, CU_TENSOR_MAP_FLOAT_OOB_FILL_NONE);
        }
        for (int i = 0; i < 10; i++) cached[i] = cur[i];
    }

    cudaStream_t st = cudaStreamPerThread;
    int4 tq = make_int4(100, 200, 700, 60), tk = make_int4(50, 300, 800, 40);
    int2 t0 = make_int2(13000, 16000);
    cudaLaunchConfig_t cfg = {};
    cfg.gridDim = dim3(96); cfg.blockDim = dim3(384); cfg.dynamicSmemBytes = R_SMEM; cfg.stream = st;
    cudaLaunchAttribute at[1];
    at[0].id = cudaLaunchAttributeClusterDimension;
    at[0].val.clusterDim.x = 3; at[0].val.clusterDim.y = 1; at[0].val.clusterDim.z = 1;
    cfg.attrs = at; cfg.numAttrs = 1;
    cudaLaunchKernelEx(&cfg, k_rec, mp.post, mp.wk16, mp.wv16, mp.wo128, mp.x32, A_mem, A_x, tq, tk, t0, 1);
    cfg.gridDim = dim3(mp.post.list.nworker - 96);
    at[0].id = cudaLaunchAttributeProgrammaticStreamSerialization;
    at[0].val.programmaticStreamSerializationAllowed = 1;
    cudaLaunchKernelEx(&cfg, k_rec, mp.post, mp.wk16, mp.wv16, mp.wo128, mp.x32, A_mem, A_x, tq, tk, t0, 0);
}
```

```cpp
#include <cuda_runtime.h>
#include <cuda_bf16.h>
#include <cuda.h>
#include <stdint.h>

typedef __nv_bfloat16 bf16;

constexpr int S_TOK = 2048;
constexpr int DM    = 1024;
constexpr int NH    = 32;
constexpr int DH    = 128;
constexpr int NSEG  = 64;
constexpr int HD    = NH * DH;

__device__ __align__(1024) bf16 g_qx[NSEG * NH * 4 * DH * 8];
__device__ __align__(1024) bf16 g_ox[S_TOK * HD];
__device__ __align__(1024) bf16 g_bqkv[S_TOK * 3 * DM];
__device__ __align__(1024) bf16 g_bo[S_TOK * DM];
__device__ __align__(1024) uint8_t g_acc[192 * 1024];

#define EV(cond, s, k) do {} while (0)
#define EVCAL(s) do {} while (0)

constexpr int P_NSK = 4;
__device__ unsigned g_epoch, g_qctr, g_done, g_zero;
enum { C_B1 = 0, C_B2 = 8, C_Q = 16, C_QH = 24, C_NONE = 31 };
__device__ unsigned g_cnt[32], g_prog[32], g_cnt_sk[P_NSK * 32];
constexpr int P_SPLIT = 4;
__device__ __align__(1024) uint4 g_skp[P_NSK * 8 * P_SPLIT * 2 * 8 * 128];
#define TLOG(i, k, v) do {} while (0)

#define DEVI __device__ __forceinline__

DEVI uint32_t opaque(uint32_t v) { uint32_t r; asm volatile("mov.u32 %0, %1;" : "=r"(r) : "r"(v)); return r; }
DEVI uint32_t smem_u32(const void* p) { return (uint32_t)__cvta_generic_to_shared(p); }

constexpr int SPIN_LIMIT = 1 << 22;
#define MBAR_HINT_NS 20000u
constexpr int SPIN_LIMIT_MBAR = 1 << 17;

DEVI void mbar_init(uint32_t bar, uint32_t cnt) { asm volatile("mbarrier.init.shared::cta.b64 [%0], %1;" :: "r"(bar), "r"(cnt)); }
DEVI void mbar_expect_tx(uint32_t bar, uint32_t bytes) {
    asm volatile("mbarrier.arrive.expect_tx.shared::cta.b64 _, [%0], %1;" :: "r"(bar), "r"(bytes) : "memory");
}
DEVI void mbar_arrive(uint32_t bar) { asm volatile("mbarrier.arrive.shared::cta.b64 _, [%0];" :: "r"(bar) : "memory"); }
DEVI bool mbar_try(uint32_t bar, uint32_t parity) {
    uint32_t ok;
    asm volatile("{.reg .pred p; mbarrier.try_wait.parity.shared::cta.b64 p, [%1], %2; selp.u32 %0, 1, 0, p;}"
                 : "=r"(ok) : "r"(bar), "r"(parity) : "memory");
    return ok;
}
DEVI bool mbar_try_hint(uint32_t bar, uint32_t parity) {
    uint32_t ok;
    asm volatile("{.reg .pred p; mbarrier.try_wait.parity.shared::cta.b64 p, [%1], %2, %3; selp.u32 %0, 1, 0, p;}"
                 : "=r"(ok) : "r"(bar), "r"(parity), "r"(MBAR_HINT_NS) : "memory");
    return ok;
}
DEVI bool mbar_test(uint32_t bar, uint32_t parity) {
    uint32_t ok;
    asm volatile("{.reg .pred p; mbarrier.test_wait.parity.shared::cta.b64 p, [%1], %2; selp.u32 %0, 1, 0, p;}"
                 : "=r"(ok) : "r"(bar), "r"(parity) : "memory");
    return ok;
}
DEVI void mbar_wait(uint32_t bar, uint32_t parity) {
    int n = 0;
    while (!mbar_try(bar, parity)) { if (++n > SPIN_LIMIT) __trap(); }
}
DEVI void mbar_wait_sleepy(uint32_t bar, uint32_t parity) {
    int n = 0;
    while (!mbar_try_hint(bar, parity)) { if (++n > SPIN_LIMIT_MBAR) __trap(); }
}
DEVI void fence_mbar_init() { asm volatile("fence.mbarrier_init.release.cluster;" ::: "memory"); }
DEVI void fence_proxy_async() { asm volatile("fence.proxy.async.shared::cta;" ::: "memory"); }
DEVI bool elect_one() {
    uint32_t e; asm volatile("{.reg .pred p; elect.sync _|p, 0xffffffff; selp.u32 %0, 1, 0, p;}" : "=r"(e)); return e;
}
DEVI void fence_proxy_global() { asm volatile("fence.proxy.async.global;" ::: "memory"); }
DEVI void cluster_wait() { asm volatile("barrier.cluster.wait.acquire.aligned;" ::: "memory"); }
DEVI void nbar_sync(int id, int n) { asm volatile("bar.sync %0, %1;" :: "r"(id), "r"(n) : "memory"); }
DEVI void nbar_arrive(int id, int n) { asm volatile("bar.arrive %0, %1;" :: "r"(id), "r"(n) : "memory"); }

DEVI void tma_load_2d(uint32_t dst, const CUtensorMap* map, int x, int y, uint32_t bar) {
    asm volatile("cp.async.bulk.tensor.2d.shared::cluster.global.mbarrier::complete_tx::bytes [%0], [%1, {%3, %4}], [%2];"
                 :: "r"(dst), "l"(map), "r"(bar), "r"(x), "r"(y) : "memory");
}
DEVI void tma_load_3d(uint32_t dst, const CUtensorMap* map, int x, int y, int z, uint32_t bar) {
    asm volatile("cp.async.bulk.tensor.3d.shared::cluster.global.mbarrier::complete_tx::bytes [%0], [%1, {%3, %4, %5}], [%2];"
                 :: "r"(dst), "l"(map), "r"(bar), "r"(x), "r"(y), "r"(z) : "memory");
}
DEVI void tma_load_wo(uint32_t dst, const CUtensorMap* map, int col, int k32, uint32_t bar) {
    asm volatile("cp.async.bulk.tensor.5d.shared::cluster.global.mbarrier::complete_tx::bytes [%0], [%1, {%3, %5, %5, %5, %4}], [%2];"
                 :: "r"(dst), "l"(map), "r"(bar), "r"(col), "r"(k32), "r"(0) : "memory");
}
DEVI void tma_store_2d(const CUtensorMap* map, uint32_t src, int x, int y) {
    asm volatile("cp.async.bulk.tensor.2d.global.shared::cta.bulk_group [%0, {%2, %3}], [%1];"
                 :: "l"(map), "r"(src), "r"(x), "r"(y) : "memory");
}
DEVI void bulk_load(uint32_t dst, const void* src, uint32_t bytes, uint32_t bar) {
    asm volatile("cp.async.bulk.shared::cluster.global.mbarrier::complete_tx::bytes [%0], [%1], %2, [%3];"
                 :: "r"(dst), "l"(src), "r"(bytes), "r"(bar) : "memory");
}
DEVI void bulk_copy_s2c(uint32_t dst_cluster, uint32_t src, uint32_t bytes, uint32_t bar_cluster) {
    asm volatile("cp.async.bulk.shared::cluster.shared::cta.mbarrier::complete_tx::bytes [%0], [%1], %2, [%3];"
                 :: "r"(dst_cluster), "r"(src), "r"(bytes), "r"(bar_cluster) : "memory");
}
DEVI void bulk_wait_read() { asm volatile("cp.async.bulk.wait_group.read 0;" ::: "memory"); }
DEVI void mbar_arrive_remote(uint32_t bar_cluster) {
    asm volatile("mbarrier.arrive.shared::cluster.b64 _, [%0];" :: "r"(bar_cluster) : "memory");
}
DEVI void l2_prefetch(const void* p, uint32_t bytes) {
    asm volatile("cp.async.bulk.prefetch.L2.global [%0], %1;" :: "l"(p), "r"(bytes) : "memory");
}
DEVI void bulk_commit() { asm volatile("cp.async.bulk.commit_group;" ::: "memory"); }
DEVI void bulk_wait_all() { asm volatile("cp.async.bulk.wait_group 0;" ::: "memory"); }

DEVI void wg_fence() { asm volatile("wgmma.fence.sync.aligned;" ::: "memory"); }
DEVI void wg_commit() { asm volatile("wgmma.commit_group.sync.aligned;" ::: "memory"); }
template <int N> DEVI void wg_wait() { asm volatile("wgmma.wait_group.sync.aligned %0;" :: "n"(N) : "memory"); }

template <int R> DEVI void reg_dec() { asm volatile("setmaxnreg.dec.sync.aligned.u32 %0;" :: "n"(R)); }
template <int R> DEVI void reg_inc() { asm volatile("setmaxnreg.inc.sync.aligned.u32 %0;" :: "n"(R)); }

DEVI uint64_t mk_desc(uint32_t addr, uint32_t lbo, uint32_t sbo, uint32_t sw) {
    return (uint64_t)((addr & 0x3FFFF) >> 4) | ((uint64_t)(lbo >> 4) << 16) | ((uint64_t)(sbo >> 4) << 32) | ((uint64_t)sw << 62);
}

constexpr uint32_t DHI_SW128 = (1024u >> 4) | (1u << 30);
constexpr uint32_t DHI_SW64  = (512u >> 4) | (2u << 30);
constexpr uint32_t DHI_NONE  = (128u >> 4);

template <int TB, int SCALE_D>
DEVI void wgmma_n8_ss(float* d, uint32_t alo, uint32_t blo) {
    asm volatile("{.reg .b64 da, db; mov.b64 da, {%4, %6}; mov.b64 db, {%5, %7};\n"
                 "wgmma.mma_async.sync.aligned.m64n8k16.f32.bf16.bf16 {%0,%1,%2,%3}, da, db, %8, 1, 1, 1, %9;}"
                 : "+f"(d[0]), "+f"(d[1]), "+f"(d[2]), "+f"(d[3])
                 : "r"(alo), "r"(blo), "n"(DHI_SW128), "n"(DHI_NONE), "n"(SCALE_D), "n"(TB));
}

template <int TB>
DEVI void wgmma_n8_ss_first(float* d, uint32_t alo, uint32_t blo) {
    asm volatile("{.reg .b64 da, db; mov.b64 da, {%4, %6}; mov.b64 db, {%5, %7};\n"
                 "wgmma.mma_async.sync.aligned.m64n8k16.f32.bf16.bf16 {%0,%1,%2,%3}, da, db, 0, 1, 1, 1, %8;}"
                 : "=f"(d[0]), "=f"(d[1]), "=f"(d[2]), "=f"(d[3])
                 : "r"(alo), "r"(blo), "n"(DHI_SW128), "n"(DHI_NONE), "n"(TB));
}
DEVI void wgmma_n32_rs_first(float* d, const uint32_t* a, uint32_t blo) {
    asm volatile("{.reg .b64 db; mov.b64 db, {%20, %21};\n"
                 "wgmma.mma_async.sync.aligned.m64n32k16.f32.bf16.bf16 {%0,%1,%2,%3,%4,%5,%6,%7,%8,%9,%10,%11,%12,%13,%14,%15}, "
                 "{%16,%17,%18,%19}, db, 0, 1, 1, 0;}"
                 : "=f"(d[0]), "=f"(d[1]), "=f"(d[2]), "=f"(d[3]), "=f"(d[4]), "=f"(d[5]), "=f"(d[6]), "=f"(d[7]),
                   "=f"(d[8]), "=f"(d[9]), "=f"(d[10]), "=f"(d[11]), "=f"(d[12]), "=f"(d[13]), "=f"(d[14]), "=f"(d[15])
                 : "r"(a[0]), "r"(a[1]), "r"(a[2]), "r"(a[3]), "r"(blo), "n"(DHI_SW64));
}
template <int N> DEVI void reg_fence(float* d) {
#pragma unroll
    for (int i = 0; i < N; i++) asm volatile("" : "+f"(d[i]) :: "memory");
}
DEVI void wgmma_n32_rs(float* d, const uint32_t* a, uint32_t blo) {
    asm volatile("{.reg .b64 db; mov.b64 db, {%20, %21};\n"
                 "wgmma.mma_async.sync.aligned.m64n32k16.f32.bf16.bf16 {%0,%1,%2,%3,%4,%5,%6,%7,%8,%9,%10,%11,%12,%13,%14,%15}, "
                 "{%16,%17,%18,%19}, db, 1, 1, 1, 0;}"
                 : "+f"(d[0]), "+f"(d[1]), "+f"(d[2]), "+f"(d[3]), "+f"(d[4]), "+f"(d[5]), "+f"(d[6]), "+f"(d[7]),
                   "+f"(d[8]), "+f"(d[9]), "+f"(d[10]), "+f"(d[11]), "+f"(d[12]), "+f"(d[13]), "+f"(d[14]), "+f"(d[15])
                 : "r"(a[0]), "r"(a[1]), "r"(a[2]), "r"(a[3]), "r"(blo), "n"(DHI_SW64));
}
DEVI void wgmma_n32_ss(float* d, uint32_t alo, uint32_t blo) {
    asm volatile("{.reg .b64 da, db; mov.b64 da, {%16, %18}; mov.b64 db, {%17, %19};\n"
                 "wgmma.mma_async.sync.aligned.m64n32k16.f32.bf16.bf16 {%0,%1,%2,%3,%4,%5,%6,%7,%8,%9,%10,%11,%12,%13,%14,%15}, "
                 "da, db, 1, 1, 1, 1, 0;}"
                 : "+f"(d[0]), "+f"(d[1]), "+f"(d[2]), "+f"(d[3]), "+f"(d[4]), "+f"(d[5]), "+f"(d[6]), "+f"(d[7]),
                   "+f"(d[8]), "+f"(d[9]), "+f"(d[10]), "+f"(d[11]), "+f"(d[12]), "+f"(d[13]), "+f"(d[14]), "+f"(d[15])
                 : "r"(alo), "r"(blo), "n"(DHI_SW128), "n"(DHI_SW64));
}

template <bool FIRST>
DEVI void wgmma_n256_ss(float* d, uint64_t a, uint64_t b) {
    if (FIRST)
        asm volatile("wgmma.mma_async.sync.aligned.m64n256k16.f32.bf16.bf16 {%0,%1,%2,%3,%4,%5,%6,%7,%8,%9,%10,%11,%12,%13,%14,%15,%16,%17,%18,%19,%20,%21,%22,%23,%24,%25,%26,%27,%28,%29,%30,%31,%32,%33,%34,%35,%36,%37,%38,%39,%40,%41,%42,%43,%44,%45,%46,%47,%48,%49,%50,%51,%52,%53,%54,%55,%56,%57,%58,%59,%60,%61,%62,%63,%64,%65,%66,%67,%68,%69,%70,%71,%72,%73,%74,%75,%76,%77,%78,%79,%80,%81,%82,%83,%84,%85,%86,%87,%88,%89,%90,%91,%92,%93,%94,%95,%96,%97,%98,%99,%100,%101,%102,%103,%104,%105,%106,%107,%108,%109,%110,%111,%112,%113,%114,%115,%116,%117,%118,%119,%120,%121,%122,%123,%124,%125,%126,%127}, %128, %129, 0, 1, 1, 1, 0;"
            : "=f"(d[0]), "=f"(d[1]), "=f"(d[2]), "=f"(d[3]), "=f"(d[4]), "=f"(d[5]), "=f"(d[6]), "=f"(d[7]), "=f"(d[8]), "=f"(d[9]), "=f"(d[10]), "=f"(d[11]), "=f"(d[12]), "=f"(d[13]), "=f"(d[14]), "=f"(d[15]), "=f"(d[16]), "=f"(d[17]), "=f"(d[18]), "=f"(d[19]), "=f"(d[20]), "=f"(d[21]), "=f"(d[22]), "=f"(d[23]), "=f"(d[24]), "=f"(d[25]), "=f"(d[26]), "=f"(d[27]), "=f"(d[28]), "=f"(d[29]), "=f"(d[30]), "=f"(d[31]), "=f"(d[32]), "=f"(d[33]), "=f"(d[34]), "=f"(d[35]), "=f"(d[36]), "=f"(d[37]), "=f"(d[38]), "=f"(d[39]), "=f"(d[40]), "=f"(d[41]), "=f"(d[42]), "=f"(d[43]), "=f"(d[44]), "=f"(d[45]), "=f"(d[46]), "=f"(d[47]), "=f"(d[48]), "=f"(d[49]), "=f"(d[50]), "=f"(d[51]), "=f"(d[52]), "=f"(d[53]), "=f"(d[54]), "=f"(d[55]), "=f"(d[56]), "=f"(d[57]), "=f"(d[58]), "=f"(d[59]), "=f"(d[60]), "=f"(d[61]), "=f"(d[62]), "=f"(d[63]), "=f"(d[64]), "=f"(d[65]), "=f"(d[66]), "=f"(d[67]), "=f"(d[68]), "=f"(d[69]), "=f"(d[70]), "=f"(d[71]), "=f"(d[72]), "=f"(d[73]), "=f"(d[74]), "=f"(d[75]), "=f"(d[76]), "=f"(d[77]), "=f"(d[78]), "=f"(d[79]), "=f"(d[80]), "=f"(d[81]), "=f"(d[82]), "=f"(d[83]), "=f"(d[84]), "=f"(d[85]), "=f"(d[86]), "=f"(d[87]), "=f"(d[88]), "=f"(d[89]), "=f"(d[90]), "=f"(d[91]), "=f"(d[92]), "=f"(d[93]), "=f"(d[94]), "=f"(d[95]), "=f"(d[96]), "=f"(d[97]), "=f"(d[98]), "=f"(d[99]), "=f"(d[100]), "=f"(d[101]), "=f"(d[102]), "=f"(d[103]), "=f"(d[104]), "=f"(d[105]), "=f"(d[106]), "=f"(d[107]), "=f"(d[108]), "=f"(d[109]), "=f"(d[110]), "=f"(d[111]), "=f"(d[112]), "=f"(d[113]), "=f"(d[114]), "=f"(d[115]), "=f"(d[116]), "=f"(d[117]), "=f"(d[118]), "=f"(d[119]), "=f"(d[120]), "=f"(d[121]), "=f"(d[122]), "=f"(d[123]), "=f"(d[124]), "=f"(d[125]), "=f"(d[126]), "=f"(d[127]) : "l"(a), "l"(b));
    else
        asm volatile("wgmma.mma_async.sync.aligned.m64n256k16.f32.bf16.bf16 {%0,%1,%2,%3,%4,%5,%6,%7,%8,%9,%10,%11,%12,%13,%14,%15,%16,%17,%18,%19,%20,%21,%22,%23,%24,%25,%26,%27,%28,%29,%30,%31,%32,%33,%34,%35,%36,%37,%38,%39,%40,%41,%42,%43,%44,%45,%46,%47,%48,%49,%50,%51,%52,%53,%54,%55,%56,%57,%58,%59,%60,%61,%62,%63,%64,%65,%66,%67,%68,%69,%70,%71,%72,%73,%74,%75,%76,%77,%78,%79,%80,%81,%82,%83,%84,%85,%86,%87,%88,%89,%90,%91,%92,%93,%94,%95,%96,%97,%98,%99,%100,%101,%102,%103,%104,%105,%106,%107,%108,%109,%110,%111,%112,%113,%114,%115,%116,%117,%118,%119,%120,%121,%122,%123,%124,%125,%126,%127}, %128, %129, 1, 1, 1, 1, 0;"
            : "+f"(d[0]), "+f"(d[1]), "+f"(d[2]), "+f"(d[3]), "+f"(d[4]), "+f"(d[5]), "+f"(d[6]), "+f"(d[7]), "+f"(d[8]), "+f"(d[9]), "+f"(d[10]), "+f"(d[11]), "+f"(d[12]), "+f"(d[13]), "+f"(d[14]), "+f"(d[15]), "+f"(d[16]), "+f"(d[17]), "+f"(d[18]), "+f"(d[19]), "+f"(d[20]), "+f"(d[21]), "+f"(d[22]), "+f"(d[23]), "+f"(d[24]), "+f"(d[25]), "+f"(d[26]), "+f"(d[27]), "+f"(d[28]), "+f"(d[29]), "+f"(d[30]), "+f"(d[31]), "+f"(d[32]), "+f"(d[33]), "+f"(d[34]), "+f"(d[35]), "+f"(d[36]), "+f"(d[37]), "+f"(d[38]), "+f"(d[39]), "+f"(d[40]), "+f"(d[41]), "+f"(d[42]), "+f"(d[43]), "+f"(d[44]), "+f"(d[45]), "+f"(d[46]), "+f"(d[47]), "+f"(d[48]), "+f"(d[49]), "+f"(d[50]), "+f"(d[51]), "+f"(d[52]), "+f"(d[53]), "+f"(d[54]), "+f"(d[55]), "+f"(d[56]), "+f"(d[57]), "+f"(d[58]), "+f"(d[59]), "+f"(d[60]), "+f"(d[61]), "+f"(d[62]), "+f"(d[63]), "+f"(d[64]), "+f"(d[65]), "+f"(d[66]), "+f"(d[67]), "+f"(d[68]), "+f"(d[69]), "+f"(d[70]), "+f"(d[71]), "+f"(d[72]), "+f"(d[73]), "+f"(d[74]), "+f"(d[75]), "+f"(d[76]), "+f"(d[77]), "+f"(d[78]), "+f"(d[79]), "+f"(d[80]), "+f"(d[81]), "+f"(d[82]), "+f"(d[83]), "+f"(d[84]), "+f"(d[85]), "+f"(d[86]), "+f"(d[87]), "+f"(d[88]), "+f"(d[89]), "+f"(d[90]), "+f"(d[91]), "+f"(d[92]), "+f"(d[93]), "+f"(d[94]), "+f"(d[95]), "+f"(d[96]), "+f"(d[97]), "+f"(d[98]), "+f"(d[99]), "+f"(d[100]), "+f"(d[101]), "+f"(d[102]), "+f"(d[103]), "+f"(d[104]), "+f"(d[105]), "+f"(d[106]), "+f"(d[107]), "+f"(d[108]), "+f"(d[109]), "+f"(d[110]), "+f"(d[111]), "+f"(d[112]), "+f"(d[113]), "+f"(d[114]), "+f"(d[115]), "+f"(d[116]), "+f"(d[117]), "+f"(d[118]), "+f"(d[119]), "+f"(d[120]), "+f"(d[121]), "+f"(d[122]), "+f"(d[123]), "+f"(d[124]), "+f"(d[125]), "+f"(d[126]), "+f"(d[127]) : "l"(a), "l"(b));
}
template <bool FIRST>
DEVI void wgmma_n128_ss(float* d, uint64_t a, uint64_t b) {
    if (FIRST)
        asm volatile("wgmma.mma_async.sync.aligned.m64n128k16.f32.bf16.bf16 {%0,%1,%2,%3,%4,%5,%6,%7,%8,%9,%10,%11,%12,%13,%14,%15,%16,%17,%18,%19,%20,%21,%22,%23,%24,%25,%26,%27,%28,%29,%30,%31,%32,%33,%34,%35,%36,%37,%38,%39,%40,%41,%42,%43,%44,%45,%46,%47,%48,%49,%50,%51,%52,%53,%54,%55,%56,%57,%58,%59,%60,%61,%62,%63}, %64, %65, 0, 1, 1, 1, 0;"
            : "=f"(d[0]), "=f"(d[1]), "=f"(d[2]), "=f"(d[3]), "=f"(d[4]), "=f"(d[5]), "=f"(d[6]), "=f"(d[7]), "=f"(d[8]), "=f"(d[9]), "=f"(d[10]), "=f"(d[11]), "=f"(d[12]), "=f"(d[13]), "=f"(d[14]), "=f"(d[15]), "=f"(d[16]), "=f"(d[17]), "=f"(d[18]), "=f"(d[19]), "=f"(d[20]), "=f"(d[21]), "=f"(d[22]), "=f"(d[23]), "=f"(d[24]), "=f"(d[25]), "=f"(d[26]), "=f"(d[27]), "=f"(d[28]), "=f"(d[29]), "=f"(d[30]), "=f"(d[31]), "=f"(d[32]), "=f"(d[33]), "=f"(d[34]), "=f"(d[35]), "=f"(d[36]), "=f"(d[37]), "=f"(d[38]), "=f"(d[39]), "=f"(d[40]), "=f"(d[41]), "=f"(d[42]), "=f"(d[43]), "=f"(d[44]), "=f"(d[45]), "=f"(d[46]), "=f"(d[47]), "=f"(d[48]), "=f"(d[49]), "=f"(d[50]), "=f"(d[51]), "=f"(d[52]), "=f"(d[53]), "=f"(d[54]), "=f"(d[55]), "=f"(d[56]), "=f"(d[57]), "=f"(d[58]), "=f"(d[59]), "=f"(d[60]), "=f"(d[61]), "=f"(d[62]), "=f"(d[63]) : "l"(a), "l"(b));
    else
        asm volatile("wgmma.mma_async.sync.aligned.m64n128k16.f32.bf16.bf16 {%0,%1,%2,%3,%4,%5,%6,%7,%8,%9,%10,%11,%12,%13,%14,%15,%16,%17,%18,%19,%20,%21,%22,%23,%24,%25,%26,%27,%28,%29,%30,%31,%32,%33,%34,%35,%36,%37,%38,%39,%40,%41,%42,%43,%44,%45,%46,%47,%48,%49,%50,%51,%52,%53,%54,%55,%56,%57,%58,%59,%60,%61,%62,%63}, %64, %65, 1, 1, 1, 1, 0;"
            : "+f"(d[0]), "+f"(d[1]), "+f"(d[2]), "+f"(d[3]), "+f"(d[4]), "+f"(d[5]), "+f"(d[6]), "+f"(d[7]), "+f"(d[8]), "+f"(d[9]), "+f"(d[10]), "+f"(d[11]), "+f"(d[12]), "+f"(d[13]), "+f"(d[14]), "+f"(d[15]), "+f"(d[16]), "+f"(d[17]), "+f"(d[18]), "+f"(d[19]), "+f"(d[20]), "+f"(d[21]), "+f"(d[22]), "+f"(d[23]), "+f"(d[24]), "+f"(d[25]), "+f"(d[26]), "+f"(d[27]), "+f"(d[28]), "+f"(d[29]), "+f"(d[30]), "+f"(d[31]), "+f"(d[32]), "+f"(d[33]), "+f"(d[34]), "+f"(d[35]), "+f"(d[36]), "+f"(d[37]), "+f"(d[38]), "+f"(d[39]), "+f"(d[40]), "+f"(d[41]), "+f"(d[42]), "+f"(d[43]), "+f"(d[44]), "+f"(d[45]), "+f"(d[46]), "+f"(d[47]), "+f"(d[48]), "+f"(d[49]), "+f"(d[50]), "+f"(d[51]), "+f"(d[52]), "+f"(d[53]), "+f"(d[54]), "+f"(d[55]), "+f"(d[56]), "+f"(d[57]), "+f"(d[58]), "+f"(d[59]), "+f"(d[60]), "+f"(d[61]), "+f"(d[62]), "+f"(d[63]) : "l"(a), "l"(b));
}

template <bool FIRST>
DEVI void wgmma_n64_ss(float* d, uint64_t a, uint64_t b) {
    if (FIRST)
        asm volatile("wgmma.mma_async.sync.aligned.m64n64k16.f32.bf16.bf16 {%0,%1,%2,%3,%4,%5,%6,%7,%8,%9,%10,%11,%12,%13,%14,%15,%16,%17,%18,%19,%20,%21,%22,%23,%24,%25,%26,%27,%28,%29,%30,%31}, %32, %33, 0, 1, 1, 1, 0;"
            : "=f"(d[0]), "=f"(d[1]), "=f"(d[2]), "=f"(d[3]), "=f"(d[4]), "=f"(d[5]), "=f"(d[6]), "=f"(d[7]), "=f"(d[8]), "=f"(d[9]), "=f"(d[10]), "=f"(d[11]), "=f"(d[12]), "=f"(d[13]), "=f"(d[14]), "=f"(d[15]), "=f"(d[16]), "=f"(d[17]), "=f"(d[18]), "=f"(d[19]), "=f"(d[20]), "=f"(d[21]), "=f"(d[22]), "=f"(d[23]), "=f"(d[24]), "=f"(d[25]), "=f"(d[26]), "=f"(d[27]), "=f"(d[28]), "=f"(d[29]), "=f"(d[30]), "=f"(d[31]) : "l"(a), "l"(b));
    else
        asm volatile("wgmma.mma_async.sync.aligned.m64n64k16.f32.bf16.bf16 {%0,%1,%2,%3,%4,%5,%6,%7,%8,%9,%10,%11,%12,%13,%14,%15,%16,%17,%18,%19,%20,%21,%22,%23,%24,%25,%26,%27,%28,%29,%30,%31}, %32, %33, 1, 1, 1, 1, 0;"
            : "+f"(d[0]), "+f"(d[1]), "+f"(d[2]), "+f"(d[3]), "+f"(d[4]), "+f"(d[5]), "+f"(d[6]), "+f"(d[7]), "+f"(d[8]), "+f"(d[9]), "+f"(d[10]), "+f"(d[11]), "+f"(d[12]), "+f"(d[13]), "+f"(d[14]), "+f"(d[15]), "+f"(d[16]), "+f"(d[17]), "+f"(d[18]), "+f"(d[19]), "+f"(d[20]), "+f"(d[21]), "+f"(d[22]), "+f"(d[23]), "+f"(d[24]), "+f"(d[25]), "+f"(d[26]), "+f"(d[27]), "+f"(d[28]), "+f"(d[29]), "+f"(d[30]), "+f"(d[31]) : "l"(a), "l"(b));
}

DEVI void mma16816(float* d, const uint32_t* a, uint32_t b0, uint32_t b1) {
    asm volatile("mma.sync.aligned.m16n8k16.row.col.f32.bf16.bf16.f32 {%0,%1,%2,%3}, {%4,%5,%6,%7}, {%8,%9}, {%0,%1,%2,%3};"
                 : "+f"(d[0]), "+f"(d[1]), "+f"(d[2]), "+f"(d[3])
                 : "r"(a[0]), "r"(a[1]), "r"(a[2]), "r"(a[3]), "r"(b0), "r"(b1));
}
DEVI void mma1688(float* d, uint32_t a0, uint32_t a1, uint32_t b0) {
    asm volatile("mma.sync.aligned.m16n8k8.row.col.f32.bf16.bf16.f32 {%0,%1,%2,%3}, {%4,%5}, {%6}, {%0,%1,%2,%3};"
                 : "+f"(d[0]), "+f"(d[1]), "+f"(d[2]), "+f"(d[3]) : "r"(a0), "r"(a1), "r"(b0));
}
DEVI void ldsm4(uint32_t* r, uint32_t addr) {
    asm volatile("ldmatrix.sync.aligned.m8n8.x4.shared.b16 {%0,%1,%2,%3}, [%4];"
                 : "=r"(r[0]), "=r"(r[1]), "=r"(r[2]), "=r"(r[3]) : "r"(addr) : "memory");
}
DEVI void ldsm4t(uint32_t* r, uint32_t addr) {
    asm volatile("ldmatrix.sync.aligned.m8n8.x4.trans.shared.b16 {%0,%1,%2,%3}, [%4];"
                 : "=r"(r[0]), "=r"(r[1]), "=r"(r[2]), "=r"(r[3]) : "r"(addr) : "memory");
}
DEVI void stsm4(uint32_t addr, uint32_t r0, uint32_t r1, uint32_t r2, uint32_t r3) {
    asm volatile("stmatrix.sync.aligned.m8n8.x4.shared.b16 [%0], {%1,%2,%3,%4};" :: "r"(addr), "r"(r0), "r"(r1), "r"(r2), "r"(r3) : "memory");
}
DEVI void stsm4t(uint32_t addr, uint32_t r0, uint32_t r1, uint32_t r2, uint32_t r3) {
    asm volatile("stmatrix.sync.aligned.m8n8.x4.trans.shared.b16 [%0], {%1,%2,%3,%4};" :: "r"(addr), "r"(r0), "r"(r1), "r"(r2), "r"(r3) : "memory");
}
DEVI uint32_t pack_bf16(float lo, float hi) {
    uint32_t r; asm("cvt.rn.bf16x2.f32 %0, %1, %2;" : "=r"(r) : "f"(hi), "f"(lo)); return r;
}
DEVI float ex2(float x) { float y; asm("ex2.approx.ftz.f32 %0, %1;" : "=f"(y) : "f"(x)); return y; }

DEVI uint4 ld_rlx4(const void* p) {
    uint4 v;
    asm volatile("ld.relaxed.gpu.global.v4.u32 {%0,%1,%2,%3}, [%4];" : "=r"(v.x), "=r"(v.y), "=r"(v.z), "=r"(v.w) : "l"(p) : "memory");
    return v;
}
DEVI void st_rlx4(void* p, uint32_t a, uint32_t b, uint32_t c, uint32_t d) {
    asm volatile("st.relaxed.gpu.global.v4.u32 [%0], {%1,%2,%3,%4};" :: "l"(p), "r"(a), "r"(b), "r"(c), "r"(d) : "memory");
}
DEVI void sts128(uint32_t addr, uint4 v) {
    asm volatile("st.shared.v4.u32 [%0], {%1,%2,%3,%4};" :: "r"(addr), "r"(v.x), "r"(v.y), "r"(v.z), "r"(v.w) : "memory");
}
DEVI void sts64(uint32_t addr, uint32_t a, uint32_t b) { asm volatile("st.shared.v2.u32 [%0], {%1,%2};" :: "r"(addr), "r"(a), "r"(b) : "memory"); }
DEVI void sts32(uint32_t addr, uint32_t v) { asm volatile("st.shared.u32 [%0], %1;" :: "r"(addr), "r"(v) : "memory"); }
DEVI uint4 lds128(uint32_t addr) {
    uint4 v; asm volatile("ld.shared.v4.u32 {%0,%1,%2,%3}, [%4];" : "=r"(v.x), "=r"(v.y), "=r"(v.z), "=r"(v.w) : "r"(addr) : "memory"); return v;
}
DEVI float2 lds64f(uint32_t addr) {
    float2 v; asm volatile("ld.shared.v2.f32 {%0,%1}, [%2];" : "=f"(v.x), "=f"(v.y) : "r"(addr) : "memory"); return v;
}
DEVI uint32_t lds32(uint32_t addr) { uint32_t v; asm volatile("ld.shared.u32 %0, [%1];" : "=r"(v) : "r"(addr) : "memory"); return v; }
DEVI float rcp_fast(float x) { float y; asm("rcp.approx.ftz.f32 %0, %1;" : "=f"(y) : "f"(x)); return y; }
DEVI uint32_t mapa(uint32_t addr, uint32_t rank) {
    uint32_t r; asm("mapa.shared::cluster.u32 %0, %1, %2;" : "=r"(r) : "r"(addr), "r"(rank)); return r;
}
DEVI void st_async32(uint32_t dst, uint32_t a, uint32_t bar) {
    asm volatile("st.async.weak.shared::cluster.mbarrier::complete_tx::bytes.b32 [%0], %1, [%2];" :: "r"(dst), "r"(a), "r"(bar) : "memory");
}

DEVI void st_async128(uint32_t dst, uint32_t a, uint32_t b, uint32_t c, uint32_t d, uint32_t bar) {
    asm volatile("st.async.weak.shared::cluster.mbarrier::complete_tx::bytes.v4.b32 [%0], {%1,%2,%3,%4}, [%5];"
                 :: "r"(dst), "r"(a), "r"(b), "r"(c), "r"(d), "r"(bar) : "memory");
}

DEVI uint32_t b_addr(uint32_t sb, int row, int which, int chunk) { const int l = 3 * row + which; return sb + l * 128 + ((chunk ^ (l & 7)) * 16); }
DEVI void battn_warp(uint32_t st, uint32_t ebar, int i0, int par, int head, int hh, int mt, int lane) {
    const int gq = lane >> 2, t = lane & 3, r = 16 * mt + (lane & 7), b3 = (lane >> 3) & 1, b4 = lane >> 4;
    uint32_t a[8], k[8], k2[4], v[8], v2[4];
#pragma unroll
    for (int ks = 0; ks < 2; ks++) {
        ldsm4(a + 4 * ks, b_addr(st, 8 + r + b3 * 8, 0, hh * 4 + ks * 2 + b4));
        ldsm4(k + 4 * ks, b_addr(st, r + b4 * 8, 1, hh * 4 + ks * 2 + b3));
    }
    ldsm4(k2, b_addr(st, r + 16, 1, hh * 4 + (lane >> 3)));
#pragma unroll
    for (int n = 0; n < 2; n++) ldsm4t(v + 4 * n, b_addr(st, r + b3 * 8, 2, hh * 4 + 2 * n + b4));
    ldsm4t(v2, b_addr(st, r + 16, 2, hh * 4 + (lane >> 3)));
    float s[3][4];
#pragma unroll
    for (int n = 0; n < 3; n++) { s[n][0] = s[n][1] = s[n][2] = s[n][3] = 0.f; }
#pragma unroll
    for (int ks = 0; ks < 2; ks++) {
        mma16816(s[0], a + 4 * ks, k[4 * ks], k[4 * ks + 1]);
        mma16816(s[1], a + 4 * ks, k[4 * ks + 2], k[4 * ks + 3]);
        mma16816(s[2], a + 4 * ks, k2[2 * ks], k2[2 * ks + 1]);
    }
    const bool ex = i0 + 16 * mt > 0;
    float x[4], y[4];
#pragma unroll
    for (int c = 0; c < 2; c++) {
        const bool low = 2 * t + c <= gq;
        x[c] = !low && ex ? s[0][c] : -INFINITY; x[2 + c] = low ? s[1][c] : -INFINITY;
        y[c] = !low ? s[1][2 + c] : -INFINITY;   y[2 + c] = low ? s[2][2 + c] : -INFINITY;
    }
    float m0 = fmaxf(fmaxf(x[0], x[1]), fmaxf(x[2], x[3])), m1 = fmaxf(fmaxf(y[0], y[1]), fmaxf(y[2], y[3]));
    m0 = fmaxf(fmaxf(m0, __shfl_xor_sync(0xffffffffu, m0, 1)), fmaxf(__shfl_xor_sync(0xffffffffu, m0, 2), __shfl_xor_sync(0xffffffffu, m0, 3)));
    m1 = fmaxf(fmaxf(m1, __shfl_xor_sync(0xffffffffu, m1, 1)), fmaxf(__shfl_xor_sync(0xffffffffu, m1, 2), __shfl_xor_sync(0xffffffffu, m1, 3)));
    constexpr float C = 0.17677669529663687f * 1.4426950408889634f;
    auto e = [](float v, float mx) { return ex2((v - mx) * C); };
    const uint32_t p0[4] = {pack_bf16(e(x[0], m0), e(x[1], m0)), 0u, pack_bf16(e(x[2], m0), e(x[3], m0)), pack_bf16(e(y[0], m1), e(y[1], m1))};
    const uint32_t p1 = pack_bf16(e(y[2], m1), e(y[3], m1));
    float o[4][4], l[4] = {0.f, 0.f, 0.f, 0.f};
#pragma unroll
    for (int n = 0; n < 4; n++) { o[n][0] = o[n][1] = o[n][2] = o[n][3] = 0.f; }
    mma16816(l, p0, 0x3F803F80u, 0x3F803F80u);
#pragma unroll
    for (int n = 0; n < 4; n++) mma16816(o[n], p0, v[2 * n], v[2 * n + 1]);
    mma1688(l, 0u, p1, 0x3F803F80u);
#pragma unroll
    for (int n = 0; n < 4; n++) mma1688(o[n], 0u, p1, v2[n]);
    if (lane == 0) mbar_arrive(ebar);
    const float i0f = rcp_fast(l[0]), i1f = rcp_fast(l[2]);
    uint4* dst = (uint4*)(g_bo + (uint32_t)((2 * (i0 + 16 * mt + gq) + par) * DM + head * 32 + t * 8));
    dst[0] = make_uint4(pack_bf16(o[0][0] * i0f, o[0][1] * i0f), pack_bf16(o[1][0] * i0f, o[1][1] * i0f),
                        pack_bf16(o[2][0] * i0f, o[2][1] * i0f), pack_bf16(o[3][0] * i0f, o[3][1] * i0f));
    dst[16 * DM / 8] = make_uint4(pack_bf16(o[0][2] * i1f, o[0][3] * i1f), pack_bf16(o[1][2] * i1f, o[1][3] * i1f),
                                  pack_bf16(o[2][2] * i1f, o[2][3] * i1f), pack_bf16(o[3][2] * i1f, o[3][3] * i1f));
}

constexpr float SCALE_LOG2E = 0.08838834764831845f * 1.4426950408889634f;

constexpr int P_UNITS = 12, P_STAGES = 6;
constexpr int PS_STG = P_UNITS * 16384;
constexpr int P_SMEM = 232448;
constexpr int PS_BAR = P_SMEM - 256;
static_assert(PS_STG + 32768 <= PS_BAR, "smem");
enum { K_Q, K_B1, K_B3, K_A4, K_QH, K_A3, K_SK, K_B2, K_SN, K_END };
struct PList { int n, nworker, late; int4 run[16]; };
struct PTask { int kind, a, b, c, id; };
DEVI PTask p_decode(const PList& pl, int id) {
    int i = pl.n - 1;
    if (id >= pl.run[i].w) return {K_END, 0, 0, 0, id};
    while (id < pl.run[i].z) i--;
    const int4 r = pl.run[i];
    const int j = id - r.z;
    if (r.x == K_Q || r.x == K_QH) return {r.x, j & 31, r.y + (j >> 5), 0, id};
    if (r.x == K_B1) return {r.x, j % 24, r.y + j / 24, 0, id};
    if (r.x == K_B2) return {r.x, 0, r.y + j, 0, id};
    if (r.x == K_SK || r.x == K_SN) return {r.x, (j / P_SPLIT) & 7, r.y + j / (8 * P_SPLIT), j % P_SPLIT, id};
    return {r.x, j & 7, r.y + (j >> 3), 0, id};
}
DEVI void wait_count_warp(const unsigned* p, unsigned target) {
    int n = 0;
    while (true) {
        unsigned v; asm volatile("ld.acquire.gpu.global.u32 %0, [%1];" : "=r"(v) : "l"(p) : "memory");
        if (__all_sync(0xffffffffu, (int)(v - target) >= 0)) break;
        __nanosleep(100);
        if (++n > SPIN_LIMIT) __trap();
    }
}
DEVI void signal_count(unsigned* p) { __threadfence(); atomicAdd(p, 1u); }

struct PMaps { CUtensorMap wq, bw, bwo, wo, x, bx, bo, ox, ox64, cb, cout, cq, b40; PList list; };
constexpr int PB_F = PS_BAR, PB_E = PB_F + 48, PB_TF = PB_F + 96, PB_TE = PB_F + 112, PB_S = PB_F + 128;
constexpr int PS_T = PB_F + 160, PS_SIG = PS_T + 32, PS_SK = PS_SIG + 16;

struct PRing {
    int st, ph, u;
    DEVI void next(int n) { u += n; if (u >= P_UNITS) u -= P_UNITS; if (++st == P_STAGES) { st = 0; ph ^= 1; } }
    DEVI uint32_t w(bool wide) const { return wide && u == P_UNITS - 2 ? 0u : u * 16384u; }
    DEVI uint32_t x(bool wide) const { return wide && u == P_UNITS - 2 ? u * 16384u : (u == P_UNITS - 1 ? 0u : (u + 1) * 16384u); }
};
struct POut { const CUtensorMap* map; int col, tok, cnt; bool blocked; };
DEVI void p_store(const uint32_t* pk, const POut& o, int c, uint32_t stg, int warp, int lane_, int barid) {
    const int lane = (int)opaque((uint32_t)lane_);
    const int mi = lane >> 3, r = lane & 7;
    const uint32_t buf = stg + (c & 1) * 8192;
    if (warp == 0) asm volatile("cp.async.bulk.wait_group.read 1;" ::: "memory");
    nbar_sync(barid, 128);
    if (o.blocked) {
#pragma unroll
        for (int j = 0; j < 8; j += 2)
            stsm4(buf + (j + (mi >> 1)) * 1024 + (warp * 16 + (mi & 1) * 8 + r) * 16, pk[2 * j], pk[2 * j + 1], pk[2 * j + 2], pk[2 * j + 3]);
    } else {
#pragma unroll
        for (int j = 0; j < 8; j += 2)
            stsm4t(buf + (8 * (j + (mi >> 1)) + r) * 128 + ((2 * warp + (mi & 1)) ^ r) * 16, pk[2 * j], pk[2 * j + 1], pk[2 * j + 2], pk[2 * j + 3]);
    }
    fence_proxy_async();
    nbar_sync(barid, 128);
    if (warp == 0 && elect_one()) {
        if (o.blocked)
            asm volatile("cp.async.bulk.tensor.4d.global.shared::cta.bulk_group [%0, {%2, %3, %4, %5}], [%1];"
                         :: "l"(o.map), "r"(buf), "r"(0), "r"((o.col >> 5) & 2), "r"((o.col >> 7) * 4), "r"((o.tok >> 5) + 2 * c) : "memory");
        else tma_store_2d(o.map, buf, o.col, o.tok + c * 64);
        bulk_commit();
    }
}
DEVI void p_signal(uint32_t sb, int g, int cnt, int& nsig) {
    if (elect_one()) {
        sts32(sb + PS_SIG + g * 8 + (nsig & 1) * 4, (uint32_t)cnt);
        mbar_arrive(sb + PB_S + g * 16 + (nsig & 1) * 8);
    }
    nsig++;
}
DEVI void p_release(uint32_t sb, const PRing& r) {
    if (elect_one()) mbar_arrive(sb + PB_E + (r.st ? r.st - 1 : P_STAGES - 1) * 8);
}
template <int BN, bool FIRST>
DEVI void p_kblock(float* d, uint32_t sb, int g, PRing& r) {
    mbar_wait(sb + PB_F + r.st * 8, r.ph);
    const uint64_t da = mk_desc(sb + r.w(BN == 256) + g * 8192, 16, 1024, 1), db = mk_desc(sb + r.x(BN == 256), 16, 1024, 1);
    wg_fence();
#pragma unroll
    for (int kk = 0; kk < 4; kk++) {
        if (BN == 256) { if (FIRST && kk == 0) wgmma_n256_ss<true>(d, da, db); else wgmma_n256_ss<false>(d, da + (uint64_t)(kk * 128), db + (uint64_t)(kk * 2)); }
        if (BN == 128) { if (FIRST && kk == 0) wgmma_n128_ss<true>(d, da, db); else wgmma_n128_ss<false>(d, da + (uint64_t)(kk * 128), db + (uint64_t)(kk * 2)); }
        if (BN == 64)  { if (FIRST && kk == 0) wgmma_n64_ss<true>(d, da, db); else wgmma_n64_ss<false>(d, da + (uint64_t)(kk * 128), db + (uint64_t)(kk * 2)); }
    }
    wg_commit();
    if (!FIRST) {
        wg_wait<1>();
        p_release(sb, r);
    }
    r.next(BN == 256 ? 3 : 2);
}

DEVI PTask post_claim(const PMaps& mp, unsigned E) {
    unsigned v = 0;
    if ((threadIdx.x & 31) == 0) v = atomicAdd(&g_qctr, 1u);
    return p_decode(mp.list, (int)(__shfl_sync(0xffffffffu, v, 0) - (E - 1) * (unsigned)(mp.list.run[mp.list.n - 1].w + mp.list.nworker)));
}
DEVI void post_producer(const PMaps& mp, uint32_t sb, unsigned E, bool early) {
    PRing r = {0, 0, 0};
    int ts = 0, tp = 0, used = 0;
    uint32_t big = 0;
    auto reserve = [&](int n) {
        while (used + n > P_UNITS) {
            mbar_wait(sb + PB_E + ts * 8, tp);
            used -= 2 + ((big >> ts) & 1);
            if (++ts == P_STAGES) { ts = 0; tp ^= 1; }
        }
        used += n;
        big = (big & ~(1u << r.st)) | ((uint32_t)(n & 1) << r.st);
    };
    for (int i = 0;; i++) {
        if (i > 0) mbar_wait(sb + PB_TE + (i & 1) * 8, ((i >> 1) & 1) ^ 1);
        else if (!early) nbar_sync(0, 384);
        const PTask tk = post_claim(mp, E);
        if (i == 0) { if (early) nbar_sync(0, 384); fence_proxy_async(); }
        const bool sn = tk.kind == K_SN, split = tk.kind == K_SK || sn, wide = tk.kind <= K_A4;
        const bool qk = tk.kind == K_Q || tk.kind == K_QH, ak = tk.kind == K_A4 || tk.kind == K_A3 || split;
        const int nk = split ? HD / 64 / P_SPLIT : (ak ? HD / 64 : DM / 64), kb0 = tk.c * (HD / 64 / P_SPLIT);
        const int tok0 = tk.b * (wide ? 256 : (sn ? 64 : 128)), grp = (tok0 >> 6) + (wide ? 3 : (sn ? 0 : 1));
        const uint32_t bytes = wide ? 49152 : (sn ? 24576 : 32768);
        const CUtensorMap* tx = tk.kind == K_B1 ? &mp.bx : (qk ? &mp.x : (sn ? &mp.ox64 : (ak ? &mp.ox : &mp.bo)));
        const int npre = split && (i == 0 || __any_sync(0xffffffffu, (int)(*(volatile unsigned*)&g_prog[grp] - 64 * E) < 0)) ? P_STAGES : 0;
        PRing rp = r;
        for (int kb = kb0; kb < kb0 + npre; kb++) {
            reserve(2);
            const uint32_t bar = sb + PB_F + r.st * 8;
            if (elect_one()) {
                mbar_expect_tx(bar, bytes);
                tma_load_wo(sb + r.w(false), &mp.wo, tk.a * 128, kb * 2, bar);
                tma_load_wo(sb + r.w(false) + 8192, &mp.wo, tk.a * 128 + 64, kb * 2, bar);
            }
            r.next(2);
        }
        if (tk.kind == K_B2) {
            wait_count_warp(&g_cnt[C_B1 + (tk.b >> 2)], 48 * E);
            if ((tk.b & 3) == 0 && tk.b > 0) wait_count_warp(&g_cnt[C_B1 + (tk.b >> 2) - 1], 48 * E);
        } else if (tk.kind == K_B3) wait_count_warp(&g_cnt[C_B2 + tk.b], 8 * E);
        else if (ak) wait_count_warp(&g_prog[grp], 64 * E);
        fence_proxy_global();
        for (int kb = kb0; kb < kb0 + npre; kb++) {
            if (elect_one()) tma_load_2d(sb + rp.x(false), tx, kb * 64, tok0, sb + PB_F + rp.st * 8);
            rp.next(2);
        }
        if (elect_one()) {
            sts128(sb + PS_T + (i & 1) * 16, make_uint4((uint32_t)tk.kind | ((uint32_t)tk.id << 8), (uint32_t)tk.a, (uint32_t)tk.b, (uint32_t)tk.c));
            mbar_arrive(sb + PB_TF + (i & 1) * 8);
        }
        if (tk.kind == K_END) break;
        if (tk.kind == K_B2) {
            for (int j = 0; j < 16; j++) {
                reserve(2);
                const uint32_t bar = sb + PB_F + r.st * 8;
                if (elect_one()) {
                    mbar_expect_tx(bar, 2 * 15360);
#pragma unroll
                    for (int u = 0; u < 2; u++) asm volatile("cp.async.bulk.tensor.4d.shared::cluster.global.mbarrier::complete_tx::bytes [%0], [%1, {%3, %4, %5, %6}], [%2];"
                                 :: "r"(sb + (u ? r.x(false) : r.w(false))), "l"(&mp.b40), "r"(bar), "r"(j * 64), "r"(0), "r"(u), "r"(tk.b * 32 - 8) : "memory");
                }
                r.next(2);
            }
            continue;
        }
        const CUtensorMap* tw = tk.kind == K_B1 ? &mp.bw : (qk ? &mp.wq : (ak ? &mp.wo : &mp.bwo));
        for (int kb = kb0 + npre; kb < kb0 + nk; kb++) {
            reserve(wide ? 3 : 2);
            const uint32_t aw = sb + r.w(wide), ax = sb + r.x(wide), bar = sb + PB_F + r.st * 8;
            if (elect_one()) {
                mbar_expect_tx(bar, bytes);
                if (ak || tk.kind == K_B3) {
                    tma_load_wo(aw, tw, tk.a * 128, kb * 2, bar);
                    tma_load_wo(aw + 8192, tw, tk.a * 128 + 64, kb * 2, bar);
                } else {
                    tma_load_2d(aw, tw, tk.a * 128, kb * 64, bar);
                    tma_load_2d(aw + 8192, tw, tk.a * 128 + 64, kb * 64, bar);
                }
                tma_load_2d(ax, tx, kb * 64, tok0, bar);
                if (wide) tma_load_2d(ax + 16384, tx, kb * 64, tok0 + 128, bar);
            }
            r.next(wide ? 3 : 2);
        }
        if (tk.id >= mp.list.late) { reserve(P_UNITS - 3); used -= P_UNITS - 3; }
    }
    if (elect_one()) {
        __threadfence();
        if (atomicAdd(&g_done, 1u) == E * mp.list.nworker - 1) { __threadfence(); *(volatile unsigned*)&g_epoch = E; }
    }
}
DEVI void post_helper(uint32_t sb, int g) {
    for (int n = 0;; n++) {
        mbar_wait_sleepy(sb + PB_S + g * 16 + (n & 1) * 8, (n >> 1) & 1);
        const int cnt = (int)lds32(sb + PS_SIG + g * 8 + (n & 1) * 4);
        if (cnt < 0) break;
        signal_count(&g_cnt[cnt]);
    }
}
template <int BN>
DEVI void p_narrow(const PMaps& mp, const PTask& tk, uint32_t sb, int g, int warp, PRing& r, int& nsig) {
    const int barid = 1 + g, tid = threadIdx.x;
    const bool split = BN == 64 || tk.kind == K_SK;
    constexpr int NV = BN / 16;
    float d[BN / 2];
    const int nk = split ? HD / 64 / P_SPLIT : (tk.kind == K_A3 ? HD / 64 : DM / 64);
    p_kblock<BN, true>(d, sb, g, r);
#pragma unroll 1
    for (int kb = 1; kb < nk; kb++) p_kblock<BN, false>(d, sb, g, r);
    wg_wait<0>();
    reg_fence<BN / 2>(d);
    p_release(sb, r);
    if (split) {
        const int tile = (tk.b * (BN / 64) - 2 * (16 - P_NSK)) * 8 + tk.a * (BN / 64);
        uint4* const base = g_skp + (uint32_t)(tile * P_SPLIT * 1024 + g * NV * 128 + (tid & 127));
#pragma unroll
        for (int j = 0; j < NV; j++)
            base[tk.c * NV * 256 + j * 128] = make_uint4(pack_bf16(d[8 * j], d[8 * j + 1]), pack_bf16(d[8 * j + 2], d[8 * j + 3]),
                                                         pack_bf16(d[8 * j + 4], d[8 * j + 5]), pack_bf16(d[8 * j + 6], d[8 * j + 7]));
        nbar_sync(barid, 128);
        if (warp == 0 && elect_one()) {
            unsigned old;
            asm volatile("atom.acq_rel.gpu.global.add.u32 %0, [%1], 1;" : "=r"(old) : "l"(&g_cnt_sk[tile * 2 + g]) : "memory");
            sts32(sb + PS_SK + g * 4, old % P_SPLIT);
        }
        nbar_sync(barid, 128);
        const bool last = __any_sync(0xffffffffu, lds32(sb + PS_SK + g * 4) == P_SPLIT - 1);
        nbar_sync(barid, 128);
        if (!last) return;
        uint4 v[(P_SPLIT - 1) * NV];
#pragma unroll
        for (int j = 0; j < (P_SPLIT - 1) * NV; j++) v[j] = __ldcg(base + ((tk.c + 1 + j / NV) % P_SPLIT) * NV * 256 + (j % NV) * 128);
#pragma unroll
        for (int j = 0; j < (P_SPLIT - 1) * NV; j++) {
            float* e = d + 8 * (j % NV);
            e[0] += __uint_as_float(v[j].x << 16); e[1] += __uint_as_float(v[j].x & 0xFFFF0000u);
            e[2] += __uint_as_float(v[j].y << 16); e[3] += __uint_as_float(v[j].y & 0xFFFF0000u);
            e[4] += __uint_as_float(v[j].z << 16); e[5] += __uint_as_float(v[j].z & 0xFFFF0000u);
            e[6] += __uint_as_float(v[j].w << 16); e[7] += __uint_as_float(v[j].w & 0xFFFF0000u);
        }
    }
    const bool qh = BN == 128 && tk.kind == K_QH;
    const POut o = {qh ? &mp.cq : &mp.cout, tk.a * 128 + g * 64, tk.b * BN, 0, qh};
    uint32_t q[BN / 4];
#pragma unroll
    for (int j = 0; j < BN / 4; j++) q[j] = pack_bf16(d[2 * j], d[2 * j + 1]);
    if (BN == 64 && warp == 0) bulk_wait_read();
#pragma unroll
    for (int c = 0; c < BN / 64; c++) p_store(q + 16 * c, o, c, sb + PS_STG + g * 16384, warp, tid & 31, barid);
    if (BN == 64 && warp == 0) bulk_wait_read();
    if (warp == 0 && qh) { bulk_wait_all(); p_signal(sb, g, tk.b == 0 ? C_QH : C_Q, nsig); }
}
DEVI void post_consumer(const PMaps& mp, uint32_t sb, int g, int warp) {
    const int barid = 1 + g, tid = threadIdx.x, lane = tid & 31;
    const uint32_t stg = sb + PS_STG + g * 16384;
    int nsig = 0;
    PRing r = {0, 0, 0};
    uint32_t pk[64];
    POut out;
    bool pend = false;
#pragma unroll
    for (int i = 0; i < 64; i++) pk[i] = 0u;
    for (int i = 0;; i++) {
        const uint32_t bTF = sb + PB_TF + (i & 1) * 8;
        if (pend) {
            uint32_t now;
            asm volatile("{.reg .pred p, q; mbarrier.test_wait.parity.shared::cta.b64 p, [%1], %2; bar.red.and.pred q, %3, 128, p; selp.u32 %0, 1, 0, q;}"
                         : "=r"(now) : "r"(bTF), "r"((i >> 1) & 1), "r"(barid) : "memory");
            if (__any_sync(0xffffffffu, !now || (lds32(sb + PS_T + (i & 1) * 16) & 255u) > K_A4)) {
#pragma unroll
                for (int c = 0; c < 4; c++) p_store(pk + 16 * c, out, c, stg, warp, lane, barid);
                if (warp == 0 && out.cnt != C_NONE) { bulk_wait_all(); p_signal(sb, g, out.cnt, nsig); }
                pend = false;
            }
        }
        mbar_wait(bTF, (i >> 1) & 1);
        uint4 tw = lds128(sb + PS_T + (i & 1) * 16);
        tw = make_uint4(__shfl_sync(0xffffffffu, tw.x, 0), __shfl_sync(0xffffffffu, tw.y, 0), __shfl_sync(0xffffffffu, tw.z, 0), __shfl_sync(0xffffffffu, tw.w, 0));
        mbar_arrive(sb + PB_TE + (i & 1) * 8);
        const PTask tk = {(int)(tw.x & 255u), (int)tw.y, (int)tw.z, (int)tw.w, 0};
        if (tk.kind == K_END) break;
        if (tk.kind <= K_A4) {
            float d[128];
            const int nk = tk.kind == K_A4 ? HD / 64 : DM / 64;
            p_kblock<256, true>(d, sb, g, r);
            if (pend) p_store(pk, out, 0, stg, warp, lane, barid);
#pragma unroll
            for (int c = 1; c < 4; c++) {
                p_kblock<256, false>(d, sb, g, r);
                if (pend) p_store(pk + 16 * c, out, c, stg, warp, lane, barid);
            }
#pragma unroll 1
            for (int kb = 4; kb < nk; kb++) {
                p_kblock<256, false>(d, sb, g, r);
                if (kb == 6 && pend && warp == 0 && out.cnt != C_NONE) { bulk_wait_all(); p_signal(sb, g, out.cnt, nsig); }
            }
            wg_wait<0>();
            reg_fence<128>(d);
            p_release(sb, r);
#pragma unroll
            for (int j = 0; j < 64; j++) pk[j] = pack_bf16(d[2 * j], d[2 * j + 1]);
            out.map = tk.kind == K_Q ? &mp.cq : (tk.kind == K_B1 ? &mp.cb : &mp.cout);
            out.col = tk.a * 128 + g * 64 + (tk.kind == K_B3 ? DM : 0);
            out.tok = tk.b * 256;
            out.cnt = tk.kind == K_Q ? C_Q + tk.b : (tk.kind == K_B1 ? C_B1 + tk.b : C_NONE);
            out.blocked = tk.kind == K_Q;
            pend = true;
        } else if (tk.kind == K_B2) {
#pragma unroll 2
            for (int j = 0; j < 16; j++) {
                mbar_wait(sb + PB_F + r.st * 8, r.ph);
                const uint32_t a = sb + (g ? r.x(false) : r.w(false));
                battn_warp(a, sb + PB_E + r.st * 8, tk.b * 32, g, j * 2 + (warp >> 1), warp >> 1, warp & 1, lane);
                r.next(2);
            }
            nbar_sync(barid, 128);
            if (warp == 0) p_signal(sb, g, C_B2 + (tk.b >> 2), nsig);
#pragma unroll
            for (int j = 0; j < 64; j++) pk[j] = 0u;
        } else {
            if (tk.kind == K_SN) p_narrow<64>(mp, tk, sb, g, warp, r, nsig); else p_narrow<128>(mp, tk, sb, g, warp, r, nsig);
#pragma unroll
            for (int j = 0; j < 64; j++) pk[j] = 0u;
        }
    }
    if (warp == 0) { bulk_wait_all(); p_signal(sb, g, -1, nsig); }
}
DEVI void post_init(uint32_t sb) {
    for (int i = 0; i < P_STAGES; i++) { mbar_init(sb + PB_F + i * 8, 1); mbar_init(sb + PB_E + i * 8, 8); }
    for (int i = 0; i < 2; i++) { mbar_init(sb + PB_TF + i * 8, 1); mbar_init(sb + PB_TE + i * 8, 256); }
    for (int i = 0; i < 4; i++) mbar_init(sb + PB_S + i * 8, 1);
    fence_mbar_init();
}

constexpr unsigned long long R_TORD_PACK = 0xfae93542dc187b60ull;
__host__ __device__ constexpr int r_tord(int pos) { return (int)((R_TORD_PACK >> (4 * pos)) & 15ull); }
__host__ __device__ constexpr int r_tinv(int T) { for (int p = 0; p < 16; p++) if (r_tord(p) == T) return p; return 0; }
__host__ __device__ constexpr bool r_pos_ss(int pos) { return pos % 3 == 2; }
__host__ __device__ constexpr int r_ss(int pos) { return pos / 3; }
__host__ __device__ constexpr int r_rs(int pos) { return pos - pos / 3; }
constexpr int R_NRS = 11, R_NSS = 5;
constexpr int R_G1 = 3, R_G2 = 9, R_G3 = 12;
#define REG_KB 232
constexpr int X_SLOTS = 4;
constexpr int X_NST = 8;

constexpr int RS_WSS  = 0;
constexpr int RS_WO   = RS_WSS + R_NSS * 16384;
constexpr int RS_MEM  = RS_WO + 5 * 16384;
constexpr int RS_O    = RS_MEM + 16384;
constexpr int RS_SX   = RS_O + 2048;
constexpr int RS_BAR  = RS_SX + 2048;
constexpr int RS_TAIL = RS_BAR + 1024;
constexpr int RS_WO5  = RS_TAIL;
constexpr int RS_K    = RS_WO5 + 16384;
constexpr int RS_V    = RS_K + 10240;
constexpr int RS_Q    = RS_V + 10240;
constexpr int RS_QX   = RS_Q + 2048;
constexpr int RS_QEND = RS_QX + 8192;
constexpr int RS_X    = RS_TAIL;
constexpr int X_PITCH = X_SLOTS * 4096;
constexpr int RS_XD   = RS_X + 2 * X_PITCH;
constexpr int RS_WX   = RS_XD + 8192;
constexpr int RS_XE   = RS_WX + 4096;
constexpr int RS_KEND = RS_XE + 2048;
constexpr int RS_EV   = RS_BAR + 256;
constexpr int R_SMEM  = RS_KEND > RS_QEND ? RS_KEND : RS_QEND;
static_assert(R_SMEM <= 232448 && P_SMEM <= R_SMEM, "smem");
static_assert(RS_TAIL % 1024 == 0 && RS_MEM % 1024 == 0, "alignment");

constexpr int RB_G = RS_BAR, RB_K = RS_BAR + 24, RB_V = RS_BAR + 32, RB_KV = RS_BAR + 40, RB_QX = RS_BAR + 48, RB_O = RS_BAR + 56;
constexpr int RB_ATT = RS_BAR + 64, RB_W = RS_BAR + 72, RB_SF = RS_BAR + 80, RB_SE = RB_SF + 40, RB_XF = RB_SE + 40;
constexpr int RB_VX = RB_XF + 48, RB_WO = RB_XF + 56, RB_T = RB_XF + 64, RB_G3 = RB_XF + 72, RS_INV = RB_XF + 16;
static_assert(RB_G3 + 8 <= RS_EV, "barriers");
constexpr uint32_t SB0 = 1024;
__host__ __device__ constexpr uint32_t cdesc(uint32_t off, uint32_t lbo) { return ((SB0 + off) >> 4) | ((lbo >> 4) << 16); }
#define SCHED_FENCE() __syncwarp()
constexpr int NB_BIG = 1, NB_Q = 2, NB_AUX = 3, NB_WO = 4, NB_XS = 5, NB_WG = 6, NB_PAIR = 8, NB_PRO = 12;

DEVI int tid_now() { int t; asm volatile("mov.u32 %0, %%tid.x;" : "=r"(t)); return t; }
DEVI uint32_t a_frag_off(int lane, int warp) { return (uint32_t)((((lane >> 4) * 8 + (lane & 7)) * 128) + (((2 * warp + ((lane >> 3) & 1)) ^ (lane & 7)) * 16)); }
DEVI uint32_t b_frag_off(int lane) { return (uint32_t)((lane & 3) * 64 + (((lane >> 2) * 8) ^ ((lane & 2) * 16))); }
DEVI void lds_b(uint32_t* b, uint32_t a) {
    asm volatile("ld.shared.v2.u32 {%0,%1}, [%2];" : "=r"(b[0]), "=r"(b[1]) : "r"(a) : "memory");
    asm volatile("ld.shared.v2.u32 {%0,%1}, [%2];" : "=r"(b[2]), "=r"(b[3]) : "r"(a + 256) : "memory");
}
DEVI uint32_t clk32() { unsigned long long c; asm volatile("mov.u64 %0, %%clock64;" : "=l"(c)); return (uint32_t)c; }

__host__ __device__ constexpr int x_pair(int j) { return j < 2 || j > 5 ? j : (j == 2 ? 5 : j - 1); }
DEVI void x_load(uint32_t sb, int seg, int j, int g, const CUtensorMap* tmX) {
    const uint32_t bar = sb + RB_XF + g * 8;
    mbar_expect_tx(bar, 4096);
    tma_load_3d(sb + RS_X + g * X_PITCH + (j % X_SLOTS) * 4096, tmX + (j == 3), g * 32, seg * 32, x_pair(j) * 2, bar);
    if (j == 3) tma_load_3d(sb + RS_SX + g * (RS_XE - RS_SX), tmX + 1, g * 32, seg * 32, x_pair(3) * 2 + 1, bar);
}
DEVI void x_refill(uint32_t sb, int seg, int j, int g, int warp, const CUtensorMap* tmX) {
    const int sn = j + X_SLOTS < X_NST ? seg : seg + 1;
    if (warp == (j & 3) && sn < NSEG) {
        if (elect_one()) x_load(sb, sn, (j + X_SLOTS) % X_NST, g, tmX);
    }
}
template <int J, int Q0, int Q1, int DQ>
DEVI void x_steps(float* xa, const uint32_t* w, int g0) {
    const int g = (int)opaque((uint32_t)g0);
    const uint32_t dW0 = cdesc(RS_WSS, 16) + g * 768, dW1 = cdesc(RS_WSS + 8192, 16) - g * 256;
#pragma unroll
    for (int q = Q0; q < Q1; q += DQ) {
        const int pos = r_tinv(2 * x_pair(J) + (q >> 2)), kk = (q >> 1) & 1, mt = q & 1;
        const uint32_t db = (J == 3 && q >= 4 ? cdesc(RS_SX, 16) + g * ((RS_XE - RS_SX) >> 4)
                                                    : cdesc(RS_X + (J % X_SLOTS) * 4096, 16) + g * (X_PITCH >> 4) + (q >> 2) * 128) + kk * 2;
        if (J == 0 && q < 2)   wgmma_n32_rs_first(xa + 16 * mt, &w[((r_rs(pos) * 2 + kk) * 2 + mt) * 4], db);
        else if (J == 0 && q == 3) wgmma_n32_ss(xa + 16, cdesc(RS_WX, 16) + g * 128, db);
        else if (r_pos_ss(pos)) wgmma_n32_ss(xa + 16 * mt, (mt ? dW1 : dW0) + r_ss(pos) * 1024 + kk * 128, db);
        else                   wgmma_n32_rs(xa + 16 * mt, &w[((r_rs(pos) * 2 + kk) * 2 + mt) * 4], db);
    }
}
DEVI void x_first(float* xa, const uint32_t* w, uint32_t sb, int seg, int g0, int warp, const CUtensorMap* tmX) {
    wg_fence();
    x_steps<0, 0, 8, 1>(xa, w, g0); wg_commit();
    x_steps<1, 0, 8, 1>(xa, w, g0); wg_commit();
    x_steps<2, 0, 8, 1>(xa, w, g0); wg_commit();
    x_steps<3, 0, 4, 1>(xa, w, g0); wg_commit();
    const int g = (int)opaque((uint32_t)g0);
    wg_wait<3>(); x_refill(sb, seg, 0, g, warp, tmX);
    wg_wait<2>(); x_refill(sb, seg, 1, g, warp, tmX);
    wg_wait<1>(); x_refill(sb, seg, 2, g, warp, tmX);
    wg_wait<0>(); x_refill(sb, seg, 3, g, warp, tmX);
    reg_fence<32>(xa);
    mbar_wait(sb + RB_XF + g * 8, 1);
}
DEVI void x_second(float* xa, uint32_t* a, uint32_t aA0, const uint32_t* w, uint32_t sb, int seg, int g0, int warp, const CUtensorMap* tmX) {
    wg_fence();
    x_steps<4, 0, 8, 1>(xa, w, g0); wg_commit();
    x_steps<3, 5, 8, 2>(xa, w, g0); x_steps<5, 1, 8, 2>(xa, w, g0); x_steps<6, 1, 8, 2>(xa, w, g0); x_steps<7, 1, 8, 2>(xa, w, g0); wg_commit();
    x_steps<3, 4, 8, 2>(xa, w, g0); x_steps<5, 0, 8, 2>(xa, w, g0); x_steps<6, 0, 8, 2>(xa, w, g0); x_steps<7, 0, 8, 2>(xa, w, g0); wg_commit();
    const int g = (int)opaque((uint32_t)g0);
    wg_wait<2>(); x_refill(sb, seg, 4, g, warp, tmX);
    SCHED_FENCE();
#pragma unroll
    for (int q = 0; q < 4; q++) ldsm4t(a + 4 * q, aA0 + (q & 1) * (8192 - g * 16384) + (q >> 1) * 2048);
    SCHED_FENCE();
    wg_wait<1>();
    reg_fence<16>(xa + 16);
}
DEVI void x_finish(float* xa, uint32_t sb, int g, int warp, int lane) {
    const uint32_t d = sb + RS_XD + (lane >> 4) * 2048 + warp * 256 + (lane & 15) * 16;
#pragma unroll
    for (int i = 0; i < 2; i++) {
        const float* x = xa + 16 + 8 * i;
        sts128(d + (g ^ 1) * 1024 + i * 4096, make_uint4(pack_bf16(x[0], x[1]), pack_bf16(x[2], x[3]), pack_bf16(x[4], x[5]), pack_bf16(x[6], x[7])));
    }
    nbar_sync(NB_PAIR + warp, 64);
    float y[16];
#pragma unroll
    for (int i = 0; i < 2; i++) {
        const uint4 v = lds128(d + g * 1024 + i * 4096);
        const uint32_t u[4] = {v.x, v.y, v.z, v.w};
#pragma unroll
        for (int j = 0; j < 4; j++) { y[8 * i + 2 * j] = __uint_as_float(u[j] << 16); y[8 * i + 2 * j + 1] = __uint_as_float(u[j] & 0xFFFF0000u); }
    }
    reg_fence<16>(y);
    wg_wait<0>();
    reg_fence<16>(xa);
    uint32_t p[8];
#pragma unroll
    for (int j = 0; j < 8; j++) p[j] = pack_bf16(xa[2 * j] + y[2 * j], xa[2 * j + 1] + y[2 * j + 1]);
    __syncwarp();
    stsm4(d + g * 1024, p[0], p[1], p[2], p[3]);
    stsm4(d + g * 1024 + 4096, p[4], p[5], p[6], p[7]);
    nbar_arrive(NB_XS, 256 + 32);
}
DEVI void x_send(uint32_t sb, int seg, uint32_t rank, const CUtensorMap* tmX) {
    auto refill = [&]() {
        if (seg + 1 < NSEG && elect_one()) {
#pragma unroll
            for (int j = 1; j < 4; j++) { x_load(sb, seg + 1, j, 0, tmX); x_load(sb, seg + 1, j, 1, tmX); }
        }
        __syncwarp();
    };
    mbar_wait(sb + RB_ATT, (seg - 1) & 1);
    nbar_sync(NB_XS, 256 + 32);
    if (rank == 2) { refill(); mbar_wait(sb + RB_G3, (seg - 1) & 1); }
    if (elect_one()) {
        fence_proxy_async();
        bulk_copy_s2c(mapa(sb + (rank == 1 ? RS_K : RS_V) + 2048, 0), sb + RS_XD, 8192, mapa(sb + (rank == 1 ? RB_KV : RB_VX), 0));
    }
    __syncwarp();
    if (rank == 1) refill();
}

template <bool XP>
DEVI void mem_pass(float* c0, float* c1, uint32_t* a, const uint32_t* w, uint32_t sb, uint32_t aA0, uint32_t aB, int g, int warp, int s) {
    const uint32_t aA1 = aA0 + 8192 - g * 16384, par = (s - 1) & 1;
    uint32_t b[3][4], e[4];
    float d0[4], d1[4];
    if (XP) ldsm4t(e, aA0 + opaque((RS_WX - RS_WSS) - g * (8192 + 2048)));
#pragma unroll
    for (int q = XP ? 4 : 0; q < 4; q++) ldsm4t(a + 4 * q, ((q & 1) ? aA1 : aA0) + (q >> 1) * 2048);
#pragma unroll
    for (int i = 0; i < 4; i++) { c0[i] = 0.f; c1[i] = 0.f; d0[i] = 0.f; d1[i] = 0.f; }
    EV(EV_BIG0, s, 0);
    mbar_wait(sb + RB_G, par);
    EV(EV_BIG0, s, 1);
    lds_b(b[0], aB + r_tord(0) * 1024);
    lds_b(b[1], aB + r_tord(1) * 1024);
    bool in = false;
#pragma unroll
    for (int pos = 0; pos < 16; pos++) {
        if (pos + 2 < 16) {
            if (pos + 2 == R_G1 && !in) mbar_wait(sb + RB_G + 8, par);
            if (pos + 2 == R_G2 && !in) mbar_wait(sb + RB_G + 16, par);
            if (pos + 2 == R_G3) { if (!in) mbar_wait(sb + RB_G3, par); EV(EV_BIG0, s, 2); }
            lds_b(b[(pos + 2) % 3], aB + r_tord(pos + 2) * 1024);
        }
        if (pos + 3 == R_G1) in = mbar_try(sb + RB_G + 8, par);
        if (pos + 3 == R_G2) in = mbar_try(sb + RB_G + 16, par);
        if (pos + 3 == R_G3) in = mbar_try(sb + RB_G3, par);
        if (XP && pos == 14) in = mbar_try(sb + RB_ATT, par);
        const uint32_t* bb = b[pos % 3];
        const uint32_t* aa = r_pos_ss(pos) ? a : &w[r_rs(pos) * 16];
        mma16816(c1, aa + 4, bb[0], bb[1]);
        mma16816(d1, XP && pos == 0 ? e : aa + 12, bb[2], bb[3]);
        mma16816(c0, aa, bb[0], bb[1]);
        mma16816(d0, aa + 8, bb[2], bb[3]);
        if (pos >= 2 && pos < 14) {
            const uint32_t nx = ((pos + 1) / 3) * 16384;
            if (r_pos_ss(pos)) { ldsm4t(a + 4, aA1 + nx); ldsm4t(a + 12, aA1 + nx + 2048); }
            else ldsm4t(a + 8 * (pos % 3), aA0 + nx + (pos % 3) * 2048);
        }
        SCHED_FENCE();
    }
    if (XP && !in) mbar_wait(sb + RB_ATT, par);
#pragma unroll
    for (int i = 0; i < 4; i++) { c1[i] += d1[i]; c0[i] += d0[i]; }
}

DEVI uint32_t k_frag_off(int lane) { return (uint32_t)((((lane >> 3) & 1) * 16 + (lane >> 4) * 8 + (lane & 7)) * 16); }
DEVI uint32_t v_frag_off(int lane) { return (uint32_t)(((lane >> 3) & 1) * 2048 + ((lane >> 4) * 8 + (lane & 7)) * 16); }
DEVI void pv_pair(float (*o)[4], const uint32_t* p, const uint32_t* v) {
#pragma unroll
    for (int n = 0; n < 4; n++) mma16816(o[n], p, v[2 * n], v[2 * n + 1]);
}
DEVI void pv_single(float (*o)[4], const uint32_t* p, const uint32_t* v) {
#pragma unroll
    for (int n = 0; n < 4; n++) mma1688(o[n], p[0], p[1], v[n]);
}
DEVI void s_tile(const uint32_t* qa, const uint32_t* k, float& s0, float& s1) {
    float c[4][4];
#pragma unroll
    for (int q = 0; q < 4; q++) { c[q][0] = c[q][1] = c[q][2] = c[q][3] = 0.f; }
#pragma unroll
    for (int q = 0; q < 4; q++) {
        mma16816(c[2 * (q & 1)], qa + 4 * q, k[4 * q], k[4 * q + 1]);
        mma16816(c[2 * (q & 1) + 1], qa + 4 * q, k[4 * q + 2], k[4 * q + 3]);
    }
    s0 = (c[0][0] + c[1][2]) + (c[2][0] + c[3][2]);
    s1 = (c[0][1] + c[1][3]) + (c[2][1] + c[3][3]);
}
DEVI void mem_scores(uint32_t sb, int s, int lane) {
    const uint32_t ka = sb + RS_K + k_frag_off(lane), sa = sb + RS_SX + 1024 + lane * 8;
    uint32_t qa[16], km[16];
    nbar_sync(NB_Q, 256);
#pragma unroll
    for (int q = 0; q < 4; q++) ldsm4t(qa + 4 * q, sb + RS_Q + q * 512 + lane * 16);
    mbar_wait(sb + RB_K, s & 1);
#pragma unroll
    for (int q = 0; q < 4; q++) ldsm4t(km + 4 * q, ka + q * 512);
    SCHED_FENCE();
    float s0, s1;
    s_tile(qa, km, s0, s1);
    asm volatile("st.shared.v2.f32 [%0], {%1,%2};" :: "r"(sa), "f"(s0 * SCALE_LOG2E), "f"(s1 * SCALE_LOG2E) : "memory");
    nbar_arrive(NB_XS, 128 + 32);
}
DEVI float quad_max(float m) {
    return fmaxf(fmaxf(m, __shfl_xor_sync(0xffffffffu, m, 1)), fmaxf(__shfl_xor_sync(0xffffffffu, m, 2), __shfl_xor_sync(0xffffffffu, m, 3)));
}
DEVI void mem_attn(uint32_t sb, int s, int warp, int lane) {
    const uint32_t va = sb + RS_V + warp * 512, sa = sb + RS_SX + lane * 8;
    [[maybe_unused]] constexpr int g = 0;
    float o[4][4], mx, l = 0.f;
    {
        const uint32_t ka = sb + RS_K + k_frag_off(lane) + (1 + warp) * 2048;
        uint32_t qa[16], kx[16];
        const bool in = mbar_try(sb + RB_KV, s & 1);
        nbar_sync(NB_Q, 256);
        EV(EV_BIG0 && lds32(sb + RS_Q) != 0x12345678u, s, 8);
#pragma unroll
        for (int q = 0; q < 4; q++) ldsm4t(qa + 4 * q, sb + RS_Q + q * 512 + lane * 16);
        if (!in) mbar_wait(sb + RB_KV, s & 1);
#pragma unroll
        for (int q = 0; q < 4; q++) ldsm4t(kx + 4 * q, ka + q * 512);
        const bool vin = mbar_try(sb + RB_VX, s & 1);
        SCHED_FENCE();
        float s0, s1;
        s_tile(qa, kx, s0, s1);
        asm volatile("st.shared.v2.f32 [%0], {%1,%2};" :: "r"(sa + warp * 256), "f"(s0 * SCALE_LOG2E), "f"(s1 * SCALE_LOG2E) : "memory");
        nbar_sync(NB_WG, 128);
        float sc[8];
#pragma unroll
        for (int n = 0; n < 4; n++) { const float2 v = lds64f(sa + n * 256); sc[2 * n] = v.x; sc[2 * n + 1] = v.y; }
        if (!vin) mbar_wait(sb + RB_VX, s & 1);
        mx = quad_max(fmaxf(fmaxf(fmaxf(sc[0], sc[1]), fmaxf(sc[2], sc[3])), fmaxf(fmaxf(sc[4], sc[5]), fmaxf(sc[6], sc[7]))));
        uint32_t vx[16], p[8];
#pragma unroll
        for (int q = 0; q < 4; q++) ldsm4(vx + 4 * q, va + 2048 + (q >> 1) * 4096 + (q & 1) * 256 + v_frag_off(lane));
#pragma unroll
        for (int n = 0; n < 4; n++) {
            const float e0 = ex2(sc[2 * n] - mx), e1 = ex2(sc[2 * n + 1] - mx);
            l += e0 + e1;
            p[2 * n] = pack_bf16(e0, e1); p[2 * n + 1] = __float_as_uint(e0);
        }
#pragma unroll
        for (int n = 0; n < 4; n++) { o[n][0] = o[n][1] = o[n][2] = o[n][3] = 0.f; }
        pv_pair(o, p, vx);
        pv_pair(o, p + 4, vx + 8);
    }
    const uint32_t dst = sb + RS_O + warp * 512 + (lane & 3) * 128 + (lane >> 2) * 16, dl = sb + RS_INV + (lane & 28);
    EV(EV_BIG0, s, 5);
    mbar_wait(sb + RB_V, s & 1);
    uint32_t vm[4], p[2];
    ldsm4(vm, va + lane * 16);
    nbar_sync(NB_XS, 128 + 32);
    EV(EV_BIG0 && lds32(sb + RS_Q) != 0x12345678u, s, 9);
    const float2 sm = lds64f(sa + 1024);
    const float s0 = sm.x, s1 = sm.y;
    const float m = quad_max(fmaxf(mx, fmaxf(s0, s1)));
    const float e0 = ex2(s0 - m), e1 = ex2(s1 - m), f = ex2(mx - m);
    p[0] = pack_bf16(e0, e1); p[1] = __float_as_uint(e0);
#pragma unroll
    for (int n = 0; n < 4; n++) { o[n][0] *= f; o[n][1] *= f; }
    pv_single(o, p, vm);
    l = fmaf(l, f, e0 + e1);
    l = (l + __shfl_xor_sync(0xffffffffu, l, 1)) + (__shfl_xor_sync(0xffffffffu, l, 2) + __shfl_xor_sync(0xffffffffu, l, 3));
    const uint4 u = make_uint4(pack_bf16(o[0][0], o[0][1]), pack_bf16(o[1][0], o[1][1]), pack_bf16(o[2][0], o[2][1]), pack_bf16(o[3][0], o[3][1]));
    st_async128(mapa(dst, 1), u.x, u.y, u.z, u.w, mapa(sb + RB_O, 1));
    st_async128(mapa(dst, 2), u.x, u.y, u.z, u.w, mapa(sb + RB_O, 2));
    st_async32(mapa(dl, 1 + (warp & 1)), __float_as_uint(l), mapa(sb + RB_O, 1 + (warp & 1)));
    sts128(dst, u);
    sts32(dl, __float_as_uint(l));
    __syncwarp();
    if (elect_one()) mbar_arrive(sb + RB_O);
    EV(EV_BIG0, s, 15);
}

DEVI void ta_mask(float* c, int cw, int lane) {
    const int mt = cw >= 3, over = 8 * (cw - 3 * mt - 1) + 2 * (lane & 3) - 16 * mt - (lane >> 2);
    if (over > 0) c[0] = -INFINITY;
    if (over >= 0) c[1] = -INFINITY;
    if (over > 8) c[2] = -INFINITY;
    if (over >= 8) c[3] = -INFINITY;
}
DEVI void ta_scores(uint32_t sb, int seg, int warp, int lane) {
    const int tx = warp == 3 ? 0 : (warp == 2 ? 1 : 4 + 2 * warp), ty = warp == 3 ? 3 : tx + 1;
    const uint32_t qa = sb + RS_QX + ((warp < 2 ? 2 : 0) + ((lane >> 3) & 1)) * 2048 + ((lane >> 4) * 8 + (lane & 7)) * 16;
    const uint32_t ka = sb + RS_K + (warp < 2 ? tx - 3 : tx) * 2048 + lane * 16;
    float x[4] = {0.f, 0.f, 0.f, 0.f}, y[4] = {0.f, 0.f, 0.f, 0.f};
    mbar_wait(sb + RB_QX, seg & 1);
    if (warp < 3) {
#pragma unroll
        for (int j = 0; j < 4; j++) {
            uint32_t a0[4], a1[4], bx[4], by[4];
            ldsm4t(a0, qa + j * 512); ldsm4t(bx, ka + j * 512); ldsm4t(by, ka + 2048 + j * 512); ldsm4t(a1, qa + j * 512 + 256);
            mma16816(x, a0, bx[0], bx[1]); mma16816(y, a0, by[0], by[1]);
            mma16816(x, a1, bx[2], bx[3]); mma16816(y, a1, by[2], by[3]);
        }
        ta_mask(x, tx, lane); ta_mask(y, ty, lane);
    } else {
        mbar_wait(sb + RB_K, seg & 1);
#pragma unroll
        for (int j = 0; j < 4; j++) {
            uint32_t a0[4], a1[4], a2[4], a3[4], b[4];
            ldsm4t(a0, qa + j * 512); ldsm4t(b, ka + j * 512); ldsm4t(a2, qa + 4096 + j * 512);
            ldsm4t(a1, qa + j * 512 + 256); ldsm4t(a3, qa + 4096 + j * 512 + 256);
            mma16816(x, a0, b[0], b[1]); mma16816(y, a2, b[0], b[1]);
            mma16816(x, a1, b[2], b[3]); mma16816(y, a3, b[2], b[3]);
        }
    }
    nbar_sync(NB_WG + 1, 128);
    asm volatile("st.shared.v2.f32 [%0], {%1,%2};" :: "r"(sb + RS_QX + 4096 + tx * 256 + lane * 8), "f"(fmaxf(x[0], x[1])), "f"(fmaxf(x[2], x[3])) : "memory");
    asm volatile("st.shared.v2.f32 [%0], {%1,%2};" :: "r"(sb + RS_QX + 4096 + ty * 256 + lane * 8), "f"(fmaxf(y[0], y[1])), "f"(fmaxf(y[2], y[3])) : "memory");
    nbar_sync(NB_WG + 1, 128);
    float m[4] = {-INFINITY, -INFINITY, -INFINITY, -INFINITY};
#pragma unroll
    for (int n = 0; n < 8; n++) {
        if (n < 3 ? warp >= 2 : warp != 2) {
            const float2 v = lds64f(sb + RS_QX + 4096 + n * 256 + lane * 8);
            m[n < 3 ? 0 : 2] = fmaxf(m[n < 3 ? 0 : 2], v.x); m[n < 3 ? 1 : 3] = fmaxf(m[n < 3 ? 1 : 3], v.y);
        }
    }
#pragma unroll
    for (int o = 1; o < 4; o <<= 1) {
#pragma unroll
        for (int i = 0; i < 4; i++) m[i] = fmaxf(m[i], __shfl_xor_sync(0xffffffffu, m[i], o));
    }
    const float x0 = warp < 2 ? m[2] : m[0], x1 = warp < 2 ? m[3] : m[1], y0 = warp == 2 ? m[0] : m[2], y1 = warp == 2 ? m[1] : m[3];
    auto e = [](float v, float mx) { return ex2((v - mx) * SCALE_LOG2E); };
    sts64(sb + RS_QX + tx * 256 + lane * 8, pack_bf16(e(x[0], x0), e(x[1], x0)), pack_bf16(e(x[2], x1), e(x[3], x1)));
    sts64(sb + RS_QX + ty * 256 + lane * 8, pack_bf16(e(y[0], y0), e(y[1], y0)), pack_bf16(e(y[2], y1), e(y[3], y1)));
}
template <int MT>
DEVI void ta_output(uint32_t sb, int seg, int head, int j, int lane) {
    const uint32_t pa = sb + RS_QX + MT * 768 + lane * 8, vb = sb + RS_V + j * 512;
    uint32_t p[6 + 4 * MT], v[12 + 8 * MT];
#pragma unroll
    for (int n = 0; n < 3 + 2 * MT; n++)
        asm volatile("ld.shared.v2.u32 {%0,%1}, [%2];" : "=r"(p[2 * n]), "=r"(p[2 * n + 1]) : "r"(pa + n * 256) : "memory");
#pragma unroll
    for (int q = 0; q < 2 + 2 * MT; q++) ldsm4(v + 4 * q, vb + (q >> 1) * 4096 + (q & 1) * 256 + v_frag_off(lane));
    ldsm4(v + 8 + 8 * MT, vb + 4096 + MT * 4096 + lane * 16);
    float o[4][4], l[4] = {0.f, 0.f, 0.f, 0.f};
#pragma unroll
    for (int n = 0; n < 4; n++) { o[n][0] = o[n][1] = o[n][2] = o[n][3] = 0.f; }
    mma16816(l, p, 0x3F803F80u, 0x3F803F80u);
    pv_pair(o, p, v);
    if (MT) { mma16816(l, p + 4, 0x3F803F80u, 0x3F803F80u); pv_pair(o, p + 4, v + 8); }
    mma1688(l, p[4 + 4 * MT], p[5 + 4 * MT], 0x3F803F80u);
    pv_single(o, p + 4 + 4 * MT, v + 8 + 8 * MT);
    const float i0 = rcp_fast(l[0]), i1 = rcp_fast(l[2]);
    bf16* dst = g_ox + (uint32_t)((seg * 32 + MT * 16 + (lane >> 2)) * HD + head * DH + j * 32 + (lane & 3) * 8);
    asm volatile("st.global.v4.u32 [%0], {%1,%2,%3,%4};" :: "l"(dst), "r"(pack_bf16(o[0][0] * i0, o[0][1] * i0)), "r"(pack_bf16(o[1][0] * i0, o[1][1] * i0)),
                 "r"(pack_bf16(o[2][0] * i0, o[2][1] * i0)), "r"(pack_bf16(o[3][0] * i0, o[3][1] * i0)) : "memory");
    asm volatile("st.global.v4.u32 [%0], {%1,%2,%3,%4};" :: "l"(dst + 8 * HD), "r"(pack_bf16(o[0][2] * i1, o[0][3] * i1)), "r"(pack_bf16(o[1][2] * i1, o[1][3] * i1)),
                 "r"(pack_bf16(o[2][2] * i1, o[2][3] * i1)), "r"(pack_bf16(o[3][2] * i1, o[3][3] * i1)) : "memory");
}

template <bool XP>
DEVI void big_main(const uint32_t* w, const uint32_t sb, const int g, const int warp, const uint32_t rank, const int head,
                   const CUtensorMap* tmX, const bf16* xg, const unsigned E) {
    float xa[32];
    uint32_t a[16];
    const uint32_t aB = __shfl_sync(0xffffffffu, sb + RS_MEM + (g * 32 + (tid_now() & 31)) * 16, tid_now() & 31);
#define lane0 ((int)(opaque(aB) >> 4) & 31)
    const uint32_t aA0 = sb + RS_WSS + g * (8192 + 4096) + a_frag_off(lane0, warp);
    const uint32_t aBf = sb + RS_MEM + g * 512 + b_frag_off(lane0);
    if constexpr (XP) {
        mbar_wait(sb + RB_XF + g * 8, 0);
        x_first(xa, w, sb, 0, g, warp, tmX);
        x_second(xa, a, aA0, w, sb, 0, g, warp, tmX);
        x_finish(xa, sb, g, warp, lane0);
    }
    nbar_sync(NB_BIG, 256);
    for (int s = 0; s < NSEG; s++) {
        float c0[4], c1[4];
        mem_pass<XP>(c0, c1, a, w, sb, aA0, aBf, g, warp, s);
        EV(EV_BIG0 && c0[0] != 1.2345e30f, s, 3);
        bool xin = true;
        const uint32_t xs = sb + RS_O + warp * 256 + lane0 * 8;
        sts64(xs + g * 1024, pack_bf16(c1[0], c1[1]), pack_bf16(c1[2], c1[3]));
        {
            const uint32_t d = sb + (XP ? (rank == 1 ? RS_K : RS_V) : RS_Q) + (g * 4 + warp) * 256 + lane0 * 4;
            const uint32_t rbar = XP ? mapa(sb + (rank == 1 ? RB_K : RB_V), 0) : 0u;
            nbar_sync(NB_PAIR + warp, 64);
            const float2 v = lds64f(xs + (g ^ 1) * 1024);
            if (XP) xin = mbar_test(sb + RB_XF + g * 8, 0);
            const uint32_t v0 = __float_as_uint(v.x), v1 = __float_as_uint(v.y);
            const uint32_t p0 = pack_bf16(c0[0] + __uint_as_float(v0 << 16), c0[1] + __uint_as_float(v0 & 0xFFFF0000u));
            const uint32_t p1 = pack_bf16(c0[2] + __uint_as_float(v1 << 16), c0[3] + __uint_as_float(v1 & 0xFFFF0000u));
            if constexpr (XP) { st_async32(mapa(d, 0), p0, rbar); st_async32(mapa(d + 128, 0), p1, rbar); }
            else { sts32(d, p0); sts32(d + 128, p1); }
            EV(EV_BIG0, s, 4);
        }
        if constexpr (XP) {
            if (s == NSEG - 1) break;
            if (!xin) mbar_wait(sb + RB_XF + g * 8, 0);
            x_first(xa, w, sb, s + 1, g, warp, tmX);
            EV(EV_BIG0, s, 5);
            EVCAL(s);
            nbar_sync(NB_WO, 384);
            EV(EV_BIG0 && lds32(sb + RS_O) != 0x12345678u, s, 6);
            x_second(xa, a, aA0, w, sb, s + 1, g, warp, tmX);
            EV(EV_BIG0, s, 7);
            x_finish(xa, sb, g, warp, lane0);
        } else {
            if (g == 0) {
                if (s < NSEG - 1) mem_attn(sb, s, warp, lane0);
            } else {
                if (s < NSEG - 1) { if (warp == 3) mem_scores(sb, s, lane0); else nbar_arrive(NB_Q, 256); }
                mbar_wait(sb + RB_KV, s & 1);
                if (s == 0 && warp == 0) {
                    wait_count_warp(&g_cnt[C_QH], 64 * E);
                    if (elect_one()) {
                        fence_proxy_global();
                        mbar_expect_tx(sb + RB_QX, 8192);
                        bulk_load(sb + RS_QX, g_qx + (uint32_t)(head * 4096), 8192, sb + RB_QX);
                    }
                    __syncwarp();
                }
                ta_scores(sb, s, warp, lane0);
            }
            EVCAL(s);
            mbar_wait(sb + RB_V, s & 1);
            mbar_wait(sb + RB_VX, s & 1);
            if (s < NSEG - 1) nbar_sync(NB_WO, 384); else nbar_sync(NB_BIG, 256);
            EV(EV_BIG0 && lds32(sb + RS_O) != 0x12345678u, s, 6);
            if (g == 0) ta_output<0>(sb, s, head, warp, lane0); else ta_output<1>(sb, s, head, warp, lane0);
            nbar_sync(NB_BIG, 256);
            EV(EV_BIG0 && lds32(sb + RS_O) != 0x12345678u, s, 7);
            if (g == 0 && warp == 0 && s + 1 < NSEG) {
                if (elect_one()) {
                    mbar_arrive_remote(mapa(sb + RB_ATT, 1));
                    mbar_arrive_remote(mapa(sb + RB_ATT, 2));
                    mbar_expect_tx(sb + RB_KV, 8192);
                    mbar_expect_tx(sb + RB_K, 2048);
                    mbar_expect_tx(sb + RB_V, 2048); mbar_expect_tx(sb + RB_VX, 8192);
                    mbar_arrive(sb + RB_T);
                }
                __syncwarp();
            }
        }
    }
    if constexpr (!XP) { if (tid_now() == 0) signal_count(&g_prog[(NSEG - 1) >> 1]); }
#undef lane0
}

template <int T, int K0, int K1>
DEVI void wo_part(float* acc) {
    constexpr uint32_t dWo = cdesc(T < 5 ? RS_WO + T * 16384 : RS_WO5, 16), dO = cdesc(RS_O, 128);
#pragma unroll
    for (int kk = K0; kk < K1; kk++) {
        if (kk == 0) { if (T < 3) wgmma_n8_ss_first<0>(acc, dWo, dO); else wgmma_n8_ss<0, 0>(acc, dWo, dO); }
        else wgmma_n8_ss<0, 1>(acc, dWo + kk * 128, dO + kk * 16);
    }
    wg_commit();
}
DEVI void red3(uint8_t* p, uint32_t a, uint32_t b, uint32_t c, uint32_t one) {
    asm volatile("red.relaxed.gpu.global.add.noftz.v4.bf16x2 [%0], {%1,%2,%3,%4};" :: "l"(p), "r"(a), "r"(b), "r"(c), "r"(one) : "memory");
}
constexpr int ACC_CH = 3 * 16 * 1024;
template <bool Q>
DEVI void wo_phase(uint32_t sb, int s, int warp, uint8_t* p, uint32_t ainv, int gap) {
    float a0[4], a1[4], a2[4];
    fence_proxy_async();
    const float2 iv = lds64f(ainv);
    SCHED_FENCE();
    const float i0 = rcp_fast(iv.x), i1 = rcp_fast(iv.y);
#define WORD(a, h) pack_bf16(a[2 * h] * i0, a[2 * h + 1] * i1)
    wg_fence();
    wo_part<0, 0, 8>(a0); wo_part<1, 0, 8>(a1); wo_part<2, 0, 8>(a2);
    wg_wait<1>(); reg_fence<4>(a0); reg_fence<4>(a1);
    red3(p, WORD(a0, 0), WORD(a0, 1), WORD(a1, 0), 0x3F80u);
    SCHED_FENCE();
    EV(warp == 0 && elect_one(), s, 11);
    wg_wait<0>(); reg_fence<4>(a2);
    red3(p + ACC_CH, WORD(a2, 0), WORD(a2, 1), WORD(a1, 1), 0x3F80u);
    SCHED_FENCE();
    { const uint32_t t = clk32() + gap; while ((int)(clk32() - t) < 0) { } }
    wg_fence();
    wo_part<3, 0, 8>(a0); wo_part<4, 0, 8>(a1);
    if (Q) {
        wo_part<5, 0, 8>(a2);
        wg_wait<1>(); reg_fence<4>(a0); reg_fence<4>(a1);
        red3(p + 2 * ACC_CH, WORD(a0, 0), WORD(a0, 1), WORD(a1, 0), 0x3F80u);
        SCHED_FENCE();
        wg_wait<0>(); reg_fence<4>(a2);
        red3(p + 3 * ACC_CH, WORD(a2, 0), WORD(a2, 1), WORD(a1, 1), 0x3F80u);
        nbar_arrive(NB_WO, 384);
    } else {
        wg_wait<1>();
        nbar_arrive(NB_WO, 384);
        wg_wait<0>(); reg_fence<4>(a0); reg_fence<4>(a1);
        red3(p + 2 * ACC_CH, WORD(a0, 0), WORD(a0, 1), WORD(a1, 0), 0x3F80u);
        red3(p + 3 * ACC_CH, 0u, 0u, WORD(a1, 1), 0x3F80u);
    }
#undef WORD
}
DEVI void unit_pack(uint32_t* u, uint32_t x0, uint32_t x1, uint32_t x2, uint32_t x3) {
    u[0] = __byte_perm(x0, x1, 0x5410); u[1] = __byte_perm(x2, x3, 0x5410); u[2] = __byte_perm(x0, x1, 0x7632); u[3] = __byte_perm(x2, x3, 0x7632);
}
DEVI void unit_send(uint32_t d, const uint32_t* u, uint32_t bar, uint32_t r1, uint32_t r2) {
    st_async128(mapa(d, r1), u[0], u[1], u[2], u[3], mapa(bar, r1));
    st_async128(mapa(d, r2), u[0], u[1], u[2], u[3], mapa(bar, r2));
}
template <bool Q>
DEVI void stage_sums(uint32_t sb, int s, uint32_t rank, int warp, const uint8_t* src, uint32_t l, uint32_t gate) {
    uint4 v[4];
    while ((int)(clk32() - gate) < 0) { }
    EV(elect_one(), s, 16 + warp);
#pragma unroll
    for (int j = 0; j < 4; j++) v[j] = ld_rlx4(src + j * 1024);
    const uint32_t col = sb + RS_MEM + ((Q ? 0 : (rank == 1 ? 6 : 11)) + 3 * (warp >> 1)) * 1024 + ((l >> 2) & 0x300) + (l & 0x70);
    const uint32_t d0 = col + (warp & 1) * 2048, d1 = d0 ^ 160, d2 = (col ^ ((warp & 1) * 160)) + 1024;
    const uint32_t r1 = Q ? 1 : 0, r2 = Q ? 2 : 3 - rank, bar = sb + (warp < 2 ? RB_G + 8 * warp : (Q ? RB_G + 16 : RB_G3));
    int n = 0;
    while (!__all_sync(0xffffffffu, v[0].w == 0x4200u && v[1].w == 0x4200u && v[2].w == 0x4200u && v[3].w == 0x4200u)) {
#pragma unroll
        for (int j = 0; j < 4; j++) v[j] = ld_rlx4(src + j * 1024);
        if (++n > SPIN_LIMIT) __trap();
    }
    EV(elect_one(), s, 24 + warp);
    uint32_t u[12];
    unit_pack(u + 8, v[0].z, v[1].z, v[2].z, v[3].z);
    unit_send(d2, u + 8, bar, r1, r2);
    if (Q || warp < 3) {
        unit_pack(u, v[0].x, v[1].x, v[2].x, v[3].x);
        unit_pack(u + 4, v[0].y, v[1].y, v[2].y, v[3].y);
        unit_send(d0, u, bar, r1, r2);
        unit_send(d1, u + 4, bar, r1, r2);
        sts128(d0, make_uint4(u[0], u[1], u[2], u[3]));
        sts128(d1, make_uint4(u[4], u[5], u[6], u[7]));
    }
    sts128(d2, make_uint4(u[8], u[9], u[10], u[11]));
    __syncwarp();
    if (elect_one()) {
        mbar_expect_tx(bar, warp < 2 ? 3072u : (Q ? 0u : 1024u));
        if (warp == 0) mbar_expect_tx(sb + (Q ? RB_G3 : RB_G + 16), Q ? 4096u : 3072u);
    }
    EV(elect_one(), s, 20 + warp);
}
DEVI void wo_permute(uint32_t tile, int t) {
    const uint32_t a = tile + t * 32 + ((t >> 2) & 1) * 16;
#pragma unroll
    for (int h = 0; h < 2; h++) {
        uint4 v[3], u[3];
#pragma unroll
        for (int i = 0; i < 3; i++) if (3 * h + i < 5 || t < 32) { v[i] = lds128(a + (3 * h + i) * 3072); u[i] = lds128((a ^ 16) + (3 * h + i) * 3072); }
#pragma unroll
        for (int i = 0; i < 3; i++) if (3 * h + i < 5 || t < 32) {
            sts128(a + (3 * h + i) * 3072, make_uint4(__byte_perm(v[i].x, v[i].y, 0x5410), __byte_perm(v[i].x, v[i].y, 0x7632),
                                                      __byte_perm(u[i].x, u[i].y, 0x5410), __byte_perm(u[i].x, u[i].y, 0x7632)));
            sts128((a ^ 16) + (3 * h + i) * 3072, make_uint4(__byte_perm(v[i].z, v[i].w, 0x5410), __byte_perm(v[i].z, v[i].w, 0x7632),
                                                             __byte_perm(u[i].z, u[i].w, 0x5410), __byte_perm(u[i].z, u[i].w, 0x7632)));
        }
    }
}
DEVI uint32_t acc_clear(int slot, int idx, uint32_t lo) {
    uint8_t* p = g_acc + (uint32_t)(slot * 128 + idx * 3072 + (lo < 3072 ? lo : lo - 1024));
    st_rlx4(p, 0u, 0u, 0u, 0u);
    uint32_t z; asm volatile("ld.relaxed.gpu.global.u32 %0, [%1];" : "=r"(z) : "l"(p) : "memory");
    return z;
}

template <bool Q>
DEVI void aux_main(uint32_t sb, int warp, uint32_t rank, int head, const CUtensorMap* tmX, const bf16* xg, unsigned E, const int delay, const int gap) {
    const uint32_t lo = __shfl_sync(0xffffffffu, ((tid_now() >> 3) & 3) * 1024 + (tid_now() & 7) * 16, tid_now() & 31);
    for (int s = 0; s < NSEG - 1; s++) {
        if (!Q && warp == 0 && elect_one()) mbar_expect_tx(sb + RB_O, 2048 + 256);
        __syncwarp();
        const uint32_t slot = (s & 3) * 128;
        mbar_wait(sb + RB_O, s & 1);
        EV(warp == 0 && elect_one(), s, 10);
        wo_phase<Q>(sb, s, warp, g_acc + (uint32_t)(slot + (rank * 4 + warp) * 4096 + opaque(lo)), sb + RS_INV + ((opaque(lo) >> 1) & 24), gap);
        SCHED_FENCE();
        const uint32_t t_o = clk32();
        EV(warp == 0 && elect_one(), s, 12);
        {
            const uint32_t l = opaque(lo);
            stage_sums<Q>(sb, s, rank, warp, g_acc + (uint32_t)(slot + rank * 16384 + warp * ACC_CH + (l & 0xC00) * 4 + (l & 0x70)), l, t_o + delay);
        }
        EV(warp == 2 && elect_one(), s, 14);
        if (warp == (Q ? 3 : 1)) {
            if (Q) {
                mbar_wait(sb + RB_T, s & 1);
                if (s == 3) wait_count_warp(&g_cnt[C_Q], 64 * E);
                if (elect_one()) {
                    if (s == 3) fence_proxy_global();
                    fence_proxy_async();
                    mbar_expect_tx(sb + RB_QX, 8192);
                    bulk_load(sb + RS_QX, g_qx + (uint32_t)(((s + 1) * NH + head) * 4096), 8192, sb + RB_QX);
                    if (head == 0) { TLOG(1400 + s, 0, gtime()); TLOG(1400 + s, 1, clock64()); }
                }
                __syncwarp();
                const bool fresh = (s & 7) == 6 && s + 2 < NSEG;
                if (fresh) wait_count_warp(&g_cnt[C_Q + ((s + 2) >> 3)], 64 * E);
                if (elect_one()) {
                    if (fresh) fence_proxy_global();
                    if (s + 2 < NSEG && s != 2) l2_prefetch(g_qx + (uint32_t)(((s + 2) * NH + head) * 4096), 8192);
                    if (s + 4 < NSEG) l2_prefetch(xg + (uint32_t)(((s + 4) * 32 + head) * DM), 2048);
                    signal_count(&g_prog[s >> 1]);
                }
                __syncwarp();
            } else {
                const uint32_t zero = acc_clear((s + 2) & 3, 2 * head + (int)rank - 1, opaque(lo));
                x_send(sb, s + 1, rank, tmX);
                if (__any_sync(0xffffffffu, zero != 0u)) __trap();
            }
        }
    }
}

DEVI void load_weights(uint32_t sb, const CUtensorMap* tmW, const CUtensorMap* tmWo, int head, uint32_t rank, int2 t0) {
    const uint32_t c0 = clk32();
    if (rank == 0) while ((int)(clk32() - c0) < t0.x) { }
    const uint32_t bW = sb + RB_W, bSF = sb + RB_SF, bSE = sb + RB_SE;
    const int tile0 = rank == 0 ? 0 : (rank == 1 ? 6 : 11);
    mbar_expect_tx(bW, R_NSS * 16384);
    for (int pass = 0; pass < 2; pass++) {
        for (int pos = 0; pos < 16; pos++) {
            const int k = (int)((R_TORD_PACK >> (4 * pos)) & 15ull) * 64, rd = pos - pos / 3, slot = rd % 5;
            if (r_pos_ss(pos)) {
                if (pass) continue;
                const uint32_t dst = sb + RS_WSS + (pos / 3) * 16384;
                tma_load_2d(dst, tmW, head * DH, k, bW);
                tma_load_2d(dst + 8192, tmW, head * DH + 64, k, bW);
            } else if (pass == (rd >= 5)) {
                if (rd >= 5) mbar_wait(bSE + 8 * slot, ((rd / 5) - 1) & 1);
                mbar_expect_tx(bSF + 8 * slot, 16384);
                const uint32_t dst = sb + RS_WO + slot * 16384;
                tma_load_2d(dst, tmW, head * DH, k, bSF + 8 * slot);
                tma_load_2d(dst + 8192, tmW, head * DH + 64, k, bSF + 8 * slot);
            }
        }
    }
    while ((int)(clk32() - c0) < t0.y) { }
    if (rank == 0) { mbar_expect_tx(sb + RB_WO, 16384); tma_load_wo(sb + RS_WO5, tmWo, 5 * 64, head * 4, sb + RB_WO); }
    for (int i = 1; i <= 5; i++) {
        const int slot = i % 5, last = slot + 10 < R_NRS ? slot + 10 : slot + 5;
        mbar_wait(bSE + 8 * slot, (last / 5) & 1);
        mbar_expect_tx(bSF + 8 * slot, 16384);
        tma_load_wo(sb + RS_WO + slot * 16384, tmWo, (tile0 + slot) * 64, head * 4, bSF + 8 * slot);
    }
}
template <bool XP>
DEVI void big_prologue(uint32_t* w, uint32_t sb, int g, int warp, const bf16* __restrict__ mem0) {
    const int tid = tid_now(), lane = tid & 31;
    {
        const uint32_t* m = (const uint32_t*)(mem0 + (lane >> 2) * DM + (tid >> 5) * 16) + (lane & 3);
        uint32_t u[16];
#pragma unroll
        for (int j = 0; j < 8; j++) { u[2 * j] = m[j * 64]; u[2 * j + 1] = m[j * 64 + 4]; }
#pragma unroll
        for (int j = 0; j < 8; j++) sts64(sb + RS_MEM + ((tid >> 5) + j * 8) * 256 + b_frag_off(lane), u[2 * j], u[2 * j + 1]);
    }
    const uint32_t a0 = sb + RS_WO + g * (8192 + 4096) + a_frag_off(lane, warp), a1 = a0 + 8192 - g * 16384;
#pragma unroll
    for (int rd = 0; rd < R_NRS; rd++) {
        const int slot = rd % 5;
        mbar_wait(sb + RB_SF + 8 * slot, (rd / 5) & 1);
#pragma unroll
        for (int q = 0; q < 4; q++) {
            if (XP && rd == 0 && q == 3) {
                sts128(sb + RS_WX + g * 2048 + (tid & 127) * 16, lds128(sb + RS_WO + 8192 - g * 4096 + 2048 + (tid & 127) * 16));
                fence_proxy_async();
                nbar_sync(NB_WG + g, 128);
            } else ldsm4t(&w[rd * 16 + q * 4], ((q & 1) ? a1 : a0) + slot * 16384 + (q >> 1) * 2048);
        }
        mbar_arrive(sb + RB_SE + 8 * slot);
    }
    mbar_wait(sb + RB_W, 0);
    if (tid == 0) TLOG(1500 + blockIdx.x, 2, gtime());
}

#define REC_END() do { if (tid_now() == 0) TLOG(1024 + blockIdx.x, 1, gtime()); } while (0)
struct XMaps { CUtensorMap m[2]; };
__global__ void __launch_bounds__(384, 1)
k_rec(const __grid_constant__ PMaps mp, const __grid_constant__ CUtensorMap tmWk, const __grid_constant__ CUtensorMap tmWv,
      const __grid_constant__ CUtensorMap tmWo, const __grid_constant__ XMaps xm, const bf16* __restrict__ mem0, const bf16* __restrict__ xg,
      int4 tq, int4 tk, int2 t0, int rec) {
    extern __shared__ __align__(1024) uint8_t smem_raw[];
    const uint32_t sb = smem_u32(smem_raw);
    if ((sb & 0x3FFFFu) != SB0) __trap();
    const int tid = threadIdx.x;
    const int wg = __shfl_sync(0xffffffffu, tid >> 7, 0), warp = __shfl_sync(0xffffffffu, (tid >> 5) & 3, 0);
    uint32_t rank; asm("mov.u32 %0, %%cluster_ctarank;" : "=r"(rank));
    int head; asm("mov.u32 %0, %%clusterid.x;" : "=r"(head));
    asm volatile("griddepcontrol.launch_dependents;");
    if (tid == 0 && rec) {
        mbar_init(sb + RB_G, 1);
        mbar_init(sb + RB_G + 8, 1);
        mbar_init(sb + RB_G + 16, rank == 0 ? 2 : 1);
        mbar_init(sb + RB_G3, rank == 0 ? 1 : 2);
        mbar_init(sb + RB_T, 1); mbar_init(sb + RB_VX, 1); mbar_init(sb + RB_WO, 1);
        mbar_init(sb + RB_K, 1); mbar_init(sb + RB_V, 1); mbar_init(sb + RB_KV, 1); mbar_init(sb + RB_QX, 1);
        mbar_init(sb + RB_O, rank == 0 ? 4 : 1); mbar_init(sb + RB_ATT, 1); mbar_init(sb + RB_W, 1);
        for (int i = 0; i < 5; i++) { mbar_init(sb + RB_SF + 8 * i, 1); mbar_init(sb + RB_SE + 8 * i, 256); }
        for (int i = 0; i < 2; i++) mbar_init(sb + RB_XF + 8 * i, X_SLOTS);
        fence_mbar_init();
        if (rank == 0) { mbar_expect_tx(sb + RB_KV, 8192); mbar_expect_tx(sb + RB_K, 2048); mbar_expect_tx(sb + RB_V, 2048); mbar_expect_tx(sb + RB_VX, 8192); }
    }
    __syncthreads();
    asm volatile("barrier.cluster.arrive.release.aligned;" ::: "memory");

    if (wg < 2) {
        reg_inc<REG_KB>();
        if (rank != 0) {
            uint32_t w[R_NRS * 16];
            if ((tid & 127) == 0) for (int j = 0; j < X_SLOTS; j++) x_load(sb, 0, j, wg, xm.m);
            __syncwarp();
            cluster_wait();
            big_prologue<true>(w, sb, wg, warp, mem0);
            big_main<true>(w, sb, wg, warp, rank, head, xm.m, xg, 0u);
            REC_END();
        } else if (rec) {
            uint32_t w[R_NRS * 16];
            cluster_wait();
            big_prologue<false>(w, sb, wg, warp, mem0);
            big_main<false>(w, sb, wg, warp, rank, head, xm.m, xg, *(volatile unsigned*)&g_epoch + 1);
            REC_END();
        } else cluster_wait();
        if (rank == 0 && rec) nbar_arrive(NB_PRO, 256 + 32);
        nbar_sync(0, 384);
        post_consumer(mp, sb, wg, warp);
    } else {
        reg_dec<504 - 2 * REG_KB>();
        if (rec) {
            if (tid == 256) {
                if (rank == 0) l2_prefetch(xg + (uint32_t)(head * 8 * DM), 16384);
                load_weights(sb, rank == 0 ? &mp.wq : (rank == 1 ? &tmWk : &tmWv), &tmWo, head, rank, t0);
            }
            if (warp == 3 && rank != 0) {
                const uint32_t lo = ((tid >> 3) & 3) * 1024 + (tid & 7) * 16;
                acc_clear(0, 2 * head + (int)rank - 1, lo); acc_clear(1, 2 * head + (int)rank - 1, lo);
                __threadfence();
                __syncwarp();
                if (tid == 256 + 96) atomicAdd(&g_zero, 1u);
            }
            __syncwarp();
        }
        cluster_wait();
        const unsigned E = __shfl_sync(0xffffffffu, *(volatile unsigned*)&g_epoch + 1, 0);
        if (rec) {
            if (warp == 1) wait_count_warp(&g_zero, E * 64u);
            if (warp == 3) { if (rank != 0) x_send(sb, 0, rank, xm.m); }
            else {
                nbar_sync(NB_PRO, 96);
#pragma unroll 1
                for (int i = rank == 0 ? 0 : 1; i <= 5; i++) {
                    mbar_wait(sb + (i == 0 ? RB_WO : RB_SF + 8 * (i % 5)), i == 5);
                    if (i == 5 && tid == 288) TLOG(1500 + blockIdx.x, 0, gtime());
                    wo_permute(sb + (i == 0 ? RS_WO5 : RS_WO + (i % 5) * 16384), tid & 127);
                }
            }
            fence_proxy_async();
            nbar_sync(NB_AUX, 128);
            if (tid == 288) { TLOG(1500 + blockIdx.x, 1, gtime()); }
            if (rank == 0) aux_main<true>(sb, warp, rank, head, xm.m, xg, E, warp == 0 ? tq.x : (warp == 1 ? tq.y : tq.z), tq.w);
            else           aux_main<false>(sb, warp, rank, head, xm.m, xg, E, warp == 0 ? tk.x : (warp == 1 ? tk.y : tk.z), tk.w);
        }
        const int t = tid_now();
        if (t >= 320 && t < 320 + 13) asm volatile("prefetch.tensormap [%0];" :: "l"(&mp.wq + (t - 320)) : "memory");
        __syncwarp();
        if (warp == 0) post_producer(mp, sb, E, rank != 0 || !rec);
        else {
            if (warp == 1) {
                if (rank == 0 && rec) nbar_sync(NB_PRO, 256 + 32);
                if (elect_one()) post_init(sb);
                __syncwarp();
            }
            nbar_sync(0, 384);
            if (t == 288 || t == 320) post_helper(sb, warp - 1);
        }
    }
    __syncthreads();
    asm volatile("griddepcontrol.wait;" ::: "memory");
}

typedef CUresult (*EncodeFn)(CUtensorMap*, CUtensorMapDataType, cuuint32_t, void*, const cuuint64_t*, const cuuint64_t*,
                             const cuuint32_t*, const cuuint32_t*, CUtensorMapInterleave, CUtensorMapSwizzle,
                             CUtensorMapL2promotion, CUtensorMapFloatOOBfill);

static CUtensorMap make_map(EncodeFn fn, const void* ptr, uint64_t inner, uint64_t outer, uint32_t box_inner, uint32_t box_outer) {
    CUtensorMap m;
    cuuint64_t dims[2] = {inner, outer};
    cuuint64_t strides[1] = {inner * 2};
    cuuint32_t box[2] = {box_inner, box_outer};
    cuuint32_t es[2] = {1, 1};
    fn(&m, CU_TENSOR_MAP_DATA_TYPE_BFLOAT16, 2, const_cast<void*>(ptr), dims, strides, box, es,
       CU_TENSOR_MAP_INTERLEAVE_NONE, CU_TENSOR_MAP_SWIZZLE_128B, CU_TENSOR_MAP_L2_PROMOTION_L2_256B, CU_TENSOR_MAP_FLOAT_OOB_FILL_NONE);
    return m;
}

static CUtensorMap make_wo_map(EncodeFn fn, const void* ptr, uint64_t rows, uint32_t ngrp) {
    CUtensorMap m;
    cuuint64_t dims[5] = {DM, 2, 4, 4, rows / 32};
    cuuint64_t strides[4] = {DM * 2, 8 * DM * 2, 2 * DM * 2, 32 * DM * 2};
    cuuint32_t box[5] = {64, 2, 4, 4, ngrp};
    cuuint32_t es[5] = {1, 1, 1, 1, 1};
    fn(&m, CU_TENSOR_MAP_DATA_TYPE_BFLOAT16, 5, const_cast<void*>(ptr), dims, strides, box, es,
       CU_TENSOR_MAP_INTERLEAVE_NONE, CU_TENSOR_MAP_SWIZZLE_128B, CU_TENSOR_MAP_L2_PROMOTION_L2_256B, CU_TENSOR_MAP_FLOAT_OOB_FILL_NONE);
    return m;
}

struct Maps {
    PMaps post;
    CUtensorMap wk16, wv16, wo128;
    XMaps x32;
};

extern "C" void kernel_launch(void* const* d_in, const int* in_sizes, int n_in, void* d_out, int out_size) {
    const bf16* A_x   = (const bf16*)d_in[0];
    const bf16* A_mem = (const bf16*)d_in[1];
    const bf16* A_Wq  = (const bf16*)d_in[2];
    const bf16* A_Wk  = (const bf16*)d_in[3];
    const bf16* A_Wv  = (const bf16*)d_in[4];
    const bf16* A_Wo  = (const bf16*)d_in[5];
    const bf16* B_x   = (const bf16*)d_in[7];
    const bf16* B_w   = (const bf16*)d_in[8];
    const bf16* B_wo  = (const bf16*)d_in[9];

    static EncodeFn fn = nullptr;
    static Maps mp;
    static const void* cached[10];
    const void* cur[10] = {A_x, A_mem, A_Wq, A_Wk, A_Wv, A_Wo, B_x, B_w, B_wo, d_out};
    bool same = fn != nullptr;
    for (int i = 0; i < 10 && same; i++) same = cached[i] == cur[i];
    if (!same) {
        if (!fn) {
            void* p = nullptr; cudaDriverEntryPointQueryResult qr;
            cudaGetDriverEntryPoint("cuTensorMapEncodeTiled", &p, cudaEnableDefault, &qr);
            fn = (EncodeFn)p;
            cudaFuncSetAttribute(k_rec, cudaFuncAttributeMaxDynamicSharedMemorySize, R_SMEM);
        }
        void *p_ox, *p_bqkv, *p_bo, *p_qx;
        cudaGetSymbolAddress(&p_qx, g_qx);
        cudaGetSymbolAddress(&p_ox, g_ox); cudaGetSymbolAddress(&p_bqkv, g_bqkv); cudaGetSymbolAddress(&p_bo, g_bo);
        mp.post.wq   = make_map(fn, A_Wq, HD, DM, 64, 64);
        mp.post.wo   = make_wo_map(fn, A_Wo, HD, 2);
        mp.post.bw   = make_map(fn, B_w, 3 * DM, DM, 64, 64);
        mp.post.bwo  = make_wo_map(fn, B_wo, DM, 2);
        mp.post.x    = make_map(fn, A_x, DM, S_TOK, 64, 128);
        mp.post.bx   = make_map(fn, B_x, DM, S_TOK, 64, 128);
        mp.post.bo   = make_map(fn, p_bo, DM, S_TOK, 64, 128);
        mp.post.ox   = make_map(fn, p_ox, HD, S_TOK, 64, 128);
        mp.post.ox64 = make_map(fn, p_ox, HD, S_TOK, 64, 64);
        mp.post.cb   = make_map(fn, p_bqkv, 3 * DM, S_TOK, 64, 64);
        mp.post.cout = make_map(fn, d_out, 2 * DM, S_TOK, 64, 64);
        {
            cuuint64_t dims[4] = {256, 4, NH * 4, NSEG};
            cuuint64_t strides[3] = {512, 2048, NH * 8192};
            cuuint32_t box[4] = {256, 2, 4, 2};
            cuuint32_t es[4] = {1, 1, 1, 1};
            fn(&mp.post.cq, CU_TENSOR_MAP_DATA_TYPE_BFLOAT16, 4, p_qx, dims, strides, box, es,
               CU_TENSOR_MAP_INTERLEAVE_NONE, CU_TENSOR_MAP_SWIZZLE_NONE, CU_TENSOR_MAP_L2_PROMOTION_NONE, CU_TENSOR_MAP_FLOAT_OOB_FILL_NONE);
        }
        {
            int runs[48] = {K_QH, 0, 2, K_Q, 1, 7, K_B1, 0, 8, K_A4, 0, 4, K_B2, 0, 32, K_A4, 4, 2, K_B3, 0, 4, K_A3, 12, 2, K_B3, 4, 4,
                            K_SK, 14, 1, K_SN, 30, 2, -1};
            int nlate = 9;
            const int per[9] = {32, 24, 8, 8, 32, 8, 8 * P_SPLIT, 1, 8 * P_SPLIT};
            int n = 0, id = 0;
            for (; runs[3 * n] >= 0; n++) {
                mp.post.list.run[n] = make_int4(runs[3 * n], runs[3 * n + 1], id, id + runs[3 * n + 2] * per[runs[3 * n]]);
                id = mp.post.list.run[n].w;
            }
            mp.post.list.n = n;
            mp.post.list.late = mp.post.list.run[nlate].z;
            int dev = 0, nsm = 132;
            cudaGetDevice(&dev);
            cudaDeviceGetAttribute(&nsm, cudaDevAttrMultiProcessorCount, dev);
            mp.post.list.nworker = nsm > 96 ? nsm : 97;
        }
        {
            cuuint64_t dims[4] = {DM, 3, 2, S_TOK / 2};
            cuuint64_t strides[3] = {DM * 2, 3 * DM * 2, 3 * DM * 4};
            cuuint32_t box[4] = {64, 3, 1, 40};
            cuuint32_t es[4] = {1, 1, 1, 1};
            fn(&mp.post.b40, CU_TENSOR_MAP_DATA_TYPE_BFLOAT16, 4, p_bqkv, dims, strides, box, es,
               CU_TENSOR_MAP_INTERLEAVE_NONE, CU_TENSOR_MAP_SWIZZLE_128B, CU_TENSOR_MAP_L2_PROMOTION_L2_256B, CU_TENSOR_MAP_FLOAT_OOB_FILL_NONE);
        }
        mp.wk16 = make_map(fn, A_Wk, HD, DM, 64, 64);
        mp.wv16 = make_map(fn, A_Wv, HD, DM, 64, 64);
        mp.wo128 = make_wo_map(fn, A_Wo, HD, 4);
        for (int i = 0; i < 2; i++) {
            cuuint64_t dims[3] = {64, S_TOK, DM / 64};
            cuuint64_t strides[2] = {DM * 2, 128};
            cuuint32_t box[3] = {32, 32, 2u - i};
            cuuint32_t es[3] = {1, 1, 1};
            fn(&mp.x32.m[i], CU_TENSOR_MAP_DATA_TYPE_BFLOAT16, 3, const_cast<bf16*>(A_x), dims, strides, box, es,
               CU_TENSOR_MAP_INTERLEAVE_NONE, CU_TENSOR_MAP_SWIZZLE_64B, CU_TENSOR_MAP_L2_PROMOTION_L2_128B, CU_TENSOR_MAP_FLOAT_OOB_FILL_NONE);
        }
        for (int i = 0; i < 10; i++) cached[i] = cur[i];
    }

    cudaStream_t st = cudaStreamPerThread;
    int4 tq = make_int4(0, 100, 700, 80), tk = make_int4(0, 250, 800, 70);
    int2 t0 = make_int2(13000, 16000);
    cudaLaunchConfig_t cfg = {};
    cfg.gridDim = dim3(96); cfg.blockDim = dim3(384); cfg.dynamicSmemBytes = R_SMEM; cfg.stream = st;
    cudaLaunchAttribute at[1];
    at[0].id = cudaLaunchAttributeClusterDimension;
    at[0].val.clusterDim.x = 3; at[0].val.clusterDim.y = 1; at[0].val.clusterDim.z = 1;
    cfg.attrs = at; cfg.numAttrs = 1;
    cudaLaunchKernelEx(&cfg, k_rec, mp.post, mp.wk16, mp.wv16, mp.wo128, mp.x32, A_mem, A_x, tq, tk, t0, 1);
    cfg.gridDim = dim3(mp.post.list.nworker - 96);
    at[0].id = cudaLaunchAttributeProgrammaticStreamSerialization;
    at[0].val.programmaticStreamSerializationAllowed = 1;
    cudaLaunchKernelEx(&cfg, k_rec, mp.post, mp.wk16, mp.wv16, mp.wo128, mp.x32, A_mem, A_x, tq, tk, t0, 0);
}
```

```cpp
#include <cuda_runtime.h>
#include <cuda_bf16.h>
#include <cuda.h>
#include <stdint.h>

typedef __nv_bfloat16 bf16;

constexpr int S_TOK = 2048;
constexpr int DM    = 1024;
constexpr int NH    = 32;
constexpr int DH    = 128;
constexpr int NSEG  = 64;
constexpr int HD    = NH * DH;

__device__ __align__(1024) bf16 g_qx[NSEG * NH * 4 * DH * 8];
__device__ __align__(1024) bf16 g_ox[S_TOK * HD];
__device__ __align__(1024) bf16 g_bqkv[S_TOK * 3 * DM];
__device__ __align__(1024) bf16 g_bo[S_TOK * DM];
__device__ __align__(1024) uint8_t g_acc[192 * 1024];

#define EV(cond, s, k) do {} while (0)
#define EVCAL(s) do {} while (0)

constexpr int P_NSK = 4;
__device__ unsigned g_epoch, g_qctr, g_done, g_zero;
enum { C_B1 = 0, C_B2 = 8, C_Q = 16, C_QH = 24, C_NONE = 31 };
__device__ unsigned g_cnt[32], g_prog[32], g_cnt_sk[P_NSK * 32];
constexpr int P_SPLIT = 4;
__device__ __align__(1024) uint4 g_skp[P_NSK * 8 * P_SPLIT * 2 * 8 * 128];
#define TLOG(i, k, v) do {} while (0)

#define DEVI __device__ __forceinline__

DEVI uint32_t opaque(uint32_t v) { uint32_t r; asm volatile("mov.u32 %0, %1;" : "=r"(r) : "r"(v)); return r; }
DEVI uint32_t smem_u32(const void* p) { return (uint32_t)__cvta_generic_to_shared(p); }

constexpr int SPIN_LIMIT = 1 << 22;
#define MBAR_HINT_NS 20000u
constexpr int SPIN_LIMIT_MBAR = 1 << 17;

DEVI void mbar_init(uint32_t bar, uint32_t cnt) { asm volatile("mbarrier.init.shared::cta.b64 [%0], %1;" :: "r"(bar), "r"(cnt)); }
DEVI void mbar_expect_tx(uint32_t bar, uint32_t bytes) {
    asm volatile("mbarrier.arrive.expect_tx.shared::cta.b64 _, [%0], %1;" :: "r"(bar), "r"(bytes) : "memory");
}
DEVI void mbar_arrive(uint32_t bar) { asm volatile("mbarrier.arrive.shared::cta.b64 _, [%0];" :: "r"(bar) : "memory"); }
DEVI bool mbar_try(uint32_t bar, uint32_t parity) {
    uint32_t ok;
    asm volatile("{.reg .pred p; mbarrier.try_wait.parity.shared::cta.b64 p, [%1], %2; selp.u32 %0, 1, 0, p;}"
                 : "=r"(ok) : "r"(bar), "r"(parity) : "memory");
    return ok;
}
DEVI bool mbar_try_hint(uint32_t bar, uint32_t parity) {
    uint32_t ok;
    asm volatile("{.reg .pred p; mbarrier.try_wait.parity.shared::cta.b64 p, [%1], %2, %3; selp.u32 %0, 1, 0, p;}"
                 : "=r"(ok) : "r"(bar), "r"(parity), "r"(MBAR_HINT_NS) : "memory");
    return ok;
}
DEVI bool mbar_test(uint32_t bar, uint32_t parity) {
    uint32_t ok;
    asm volatile("{.reg .pred p; mbarrier.test_wait.parity.shared::cta.b64 p, [%1], %2; selp.u32 %0, 1, 0, p;}"
                 : "=r"(ok) : "r"(bar), "r"(parity) : "memory");
    return ok;
}
DEVI void mbar_wait(uint32_t bar, uint32_t parity) {
    int n = 0;
    while (!mbar_try(bar, parity)) { if (++n > SPIN_LIMIT) __trap(); }
}
DEVI void mbar_wait_sleepy(uint32_t bar, uint32_t parity) {
    int n = 0;
    while (!mbar_try_hint(bar, parity)) { if (++n > SPIN_LIMIT_MBAR) __trap(); }
}
DEVI void fence_mbar_init() { asm volatile("fence.mbarrier_init.release.cluster;" ::: "memory"); }
DEVI void fence_proxy_async() { asm volatile("fence.proxy.async.shared::cta;" ::: "memory"); }
DEVI bool elect_one() {
    uint32_t e; asm volatile("{.reg .pred p; elect.sync _|p, 0xffffffff; selp.u32 %0, 1, 0, p;}" : "=r"(e)); return e;
}
DEVI void fence_proxy_global() { asm volatile("fence.proxy.async.global;" ::: "memory"); }
DEVI void cluster_wait() { asm volatile("barrier.cluster.wait.acquire.aligned;" ::: "memory"); }
DEVI void nbar_sync(int id, int n) { asm volatile("bar.sync %0, %1;" :: "r"(id), "r"(n) : "memory"); }
DEVI void nbar_arrive(int id, int n) { asm volatile("bar.arrive %0, %1;" :: "r"(id), "r"(n) : "memory"); }

DEVI void tma_load_2d(uint32_t dst, const CUtensorMap* map, int x, int y, uint32_t bar) {
    asm volatile("cp.async.bulk.tensor.2d.shared::cluster.global.mbarrier::complete_tx::bytes [%0], [%1, {%3, %4}], [%2];"
                 :: "r"(dst), "l"(map), "r"(bar), "r"(x), "r"(y) : "memory");
}
DEVI void tma_load_3d(uint32_t dst, const CUtensorMap* map, int x, int y, int z, uint32_t bar) {
    asm volatile("cp.async.bulk.tensor.3d.shared::cluster.global.mbarrier::complete_tx::bytes [%0], [%1, {%3, %4, %5}], [%2];"
                 :: "r"(dst), "l"(map), "r"(bar), "r"(x), "r"(y), "r"(z) : "memory");
}
DEVI void tma_load_wo(uint32_t dst, const CUtensorMap* map, int col, int k32, uint32_t bar) {
    asm volatile("cp.async.bulk.tensor.5d.shared::cluster.global.mbarrier::complete_tx::bytes [%0], [%1, {%3, %5, %5, %5, %4}], [%2];"
                 :: "r"(dst), "l"(map), "r"(bar), "r"(col), "r"(k32), "r"(0) : "memory");
}
DEVI void tma_store_2d(const CUtensorMap* map, uint32_t src, int x, int y) {
    asm volatile("cp.async.bulk.tensor.2d.global.shared::cta.bulk_group [%0, {%2, %3}], [%1];"
                 :: "l"(map), "r"(src), "r"(x), "r"(y) : "memory");
}
DEVI void bulk_load(uint32_t dst, const void* src, uint32_t bytes, uint32_t bar) {
    asm volatile("cp.async.bulk.shared::cluster.global.mbarrier::complete_tx::bytes [%0], [%1], %2, [%3];"
                 :: "r"(dst), "l"(src), "r"(bytes), "r"(bar) : "memory");
}
DEVI void bulk_copy_s2c(uint32_t dst_cluster, uint32_t src, uint32_t bytes, uint32_t bar_cluster) {
    asm volatile("cp.async.bulk.shared::cluster.shared::cta.mbarrier::complete_tx::bytes [%0], [%1], %2, [%3];"
                 :: "r"(dst_cluster), "r"(src), "r"(bytes), "r"(bar_cluster) : "memory");
}
DEVI void bulk_wait_read() { asm volatile("cp.async.bulk.wait_group.read 0;" ::: "memory"); }
DEVI void mbar_arrive_remote(uint32_t bar_cluster) {
    asm volatile("mbarrier.arrive.shared::cluster.b64 _, [%0];" :: "r"(bar_cluster) : "memory");
}
DEVI void l2_prefetch(const void* p, uint32_t bytes) {
    asm volatile("cp.async.bulk.prefetch.L2.global [%0], %1;" :: "l"(p), "r"(bytes) : "memory");
}
DEVI void bulk_commit() { asm volatile("cp.async.bulk.commit_group;" ::: "memory"); }
DEVI void bulk_wait_all() { asm volatile("cp.async.bulk.wait_group 0;" ::: "memory"); }

DEVI void wg_fence() { asm volatile("wgmma.fence.sync.aligned;" ::: "memory"); }
DEVI void wg_commit() { asm volatile("wgmma.commit_group.sync.aligned;" ::: "memory"); }
template <int N> DEVI void wg_wait() { asm volatile("wgmma.wait_group.sync.aligned %0;" :: "n"(N) : "memory"); }

template <int R> DEVI void reg_dec() { asm volatile("setmaxnreg.dec.sync.aligned.u32 %0;" :: "n"(R)); }
template <int R> DEVI void reg_inc() { asm volatile("setmaxnreg.inc.sync.aligned.u32 %0;" :: "n"(R)); }

DEVI uint64_t mk_desc(uint32_t addr, uint32_t lbo, uint32_t sbo, uint32_t sw) {
    return (uint64_t)((addr & 0x3FFFF) >> 4) | ((uint64_t)(lbo >> 4) << 16) | ((uint64_t)(sbo >> 4) << 32) | ((uint64_t)sw << 62);
}

constexpr uint32_t DHI_SW128 = (1024u >> 4) | (1u << 30);
constexpr uint32_t DHI_SW64  = (512u >> 4) | (2u << 30);
constexpr uint32_t DHI_NONE  = (128u >> 4);

template <int TB, int SCALE_D>
DEVI void wgmma_n8_ss(float* d, uint32_t alo, uint32_t blo) {
    asm volatile("{.reg .b64 da, db; mov.b64 da, {%4, %6}; mov.b64 db, {%5, %7};\n"
                 "wgmma.mma_async.sync.aligned.m64n8k16.f32.bf16.bf16 {%0,%1,%2,%3}, da, db, %8, 1, 1, 1, %9;}"
                 : "+f"(d[0]), "+f"(d[1]), "+f"(d[2]), "+f"(d[3])
                 : "r"(alo), "r"(blo), "n"(DHI_SW128), "n"(DHI_NONE), "n"(SCALE_D), "n"(TB));
}

template <int TB>
DEVI void wgmma_n8_ss_first(float* d, uint32_t alo, uint32_t blo) {
    asm volatile("{.reg .b64 da, db; mov.b64 da, {%4, %6}; mov.b64 db, {%5, %7};\n"
                 "wgmma.mma_async.sync.aligned.m64n8k16.f32.bf16.bf16 {%0,%1,%2,%3}, da, db, 0, 1, 1, 1, %8;}"
                 : "=f"(d[0]), "=f"(d[1]), "=f"(d[2]), "=f"(d[3])
                 : "r"(alo), "r"(blo), "n"(DHI_SW128), "n"(DHI_NONE), "n"(TB));
}
DEVI void wgmma_n32_rs_first(float* d, const uint32_t* a, uint32_t blo) {
    asm volatile("{.reg .b64 db; mov.b64 db, {%20, %21};\n"
                 "wgmma.mma_async.sync.aligned.m64n32k16.f32.bf16.bf16 {%0,%1,%2,%3,%4,%5,%6,%7,%8,%9,%10,%11,%12,%13,%14,%15}, "
                 "{%16,%17,%18,%19}, db, 0, 1, 1, 0;}"
                 : "=f"(d[0]), "=f"(d[1]), "=f"(d[2]), "=f"(d[3]), "=f"(d[4]), "=f"(d[5]), "=f"(d[6]), "=f"(d[7]),
                   "=f"(d[8]), "=f"(d[9]), "=f"(d[10]), "=f"(d[11]), "=f"(d[12]), "=f"(d[13]), "=f"(d[14]), "=f"(d[15])
                 : "r"(a[0]), "r"(a[1]), "r"(a[2]), "r"(a[3]), "r"(blo), "n"(DHI_SW64));
}
template <int N> DEVI void reg_fence(float* d) {
#pragma unroll
    for (int i = 0; i < N; i++) asm volatile("" : "+f"(d[i]) :: "memory");
}
DEVI void wgmma_n32_rs(float* d, const uint32_t* a, uint32_t blo) {
    asm volatile("{.reg .b64 db; mov.b64 db, {%20, %21};\n"
                 "wgmma.mma_async.sync.aligned.m64n32k16.f32.bf16.bf16 {%0,%1,%2,%3,%4,%5,%6,%7,%8,%9,%10,%11,%12,%13,%14,%15}, "
                 "{%16,%17,%18,%19}, db, 1, 1, 1, 0;}"
                 : "+f"(d[0]), "+f"(d[1]), "+f"(d[2]), "+f"(d[3]), "+f"(d[4]), "+f"(d[5]), "+f"(d[6]), "+f"(d[7]),
                   "+f"(d[8]), "+f"(d[9]), "+f"(d[10]), "+f"(d[11]), "+f"(d[12]), "+f"(d[13]), "+f"(d[14]), "+f"(d[15])
                 : "r"(a[0]), "r"(a[1]), "r"(a[2]), "r"(a[3]), "r"(blo), "n"(DHI_SW64));
}
DEVI void wgmma_n32_ss(float* d, uint32_t alo, uint32_t blo) {
    asm volatile("{.reg .b64 da, db; mov.b64 da, {%16, %18}; mov.b64 db, {%17, %19};\n"
                 "wgmma.mma_async.sync.aligned.m64n32k16.f32.bf16.bf16 {%0,%1,%2,%3,%4,%5,%6,%7,%8,%9,%10,%11,%12,%13,%14,%15}, "
                 "da, db, 1, 1, 1, 1, 0;}"
                 : "+f"(d[0]), "+f"(d[1]), "+f"(d[2]), "+f"(d[3]), "+f"(d[4]), "+f"(d[5]), "+f"(d[6]), "+f"(d[7]),
                   "+f"(d[8]), "+f"(d[9]), "+f"(d[10]), "+f"(d[11]), "+f"(d[12]), "+f"(d[13]), "+f"(d[14]), "+f"(d[15])
                 : "r"(alo), "r"(blo), "n"(DHI_SW128), "n"(DHI_SW64));
}

template <bool FIRST>
DEVI void wgmma_n256_ss(float* d, uint64_t a, uint64_t b) {
    if (FIRST)
        asm volatile("wgmma.mma_async.sync.aligned.m64n256k16.f32.bf16.bf16 {%0,%1,%2,%3,%4,%5,%6,%7,%8,%9,%10,%11,%12,%13,%14,%15,%16,%17,%18,%19,%20,%21,%22,%23,%24,%25,%26,%27,%28,%29,%30,%31,%32,%33,%34,%35,%36,%37,%38,%39,%40,%41,%42,%43,%44,%45,%46,%47,%48,%49,%50,%51,%52,%53,%54,%55,%56,%57,%58,%59,%60,%61,%62,%63,%64,%65,%66,%67,%68,%69,%70,%71,%72,%73,%74,%75,%76,%77,%78,%79,%80,%81,%82,%83,%84,%85,%86,%87,%88,%89,%90,%91,%92,%93,%94,%95,%96,%97,%98,%99,%100,%101,%102,%103,%104,%105,%106,%107,%108,%109,%110,%111,%112,%113,%114,%115,%116,%117,%118,%119,%120,%121,%122,%123,%124,%125,%126,%127}, %128, %129, 0, 1, 1, 1, 0;"
            : "=f"(d[0]), "=f"(d[1]), "=f"(d[2]), "=f"(d[3]), "=f"(d[4]), "=f"(d[5]), "=f"(d[6]), "=f"(d[7]), "=f"(d[8]), "=f"(d[9]), "=f"(d[10]), "=f"(d[11]), "=f"(d[12]), "=f"(d[13]), "=f"(d[14]), "=f"(d[15]), "=f"(d[16]), "=f"(d[17]), "=f"(d[18]), "=f"(d[19]), "=f"(d[20]), "=f"(d[21]), "=f"(d[22]), "=f"(d[23]), "=f"(d[24]), "=f"(d[25]), "=f"(d[26]), "=f"(d[27]), "=f"(d[28]), "=f"(d[29]), "=f"(d[30]), "=f"(d[31]), "=f"(d[32]), "=f"(d[33]), "=f"(d[34]), "=f"(d[35]), "=f"(d[36]), "=f"(d[37]), "=f"(d[38]), "=f"(d[39]), "=f"(d[40]), "=f"(d[41]), "=f"(d[42]), "=f"(d[43]), "=f"(d[44]), "=f"(d[45]), "=f"(d[46]), "=f"(d[47]), "=f"(d[48]), "=f"(d[49]), "=f"(d[50]), "=f"(d[51]), "=f"(d[52]), "=f"(d[53]), "=f"(d[54]), "=f"(d[55]), "=f"(d[56]), "=f"(d[57]), "=f"(d[58]), "=f"(d[59]), "=f"(d[60]), "=f"(d[61]), "=f"(d[62]), "=f"(d[63]), "=f"(d[64]), "=f"(d[65]), "=f"(d[66]), "=f"(d[67]), "=f"(d[68]), "=f"(d[69]), "=f"(d[70]), "=f"(d[71]), "=f"(d[72]), "=f"(d[73]), "=f"(d[74]), "=f"(d[75]), "=f"(d[76]), "=f"(d[77]), "=f"(d[78]), "=f"(d[79]), "=f"(d[80]), "=f"(d[81]), "=f"(d[82]), "=f"(d[83]), "=f"(d[84]), "=f"(d[85]), "=f"(d[86]), "=f"(d[87]), "=f"(d[88]), "=f"(d[89]), "=f"(d[90]), "=f"(d[91]), "=f"(d[92]), "=f"(d[93]), "=f"(d[94]), "=f"(d[95]), "=f"(d[96]), "=f"(d[97]), "=f"(d[98]), "=f"(d[99]), "=f"(d[100]), "=f"(d[101]), "=f"(d[102]), "=f"(d[103]), "=f"(d[104]), "=f"(d[105]), "=f"(d[106]), "=f"(d[107]), "=f"(d[108]), "=f"(d[109]), "=f"(d[110]), "=f"(d[111]), "=f"(d[112]), "=f"(d[113]), "=f"(d[114]), "=f"(d[115]), "=f"(d[116]), "=f"(d[117]), "=f"(d[118]), "=f"(d[119]), "=f"(d[120]), "=f"(d[121]), "=f"(d[122]), "=f"(d[123]), "=f"(d[124]), "=f"(d[125]), "=f"(d[126]), "=f"(d[127]) : "l"(a), "l"(b));
    else
        asm volatile("wgmma.mma_async.sync.aligned.m64n256k16.f32.bf16.bf16 {%0,%1,%2,%3,%4,%5,%6,%7,%8,%9,%10,%11,%12,%13,%14,%15,%16,%17,%18,%19,%20,%21,%22,%23,%24,%25,%26,%27,%28,%29,%30,%31,%32,%33,%34,%35,%36,%37,%38,%39,%40,%41,%42,%43,%44,%45,%46,%47,%48,%49,%50,%51,%52,%53,%54,%55,%56,%57,%58,%59,%60,%61,%62,%63,%64,%65,%66,%67,%68,%69,%70,%71,%72,%73,%74,%75,%76,%77,%78,%79,%80,%81,%82,%83,%84,%85,%86,%87,%88,%89,%90,%91,%92,%93,%94,%95,%96,%97,%98,%99,%100,%101,%102,%103,%104,%105,%106,%107,%108,%109,%110,%111,%112,%113,%114,%115,%116,%117,%118,%119,%120,%121,%122,%123,%124,%125,%126,%127}, %128, %129, 1, 1, 1, 1, 0;"
            : "+f"(d[0]), "+f"(d[1]), "+f"(d[2]), "+f"(d[3]), "+f"(d[4]), "+f"(d[5]), "+f"(d[6]), "+f"(d[7]), "+f"(d[8]), "+f"(d[9]), "+f"(d[10]), "+f"(d[11]), "+f"(d[12]), "+f"(d[13]), "+f"(d[14]), "+f"(d[15]), "+f"(d[16]), "+f"(d[17]), "+f"(d[18]), "+f"(d[19]), "+f"(d[20]), "+f"(d[21]), "+f"(d[22]), "+f"(d[23]), "+f"(d[24]), "+f"(d[25]), "+f"(d[26]), "+f"(d[27]), "+f"(d[28]), "+f"(d[29]), "+f"(d[30]), "+f"(d[31]), "+f"(d[32]), "+f"(d[33]), "+f"(d[34]), "+f"(d[35]), "+f"(d[36]), "+f"(d[37]), "+f"(d[38]), "+f"(d[39]), "+f"(d[40]), "+f"(d[41]), "+f"(d[42]), "+f"(d[43]), "+f"(d[44]), "+f"(d[45]), "+f"(d[46]), "+f"(d[47]), "+f"(d[48]), "+f"(d[49]), "+f"(d[50]), "+f"(d[51]), "+f"(d[52]), "+f"(d[53]), "+f"(d[54]), "+f"(d[55]), "+f"(d[56]), "+f"(d[57]), "+f"(d[58]), "+f"(d[59]), "+f"(d[60]), "+f"(d[61]), "+f"(d[62]), "+f"(d[63]), "+f"(d[64]), "+f"(d[65]), "+f"(d[66]), "+f"(d[67]), "+f"(d[68]), "+f"(d[69]), "+f"(d[70]), "+f"(d[71]), "+f"(d[72]), "+f"(d[73]), "+f"(d[74]), "+f"(d[75]), "+f"(d[76]), "+f"(d[77]), "+f"(d[78]), "+f"(d[79]), "+f"(d[80]), "+f"(d[81]), "+f"(d[82]), "+f"(d[83]), "+f"(d[84]), "+f"(d[85]), "+f"(d[86]), "+f"(d[87]), "+f"(d[88]), "+f"(d[89]), "+f"(d[90]), "+f"(d[91]), "+f"(d[92]), "+f"(d[93]), "+f"(d[94]), "+f"(d[95]), "+f"(d[96]), "+f"(d[97]), "+f"(d[98]), "+f"(d[99]), "+f"(d[100]), "+f"(d[101]), "+f"(d[102]), "+f"(d[103]), "+f"(d[104]), "+f"(d[105]), "+f"(d[106]), "+f"(d[107]), "+f"(d[108]), "+f"(d[109]), "+f"(d[110]), "+f"(d[111]), "+f"(d[112]), "+f"(d[113]), "+f"(d[114]), "+f"(d[115]), "+f"(d[116]), "+f"(d[117]), "+f"(d[118]), "+f"(d[119]), "+f"(d[120]), "+f"(d[121]), "+f"(d[122]), "+f"(d[123]), "+f"(d[124]), "+f"(d[125]), "+f"(d[126]), "+f"(d[127]) : "l"(a), "l"(b));
}
template <bool FIRST>
DEVI void wgmma_n128_ss(float* d, uint64_t a, uint64_t b) {
    if (FIRST)
        asm volatile("wgmma.mma_async.sync.aligned.m64n128k16.f32.bf16.bf16 {%0,%1,%2,%3,%4,%5,%6,%7,%8,%9,%10,%11,%12,%13,%14,%15,%16,%17,%18,%19,%20,%21,%22,%23,%24,%25,%26,%27,%28,%29,%30,%31,%32,%33,%34,%35,%36,%37,%38,%39,%40,%41,%42,%43,%44,%45,%46,%47,%48,%49,%50,%51,%52,%53,%54,%55,%56,%57,%58,%59,%60,%61,%62,%63}, %64, %65, 0, 1, 1, 1, 0;"
            : "=f"(d[0]), "=f"(d[1]), "=f"(d[2]), "=f"(d[3]), "=f"(d[4]), "=f"(d[5]), "=f"(d[6]), "=f"(d[7]), "=f"(d[8]), "=f"(d[9]), "=f"(d[10]), "=f"(d[11]), "=f"(d[12]), "=f"(d[13]), "=f"(d[14]), "=f"(d[15]), "=f"(d[16]), "=f"(d[17]), "=f"(d[18]), "=f"(d[19]), "=f"(d[20]), "=f"(d[21]), "=f"(d[22]), "=f"(d[23]), "=f"(d[24]), "=f"(d[25]), "=f"(d[26]), "=f"(d[27]), "=f"(d[28]), "=f"(d[29]), "=f"(d[30]), "=f"(d[31]), "=f"(d[32]), "=f"(d[33]), "=f"(d[34]), "=f"(d[35]), "=f"(d[36]), "=f"(d[37]), "=f"(d[38]), "=f"(d[39]), "=f"(d[40]), "=f"(d[41]), "=f"(d[42]), "=f"(d[43]), "=f"(d[44]), "=f"(d[45]), "=f"(d[46]), "=f"(d[47]), "=f"(d[48]), "=f"(d[49]), "=f"(d[50]), "=f"(d[51]), "=f"(d[52]), "=f"(d[53]), "=f"(d[54]), "=f"(d[55]), "=f"(d[56]), "=f"(d[57]), "=f"(d[58]), "=f"(d[59]), "=f"(d[60]), "=f"(d[61]), "=f"(d[62]), "=f"(d[63]) : "l"(a), "l"(b));
    else
        asm volatile("wgmma.mma_async.sync.aligned.m64n128k16.f32.bf16.bf16 {%0,%1,%2,%3,%4,%5,%6,%7,%8,%9,%10,%11,%12,%13,%14,%15,%16,%17,%18,%19,%20,%21,%22,%23,%24,%25,%26,%27,%28,%29,%30,%31,%32,%33,%34,%35,%36,%37,%38,%39,%40,%41,%42,%43,%44,%45,%46,%47,%48,%49,%50,%51,%52,%53,%54,%55,%56,%57,%58,%59,%60,%61,%62,%63}, %64, %65, 1, 1, 1, 1, 0;"
            : "+f"(d[0]), "+f"(d[1]), "+f"(d[2]), "+f"(d[3]), "+f"(d[4]), "+f"(d[5]), "+f"(d[6]), "+f"(d[7]), "+f"(d[8]), "+f"(d[9]), "+f"(d[10]), "+f"(d[11]), "+f"(d[12]), "+f"(d[13]), "+f"(d[14]), "+f"(d[15]), "+f"(d[16]), "+f"(d[17]), "+f"(d[18]), "+f"(d[19]), "+f"(d[20]), "+f"(d[21]), "+f"(d[22]), "+f"(d[23]), "+f"(d[24]), "+f"(d[25]), "+f"(d[26]), "+f"(d[27]), "+f"(d[28]), "+f"(d[29]), "+f"(d[30]), "+f"(d[31]), "+f"(d[32]), "+f"(d[33]), "+f"(d[34]), "+f"(d[35]), "+f"(d[36]), "+f"(d[37]), "+f"(d[38]), "+f"(d[39]), "+f"(d[40]), "+f"(d[41]), "+f"(d[42]), "+f"(d[43]), "+f"(d[44]), "+f"(d[45]), "+f"(d[46]), "+f"(d[47]), "+f"(d[48]), "+f"(d[49]), "+f"(d[50]), "+f"(d[51]), "+f"(d[52]), "+f"(d[53]), "+f"(d[54]), "+f"(d[55]), "+f"(d[56]), "+f"(d[57]), "+f"(d[58]), "+f"(d[59]), "+f"(d[60]), "+f"(d[61]), "+f"(d[62]), "+f"(d[63]) : "l"(a), "l"(b));
}

template <bool FIRST>
DEVI void wgmma_n64_ss(float* d, uint64_t a, uint64_t b) {
    if (FIRST)
        asm volatile("wgmma.mma_async.sync.aligned.m64n64k16.f32.bf16.bf16 {%0,%1,%2,%3,%4,%5,%6,%7,%8,%9,%10,%11,%12,%13,%14,%15,%16,%17,%18,%19,%20,%21,%22,%23,%24,%25,%26,%27,%28,%29,%30,%31}, %32, %33, 0, 1, 1, 1, 0;"
            : "=f"(d[0]), "=f"(d[1]), "=f"(d[2]), "=f"(d[3]), "=f"(d[4]), "=f"(d[5]), "=f"(d[6]), "=f"(d[7]), "=f"(d[8]), "=f"(d[9]), "=f"(d[10]), "=f"(d[11]), "=f"(d[12]), "=f"(d[13]), "=f"(d[14]), "=f"(d[15]), "=f"(d[16]), "=f"(d[17]), "=f"(d[18]), "=f"(d[19]), "=f"(d[20]), "=f"(d[21]), "=f"(d[22]), "=f"(d[23]), "=f"(d[24]), "=f"(d[25]), "=f"(d[26]), "=f"(d[27]), "=f"(d[28]), "=f"(d[29]), "=f"(d[30]), "=f"(d[31]) : "l"(a), "l"(b));
    else
        asm volatile("wgmma.mma_async.sync.aligned.m64n64k16.f32.bf16.bf16 {%0,%1,%2,%3,%4,%5,%6,%7,%8,%9,%10,%11,%12,%13,%14,%15,%16,%17,%18,%19,%20,%21,%22,%23,%24,%25,%26,%27,%28,%29,%30,%31}, %32, %33, 1, 1, 1, 1, 0;"
            : "+f"(d[0]), "+f"(d[1]), "+f"(d[2]), "+f"(d[3]), "+f"(d[4]), "+f"(d[5]), "+f"(d[6]), "+f"(d[7]), "+f"(d[8]), "+f"(d[9]), "+f"(d[10]), "+f"(d[11]), "+f"(d[12]), "+f"(d[13]), "+f"(d[14]), "+f"(d[15]), "+f"(d[16]), "+f"(d[17]), "+f"(d[18]), "+f"(d[19]), "+f"(d[20]), "+f"(d[21]), "+f"(d[22]), "+f"(d[23]), "+f"(d[24]), "+f"(d[25]), "+f"(d[26]), "+f"(d[27]), "+f"(d[28]), "+f"(d[29]), "+f"(d[30]), "+f"(d[31]) : "l"(a), "l"(b));
}

DEVI void mma16816(float* d, const uint32_t* a, uint32_t b0, uint32_t b1) {
    asm volatile("mma.sync.aligned.m16n8k16.row.col.f32.bf16.bf16.f32 {%0,%1,%2,%3}, {%4,%5,%6,%7}, {%8,%9}, {%0,%1,%2,%3};"
                 : "+f"(d[0]), "+f"(d[1]), "+f"(d[2]), "+f"(d[3])
                 : "r"(a[0]), "r"(a[1]), "r"(a[2]), "r"(a[3]), "r"(b0), "r"(b1));
}
DEVI void mma1688(float* d, uint32_t a0, uint32_t a1, uint32_t b0) {
    asm volatile("mma.sync.aligned.m16n8k8.row.col.f32.bf16.bf16.f32 {%0,%1,%2,%3}, {%4,%5}, {%6}, {%0,%1,%2,%3};"
                 : "+f"(d[0]), "+f"(d[1]), "+f"(d[2]), "+f"(d[3]) : "r"(a0), "r"(a1), "r"(b0));
}
DEVI void ldsm4(uint32_t* r, uint32_t addr) {
    asm volatile("ldmatrix.sync.aligned.m8n8.x4.shared.b16 {%0,%1,%2,%3}, [%4];"
                 : "=r"(r[0]), "=r"(r[1]), "=r"(r[2]), "=r"(r[3]) : "r"(addr) : "memory");
}
DEVI void ldsm4t(uint32_t* r, uint32_t addr) {
    asm volatile("ldmatrix.sync.aligned.m8n8.x4.trans.shared.b16 {%0,%1,%2,%3}, [%4];"
                 : "=r"(r[0]), "=r"(r[1]), "=r"(r[2]), "=r"(r[3]) : "r"(addr) : "memory");
}
DEVI void stsm4(uint32_t addr, uint32_t r0, uint32_t r1, uint32_t r2, uint32_t r3) {
    asm volatile("stmatrix.sync.aligned.m8n8.x4.shared.b16 [%0], {%1,%2,%3,%4};" :: "r"(addr), "r"(r0), "r"(r1), "r"(r2), "r"(r3) : "memory");
}
DEVI void stsm4t(uint32_t addr, uint32_t r0, uint32_t r1, uint32_t r2, uint32_t r3) {
    asm volatile("stmatrix.sync.aligned.m8n8.x4.trans.shared.b16 [%0], {%1,%2,%3,%4};" :: "r"(addr), "r"(r0), "r"(r1), "r"(r2), "r"(r3) : "memory");
}
DEVI uint32_t pack_bf16(float lo, float hi) {
    uint32_t r; asm("cvt.rn.bf16x2.f32 %0, %1, %2;" : "=r"(r) : "f"(hi), "f"(lo)); return r;
}
DEVI float ex2(float x) { float y; asm("ex2.approx.ftz.f32 %0, %1;" : "=f"(y) : "f"(x)); return y; }

DEVI uint4 ld_rlx4(const void* p) {
    uint4 v;
    asm volatile("ld.relaxed.gpu.global.v4.u32 {%0,%1,%2,%3}, [%4];" : "=r"(v.x), "=r"(v.y), "=r"(v.z), "=r"(v.w) : "l"(p) : "memory");
    return v;
}
DEVI void st_rlx4(void* p, uint32_t a, uint32_t b, uint32_t c, uint32_t d) {
    asm volatile("st.relaxed.gpu.global.v4.u32 [%0], {%1,%2,%3,%4};" :: "l"(p), "r"(a), "r"(b), "r"(c), "r"(d) : "memory");
}
DEVI void sts128(uint32_t addr, uint4 v) {
    asm volatile("st.shared.v4.u32 [%0], {%1,%2,%3,%4};" :: "r"(addr), "r"(v.x), "r"(v.y), "r"(v.z), "r"(v.w) : "memory");
}
DEVI void sts64(uint32_t addr, uint32_t a, uint32_t b) { asm volatile("st.shared.v2.u32 [%0], {%1,%2};" :: "r"(addr), "r"(a), "r"(b) : "memory"); }
DEVI void sts32(uint32_t addr, uint32_t v) { asm volatile("st.shared.u32 [%0], %1;" :: "r"(addr), "r"(v) : "memory"); }
DEVI uint4 lds128(uint32_t addr) {
    uint4 v; asm volatile("ld.shared.v4.u32 {%0,%1,%2,%3}, [%4];" : "=r"(v.x), "=r"(v.y), "=r"(v.z), "=r"(v.w) : "r"(addr) : "memory"); return v;
}
DEVI float2 lds64f(uint32_t addr) {
    float2 v; asm volatile("ld.shared.v2.f32 {%0,%1}, [%2];" : "=f"(v.x), "=f"(v.y) : "r"(addr) : "memory"); return v;
}
DEVI uint32_t lds32(uint32_t addr) { uint32_t v; asm volatile("ld.shared.u32 %0, [%1];" : "=r"(v) : "r"(addr) : "memory"); return v; }
DEVI float rcp_fast(float x) { float y; asm("rcp.approx.ftz.f32 %0, %1;" : "=f"(y) : "f"(x)); return y; }
DEVI uint32_t mapa(uint32_t addr, uint32_t rank) {
    uint32_t r; asm("mapa.shared::cluster.u32 %0, %1, %2;" : "=r"(r) : "r"(addr), "r"(rank)); return r;
}
DEVI void st_async32(uint32_t dst, uint32_t a, uint32_t bar) {
    asm volatile("st.async.weak.shared::cluster.mbarrier::complete_tx::bytes.b32 [%0], %1, [%2];" :: "r"(dst), "r"(a), "r"(bar) : "memory");
}

DEVI void st_async128(uint32_t dst, uint32_t a, uint32_t b, uint32_t c, uint32_t d, uint32_t bar) {
    asm volatile("st.async.weak.shared::cluster.mbarrier::complete_tx::bytes.v4.b32 [%0], {%1,%2,%3,%4}, [%5];"
                 :: "r"(dst), "r"(a), "r"(b), "r"(c), "r"(d), "r"(bar) : "memory");
}

DEVI uint32_t b_addr(uint32_t sb, int row, int which, int chunk) { const int l = 3 * row + which; return sb + l * 128 + ((chunk ^ (l & 7)) * 16); }
DEVI void battn_warp(uint32_t st, uint32_t ebar, int i0, int par, int head, int hh, int mt, int lane) {
    const int gq = lane >> 2, t = lane & 3, r = 16 * mt + (lane & 7), b3 = (lane >> 3) & 1, b4 = lane >> 4;
    uint32_t a[8], k[8], k2[4], v[8], v2[4];
#pragma unroll
    for (int ks = 0; ks < 2; ks++) {
        ldsm4(a + 4 * ks, b_addr(st, 8 + r + b3 * 8, 0, hh * 4 + ks * 2 + b4));
        ldsm4(k + 4 * ks, b_addr(st, r + b4 * 8, 1, hh * 4 + ks * 2 + b3));
    }
    ldsm4(k2, b_addr(st, r + 16, 1, hh * 4 + (lane >> 3)));
#pragma unroll
    for (int n = 0; n < 2; n++) ldsm4t(v + 4 * n, b_addr(st, r + b3 * 8, 2, hh * 4 + 2 * n + b4));
    ldsm4t(v2, b_addr(st, r + 16, 2, hh * 4 + (lane >> 3)));
    float s[3][4];
#pragma unroll
    for (int n = 0; n < 3; n++) { s[n][0] = s[n][1] = s[n][2] = s[n][3] = 0.f; }
#pragma unroll
    for (int ks = 0; ks < 2; ks++) {
        mma16816(s[0], a + 4 * ks, k[4 * ks], k[4 * ks + 1]);
        mma16816(s[1], a + 4 * ks, k[4 * ks + 2], k[4 * ks + 3]);
        mma16816(s[2], a + 4 * ks, k2[2 * ks], k2[2 * ks + 1]);
    }
    const bool ex = i0 + 16 * mt > 0;
    float x[4], y[4];
#pragma unroll
    for (int c = 0; c < 2; c++) {
        const bool low = 2 * t + c <= gq;
        x[c] = !low && ex ? s[0][c] : -INFINITY; x[2 + c] = low ? s[1][c] : -INFINITY;
        y[c] = !low ? s[1][2 + c] : -INFINITY;   y[2 + c] = low ? s[2][2 + c] : -INFINITY;
    }
    float m0 = fmaxf(fmaxf(x[0], x[1]), fmaxf(x[2], x[3])), m1 = fmaxf(fmaxf(y[0], y[1]), fmaxf(y[2], y[3]));
    m0 = fmaxf(fmaxf(m0, __shfl_xor_sync(0xffffffffu, m0, 1)), fmaxf(__shfl_xor_sync(0xffffffffu, m0, 2), __shfl_xor_sync(0xffffffffu, m0, 3)));
    m1 = fmaxf(fmaxf(m1, __shfl_xor_sync(0xffffffffu, m1, 1)), fmaxf(__shfl_xor_sync(0xffffffffu, m1, 2), __shfl_xor_sync(0xffffffffu, m1, 3)));
    constexpr float C = 0.17677669529663687f * 1.4426950408889634f;
    auto e = [](float v, float mx) { return ex2((v - mx) * C); };
    const uint32_t p0[4] = {pack_bf16(e(x[0], m0), e(x[1], m0)), 0u, pack_bf16(e(x[2], m0), e(x[3], m0)), pack_bf16(e(y[0], m1), e(y[1], m1))};
    const uint32_t p1 = pack_bf16(e(y[2], m1), e(y[3], m1));
    float o[4][4], l[4] = {0.f, 0.f, 0.f, 0.f};
#pragma unroll
    for (int n = 0; n < 4; n++) { o[n][0] = o[n][1] = o[n][2] = o[n][3] = 0.f; }
    mma16816(l, p0, 0x3F803F80u, 0x3F803F80u);
#pragma unroll
    for (int n = 0; n < 4; n++) mma16816(o[n], p0, v[2 * n], v[2 * n + 1]);
    mma1688(l, 0u, p1, 0x3F803F80u);
#pragma unroll
    for (int n = 0; n < 4; n++) mma1688(o[n], 0u, p1, v2[n]);
    if (lane == 0) mbar_arrive(ebar);
    const float i0f = rcp_fast(l[0]), i1f = rcp_fast(l[2]);
    uint4* dst = (uint4*)(g_bo + (uint32_t)((2 * (i0 + 16 * mt + gq) + par) * DM + head * 32 + t * 8));
    dst[0] = make_uint4(pack_bf16(o[0][0] * i0f, o[0][1] * i0f), pack_bf16(o[1][0] * i0f, o[1][1] * i0f),
                        pack_bf16(o[2][0] * i0f, o[2][1] * i0f), pack_bf16(o[3][0] * i0f, o[3][1] * i0f));
    dst[16 * DM / 8] = make_uint4(pack_bf16(o[0][2] * i1f, o[0][3] * i1f), pack_bf16(o[1][2] * i1f, o[1][3] * i1f),
                                  pack_bf16(o[2][2] * i1f, o[2][3] * i1f), pack_bf16(o[3][2] * i1f, o[3][3] * i1f));
}

constexpr float SCALE_LOG2E = 0.08838834764831845f * 1.4426950408889634f;

constexpr int P_UNITS = 12, P_STAGES = 6;
constexpr int PS_STG = P_UNITS * 16384;
constexpr int P_SMEM = 232448;
constexpr int PS_BAR = P_SMEM - 256;
static_assert(PS_STG + 32768 <= PS_BAR, "smem");
enum { K_Q, K_B1, K_B3, K_A4, K_QH, K_A3, K_SK, K_B2, K_SN, K_END };
struct PList { int n, nworker, late; int4 run[16]; };
struct PTask { int kind, a, b, c, id; };
DEVI PTask p_decode(const PList& pl, int id) {
    int i = pl.n - 1;
    if (id >= pl.run[i].w) return {K_END, 0, 0, 0, id};
    while (id < pl.run[i].z) i--;
    const int4 r = pl.run[i];
    const int j = id - r.z;
    if (r.x == K_Q || r.x == K_QH) return {r.x, j & 31, r.y + (j >> 5), 0, id};
    if (r.x == K_B1) return {r.x, j % 24, r.y + j / 24, 0, id};
    if (r.x == K_B2) return {r.x, 0, r.y + j, 0, id};
    if (r.x == K_SK || r.x == K_SN) return {r.x, (j / P_SPLIT) & 7, r.y + j / (8 * P_SPLIT), j % P_SPLIT, id};
    return {r.x, j & 7, r.y + (j >> 3), 0, id};
}
DEVI void wait_count_warp(const unsigned* p, unsigned target) {
    int n = 0;
    while (true) {
        unsigned v; asm volatile("ld.acquire.gpu.global.u32 %0, [%1];" : "=r"(v) : "l"(p) : "memory");
        if (__all_sync(0xffffffffu, (int)(v - target) >= 0)) break;
        __nanosleep(100);
        if (++n > SPIN_LIMIT) __trap();
    }
}
DEVI void signal_count(unsigned* p) { __threadfence(); atomicAdd(p, 1u); }

struct PMaps { CUtensorMap wq, bw, bwo, wo, x, bx, bo, ox, ox64, cb, cout, cq, b40; PList list; };
constexpr int PB_F = PS_BAR, PB_E = PB_F + 48, PB_TF = PB_F + 96, PB_TE = PB_F + 112, PB_S = PB_F + 128;
constexpr int PS_T = PB_F + 160, PS_SIG = PS_T + 32, PS_SK = PS_SIG + 16;

struct PRing {
    int st, ph, u;
    DEVI void next(int n) { u += n; if (u >= P_UNITS) u -= P_UNITS; if (++st == P_STAGES) { st = 0; ph ^= 1; } }
    DEVI uint32_t w(bool wide) const { return wide && u == P_UNITS - 2 ? 0u : u * 16384u; }
    DEVI uint32_t x(bool wide) const { return wide && u == P_UNITS - 2 ? u * 16384u : (u == P_UNITS - 1 ? 0u : (u + 1) * 16384u); }
};
struct POut { const CUtensorMap* map; int col, tok, cnt; bool blocked; };
DEVI void p_store(const uint32_t* pk, const POut& o, int c, uint32_t stg, int warp, int lane_, int barid) {
    const int lane = (int)opaque((uint32_t)lane_);
    const int mi = lane >> 3, r = lane & 7;
    const uint32_t buf = stg + (c & 1) * 8192;
    if (warp == 0) asm volatile("cp.async.bulk.wait_group.read 1;" ::: "memory");
    nbar_sync(barid, 128);
    if (o.blocked) {
#pragma unroll
        for (int j = 0; j < 8; j += 2)
            stsm4(buf + (j + (mi >> 1)) * 1024 + (warp * 16 + (mi & 1) * 8 + r) * 16, pk[2 * j], pk[2 * j + 1], pk[2 * j + 2], pk[2 * j + 3]);
    } else {
#pragma unroll
        for (int j = 0; j < 8; j += 2)
            stsm4t(buf + (8 * (j + (mi >> 1)) + r) * 128 + ((2 * warp + (mi & 1)) ^ r) * 16, pk[2 * j], pk[2 * j + 1], pk[2 * j + 2], pk[2 * j + 3]);
    }
    fence_proxy_async();
    nbar_sync(barid, 128);
    if (warp == 0 && elect_one()) {
        if (o.blocked)
            asm volatile("cp.async.bulk.tensor.4d.global.shared::cta.bulk_group [%0, {%2, %3, %4, %5}], [%1];"
                         :: "l"(o.map), "r"(buf), "r"(0), "r"((o.col >> 5) & 2), "r"((o.col >> 7) * 4), "r"((o.tok >> 5) + 2 * c) : "memory");
        else tma_store_2d(o.map, buf, o.col, o.tok + c * 64);
        bulk_commit();
    }
}
DEVI void p_signal(uint32_t sb, int g, int cnt, int& nsig) {
    if (elect_one()) {
        sts32(sb + PS_SIG + g * 8 + (nsig & 1) * 4, (uint32_t)cnt);
        mbar_arrive(sb + PB_S + g * 16 + (nsig & 1) * 8);
    }
    nsig++;
}
DEVI void p_release(uint32_t sb, const PRing& r) {
    if (elect_one()) mbar_arrive(sb + PB_E + (r.st ? r.st - 1 : P_STAGES - 1) * 8);
}
template <int BN, bool FIRST>
DEVI void p_kblock(float* d, uint32_t sb, int g, PRing& r) {
    mbar_wait(sb + PB_F + r.st * 8, r.ph);
    const uint64_t da = mk_desc(sb + r.w(BN == 256) + g * 8192, 16, 1024, 1), db = mk_desc(sb + r.x(BN == 256), 16, 1024, 1);
    wg_fence();
#pragma unroll
    for (int kk = 0; kk < 4; kk++) {
        if (BN == 256) { if (FIRST && kk == 0) wgmma_n256_ss<true>(d, da, db); else wgmma_n256_ss<false>(d, da + (uint64_t)(kk * 128), db + (uint64_t)(kk * 2)); }
        if (BN == 128) { if (FIRST && kk == 0) wgmma_n128_ss<true>(d, da, db); else wgmma_n128_ss<false>(d, da + (uint64_t)(kk * 128), db + (uint64_t)(kk * 2)); }
        if (BN == 64)  { if (FIRST && kk == 0) wgmma_n64_ss<true>(d, da, db); else wgmma_n64_ss<false>(d, da + (uint64_t)(kk * 128), db + (uint64_t)(kk * 2)); }
    }
    wg_commit();
    if (!FIRST) {
        wg_wait<1>();
        p_release(sb, r);
    }
    r.next(BN == 256 ? 3 : 2);
}

DEVI PTask post_claim(const PMaps& mp, unsigned E) {
    unsigned v = 0;
    if ((threadIdx.x & 31) == 0) v = atomicAdd(&g_qctr, 1u);
    return p_decode(mp.list, (int)(__shfl_sync(0xffffffffu, v, 0) - (E - 1) * (unsigned)(mp.list.run[mp.list.n - 1].w + mp.list.nworker)));
}
DEVI void post_producer(const PMaps& mp, uint32_t sb, unsigned E, bool early) {
    PRing r = {0, 0, 0};
    int ts = 0, tp = 0, used = 0;
    uint32_t big = 0;
    auto reserve = [&](int n) {
        while (used + n > P_UNITS) {
            mbar_wait(sb + PB_E + ts * 8, tp);
            used -= 2 + ((big >> ts) & 1);
            if (++ts == P_STAGES) { ts = 0; tp ^= 1; }
        }
        used += n;
        big = (big & ~(1u << r.st)) | ((uint32_t)(n & 1) << r.st);
    };
    for (int i = 0;; i++) {
        if (i > 0) mbar_wait(sb + PB_TE + (i & 1) * 8, ((i >> 1) & 1) ^ 1);
        else if (!early) nbar_sync(0, 384);
        const PTask tk = post_claim(mp, E);
        if (i == 0) { if (early) nbar_sync(0, 384); fence_proxy_async(); }
        const bool sn = tk.kind == K_SN, split = tk.kind == K_SK || sn, wide = tk.kind <= K_A4;
        const bool qk = tk.kind == K_Q || tk.kind == K_QH, ak = tk.kind == K_A4 || tk.kind == K_A3 || split;
        const int nk = split ? HD / 64 / P_SPLIT : (ak ? HD / 64 : DM / 64), kb0 = tk.c * (HD / 64 / P_SPLIT);
        const int tok0 = tk.b * (wide ? 256 : (sn ? 64 : 128)), grp = (tok0 >> 6) + (wide ? 3 : (sn ? 0 : 1));
        const uint32_t bytes = wide ? 49152 : (sn ? 24576 : 32768);
        const CUtensorMap* tx = tk.kind == K_B1 ? &mp.bx : (qk ? &mp.x : (sn ? &mp.ox64 : (ak ? &mp.ox : &mp.bo)));
        const int npre = split && (i == 0 || __any_sync(0xffffffffu, (int)(*(volatile unsigned*)&g_prog[grp] - 64 * E) < 0)) ? P_STAGES : 0;
        PRing rp = r;
        for (int kb = kb0; kb < kb0 + npre; kb++) {
            reserve(2);
            const uint32_t bar = sb + PB_F + r.st * 8;
            if (elect_one()) {
                mbar_expect_tx(bar, bytes);
                tma_load_wo(sb + r.w(false), &mp.wo, tk.a * 128, kb * 2, bar);
                tma_load_wo(sb + r.w(false) + 8192, &mp.wo, tk.a * 128 + 64, kb * 2, bar);
            }
            r.next(2);
        }
        if (tk.kind == K_B2) {
            wait_count_warp(&g_cnt[C_B1 + (tk.b >> 2)], 48 * E);
            if ((tk.b & 3) == 0 && tk.b > 0) wait_count_warp(&g_cnt[C_B1 + (tk.b >> 2) - 1], 48 * E);
        } else if (tk.kind == K_B3) wait_count_warp(&g_cnt[C_B2 + tk.b], 8 * E);
        else if (ak) wait_count_warp(&g_prog[grp], 64 * E);
        fence_proxy_global();
        for (int kb = kb0; kb < kb0 + npre; kb++) {
            if (elect_one()) tma_load_2d(sb + rp.x(false), tx, kb * 64, tok0, sb + PB_F + rp.st * 8);
            rp.next(2);
        }
        if (elect_one()) {
            sts128(sb + PS_T + (i & 1) * 16, make_uint4((uint32_t)tk.kind | ((uint32_t)tk.id << 8), (uint32_t)tk.a, (uint32_t)tk.b, (uint32_t)tk.c));
            mbar_arrive(sb + PB_TF + (i & 1) * 8);
        }
        if (tk.kind == K_END) break;
        if (tk.kind == K_B2) {
            for (int j = 0; j < 16; j++) {
                reserve(2);
                const uint32_t bar = sb + PB_F + r.st * 8;
                if (elect_one()) {
                    mbar_expect_tx(bar, 2 * 15360);
#pragma unroll
                    for (int u = 0; u < 2; u++) asm volatile("cp.async.bulk.tensor.4d.shared::cluster.global.mbarrier::complete_tx::bytes [%0], [%1, {%3, %4, %5, %6}], [%2];"
                                 :: "r"(sb + (u ? r.x(false) : r.w(false))), "l"(&mp.b40), "r"(bar), "r"(j * 64), "r"(0), "r"(u), "r"(tk.b * 32 - 8) : "memory");
                }
                r.next(2);
            }
            continue;
        }
        const CUtensorMap* tw = tk.kind == K_B1 ? &mp.bw : (qk ? &mp.wq : (ak ? &mp.wo : &mp.bwo));
        for (int kb = kb0 + npre; kb < kb0 + nk; kb++) {
            reserve(wide ? 3 : 2);
            const uint32_t aw = sb + r.w(wide), ax = sb + r.x(wide), bar = sb + PB_F + r.st * 8;
            if (elect_one()) {
                mbar_expect_tx(bar, bytes);
                if (ak || tk.kind == K_B3) {
                    tma_load_wo(aw, tw, tk.a * 128, kb * 2, bar);
                    tma_load_wo(aw + 8192, tw, tk.a * 128 + 64, kb * 2, bar);
                } else {
                    tma_load_2d(aw, tw, tk.a * 128, kb * 64, bar);
                    tma_load_2d(aw + 8192, tw, tk.a * 128 + 64, kb * 64, bar);
                }
                tma_load_2d(ax, tx, kb * 64, tok0, bar);
                if (wide) tma_load_2d(ax + 16384, tx, kb * 64, tok0 + 128, bar);
            }
            r.next(wide ? 3 : 2);
        }
        if (tk.id >= mp.list.late) { reserve(P_UNITS - 3); used -= P_UNITS - 3; }
    }
    if (elect_one()) {
        __threadfence();
        if (atomicAdd(&g_done, 1u) == E * mp.list.nworker - 1) { __threadfence(); *(volatile unsigned*)&g_epoch = E; }
    }
}
DEVI void post_helper(uint32_t sb, int g) {
    for (int n = 0;; n++) {
        mbar_wait_sleepy(sb + PB_S + g * 16 + (n & 1) * 8, (n >> 1) & 1);
        const int cnt = (int)lds32(sb + PS_SIG + g * 8 + (n & 1) * 4);
        if (cnt < 0) break;
        signal_count(&g_cnt[cnt]);
    }
}
template <int BN>
DEVI void p_narrow(const PMaps& mp, const PTask& tk, uint32_t sb, int g, int warp, PRing& r, int& nsig) {
    const int barid = 1 + g, tid = threadIdx.x;
    const bool split = BN == 64 || tk.kind == K_SK;
    constexpr int NV = BN / 16;
    float d[BN / 2];
    const int nk = split ? HD / 64 / P_SPLIT : (tk.kind == K_A3 ? HD / 64 : DM / 64);
    p_kblock<BN, true>(d, sb, g, r);
#pragma unroll 1
    for (int kb = 1; kb < nk; kb++) p_kblock<BN, false>(d, sb, g, r);
    wg_wait<0>();
    reg_fence<BN / 2>(d);
    p_release(sb, r);
    if (split) {
        const int tile = (tk.b * (BN / 64) - 2 * (16 - P_NSK)) * 8 + tk.a * (BN / 64);
        uint4* const base = g_skp + (uint32_t)(tile * P_SPLIT * 1024 + g * NV * 128 + (tid & 127));
#pragma unroll
        for (int j = 0; j < NV; j++)
            base[tk.c * NV * 256 + j * 128] = make_uint4(pack_bf16(d[8 * j], d[8 * j + 1]), pack_bf16(d[8 * j + 2], d[8 * j + 3]),
                                                         pack_bf16(d[8 * j + 4], d[8 * j + 5]), pack_bf16(d[8 * j + 6], d[8 * j + 7]));
        nbar_sync(barid, 128);
        if (warp == 0 && elect_one()) {
            unsigned old;
            asm volatile("atom.acq_rel.gpu.global.add.u32 %0, [%1], 1;" : "=r"(old) : "l"(&g_cnt_sk[tile * 2 + g]) : "memory");
            sts32(sb + PS_SK + g * 4, old % P_SPLIT);
        }
        nbar_sync(barid, 128);
        const bool last = __any_sync(0xffffffffu, lds32(sb + PS_SK + g * 4) == P_SPLIT - 1);
        nbar_sync(barid, 128);
        if (!last) return;
        uint4 v[(P_SPLIT - 1) * NV];
#pragma unroll
        for (int j = 0; j < (P_SPLIT - 1) * NV; j++) v[j] = __ldcg(base + ((tk.c + 1 + j / NV) % P_SPLIT) * NV * 256 + (j % NV) * 128);
#pragma unroll
        for (int j = 0; j < (P_SPLIT - 1) * NV; j++) {
            float* e = d + 8 * (j % NV);
            e[0] += __uint_as_float(v[j].x << 16); e[1] += __uint_as_float(v[j].x & 0xFFFF0000u);
            e[2] += __uint_as_float(v[j].y << 16); e[3] += __uint_as_float(v[j].y & 0xFFFF0000u);
            e[4] += __uint_as_float(v[j].z << 16); e[5] += __uint_as_float(v[j].z & 0xFFFF0000u);
            e[6] += __uint_as_float(v[j].w << 16); e[7] += __uint_as_float(v[j].w & 0xFFFF0000u);
        }
    }
    const bool qh = BN == 128 && tk.kind == K_QH;
    const POut o = {qh ? &mp.cq : &mp.cout, tk.a * 128 + g * 64, tk.b * BN, 0, qh};
    uint32_t q[BN / 4];
#pragma unroll
    for (int j = 0; j < BN / 4; j++) q[j] = pack_bf16(d[2 * j], d[2 * j + 1]);
    if (BN == 64 && warp == 0) bulk_wait_read();
#pragma unroll
    for (int c = 0; c < BN / 64; c++) p_store(q + 16 * c, o, c, sb + PS_STG + g * 16384, warp, tid & 31, barid);
    if (BN == 64 && warp == 0) bulk_wait_read();
    if (warp == 0 && qh) { bulk_wait_all(); p_signal(sb, g, tk.b == 0 ? C_QH : C_Q, nsig); }
}
DEVI void post_consumer(const PMaps& mp, uint32_t sb, int g, int warp) {
    const int barid = 1 + g, tid = threadIdx.x, lane = tid & 31;
    const uint32_t stg = sb + PS_STG + g * 16384;
    int nsig = 0;
    PRing r = {0, 0, 0};
    uint32_t pk[64];
    POut out;
    bool pend = false;
#pragma unroll
    for (int i = 0; i < 64; i++) pk[i] = 0u;
    for (int i = 0;; i++) {
        const uint32_t bTF = sb + PB_TF + (i & 1) * 8;
        if (pend) {
            uint32_t now;
            asm volatile("{.reg .pred p, q; mbarrier.test_wait.parity.shared::cta.b64 p, [%1], %2; bar.red.and.pred q, %3, 128, p; selp.u32 %0, 1, 0, q;}"
                         : "=r"(now) : "r"(bTF), "r"((i >> 1) & 1), "r"(barid) : "memory");
            if (__any_sync(0xffffffffu, !now || (lds32(sb + PS_T + (i & 1) * 16) & 255u) > K_A4)) {
#pragma unroll
                for (int c = 0; c < 4; c++) p_store(pk + 16 * c, out, c, stg, warp, lane, barid);
                if (warp == 0 && out.cnt != C_NONE) { bulk_wait_all(); p_signal(sb, g, out.cnt, nsig); }
                pend = false;
            }
        }
        mbar_wait(bTF, (i >> 1) & 1);
        uint4 tw = lds128(sb + PS_T + (i & 1) * 16);
        tw = make_uint4(__shfl_sync(0xffffffffu, tw.x, 0), __shfl_sync(0xffffffffu, tw.y, 0), __shfl_sync(0xffffffffu, tw.z, 0), __shfl_sync(0xffffffffu, tw.w, 0));
        mbar_arrive(sb + PB_TE + (i & 1) * 8);
        const PTask tk = {(int)(tw.x & 255u), (int)tw.y, (int)tw.z, (int)tw.w, 0};
        if (tk.kind == K_END) break;
        if (tk.kind <= K_A4) {
            float d[128];
            const int nk = tk.kind == K_A4 ? HD / 64 : DM / 64;
            p_kblock<256, true>(d, sb, g, r);
            if (pend) p_store(pk, out, 0, stg, warp, lane, barid);
#pragma unroll
            for (int c = 1; c < 4; c++) {
                p_kblock<256, false>(d, sb, g, r);
                if (pend) p_store(pk + 16 * c, out, c, stg, warp, lane, barid);
            }
#pragma unroll 1
            for (int kb = 4; kb < nk; kb++) {
                p_kblock<256, false>(d, sb, g, r);
                if (kb == 6 && pend && warp == 0 && out.cnt != C_NONE) { bulk_wait_all(); p_signal(sb, g, out.cnt, nsig); }
            }
            wg_wait<0>();
            reg_fence<128>(d);
            p_release(sb, r);
#pragma unroll
            for (int j = 0; j < 64; j++) pk[j] = pack_bf16(d[2 * j], d[2 * j + 1]);
            out.map = tk.kind == K_Q ? &mp.cq : (tk.kind == K_B1 ? &mp.cb : &mp.cout);
            out.col = tk.a * 128 + g * 64 + (tk.kind == K_B3 ? DM : 0);
            out.tok = tk.b * 256;
            out.cnt = tk.kind == K_Q ? C_Q + tk.b : (tk.kind == K_B1 ? C_B1 + tk.b : C_NONE);
            out.blocked = tk.kind == K_Q;
            pend = true;
        } else if (tk.kind == K_B2) {
#pragma unroll 2
            for (int j = 0; j < 16; j++) {
                mbar_wait(sb + PB_F + r.st * 8, r.ph);
                const uint32_t a = sb + (g ? r.x(false) : r.w(false));
                battn_warp(a, sb + PB_E + r.st * 8, tk.b * 32, g, j * 2 + (warp >> 1), warp >> 1, warp & 1, lane);
                r.next(2);
            }
            nbar_sync(barid, 128);
            if (warp == 0) p_signal(sb, g, C_B2 + (tk.b >> 2), nsig);
#pragma unroll
            for (int j = 0; j < 64; j++) pk[j] = 0u;
        } else {
            if (tk.kind == K_SN) p_narrow<64>(mp, tk, sb, g, warp, r, nsig); else p_narrow<128>(mp, tk, sb, g, warp, r, nsig);
#pragma unroll
            for (int j = 0; j < 64; j++) pk[j] = 0u;
        }
    }
    if (warp == 0) { bulk_wait_all(); p_signal(sb, g, -1, nsig); }
}
DEVI void post_init(uint32_t sb) {
    for (int i = 0; i < P_STAGES; i++) { mbar_init(sb + PB_F + i * 8, 1); mbar_init(sb + PB_E + i * 8, 8); }
    for (int i = 0; i < 2; i++) { mbar_init(sb + PB_TF + i * 8, 1); mbar_init(sb + PB_TE + i * 8, 256); }
    for (int i = 0; i < 4; i++) mbar_init(sb + PB_S + i * 8, 1);
    fence_mbar_init();
}

constexpr unsigned long long R_TORD_PACK = 0xafe9354d2c81760bull;
__host__ __device__ constexpr int r_tord(int pos) { return (int)((R_TORD_PACK >> (4 * pos)) & 15ull); }
__host__ __device__ constexpr int r_tinv(int T) { for (int p = 0; p < 16; p++) if (r_tord(p) == T) return p; return 0; }
__host__ __device__ constexpr bool r_pos_ss(int pos) { return (0xC0Eu >> r_tord(pos)) & 1u; }
constexpr unsigned long long r_table(bool since) {
    unsigned long long v = 0; int n = 0, d = 7;
    for (int p = 0; p < 16; p++) { n += r_pos_ss(p); d = r_pos_ss(p) ? 0 : (d < 7 ? d + 1 : 7); v |= (unsigned long long)(since ? d : n) << (4 * p); }
    return v;
}
constexpr unsigned long long R_CNT_PACK = r_table(false), R_SINCE_PACK = r_table(true);
__host__ __device__ constexpr int r_ss(int pos) { return pos ? (int)((R_CNT_PACK >> (4 * pos - 4)) & 15ull) : 0; }
__host__ __device__ constexpr int r_rs(int pos) { return pos - r_ss(pos); }
__host__ __device__ constexpr int r_since(int pos) { return (int)((R_SINCE_PACK >> (4 * pos)) & 15ull); }
constexpr int R_NRS = 11, R_NSS = 5;
constexpr int R_G1 = 3, R_G2 = 9, R_G3 = 12;
#define REG_KB 232
constexpr int X_SLOTS = 4;
constexpr int X_NST = 8;

constexpr int RS_WSS  = 0;
constexpr int RS_WO   = RS_WSS + R_NSS * 16384;
constexpr int RS_MEM  = RS_WO + 5 * 16384;
constexpr int RS_O    = RS_MEM + 16384;
constexpr int RS_SX   = RS_O + 2048;
constexpr int RS_BAR  = RS_SX + 2048;
constexpr int RS_TAIL = RS_BAR + 1024;
constexpr int RS_WO5  = RS_TAIL;
constexpr int RS_K    = RS_WO5 + 16384;
constexpr int RS_V    = RS_K + 10240;
constexpr int RS_Q    = RS_V + 10240;
constexpr int RS_QX   = RS_Q + 2048;
constexpr int RS_QEND = RS_QX + 8192;
constexpr int RS_X    = RS_TAIL;
constexpr int X_PITCH = X_SLOTS * 4096;
constexpr int RS_XD   = RS_X + 2 * X_PITCH;
constexpr int RS_WX   = RS_XD + 8192;
constexpr int RS_XE   = RS_WX + 4096;
constexpr int RS_KEND = RS_XE + 2048;
constexpr int RS_EV   = RS_BAR + 256;
constexpr int R_SMEM  = RS_KEND > RS_QEND ? RS_KEND : RS_QEND;
static_assert(R_SMEM <= 232448 && P_SMEM <= R_SMEM, "smem");
static_assert(RS_TAIL % 1024 == 0 && RS_MEM % 1024 == 0, "alignment");

constexpr int RB_G = RS_BAR, RB_K = RS_BAR + 24, RB_V = RS_BAR + 32, RB_KV = RS_BAR + 40, RB_QX = RS_BAR + 48, RB_O = RS_BAR + 56;
constexpr int RB_ATT = RS_BAR + 64, RB_W = RS_BAR + 72, RB_SF = RS_BAR + 80, RB_SE = RB_SF + 40, RB_XF = RB_SE + 40;
constexpr int RB_VX = RB_XF + 48, RB_WO = RB_XF + 56, RB_T = RB_XF + 64, RB_G3 = RB_XF + 72, RS_INV = RB_XF + 16;
static_assert(RB_G3 + 8 <= RS_EV, "barriers");
constexpr uint32_t SB0 = 1024;
__host__ __device__ constexpr uint32_t cdesc(uint32_t off, uint32_t lbo) { return ((SB0 + off) >> 4) | ((lbo >> 4) << 16); }
#define SCHED_FENCE() __syncwarp()
constexpr int NB_BIG = 1, NB_Q = 2, NB_AUX = 3, NB_WO = 4, NB_XS = 5, NB_WG = 6, NB_PAIR = 8, NB_PRO = 12;

DEVI int tid_now() { int t; asm volatile("mov.u32 %0, %%tid.x;" : "=r"(t)); return t; }
DEVI uint32_t a_frag_off(int lane, int warp) { return (uint32_t)((((lane >> 4) * 8 + (lane & 7)) * 128) + (((2 * warp + ((lane >> 3) & 1)) ^ (lane & 7)) * 16)); }
DEVI uint32_t b_frag_off(int lane) { return (uint32_t)((lane & 3) * 64 + (((lane >> 2) * 8) ^ ((lane & 2) * 16))); }
DEVI void lds_b(uint32_t* b, uint32_t a) {
    asm volatile("ld.shared.v2.u32 {%0,%1}, [%2];" : "=r"(b[0]), "=r"(b[1]) : "r"(a) : "memory");
    asm volatile("ld.shared.v2.u32 {%0,%1}, [%2];" : "=r"(b[2]), "=r"(b[3]) : "r"(a + 256) : "memory");
}
DEVI uint32_t clk32() { unsigned long long c; asm volatile("mov.u64 %0, %%clock64;" : "=l"(c)); return (uint32_t)c; }

__host__ __device__ constexpr int x_pair(int j) { return j < 2 || j > 5 ? j : (j == 2 ? 5 : j - 1); }
DEVI void x_load(uint32_t sb, int seg, int j, int g, const CUtensorMap* tmX) {
    const uint32_t bar = sb + RB_XF + g * 8;
    mbar_expect_tx(bar, 4096);
    tma_load_3d(sb + RS_X + g * X_PITCH + (j % X_SLOTS) * 4096, tmX + (j == 3), g * 32, seg * 32, x_pair(j) * 2, bar);
    if (j == 3) tma_load_3d(sb + RS_SX + g * (RS_XE - RS_SX), tmX + 1, g * 32, seg * 32, x_pair(3) * 2 + 1, bar);
}
DEVI void x_refill(uint32_t sb, int seg, int j, int g, int warp, const CUtensorMap* tmX) {
    const int sn = j + X_SLOTS < X_NST ? seg : seg + 1;
    if (warp == (j & 3) && sn < NSEG) {
        if (elect_one()) x_load(sb, sn, (j + X_SLOTS) % X_NST, g, tmX);
    }
}
template <int J, int Q0, int Q1, int DQ>
DEVI void x_steps(float* xa, const uint32_t* w, int g0) {
    const int g = (int)opaque((uint32_t)g0);
    const uint32_t dW0 = cdesc(RS_WSS, 16) + g * 768, dW1 = cdesc(RS_WSS + 8192, 16) - g * 256;
#pragma unroll
    for (int q = Q0; q < Q1; q += DQ) {
        const int pos = r_tinv(2 * x_pair(J) + (q >> 2)), kk = (q >> 1) & 1, mt = q & 1;
        const uint32_t db = (J == 3 && q >= 4 ? cdesc(RS_SX, 16) + g * ((RS_XE - RS_SX) >> 4)
                                                    : cdesc(RS_X + (J % X_SLOTS) * 4096, 16) + g * (X_PITCH >> 4) + (q >> 2) * 128) + kk * 2;
        if (J == 0 && q < 2)   wgmma_n32_rs_first(xa + 16 * mt, &w[((r_rs(pos) * 2 + kk) * 2 + mt) * 4], db);
        else if (J == 0 && q == 3) wgmma_n32_ss(xa + 16, cdesc(RS_WX, 16) + g * 128, db);
        else if (r_pos_ss(pos)) wgmma_n32_ss(xa + 16 * mt, (mt ? dW1 : dW0) + r_ss(pos) * 1024 + kk * 128, db);
        else                   wgmma_n32_rs(xa + 16 * mt, &w[((r_rs(pos) * 2 + kk) * 2 + mt) * 4], db);
    }
}
DEVI void x_first(float* xa, const uint32_t* w, uint32_t sb, int seg, int g0, int warp, const CUtensorMap* tmX) {
    wg_fence();
    x_steps<0, 0, 8, 1>(xa, w, g0); wg_commit();
    x_steps<1, 0, 8, 1>(xa, w, g0); wg_commit();
    x_steps<2, 0, 8, 1>(xa, w, g0); wg_commit();
    x_steps<3, 0, 4, 1>(xa, w, g0); wg_commit();
    const int g = (int)opaque((uint32_t)g0);
    wg_wait<3>(); x_refill(sb, seg, 0, g, warp, tmX);
    wg_wait<2>(); x_refill(sb, seg, 1, g, warp, tmX);
    wg_wait<1>(); x_refill(sb, seg, 2, g, warp, tmX);
    wg_wait<0>(); x_refill(sb, seg, 3, g, warp, tmX);
    reg_fence<32>(xa);
    mbar_wait(sb + RB_XF + g * 8, 1);
}
DEVI void x_second(float* xa, uint32_t* a, uint32_t aA0, const uint32_t* w, uint32_t sb, int seg, int g0, int warp, const CUtensorMap* tmX) {
    wg_fence();
    x_steps<4, 0, 8, 1>(xa, w, g0); wg_commit();
    x_steps<3, 5, 8, 2>(xa, w, g0); x_steps<5, 1, 8, 2>(xa, w, g0); x_steps<6, 1, 8, 2>(xa, w, g0); x_steps<7, 1, 8, 2>(xa, w, g0); wg_commit();
    x_steps<3, 4, 8, 2>(xa, w, g0); x_steps<5, 0, 8, 2>(xa, w, g0); x_steps<6, 0, 8, 2>(xa, w, g0); x_steps<7, 0, 8, 2>(xa, w, g0); wg_commit();
    const int g = (int)opaque((uint32_t)g0);
    wg_wait<2>(); x_refill(sb, seg, 4, g, warp, tmX);
    SCHED_FENCE();
#pragma unroll
    for (int q = 0; q < 4; q++) ldsm4t(a + 4 * q, aA0 + (q & 1) * (8192 - g * 16384) + (q >> 1) * 2048);
    SCHED_FENCE();
    wg_wait<1>();
    reg_fence<16>(xa + 16);
}
DEVI void x_finish(float* xa, uint32_t sb, int g, int warp, int lane) {
    const uint32_t d = sb + RS_XD + (lane >> 4) * 2048 + warp * 256 + (lane & 15) * 16;
#pragma unroll
    for (int i = 0; i < 2; i++) {
        const float* x = xa + 16 + 8 * i;
        sts128(d + (g ^ 1) * 1024 + i * 4096, make_uint4(pack_bf16(x[0], x[1]), pack_bf16(x[2], x[3]), pack_bf16(x[4], x[5]), pack_bf16(x[6], x[7])));
    }
    nbar_sync(NB_PAIR + warp, 64);
    float y[16];
#pragma unroll
    for (int i = 0; i < 2; i++) {
        const uint4 v = lds128(d + g * 1024 + i * 4096);
        const uint32_t u[4] = {v.x, v.y, v.z, v.w};
#pragma unroll
        for (int j = 0; j < 4; j++) { y[8 * i + 2 * j] = __uint_as_float(u[j] << 16); y[8 * i + 2 * j + 1] = __uint_as_float(u[j] & 0xFFFF0000u); }
    }
    reg_fence<16>(y);
    wg_wait<0>();
    reg_fence<16>(xa);
    uint32_t p[8];
#pragma unroll
    for (int j = 0; j < 8; j++) p[j] = pack_bf16(xa[2 * j] + y[2 * j], xa[2 * j + 1] + y[2 * j + 1]);
    __syncwarp();
    stsm4(d + g * 1024, p[0], p[1], p[2], p[3]);
    stsm4(d + g * 1024 + 4096, p[4], p[5], p[6], p[7]);
    nbar_arrive(NB_XS, 256 + 32);
}
DEVI void x_send(uint32_t sb, int seg, uint32_t rank, const CUtensorMap* tmX) {
    auto refill = [&]() {
        if (seg + 1 < NSEG && elect_one()) {
#pragma unroll
            for (int j = 1; j < 4; j++) { x_load(sb, seg + 1, j, 0, tmX); x_load(sb, seg + 1, j, 1, tmX); }
        }
        __syncwarp();
    };
    mbar_wait(sb + RB_ATT, (seg - 1) & 1);
    nbar_sync(NB_XS, 256 + 32);
    if (rank == 2) { refill(); mbar_wait(sb + RB_G3, (seg - 1) & 1); }
    if (elect_one()) {
        fence_proxy_async();
        bulk_copy_s2c(mapa(sb + (rank == 1 ? RS_K : RS_V) + 2048, 0), sb + RS_XD, 8192, mapa(sb + (rank == 1 ? RB_KV : RB_VX), 0));
    }
    __syncwarp();
    if (rank == 1) refill();
}

template <bool XP>
DEVI void mem_pass(float* c0, float* c1, uint32_t* a, const uint32_t* w, uint32_t sb, uint32_t aA0, uint32_t aB, int g, int warp, int s) {
    const uint32_t aA1 = aA0 + 8192 - g * 16384, par = (s - 1) & 1;
    uint32_t b[3][4], e[4];
    float d0[4], d1[4];
    if (XP) ldsm4t(e, aA0 + opaque((RS_WX - RS_WSS) - g * (8192 + 2048)));
#pragma unroll
    for (int q = XP ? 4 : 0; q < 4; q++) ldsm4t(a + 4 * q, ((q & 1) ? aA1 : aA0) + (q >> 1) * 2048);
#pragma unroll
    for (int i = 0; i < 4; i++) { c0[i] = 0.f; c1[i] = 0.f; d0[i] = 0.f; d1[i] = 0.f; }
    EV(EV_BIG0, s, 0);
    mbar_wait(sb + RB_G, par);
    EV(EV_BIG0, s, 1);
    lds_b(b[0], aB + r_tord(0) * 1024);
    lds_b(b[1], aB + r_tord(1) * 1024);
    bool in = false;
#pragma unroll
    for (int pos = 0; pos < 16; pos++) {
        if (pos + 2 < 16) {
            if (pos + 2 == R_G1 && !in) mbar_wait(sb + RB_G + 8, par);
            if (pos + 2 == R_G2 && !in) mbar_wait(sb + RB_G + 16, par);
            if (pos + 2 == R_G3) { if (!in) mbar_wait(sb + RB_G3, par); EV(EV_BIG0, s, 2); }
            lds_b(b[(pos + 2) % 3], aB + r_tord(pos + 2) * 1024);
        }
        if (pos + 3 == R_G1) in = mbar_try(sb + RB_G + 8, par);
        if (pos + 3 == R_G2) in = mbar_try(sb + RB_G + 16, par);
        if (pos + 3 == R_G3) in = mbar_try(sb + RB_G3, par);
        if (XP && pos == 14) in = mbar_try(sb + RB_ATT, par);
        const uint32_t* bb = b[pos % 3];
        const uint32_t* aa = r_pos_ss(pos) ? a : &w[r_rs(pos) * 16];
        mma16816(c1, aa + 4, bb[0], bb[1]);
        mma16816(d1, XP && r_tord(pos) == 0 ? e : aa + 12, bb[2], bb[3]);
        mma16816(c0, aa, bb[0], bb[1]);
        mma16816(d0, aa + 8, bb[2], bb[3]);
        if (r_ss(pos + 1) > 0 && r_ss(pos + 1) < R_NSS) {
            const uint32_t nx = r_ss(pos + 1) * 16384;
            if (r_since(pos) == 0) { ldsm4t(a + 4, aA1 + nx); ldsm4t(a + 12, aA1 + nx + 2048); }
            else if (r_since(pos) < 3) ldsm4t(a + 8 * (r_since(pos) - 1), aA0 + nx + (r_since(pos) - 1) * 2048);
        }
        SCHED_FENCE();
    }
    if (XP && !in) mbar_wait(sb + RB_ATT, par);
#pragma unroll
    for (int i = 0; i < 4; i++) { c1[i] += d1[i]; c0[i] += d0[i]; }
}

DEVI uint32_t k_frag_off(int lane) { return (uint32_t)((((lane >> 3) & 1) * 16 + (lane >> 4) * 8 + (lane & 7)) * 16); }
DEVI uint32_t v_frag_off(int lane) { return (uint32_t)(((lane >> 3) & 1) * 2048 + ((lane >> 4) * 8 + (lane & 7)) * 16); }
DEVI void pv_pair(float (*o)[4], const uint32_t* p, const uint32_t* v) {
#pragma unroll
    for (int n = 0; n < 4; n++) mma16816(o[n], p, v[2 * n], v[2 * n + 1]);
}
DEVI void pv_single(float (*o)[4], const uint32_t* p, const uint32_t* v) {
#pragma unroll
    for (int n = 0; n < 4; n++) mma1688(o[n], p[0], p[1], v[n]);
}
DEVI void s_tile(const uint32_t* qa, const uint32_t* k, float& s0, float& s1) {
    float c[4][4];
#pragma unroll
    for (int q = 0; q < 4; q++) { c[q][0] = c[q][1] = c[q][2] = c[q][3] = 0.f; }
#pragma unroll
    for (int q = 0; q < 4; q++) {
        mma16816(c[2 * (q & 1)], qa + 4 * q, k[4 * q], k[4 * q + 1]);
        mma16816(c[2 * (q & 1) + 1], qa + 4 * q, k[4 * q + 2], k[4 * q + 3]);
    }
    s0 = (c[0][0] + c[1][2]) + (c[2][0] + c[3][2]);
    s1 = (c[0][1] + c[1][3]) + (c[2][1] + c[3][3]);
}
DEVI void mem_scores(uint32_t sb, int s, int lane) {
    const uint32_t ka = sb + RS_K + k_frag_off(lane), sa = sb + RS_SX + 1024 + lane * 8;
    uint32_t qa[16], km[16];
    nbar_sync(NB_Q, 256);
#pragma unroll
    for (int q = 0; q < 4; q++) ldsm4t(qa + 4 * q, sb + RS_Q + q * 512 + lane * 16);
    mbar_wait(sb + RB_K, s & 1);
#pragma unroll
    for (int q = 0; q < 4; q++) ldsm4t(km + 4 * q, ka + q * 512);
    SCHED_FENCE();
    float s0, s1;
    s_tile(qa, km, s0, s1);
    asm volatile("st.shared.v2.f32 [%0], {%1,%2};" :: "r"(sa), "f"(s0 * SCALE_LOG2E), "f"(s1 * SCALE_LOG2E) : "memory");
    nbar_arrive(NB_XS, 128 + 32);
}
DEVI float quad_max(float m) {
    return fmaxf(fmaxf(m, __shfl_xor_sync(0xffffffffu, m, 1)), fmaxf(__shfl_xor_sync(0xffffffffu, m, 2), __shfl_xor_sync(0xffffffffu, m, 3)));
}
DEVI void mem_attn(uint32_t sb, int s, int warp, int lane) {
    const uint32_t va = sb + RS_V + warp * 512, sa = sb + RS_SX + lane * 8;
    [[maybe_unused]] constexpr int g = 0;
    float o[4][4], mx, l = 0.f;
    {
        const uint32_t ka = sb + RS_K + k_frag_off(lane) + (1 + warp) * 2048;
        uint32_t qa[16], kx[16];
        const bool in = mbar_try(sb + RB_KV, s & 1);
        nbar_sync(NB_Q, 256);
        EV(EV_BIG0 && lds32(sb + RS_Q) != 0x12345678u, s, 8);
#pragma unroll
        for (int q = 0; q < 4; q++) ldsm4t(qa + 4 * q, sb + RS_Q + q * 512 + lane * 16);
        if (!in) mbar_wait(sb + RB_KV, s & 1);
#pragma unroll
        for (int q = 0; q < 4; q++) ldsm4t(kx + 4 * q, ka + q * 512);
        const bool vin = mbar_try(sb + RB_VX, s & 1);
        SCHED_FENCE();
        float s0, s1;
        s_tile(qa, kx, s0, s1);
        asm volatile("st.shared.v2.f32 [%0], {%1,%2};" :: "r"(sa + warp * 256), "f"(s0 * SCALE_LOG2E), "f"(s1 * SCALE_LOG2E) : "memory");
        nbar_sync(NB_WG, 128);
        float sc[8];
#pragma unroll
        for (int n = 0; n < 4; n++) { const float2 v = lds64f(sa + n * 256); sc[2 * n] = v.x; sc[2 * n + 1] = v.y; }
        if (!vin) mbar_wait(sb + RB_VX, s & 1);
        mx = quad_max(fmaxf(fmaxf(fmaxf(sc[0], sc[1]), fmaxf(sc[2], sc[3])), fmaxf(fmaxf(sc[4], sc[5]), fmaxf(sc[6], sc[7]))));
        uint32_t vx[16], p[8];
#pragma unroll
        for (int q = 0; q < 4; q++) ldsm4(vx + 4 * q, va + 2048 + (q >> 1) * 4096 + (q & 1) * 256 + v_frag_off(lane));
#pragma unroll
        for (int n = 0; n < 4; n++) {
            const float e0 = ex2(sc[2 * n] - mx), e1 = ex2(sc[2 * n + 1] - mx);
            l += e0 + e1;
            p[2 * n] = pack_bf16(e0, e1); p[2 * n + 1] = __float_as_uint(e0);
        }
#pragma unroll
        for (int n = 0; n < 4; n++) { o[n][0] = o[n][1] = o[n][2] = o[n][3] = 0.f; }
        pv_pair(o, p, vx);
        pv_pair(o, p + 4, vx + 8);
    }
    const uint32_t dst = sb + RS_O + warp * 512 + (lane & 3) * 128 + (lane >> 2) * 16, dl = sb + RS_INV + (lane & 28);
    EV(EV_BIG0, s, 5);
    mbar_wait(sb + RB_V, s & 1);
    uint32_t vm[4], p[2];
    ldsm4(vm, va + lane * 16);
    nbar_sync(NB_XS, 128 + 32);
    EV(EV_BIG0 && lds32(sb + RS_Q) != 0x12345678u, s, 9);
    const float2 sm = lds64f(sa + 1024);
    const float s0 = sm.x, s1 = sm.y;
    const float m = quad_max(fmaxf(mx, fmaxf(s0, s1)));
    const float e0 = ex2(s0 - m), e1 = ex2(s1 - m), f = ex2(mx - m);
    p[0] = pack_bf16(e0, e1); p[1] = __float_as_uint(e0);
#pragma unroll
    for (int n = 0; n < 4; n++) { o[n][0] *= f; o[n][1] *= f; }
    pv_single(o, p, vm);
    l = fmaf(l, f, e0 + e1);
    l = (l + __shfl_xor_sync(0xffffffffu, l, 1)) + (__shfl_xor_sync(0xffffffffu, l, 2) + __shfl_xor_sync(0xffffffffu, l, 3));
    const uint4 u = make_uint4(pack_bf16(o[0][0], o[0][1]), pack_bf16(o[1][0], o[1][1]), pack_bf16(o[2][0], o[2][1]), pack_bf16(o[3][0], o[3][1]));
    st_async128(mapa(dst, 1), u.x, u.y, u.z, u.w, mapa(sb + RB_O, 1));
    st_async128(mapa(dst, 2), u.x, u.y, u.z, u.w, mapa(sb + RB_O, 2));
    st_async32(mapa(dl, 1 + (warp & 1)), __float_as_uint(l), mapa(sb + RB_O, 1 + (warp & 1)));
    sts128(dst, u);
    sts32(dl, __float_as_uint(l));
    __syncwarp();
    if (elect_one()) mbar_arrive(sb + RB_O);
    EV(EV_BIG0, s, 15);
}

DEVI void ta_mask(float* c, int cw, int lane) {
    const int mt = cw >= 3, over = 8 * (cw - 3 * mt - 1) + 2 * (lane & 3) - 16 * mt - (lane >> 2);
    if (over > 0) c[0] = -INFINITY;
    if (over >= 0) c[1] = -INFINITY;
    if (over > 8) c[2] = -INFINITY;
    if (over >= 8) c[3] = -INFINITY;
}
DEVI void ta_scores(uint32_t sb, int seg, int warp, int lane) {
    const int tx = warp == 3 ? 0 : (warp == 2 ? 1 : 4 + 2 * warp), ty = warp == 3 ? 3 : tx + 1;
    const uint32_t qa = sb + RS_QX + ((warp < 2 ? 2 : 0) + ((lane >> 3) & 1)) * 2048 + ((lane >> 4) * 8 + (lane & 7)) * 16;
    const uint32_t ka = sb + RS_K + (warp < 2 ? tx - 3 : tx) * 2048 + lane * 16;
    float x[4] = {0.f, 0.f, 0.f, 0.f}, y[4] = {0.f, 0.f, 0.f, 0.f};
    mbar_wait(sb + RB_QX, seg & 1);
    if (warp < 3) {
#pragma unroll
        for (int j = 0; j < 4; j++) {
            uint32_t a0[4], a1[4], bx[4], by[4];
            ldsm4t(a0, qa + j * 512); ldsm4t(bx, ka + j * 512); ldsm4t(by, ka + 2048 + j * 512); ldsm4t(a1, qa + j * 512 + 256);
            mma16816(x, a0, bx[0], bx[1]); mma16816(y, a0, by[0], by[1]);
            mma16816(x, a1, bx[2], bx[3]); mma16816(y, a1, by[2], by[3]);
        }
        ta_mask(x, tx, lane); ta_mask(y, ty, lane);
    } else {
        mbar_wait(sb + RB_K, seg & 1);
#pragma unroll
        for (int j = 0; j < 4; j++) {
            uint32_t a0[4], a1[4], a2[4], a3[4], b[4];
            ldsm4t(a0, qa + j * 512); ldsm4t(b, ka + j * 512); ldsm4t(a2, qa + 4096 + j * 512);
            ldsm4t(a1, qa + j * 512 + 256); ldsm4t(a3, qa + 4096 + j * 512 + 256);
            mma16816(x, a0, b[0], b[1]); mma16816(y, a2, b[0], b[1]);
            mma16816(x, a1, b[2], b[3]); mma16816(y, a3, b[2], b[3]);
        }
    }
    nbar_sync(NB_WG + 1, 128);
    asm volatile("st.shared.v2.f32 [%0], {%1,%2};" :: "r"(sb + RS_QX + 4096 + tx * 256 + lane * 8), "f"(fmaxf(x[0], x[1])), "f"(fmaxf(x[2], x[3])) : "memory");
    asm volatile("st.shared.v2.f32 [%0], {%1,%2};" :: "r"(sb + RS_QX + 4096 + ty * 256 + lane * 8), "f"(fmaxf(y[0], y[1])), "f"(fmaxf(y[2], y[3])) : "memory");
    nbar_sync(NB_WG + 1, 128);
    float m[4] = {-INFINITY, -INFINITY, -INFINITY, -INFINITY};
#pragma unroll
    for (int n = 0; n < 8; n++) {
        if (n < 3 ? warp >= 2 : warp != 2) {
            const float2 v = lds64f(sb + RS_QX + 4096 + n * 256 + lane * 8);
            m[n < 3 ? 0 : 2] = fmaxf(m[n < 3 ? 0 : 2], v.x); m[n < 3 ? 1 : 3] = fmaxf(m[n < 3 ? 1 : 3], v.y);
        }
    }
#pragma unroll
    for (int o = 1; o < 4; o <<= 1) {
#pragma unroll
        for (int i = 0; i < 4; i++) m[i] = fmaxf(m[i], __shfl_xor_sync(0xffffffffu, m[i], o));
    }
    const float x0 = warp < 2 ? m[2] : m[0], x1 = warp < 2 ? m[3] : m[1], y0 = warp == 2 ? m[0] : m[2], y1 = warp == 2 ? m[1] : m[3];
    auto e = [](float v, float mx) { return ex2((v - mx) * SCALE_LOG2E); };
    sts64(sb + RS_QX + tx * 256 + lane * 8, pack_bf16(e(x[0], x0), e(x[1], x0)), pack_bf16(e(x[2], x1), e(x[3], x1)));
    sts64(sb + RS_QX + ty * 256 + lane * 8, pack_bf16(e(y[0], y0), e(y[1], y0)), pack_bf16(e(y[2], y1), e(y[3], y1)));
}
template <int MT>
DEVI void ta_output(uint32_t sb, int seg, int head, int j, int lane) {
    const uint32_t pa = sb + RS_QX + MT * 768 + lane * 8, vb = sb + RS_V + j * 512;
    uint32_t p[6 + 4 * MT], v[12 + 8 * MT];
#pragma unroll
    for (int n = 0; n < 3 + 2 * MT; n++)
        asm volatile("ld.shared.v2.u32 {%0,%1}, [%2];" : "=r"(p[2 * n]), "=r"(p[2 * n + 1]) : "r"(pa + n * 256) : "memory");
#pragma unroll
    for (int q = 0; q < 2 + 2 * MT; q++) ldsm4(v + 4 * q, vb + (q >> 1) * 4096 + (q & 1) * 256 + v_frag_off(lane));
    ldsm4(v + 8 + 8 * MT, vb + 4096 + MT * 4096 + lane * 16);
    float o[4][4], l[4] = {0.f, 0.f, 0.f, 0.f};
#pragma unroll
    for (int n = 0; n < 4; n++) { o[n][0] = o[n][1] = o[n][2] = o[n][3] = 0.f; }
    mma16816(l, p, 0x3F803F80u, 0x3F803F80u);
    pv_pair(o, p, v);
    if (MT) { mma16816(l, p + 4, 0x3F803F80u, 0x3F803F80u); pv_pair(o, p + 4, v + 8); }
    mma1688(l, p[4 + 4 * MT], p[5 + 4 * MT], 0x3F803F80u);
    pv_single(o, p + 4 + 4 * MT, v + 8 + 8 * MT);
    const float i0 = rcp_fast(l[0]), i1 = rcp_fast(l[2]);
    bf16* dst = g_ox + (uint32_t)((seg * 32 + MT * 16 + (lane >> 2)) * HD + head * DH + j * 32 + (lane & 3) * 8);
    asm volatile("st.global.v4.u32 [%0], {%1,%2,%3,%4};" :: "l"(dst), "r"(pack_bf16(o[0][0] * i0, o[0][1] * i0)), "r"(pack_bf16(o[1][0] * i0, o[1][1] * i0)),
                 "r"(pack_bf16(o[2][0] * i0, o[2][1] * i0)), "r"(pack_bf16(o[3][0] * i0, o[3][1] * i0)) : "memory");
    asm volatile("st.global.v4.u32 [%0], {%1,%2,%3,%4};" :: "l"(dst + 8 * HD), "r"(pack_bf16(o[0][2] * i1, o[0][3] * i1)), "r"(pack_bf16(o[1][2] * i1, o[1][3] * i1)),
                 "r"(pack_bf16(o[2][2] * i1, o[2][3] * i1)), "r"(pack_bf16(o[3][2] * i1, o[3][3] * i1)) : "memory");
}

template <bool XP>
DEVI void big_main(const uint32_t* w, const uint32_t sb, const int g, const int warp, const uint32_t rank, const int head,
                   const CUtensorMap* tmX, const bf16* xg, const unsigned E) {
    float xa[32];
    uint32_t a[16];
    const uint32_t aB = __shfl_sync(0xffffffffu, sb + RS_MEM + (g * 32 + (tid_now() & 31)) * 16, tid_now() & 31);
#define lane0 ((int)(opaque(aB) >> 4) & 31)
    const uint32_t aA0 = sb + RS_WSS + g * (8192 + 4096) + a_frag_off(lane0, warp);
    const uint32_t aBf = sb + RS_MEM + g * 512 + b_frag_off(lane0);
    if constexpr (XP) {
        mbar_wait(sb + RB_XF + g * 8, 0);
        x_first(xa, w, sb, 0, g, warp, tmX);
        x_second(xa, a, aA0, w, sb, 0, g, warp, tmX);
        x_finish(xa, sb, g, warp, lane0);
    }
    nbar_sync(NB_BIG, 256);
    for (int s = 0; s < NSEG; s++) {
        float c0[4], c1[4];
        mem_pass<XP>(c0, c1, a, w, sb, aA0, aBf, g, warp, s);
        EV(EV_BIG0 && c0[0] != 1.2345e30f, s, 3);
        bool xin = true;
        const uint32_t xs = sb + RS_O + warp * 256 + lane0 * 8;
        sts64(xs + g * 1024, pack_bf16(c1[0], c1[1]), pack_bf16(c1[2], c1[3]));
        {
            const uint32_t d = sb + (XP ? (rank == 1 ? RS_K : RS_V) : RS_Q) + (g * 4 + warp) * 256 + lane0 * 4;
            const uint32_t rbar = XP ? mapa(sb + (rank == 1 ? RB_K : RB_V), 0) : 0u;
            nbar_sync(NB_PAIR + warp, 64);
            const float2 v = lds64f(xs + (g ^ 1) * 1024);
            if (XP) xin = mbar_test(sb + RB_XF + g * 8, 0);
            const uint32_t v0 = __float_as_uint(v.x), v1 = __float_as_uint(v.y);
            const uint32_t p0 = pack_bf16(c0[0] + __uint_as_float(v0 << 16), c0[1] + __uint_as_float(v0 & 0xFFFF0000u));
            const uint32_t p1 = pack_bf16(c0[2] + __uint_as_float(v1 << 16), c0[3] + __uint_as_float(v1 & 0xFFFF0000u));
            if constexpr (XP) { st_async32(mapa(d, 0), p0, rbar); st_async32(mapa(d + 128, 0), p1, rbar); }
            else { sts32(d, p0); sts32(d + 128, p1); }
            EV(EV_BIG0, s, 4);
        }
        if constexpr (XP) {
            if (s == NSEG - 1) break;
            if (!xin) mbar_wait(sb + RB_XF + g * 8, 0);
            x_first(xa, w, sb, s + 1, g, warp, tmX);
            EV(EV_BIG0, s, 5);
            EVCAL(s);
            nbar_sync(NB_WO, 384);
            EV(EV_BIG0 && lds32(sb + RS_O) != 0x12345678u, s, 6);
            x_second(xa, a, aA0, w, sb, s + 1, g, warp, tmX);
            EV(EV_BIG0, s, 7);
            x_finish(xa, sb, g, warp, lane0);
        } else {
            if (g == 0) {
                if (s < NSEG - 1) mem_attn(sb, s, warp, lane0);
            } else {
                if (s < NSEG - 1) { if (warp == 3) mem_scores(sb, s, lane0); else nbar_arrive(NB_Q, 256); }
                mbar_wait(sb + RB_KV, s & 1);
                if (s == 0 && warp == 0) {
                    wait_count_warp(&g_cnt[C_QH], 64 * E);
                    if (elect_one()) {
                        fence_proxy_global();
                        mbar_expect_tx(sb + RB_QX, 8192);
                        bulk_load(sb + RS_QX, g_qx + (uint32_t)(head * 4096), 8192, sb + RB_QX);
                    }
                    __syncwarp();
                }
                ta_scores(sb, s, warp, lane0);
            }
            EVCAL(s);
            mbar_wait(sb + RB_V, s & 1);
            mbar_wait(sb + RB_VX, s & 1);
            if (s < NSEG - 1) nbar_sync(NB_WO, 384); else nbar_sync(NB_BIG, 256);
            EV(EV_BIG0 && lds32(sb + RS_O) != 0x12345678u, s, 6);
            if (g == 0) ta_output<0>(sb, s, head, warp, lane0); else ta_output<1>(sb, s, head, warp, lane0);
            nbar_sync(NB_BIG, 256);
            EV(EV_BIG0 && lds32(sb + RS_O) != 0x12345678u, s, 7);
            if (g == 0 && warp == 0 && s + 1 < NSEG) {
                if (elect_one()) {
                    mbar_arrive_remote(mapa(sb + RB_ATT, 1));
                    mbar_arrive_remote(mapa(sb + RB_ATT, 2));
                    mbar_expect_tx(sb + RB_KV, 8192);
                    mbar_expect_tx(sb + RB_K, 2048);
                    mbar_expect_tx(sb + RB_V, 2048); mbar_expect_tx(sb + RB_VX, 8192);
                    mbar_arrive(sb + RB_T);
                }
                __syncwarp();
            }
        }
    }
    if constexpr (!XP) { if (tid_now() == 0) signal_count(&g_prog[(NSEG - 1) >> 1]); }
#undef lane0
}

template <int T, int K0, int K1>
DEVI void wo_part(float* acc) {
    constexpr uint32_t dWo = cdesc(T < 5 ? RS_WO + T * 16384 : RS_WO5, 16), dO = cdesc(RS_O, 128);
#pragma unroll
    for (int kk = K0; kk < K1; kk++) {
        if (kk == 0) { if (T < 3) wgmma_n8_ss_first<0>(acc, dWo, dO); else wgmma_n8_ss<0, 0>(acc, dWo, dO); }
        else wgmma_n8_ss<0, 1>(acc, dWo + kk * 128, dO + kk * 16);
    }
    wg_commit();
}
DEVI void red3(uint8_t* p, uint32_t a, uint32_t b, uint32_t c, uint32_t one) {
    asm volatile("red.relaxed.gpu.global.add.noftz.v4.bf16x2 [%0], {%1,%2,%3,%4};" :: "l"(p), "r"(a), "r"(b), "r"(c), "r"(one) : "memory");
}
constexpr int ACC_CH = 3 * 16 * 1024;
template <bool Q>
DEVI void wo_phase(uint32_t sb, int s, int warp, uint8_t* p, uint32_t ainv, int gap) {
    float a0[4], a1[4], a2[4];
    fence_proxy_async();
    const float2 iv = lds64f(ainv);
    SCHED_FENCE();
    const float i0 = rcp_fast(iv.x), i1 = rcp_fast(iv.y);
#define WORD(a, h) pack_bf16(a[2 * h] * i0, a[2 * h + 1] * i1)
    wg_fence();
    wo_part<0, 0, 8>(a0); wo_part<1, 0, 8>(a1); wo_part<2, 0, 8>(a2);
    wg_wait<1>(); reg_fence<4>(a0); reg_fence<4>(a1);
    red3(p, WORD(a0, 0), WORD(a0, 1), WORD(a1, 0), 0x3F80u);
    SCHED_FENCE();
    EV(warp == 0 && elect_one(), s, 11);
    wg_wait<0>(); reg_fence<4>(a2);
    red3(p + ACC_CH, WORD(a2, 0), WORD(a2, 1), WORD(a1, 1), 0x3F80u);
    SCHED_FENCE();
    { const uint32_t t = clk32() + gap; while ((int)(clk32() - t) < 0) { } }
    wg_fence();
    wo_part<3, 0, 8>(a0); wo_part<4, 0, 8>(a1);
    if (Q) {
        wo_part<5, 0, 8>(a2);
        wg_wait<1>(); reg_fence<4>(a0); reg_fence<4>(a1);
        red3(p + 2 * ACC_CH, WORD(a0, 0), WORD(a0, 1), WORD(a1, 0), 0x3F80u);
        SCHED_FENCE();
        wg_wait<0>(); reg_fence<4>(a2);
        red3(p + 3 * ACC_CH, WORD(a2, 0), WORD(a2, 1), WORD(a1, 1), 0x3F80u);
        nbar_arrive(NB_WO, 384);
    } else {
        wg_wait<1>();
        nbar_arrive(NB_WO, 384);
        wg_wait<0>(); reg_fence<4>(a0); reg_fence<4>(a1);
        red3(p + 2 * ACC_CH, WORD(a0, 0), WORD(a0, 1), WORD(a1, 0), 0x3F80u);
        red3(p + 3 * ACC_CH, 0u, 0u, WORD(a1, 1), 0x3F80u);
    }
#undef WORD
}
DEVI void unit_pack(uint32_t* u, uint32_t x0, uint32_t x1, uint32_t x2, uint32_t x3) {
    u[0] = __byte_perm(x0, x1, 0x5410); u[1] = __byte_perm(x2, x3, 0x5410); u[2] = __byte_perm(x0, x1, 0x7632); u[3] = __byte_perm(x2, x3, 0x7632);
}
DEVI void unit_send(uint32_t d, const uint32_t* u, uint32_t bar, uint32_t r1, uint32_t r2) {
    st_async128(mapa(d, r1), u[0], u[1], u[2], u[3], mapa(bar, r1));
    st_async128(mapa(d, r2), u[0], u[1], u[2], u[3], mapa(bar, r2));
}
template <bool Q>
DEVI void stage_sums(uint32_t sb, int s, uint32_t rank, int warp, const uint8_t* src, uint32_t l, uint32_t gate) {
    uint4 v[4];
    while ((int)(clk32() - gate) < 0) { }
    EV(elect_one(), s, 16 + warp);
#pragma unroll
    for (int j = 0; j < 4; j++) v[j] = ld_rlx4(src + j * 1024);
    const uint32_t col = sb + RS_MEM + ((Q ? 0 : (rank == 1 ? 6 : 11)) + 3 * (warp >> 1)) * 1024 + ((l >> 2) & 0x300) + (l & 0x70);
    const uint32_t d0 = col + (warp & 1) * 2048, d1 = d0 ^ 160, d2 = (col ^ ((warp & 1) * 160)) + 1024;
    const uint32_t r1 = Q ? 1 : 0, r2 = Q ? 2 : 3 - rank, bar = sb + (warp < 2 ? RB_G + 8 * warp : (Q ? RB_G + 16 : RB_G3));
    int n = 0;
    while (!__all_sync(0xffffffffu, v[0].w == 0x4200u && v[1].w == 0x4200u && v[2].w == 0x4200u && v[3].w == 0x4200u)) {
#pragma unroll
        for (int j = 0; j < 4; j++) v[j] = ld_rlx4(src + j * 1024);
        if (++n > SPIN_LIMIT) __trap();
    }
    EV(elect_one(), s, 24 + warp);
    uint32_t u[12];
    unit_pack(u + 8, v[0].z, v[1].z, v[2].z, v[3].z);
    unit_send(d2, u + 8, bar, r1, r2);
    if (Q || warp < 3) {
        unit_pack(u, v[0].x, v[1].x, v[2].x, v[3].x);
        unit_pack(u + 4, v[0].y, v[1].y, v[2].y, v[3].y);
        unit_send(d0, u, bar, r1, r2);
        unit_send(d1, u + 4, bar, r1, r2);
        sts128(d0, make_uint4(u[0], u[1], u[2], u[3]));
        sts128(d1, make_uint4(u[4], u[5], u[6], u[7]));
    }
    sts128(d2, make_uint4(u[8], u[9], u[10], u[11]));
    __syncwarp();
    if (elect_one()) {
        mbar_expect_tx(bar, warp < 2 ? 3072u : (Q ? 0u : 1024u));
        if (warp == 0) mbar_expect_tx(sb + (Q ? RB_G3 : RB_G + 16), Q ? 4096u : 3072u);
    }
    EV(elect_one(), s, 20 + warp);
}
DEVI void wo_permute(uint32_t tile, int t) {
    const uint32_t a = tile + t * 32 + ((t >> 2) & 1) * 16;
#pragma unroll
    for (int h = 0; h < 2; h++) {
        uint4 v[3], u[3];
#pragma unroll
        for (int i = 0; i < 3; i++) if (3 * h + i < 5 || t < 32) { v[i] = lds128(a + (3 * h + i) * 3072); u[i] = lds128((a ^ 16) + (3 * h + i) * 3072); }
#pragma unroll
        for (int i = 0; i < 3; i++) if (3 * h + i < 5 || t < 32) {
            sts128(a + (3 * h + i) * 3072, make_uint4(__byte_perm(v[i].x, v[i].y, 0x5410), __byte_perm(v[i].x, v[i].y, 0x7632),
                                                      __byte_perm(u[i].x, u[i].y, 0x5410), __byte_perm(u[i].x, u[i].y, 0x7632)));
            sts128((a ^ 16) + (3 * h + i) * 3072, make_uint4(__byte_perm(v[i].z, v[i].w, 0x5410), __byte_perm(v[i].z, v[i].w, 0x7632),
                                                             __byte_perm(u[i].z, u[i].w, 0x5410), __byte_perm(u[i].z, u[i].w, 0x7632)));
        }
    }
}
DEVI uint32_t acc_clear(int slot, int idx, uint32_t lo) {
    uint8_t* p = g_acc + (uint32_t)(slot * 128 + idx * 3072 + (lo < 3072 ? lo : lo - 1024));
    st_rlx4(p, 0u, 0u, 0u, 0u);
    uint32_t z; asm volatile("ld.relaxed.gpu.global.u32 %0, [%1];" : "=r"(z) : "l"(p) : "memory");
    return z;
}

template <bool Q>
DEVI void aux_main(uint32_t sb, int warp, uint32_t rank, int head, const CUtensorMap* tmX, const bf16* xg, unsigned E, const int delay, const int gap) {
    const uint32_t lo = __shfl_sync(0xffffffffu, ((tid_now() >> 3) & 3) * 1024 + (tid_now() & 7) * 16, tid_now() & 31);
    for (int s = 0; s < NSEG - 1; s++) {
        if (!Q && warp == 0 && elect_one()) mbar_expect_tx(sb + RB_O, 2048 + 256);
        __syncwarp();
        const uint32_t slot = (s & 3) * 128;
        mbar_wait(sb + RB_O, s & 1);
        EV(warp == 0 && elect_one(), s, 10);
        wo_phase<Q>(sb, s, warp, g_acc + (uint32_t)(slot + (rank * 4 + warp) * 4096 + opaque(lo)), sb + RS_INV + ((opaque(lo) >> 1) & 24), gap);
        SCHED_FENCE();
        const uint32_t t_o = clk32();
        EV(warp == 0 && elect_one(), s, 12);
        {
            const uint32_t l = opaque(lo);
            stage_sums<Q>(sb, s, rank, warp, g_acc + (uint32_t)(slot + rank * 16384 + warp * ACC_CH + (l & 0xC00) * 4 + (l & 0x70)), l, t_o + delay);
        }
        EV(warp == 2 && elect_one(), s, 14);
        if (warp == (Q ? 3 : 1)) {
            if (Q) {
                mbar_wait(sb + RB_T, s & 1);
                if (s == 3) wait_count_warp(&g_cnt[C_Q], 64 * E);
                if (elect_one()) {
                    if (s == 3) fence_proxy_global();
                    fence_proxy_async();
                    mbar_expect_tx(sb + RB_QX, 8192);
                    bulk_load(sb + RS_QX, g_qx + (uint32_t)(((s + 1) * NH + head) * 4096), 8192, sb + RB_QX);
                    if (head == 0) { TLOG(1400 + s, 0, gtime()); TLOG(1400 + s, 1, clock64()); }
                }
                __syncwarp();
                const bool fresh = (s & 7) == 6 && s + 2 < NSEG;
                if (fresh) wait_count_warp(&g_cnt[C_Q + ((s + 2) >> 3)], 64 * E);
                if (elect_one()) {
                    if (fresh) fence_proxy_global();
                    if (s + 2 < NSEG && s != 2) l2_prefetch(g_qx + (uint32_t)(((s + 2) * NH + head) * 4096), 8192);
                    if (s + 4 < NSEG) l2_prefetch(xg + (uint32_t)(((s + 4) * 32 + head) * DM), 2048);
                    signal_count(&g_prog[s >> 1]);
                }
                __syncwarp();
            } else {
                const uint32_t zero = acc_clear((s + 2) & 3, 2 * head + (int)rank - 1, opaque(lo));
                x_send(sb, s + 1, rank, tmX);
                if (__any_sync(0xffffffffu, zero != 0u)) __trap();
            }
        }
    }
}

DEVI void load_weights(uint32_t sb, const CUtensorMap* tmW, const CUtensorMap* tmWo, int head, uint32_t rank, int2 t0) {
    const uint32_t c0 = clk32();
    if (rank == 0) while ((int)(clk32() - c0) < t0.x) { }
    const uint32_t bW = sb + RB_W, bSF = sb + RB_SF, bSE = sb + RB_SE;
    const int tile0 = rank == 0 ? 0 : (rank == 1 ? 6 : 11);
    mbar_expect_tx(bW, R_NSS * 16384);
    for (int pass = 0; pass < 2; pass++) {
        for (int pos = 0; pos < 16; pos++) {
            const int k = (int)((R_TORD_PACK >> (4 * pos)) & 15ull) * 64, rd = r_rs(pos), slot = rd % 5;
            if (r_pos_ss(pos)) {
                if (pass) continue;
                const uint32_t dst = sb + RS_WSS + r_ss(pos) * 16384;
                tma_load_2d(dst, tmW, head * DH, k, bW);
                tma_load_2d(dst + 8192, tmW, head * DH + 64, k, bW);
            } else if (pass == (rd >= 5)) {
                if (rd >= 5) mbar_wait(bSE + 8 * slot, ((rd / 5) - 1) & 1);
                mbar_expect_tx(bSF + 8 * slot, 16384);
                const uint32_t dst = sb + RS_WO + slot * 16384;
                tma_load_2d(dst, tmW, head * DH, k, bSF + 8 * slot);
                tma_load_2d(dst + 8192, tmW, head * DH + 64, k, bSF + 8 * slot);
            }
        }
    }
    while ((int)(clk32() - c0) < t0.y) { }
    if (rank == 0) { mbar_expect_tx(sb + RB_WO, 16384); tma_load_wo(sb + RS_WO5, tmWo, 5 * 64, head * 4, sb + RB_WO); }
    for (int i = 1; i <= 5; i++) {
        const int slot = i % 5, last = slot + 10 < R_NRS ? slot + 10 : slot + 5;
        mbar_wait(bSE + 8 * slot, (last / 5) & 1);
        mbar_expect_tx(bSF + 8 * slot, 16384);
        tma_load_wo(sb + RS_WO + slot * 16384, tmWo, (tile0 + slot) * 64, head * 4, bSF + 8 * slot);
    }
}
template <bool XP>
DEVI void big_prologue(uint32_t* w, uint32_t sb, int g, int warp, const bf16* __restrict__ mem0) {
    const int tid = tid_now(), lane = tid & 31;
    {
        const uint32_t* m = (const uint32_t*)(mem0 + (lane >> 2) * DM + (tid >> 5) * 16) + (lane & 3);
        uint32_t u[16];
#pragma unroll
        for (int j = 0; j < 8; j++) { u[2 * j] = m[j * 64]; u[2 * j + 1] = m[j * 64 + 4]; }
#pragma unroll
        for (int j = 0; j < 8; j++) sts64(sb + RS_MEM + ((tid >> 5) + j * 8) * 256 + b_frag_off(lane), u[2 * j], u[2 * j + 1]);
    }
    const uint32_t a0 = sb + RS_WO + g * (8192 + 4096) + a_frag_off(lane, warp), a1 = a0 + 8192 - g * 16384;
#pragma unroll
    for (int rd = 0; rd < R_NRS; rd++) {
        const int slot = rd % 5;
        mbar_wait(sb + RB_SF + 8 * slot, (rd / 5) & 1);
#pragma unroll
        for (int q = 0; q < 4; q++) {
            if (XP && rd == 0 && q == 3) {
                sts128(sb + RS_WX + g * 2048 + (tid & 127) * 16, lds128(sb + RS_WO + 8192 - g * 4096 + 2048 + (tid & 127) * 16));
                fence_proxy_async();
                nbar_sync(NB_WG + g, 128);
            } else ldsm4t(&w[rd * 16 + q * 4], ((q & 1) ? a1 : a0) + slot * 16384 + (q >> 1) * 2048);
        }
        mbar_arrive(sb + RB_SE + 8 * slot);
    }
    mbar_wait(sb + RB_W, 0);
    if (tid == 0) TLOG(1500 + blockIdx.x, 2, gtime());
}

#define REC_END() do { if (tid_now() == 0) TLOG(1024 + blockIdx.x, 1, gtime()); } while (0)
struct XMaps { CUtensorMap m[2]; };
__global__ void __launch_bounds__(384, 1)
k_rec(const __grid_constant__ PMaps mp, const __grid_constant__ CUtensorMap tmWk, const __grid_constant__ CUtensorMap tmWv,
      const __grid_constant__ CUtensorMap tmWo, const __grid_constant__ XMaps xm, const bf16* __restrict__ mem0, const bf16* __restrict__ xg,
      int4 tq, int4 tk, int2 t0, int rec) {
    extern __shared__ __align__(1024) uint8_t smem_raw[];
    const uint32_t sb = smem_u32(smem_raw);
    if ((sb & 0x3FFFFu) != SB0) __trap();
    const int tid = threadIdx.x;
    const int wg = __shfl_sync(0xffffffffu, tid >> 7, 0), warp = __shfl_sync(0xffffffffu, (tid >> 5) & 3, 0);
    uint32_t rank; asm("mov.u32 %0, %%cluster_ctarank;" : "=r"(rank));
    int head; asm("mov.u32 %0, %%clusterid.x;" : "=r"(head));
    asm volatile("griddepcontrol.launch_dependents;");
    if (tid == 0 && rec) {
        mbar_init(sb + RB_G, 1);
        mbar_init(sb + RB_G + 8, 1);
        mbar_init(sb + RB_G + 16, rank == 0 ? 2 : 1);
        mbar_init(sb + RB_G3, rank == 0 ? 1 : 2);
        mbar_init(sb + RB_T, 1); mbar_init(sb + RB_VX, 1); mbar_init(sb + RB_WO, 1);
        mbar_init(sb + RB_K, 1); mbar_init(sb + RB_V, 1); mbar_init(sb + RB_KV, 1); mbar_init(sb + RB_QX, 1);
        mbar_init(sb + RB_O, rank == 0 ? 4 : 1); mbar_init(sb + RB_ATT, 1); mbar_init(sb + RB_W, 1);
        for (int i = 0; i < 5; i++) { mbar_init(sb + RB_SF + 8 * i, 1); mbar_init(sb + RB_SE + 8 * i, 256); }
        for (int i = 0; i < 2; i++) mbar_init(sb + RB_XF + 8 * i, X_SLOTS);
        fence_mbar_init();
        if (rank == 0) { mbar_expect_tx(sb + RB_KV, 8192); mbar_expect_tx(sb + RB_K, 2048); mbar_expect_tx(sb + RB_V, 2048); mbar_expect_tx(sb + RB_VX, 8192); }
    }
    __syncthreads();
    asm volatile("barrier.cluster.arrive.release.aligned;" ::: "memory");

    if (wg < 2) {
        reg_inc<REG_KB>();
        if (rank != 0) {
            uint32_t w[R_NRS * 16];
            if ((tid & 127) == 0) for (int j = 0; j < X_SLOTS; j++) x_load(sb, 0, j, wg, xm.m);
            __syncwarp();
            cluster_wait();
            big_prologue<true>(w, sb, wg, warp, mem0);
            big_main<true>(w, sb, wg, warp, rank, head, xm.m, xg, 0u);
            REC_END();
        } else if (rec) {
            uint32_t w[R_NRS * 16];
            cluster_wait();
            big_prologue<false>(w, sb, wg, warp, mem0);
            big_main<false>(w, sb, wg, warp, rank, head, xm.m, xg, *(volatile unsigned*)&g_epoch + 1);
            REC_END();
        } else cluster_wait();
        if (rank == 0 && rec) nbar_arrive(NB_PRO, 256 + 32);
        nbar_sync(0, 384);
        post_consumer(mp, sb, wg, warp);
    } else {
        reg_dec<504 - 2 * REG_KB>();
        if (rec) {
            if (tid == 256) {
                if (rank == 0) l2_prefetch(xg + (uint32_t)(head * 8 * DM), 16384);
                load_weights(sb, rank == 0 ? &mp.wq : (rank == 1 ? &tmWk : &tmWv), &tmWo, head, rank, t0);
            }
            if (warp == 3 && rank != 0) {
                const uint32_t lo = ((tid >> 3) & 3) * 1024 + (tid & 7) * 16;
                acc_clear(0, 2 * head + (int)rank - 1, lo); acc_clear(1, 2 * head + (int)rank - 1, lo);
                __threadfence();
                __syncwarp();
                if (tid == 256 + 96) atomicAdd(&g_zero, 1u);
            }
            __syncwarp();
        }
        cluster_wait();
        const unsigned E = __shfl_sync(0xffffffffu, *(volatile unsigned*)&g_epoch + 1, 0);
        if (rec) {
            if (warp == 1) wait_count_warp(&g_zero, E * 64u);
            if (warp == 3) { if (rank != 0) x_send(sb, 0, rank, xm.m); }
            else {
                nbar_sync(NB_PRO, 96);
#pragma unroll 1
                for (int i = rank == 0 ? 0 : 1; i <= 5; i++) {
                    mbar_wait(sb + (i == 0 ? RB_WO : RB_SF + 8 * (i % 5)), i == 5);
                    if (i == 5 && tid == 288) TLOG(1500 + blockIdx.x, 0, gtime());
                    wo_permute(sb + (i == 0 ? RS_WO5 : RS_WO + (i % 5) * 16384), tid & 127);
                }
            }
            fence_proxy_async();
            nbar_sync(NB_AUX, 128);
            if (tid == 288) { TLOG(1500 + blockIdx.x, 1, gtime()); }
            if (rank == 0) aux_main<true>(sb, warp, rank, head, xm.m, xg, E, warp == 0 ? tq.x : (warp == 1 ? tq.y : tq.z), tq.w);
            else           aux_main<false>(sb, warp, rank, head, xm.m, xg, E, warp == 0 ? tk.x : (warp == 1 ? tk.y : tk.z), tk.w);
        }
        const int t = tid_now();
        if (t >= 320 && t < 320 + 13) asm volatile("prefetch.tensormap [%0];" :: "l"(&mp.wq + (t - 320)) : "memory");
        __syncwarp();
        if (warp == 0) post_producer(mp, sb, E, rank != 0 || !rec);
        else {
            if (warp == 1) {
                if (rank == 0 && rec) nbar_sync(NB_PRO, 256 + 32);
                if (elect_one()) post_init(sb);
                __syncwarp();
            }
            nbar_sync(0, 384);
            if (t == 288 || t == 320) post_helper(sb, warp - 1);
        }
    }
    __syncthreads();
    asm volatile("griddepcontrol.wait;" ::: "memory");
}

typedef CUresult (*EncodeFn)(CUtensorMap*, CUtensorMapDataType, cuuint32_t, void*, const cuuint64_t*, const cuuint64_t*,
                             const cuuint32_t*, const cuuint32_t*, CUtensorMapInterleave, CUtensorMapSwizzle,
                             CUtensorMapL2promotion, CUtensorMapFloatOOBfill);

static CUtensorMap make_map(EncodeFn fn, const void* ptr, uint64_t inner, uint64_t outer, uint32_t box_inner, uint32_t box_outer) {
    CUtensorMap m;
    cuuint64_t dims[2] = {inner, outer};
    cuuint64_t strides[1] = {inner * 2};
    cuuint32_t box[2] = {box_inner, box_outer};
    cuuint32_t es[2] = {1, 1};
    fn(&m, CU_TENSOR_MAP_DATA_TYPE_BFLOAT16, 2, const_cast<void*>(ptr), dims, strides, box, es,
       CU_TENSOR_MAP_INTERLEAVE_NONE, CU_TENSOR_MAP_SWIZZLE_128B, CU_TENSOR_MAP_L2_PROMOTION_L2_256B, CU_TENSOR_MAP_FLOAT_OOB_FILL_NONE);
    return m;
}

static CUtensorMap make_wo_map(EncodeFn fn, const void* ptr, uint64_t rows, uint32_t ngrp) {
    CUtensorMap m;
    cuuint64_t dims[5] = {DM, 2, 4, 4, rows / 32};
    cuuint64_t strides[4] = {DM * 2, 8 * DM * 2, 2 * DM * 2, 32 * DM * 2};
    cuuint32_t box[5] = {64, 2, 4, 4, ngrp};
    cuuint32_t es[5] = {1, 1, 1, 1, 1};
    fn(&m, CU_TENSOR_MAP_DATA_TYPE_BFLOAT16, 5, const_cast<void*>(ptr), dims, strides, box, es,
       CU_TENSOR_MAP_INTERLEAVE_NONE, CU_TENSOR_MAP_SWIZZLE_128B, CU_TENSOR_MAP_L2_PROMOTION_L2_256B, CU_TENSOR_MAP_FLOAT_OOB_FILL_NONE);
    return m;
}

struct Maps {
    PMaps post;
    CUtensorMap wk16, wv16, wo128;
    XMaps x32;
};

extern "C" void kernel_launch(void* const* d_in, const int* in_sizes, int n_in, void* d_out, int out_size) {
    const bf16* A_x   = (const bf16*)d_in[0];
    const bf16* A_mem = (const bf16*)d_in[1];
    const bf16* A_Wq  = (const bf16*)d_in[2];
    const bf16* A_Wk  = (const bf16*)d_in[3];
    const bf16* A_Wv  = (const bf16*)d_in[4];
    const bf16* A_Wo  = (const bf16*)d_in[5];
    const bf16* B_x   = (const bf16*)d_in[7];
    const bf16* B_w   = (const bf16*)d_in[8];
    const bf16* B_wo  = (const bf16*)d_in[9];

    static EncodeFn fn = nullptr;
    static Maps mp;
    static const void* cached[10];
    const void* cur[10] = {A_x, A_mem, A_Wq, A_Wk, A_Wv, A_Wo, B_x, B_w, B_wo, d_out};
    bool same = fn != nullptr;
    for (int i = 0; i < 10 && same; i++) same = cached[i] == cur[i];
    if (!same) {
        if (!fn) {
            void* p = nullptr; cudaDriverEntryPointQueryResult qr;
            cudaGetDriverEntryPoint("cuTensorMapEncodeTiled", &p, cudaEnableDefault, &qr);
            fn = (EncodeFn)p;
            cudaFuncSetAttribute(k_rec, cudaFuncAttributeMaxDynamicSharedMemorySize, R_SMEM);
        }
        void *p_ox, *p_bqkv, *p_bo, *p_qx;
        cudaGetSymbolAddress(&p_qx, g_qx);
        cudaGetSymbolAddress(&p_ox, g_ox); cudaGetSymbolAddress(&p_bqkv, g_bqkv); cudaGetSymbolAddress(&p_bo, g_bo);
        mp.post.wq   = make_map(fn, A_Wq, HD, DM, 64, 64);
        mp.post.wo   = make_wo_map(fn, A_Wo, HD, 2);
        mp.post.bw   = make_map(fn, B_w, 3 * DM, DM, 64, 64);
        mp.post.bwo  = make_wo_map(fn, B_wo, DM, 2);
        mp.post.x    = make_map(fn, A_x, DM, S_TOK, 64, 128);
        mp.post.bx   = make_map(fn, B_x, DM, S_TOK, 64, 128);
        mp.post.bo   = make_map(fn, p_bo, DM, S_TOK, 64, 128);
        mp.post.ox   = make_map(fn, p_ox, HD, S_TOK, 64, 128);
        mp.post.ox64 = make_map(fn, p_ox, HD, S_TOK, 64, 64);
        mp.post.cb   = make_map(fn, p_bqkv, 3 * DM, S_TOK, 64, 64);
        mp.post.cout = make_map(fn, d_out, 2 * DM, S_TOK, 64, 64);
        {
            cuuint64_t dims[4] = {256, 4, NH * 4, NSEG};
            cuuint64_t strides[3] = {512, 2048, NH * 8192};
            cuuint32_t box[4] = {256, 2, 4, 2};
            cuuint32_t es[4] = {1, 1, 1, 1};
            fn(&mp.post.cq, CU_TENSOR_MAP_DATA_TYPE_BFLOAT16, 4, p_qx, dims, strides, box, es,
               CU_TENSOR_MAP_INTERLEAVE_NONE, CU_TENSOR_MAP_SWIZZLE_NONE, CU_TENSOR_MAP_L2_PROMOTION_NONE, CU_TENSOR_MAP_FLOAT_OOB_FILL_NONE);
        }
        {
            int runs[48] = {K_QH, 0, 2, K_Q, 1, 7, K_B1, 0, 8, K_A4, 0, 4, K_B2, 0, 32, K_A4, 4, 2, K_B3, 0, 4, K_A3, 12, 2, K_B3, 4, 4,
                            K_SK, 14, 1, K_SN, 30, 2, -1};
            int nlate = 9;
            const int per[9] = {32, 24, 8, 8, 32, 8, 8 * P_SPLIT, 1, 8 * P_SPLIT};
            int n = 0, id = 0;
            for (; runs[3 * n] >= 0; n++) {
                mp.post.list.run[n] = make_int4(runs[3 * n], runs[3 * n + 1], id, id + runs[3 * n + 2] * per[runs[3 * n]]);
                id = mp.post.list.run[n].w;
            }
            mp.post.list.n = n;
            mp.post.list.late = mp.post.list.run[nlate].z;
            int dev = 0, nsm = 132;
            cudaGetDevice(&dev);
            cudaDeviceGetAttribute(&nsm, cudaDevAttrMultiProcessorCount, dev);
            mp.post.list.nworker = nsm > 96 ? nsm : 97;
        }
        {
            cuuint64_t dims[4] = {DM, 3, 2, S_TOK / 2};
            cuuint64_t strides[3] = {DM * 2, 3 * DM * 2, 3 * DM * 4};
            cuuint32_t box[4] = {64, 3, 1, 40};
            cuuint32_t es[4] = {1, 1, 1, 1};
            fn(&mp.post.b40, CU_TENSOR_MAP_DATA_TYPE_BFLOAT16, 4, p_bqkv, dims, strides, box, es,
               CU_TENSOR_MAP_INTERLEAVE_NONE, CU_TENSOR_MAP_SWIZZLE_128B, CU_TENSOR_MAP_L2_PROMOTION_L2_256B, CU_TENSOR_MAP_FLOAT_OOB_FILL_NONE);
        }
        mp.wk16 = make_map(fn, A_Wk, HD, DM, 64, 64);
        mp.wv16 = make_map(fn, A_Wv, HD, DM, 64, 64);
        mp.wo128 = make_wo_map(fn, A_Wo, HD, 4);
        for (int i = 0; i < 2; i++) {
            cuuint64_t dims[3] = {64, S_TOK, DM / 64};
            cuuint64_t strides[2] = {DM * 2, 128};
            cuuint32_t box[3] = {32, 32, 2u - i};
            cuuint32_t es[3] = {1, 1, 1};
            fn(&mp.x32.m[i], CU_TENSOR_MAP_DATA_TYPE_BFLOAT16, 3, const_cast<bf16*>(A_x), dims, strides, box, es,
               CU_TENSOR_MAP_INTERLEAVE_NONE, CU_TENSOR_MAP_SWIZZLE_64B, CU_TENSOR_MAP_L2_PROMOTION_L2_128B, CU_TENSOR_MAP_FLOAT_OOB_FILL_NONE);
        }
        for (int i = 0; i < 10; i++) cached[i] = cur[i];
    }

    cudaStream_t st = cudaStreamPerThread;
    int4 tq = make_int4(0, 100, 700, 80), tk = make_int4(0, 250, 800, 70);
    int2 t0 = make_int2(13000, 16000);
    cudaLaunchConfig_t cfg = {};
    cfg.gridDim = dim3(96); cfg.blockDim = dim3(384); cfg.dynamicSmemBytes = R_SMEM; cfg.stream = st;
    cudaLaunchAttribute at[1];
    at[0].id = cudaLaunchAttributeClusterDimension;
    at[0].val.clusterDim.x = 3; at[0].val.clusterDim.y = 1; at[0].val.clusterDim.z = 1;
    cfg.attrs = at; cfg.numAttrs = 1;
    cudaLaunchKernelEx(&cfg, k_rec, mp.post, mp.wk16, mp.wv16, mp.wo128, mp.x32, A_mem, A_x, tq, tk, t0, 1);
    cfg.gridDim = dim3(mp.post.list.nworker - 96);
    at[0].id = cudaLaunchAttributeProgrammaticStreamSerialization;
    at[0].val.programmaticStreamSerializationAllowed = 1;
    cudaLaunchKernelEx(&cfg, k_rec, mp.post, mp.wk16, mp.wv16, mp.wo128, mp.x32, A_mem, A_x, tq, tk, t0, 0);
}
```

```cpp
#include <cuda_runtime.h>
#include <cuda_bf16.h>
#include <cuda.h>
#include <stdint.h>

typedef __nv_bfloat16 bf16;

constexpr int S_TOK = 2048;
constexpr int DM    = 1024;
constexpr int NH    = 32;
constexpr int DH    = 128;
constexpr int NSEG  = 64;
constexpr int HD    = NH * DH;

__device__ __align__(1024) bf16 g_qx[NSEG * NH * 4 * DH * 8];
__device__ __align__(1024) bf16 g_ox[S_TOK * HD];
__device__ __align__(1024) bf16 g_bqkv[S_TOK * 3 * DM];
__device__ __align__(1024) bf16 g_bo[S_TOK * DM];
__device__ __align__(1024) uint8_t g_acc[192 * 1024];

#define EV(cond, s, k) do {} while (0)
#define EVCAL(s) do {} while (0)

constexpr int P_NSK = 4;
__device__ unsigned g_epoch, g_qctr, g_done, g_zero;
enum { C_B1 = 0, C_B2 = 8, C_Q = 16, C_QH = 24, C_NONE = 31 };
__device__ unsigned g_cnt[32], g_prog[32], g_cnt_sk[P_NSK * 32];
constexpr int P_SPLIT = 4;
__device__ __align__(1024) uint4 g_skp[P_NSK * 8 * P_SPLIT * 2 * 8 * 128];
#define TLOG(i, k, v) do {} while (0)

#define DEVI __device__ __forceinline__

DEVI uint32_t opaque(uint32_t v) { uint32_t r; asm volatile("mov.u32 %0, %1;" : "=r"(r) : "r"(v)); return r; }
DEVI uint32_t smem_u32(const void* p) { return (uint32_t)__cvta_generic_to_shared(p); }

constexpr int SPIN_LIMIT = 1 << 22;
#define MBAR_HINT_NS 20000u
constexpr int SPIN_LIMIT_MBAR = 1 << 17;

DEVI void mbar_init(uint32_t bar, uint32_t cnt) { asm volatile("mbarrier.init.shared::cta.b64 [%0], %1;" :: "r"(bar), "r"(cnt)); }
DEVI void mbar_expect_tx(uint32_t bar, uint32_t bytes) {
    asm volatile("mbarrier.arrive.expect_tx.shared::cta.b64 _, [%0], %1;" :: "r"(bar), "r"(bytes) : "memory");
}
DEVI void mbar_arrive(uint32_t bar) { asm volatile("mbarrier.arrive.shared::cta.b64 _, [%0];" :: "r"(bar) : "memory"); }
DEVI bool mbar_try(uint32_t bar, uint32_t parity) {
    uint32_t ok;
    asm volatile("{.reg .pred p; mbarrier.try_wait.parity.shared::cta.b64 p, [%1], %2; selp.u32 %0, 1, 0, p;}"
                 : "=r"(ok) : "r"(bar), "r"(parity) : "memory");
    return ok;
}
DEVI bool mbar_try_hint(uint32_t bar, uint32_t parity) {
    uint32_t ok;
    asm volatile("{.reg .pred p; mbarrier.try_wait.parity.shared::cta.b64 p, [%1], %2, %3; selp.u32 %0, 1, 0, p;}"
                 : "=r"(ok) : "r"(bar), "r"(parity), "r"(MBAR_HINT_NS) : "memory");
    return ok;
}
DEVI bool mbar_test(uint32_t bar, uint32_t parity) {
    uint32_t ok;
    asm volatile("{.reg .pred p; mbarrier.test_wait.parity.shared::cta.b64 p, [%1], %2; selp.u32 %0, 1, 0, p;}"
                 : "=r"(ok) : "r"(bar), "r"(parity) : "memory");
    return ok;
}
DEVI void mbar_wait(uint32_t bar, uint32_t parity) {
    int n = 0;
    while (!mbar_try(bar, parity)) { if (++n > SPIN_LIMIT) __trap(); }
}
DEVI void mbar_wait_sleepy(uint32_t bar, uint32_t parity) {
    int n = 0;
    while (!mbar_try_hint(bar, parity)) { if (++n > SPIN_LIMIT_MBAR) __trap(); }
}
DEVI void fence_mbar_init() { asm volatile("fence.mbarrier_init.release.cluster;" ::: "memory"); }
DEVI void fence_proxy_async() { asm volatile("fence.proxy.async.shared::cta;" ::: "memory"); }
DEVI bool elect_one() {
    uint32_t e; asm volatile("{.reg .pred p; elect.sync _|p, 0xffffffff; selp.u32 %0, 1, 0, p;}" : "=r"(e)); return e;
}
DEVI void fence_proxy_global() { asm volatile("fence.proxy.async.global;" ::: "memory"); }
DEVI void cluster_wait() { asm volatile("barrier.cluster.wait.acquire.aligned;" ::: "memory"); }
DEVI void nbar_sync(int id, int n) { asm volatile("bar.sync %0, %1;" :: "r"(id), "r"(n) : "memory"); }
DEVI void nbar_arrive(int id, int n) { asm volatile("bar.arrive %0, %1;" :: "r"(id), "r"(n) : "memory"); }

DEVI void tma_load_2d(uint32_t dst, const CUtensorMap* map, int x, int y, uint32_t bar) {
    asm volatile("cp.async.bulk.tensor.2d.shared::cluster.global.mbarrier::complete_tx::bytes [%0], [%1, {%3, %4}], [%2];"
                 :: "r"(dst), "l"(map), "r"(bar), "r"(x), "r"(y) : "memory");
}
DEVI void tma_load_3d(uint32_t dst, const CUtensorMap* map, int x, int y, int z, uint32_t bar) {
    asm volatile("cp.async.bulk.tensor.3d.shared::cluster.global.mbarrier::complete_tx::bytes [%0], [%1, {%3, %4, %5}], [%2];"
                 :: "r"(dst), "l"(map), "r"(bar), "r"(x), "r"(y), "r"(z) : "memory");
}
DEVI void tma_load_wo(uint32_t dst, const CUtensorMap* map, int col, int k32, uint32_t bar) {
    asm volatile("cp.async.bulk.tensor.5d.shared::cluster.global.mbarrier::complete_tx::bytes [%0], [%1, {%3, %5, %5, %5, %4}], [%2];"
                 :: "r"(dst), "l"(map), "r"(bar), "r"(col), "r"(k32), "r"(0) : "memory");
}
DEVI void tma_store_2d(const CUtensorMap* map, uint32_t src, int x, int y) {
    asm volatile("cp.async.bulk.tensor.2d.global.shared::cta.bulk_group [%0, {%2, %3}], [%1];"
                 :: "l"(map), "r"(src), "r"(x), "r"(y) : "memory");
}
DEVI void bulk_load(uint32_t dst, const void* src, uint32_t bytes, uint32_t bar) {
    asm volatile("cp.async.bulk.shared::cluster.global.mbarrier::complete_tx::bytes [%0], [%1], %2, [%3];"
                 :: "r"(dst), "l"(src), "r"(bytes), "r"(bar) : "memory");
}
DEVI void bulk_copy_s2c(uint32_t dst_cluster, uint32_t src, uint32_t bytes, uint32_t bar_cluster) {
    asm volatile("cp.async.bulk.shared::cluster.shared::cta.mbarrier::complete_tx::bytes [%0], [%1], %2, [%3];"
                 :: "r"(dst_cluster), "r"(src), "r"(bytes), "r"(bar_cluster) : "memory");
}
DEVI void bulk_wait_read() { asm volatile("cp.async.bulk.wait_group.read 0;" ::: "memory"); }
DEVI void mbar_arrive_remote(uint32_t bar_cluster) {
    asm volatile("mbarrier.arrive.shared::cluster.b64 _, [%0];" :: "r"(bar_cluster) : "memory");
}
DEVI void l2_prefetch(const void* p, uint32_t bytes) {
    asm volatile("cp.async.bulk.prefetch.L2.global [%0], %1;" :: "l"(p), "r"(bytes) : "memory");
}
DEVI void bulk_commit() { asm volatile("cp.async.bulk.commit_group;" ::: "memory"); }
DEVI void bulk_wait_all() { asm volatile("cp.async.bulk.wait_group 0;" ::: "memory"); }

DEVI void wg_fence() { asm volatile("wgmma.fence.sync.aligned;" ::: "memory"); }
DEVI void wg_commit() { asm volatile("wgmma.commit_group.sync.aligned;" ::: "memory"); }
template <int N> DEVI void wg_wait() { asm volatile("wgmma.wait_group.sync.aligned %0;" :: "n"(N) : "memory"); }

template <int R> DEVI void reg_dec() { asm volatile("setmaxnreg.dec.sync.aligned.u32 %0;" :: "n"(R)); }
template <int R> DEVI void reg_inc() { asm volatile("setmaxnreg.inc.sync.aligned.u32 %0;" :: "n"(R)); }

DEVI uint64_t mk_desc(uint32_t addr, uint32_t lbo, uint32_t sbo, uint32_t sw) {
    return (uint64_t)((addr & 0x3FFFF) >> 4) | ((uint64_t)(lbo >> 4) << 16) | ((uint64_t)(sbo >> 4) << 32) | ((uint64_t)sw << 62);
}

constexpr uint32_t DHI_SW128 = (1024u >> 4) | (1u << 30);
constexpr uint32_t DHI_SW64  = (512u >> 4) | (2u << 30);
constexpr uint32_t DHI_NONE  = (128u >> 4);

template <int TB, int SCALE_D>
DEVI void wgmma_n8_ss(float* d, uint32_t alo, uint32_t blo) {
    asm volatile("{.reg .b64 da, db; mov.b64 da, {%4, %6}; mov.b64 db, {%5, %7};\n"
                 "wgmma.mma_async.sync.aligned.m64n8k16.f32.bf16.bf16 {%0,%1,%2,%3}, da, db, %8, 1, 1, 1, %9;}"
                 : "+f"(d[0]), "+f"(d[1]), "+f"(d[2]), "+f"(d[3])
                 : "r"(alo), "r"(blo), "n"(DHI_SW128), "n"(DHI_NONE), "n"(SCALE_D), "n"(TB));
}

template <int TB>
DEVI void wgmma_n8_ss_first(float* d, uint32_t alo, uint32_t blo) {
    asm volatile("{.reg .b64 da, db; mov.b64 da, {%4, %6}; mov.b64 db, {%5, %7};\n"
                 "wgmma.mma_async.sync.aligned.m64n8k16.f32.bf16.bf16 {%0,%1,%2,%3}, da, db, 0, 1, 1, 1, %8;}"
                 : "=f"(d[0]), "=f"(d[1]), "=f"(d[2]), "=f"(d[3])
                 : "r"(alo), "r"(blo), "n"(DHI_SW128), "n"(DHI_NONE), "n"(TB));
}
DEVI void wgmma_n32_rs_first(float* d, const uint32_t* a, uint32_t blo) {
    asm volatile("{.reg .b64 db; mov.b64 db, {%20, %21};\n"
                 "wgmma.mma_async.sync.aligned.m64n32k16.f32.bf16.bf16 {%0,%1,%2,%3,%4,%5,%6,%7,%8,%9,%10,%11,%12,%13,%14,%15}, "
                 "{%16,%17,%18,%19}, db, 0, 1, 1, 0;}"
                 : "=f"(d[0]), "=f"(d[1]), "=f"(d[2]), "=f"(d[3]), "=f"(d[4]), "=f"(d[5]), "=f"(d[6]), "=f"(d[7]),
                   "=f"(d[8]), "=f"(d[9]), "=f"(d[10]), "=f"(d[11]), "=f"(d[12]), "=f"(d[13]), "=f"(d[14]), "=f"(d[15])
                 : "r"(a[0]), "r"(a[1]), "r"(a[2]), "r"(a[3]), "r"(blo), "n"(DHI_SW64));
}
template <int N> DEVI void reg_fence(float* d) {
#pragma unroll
    for (int i = 0; i < N; i++) asm volatile("" : "+f"(d[i]) :: "memory");
}
DEVI void wgmma_n32_rs(float* d, const uint32_t* a, uint32_t blo) {
    asm volatile("{.reg .b64 db; mov.b64 db, {%20, %21};\n"
                 "wgmma.mma_async.sync.aligned.m64n32k16.f32.bf16.bf16 {%0,%1,%2,%3,%4,%5,%6,%7,%8,%9,%10,%11,%12,%13,%14,%15}, "
                 "{%16,%17,%18,%19}, db, 1, 1, 1, 0;}"
                 : "+f"(d[0]), "+f"(d[1]), "+f"(d[2]), "+f"(d[3]), "+f"(d[4]), "+f"(d[5]), "+f"(d[6]), "+f"(d[7]),
                   "+f"(d[8]), "+f"(d[9]), "+f"(d[10]), "+f"(d[11]), "+f"(d[12]), "+f"(d[13]), "+f"(d[14]), "+f"(d[15])
                 : "r"(a[0]), "r"(a[1]), "r"(a[2]), "r"(a[3]), "r"(blo), "n"(DHI_SW64));
}
DEVI void wgmma_n32_ss(float* d, uint32_t alo, uint32_t blo) {
    asm volatile("{.reg .b64 da, db; mov.b64 da, {%16, %18}; mov.b64 db, {%17, %19};\n"
                 "wgmma.mma_async.sync.aligned.m64n32k16.f32.bf16.bf16 {%0,%1,%2,%3,%4,%5,%6,%7,%8,%9,%10,%11,%12,%13,%14,%15}, "
                 "da, db, 1, 1, 1, 1, 0;}"
                 : "+f"(d[0]), "+f"(d[1]), "+f"(d[2]), "+f"(d[3]), "+f"(d[4]), "+f"(d[5]), "+f"(d[6]), "+f"(d[7]),
                   "+f"(d[8]), "+f"(d[9]), "+f"(d[10]), "+f"(d[11]), "+f"(d[12]), "+f"(d[13]), "+f"(d[14]), "+f"(d[15])
                 : "r"(alo), "r"(blo), "n"(DHI_SW128), "n"(DHI_SW64));
}

template <bool FIRST>
DEVI void wgmma_n256_ss(float* d, uint64_t a, uint64_t b) {
    if (FIRST)
        asm volatile("wgmma.mma_async.sync.aligned.m64n256k16.f32.bf16.bf16 {%0,%1,%2,%3,%4,%5,%6,%7,%8,%9,%10,%11,%12,%13,%14,%15,%16,%17,%18,%19,%20,%21,%22,%23,%24,%25,%26,%27,%28,%29,%30,%31,%32,%33,%34,%35,%36,%37,%38,%39,%40,%41,%42,%43,%44,%45,%46,%47,%48,%49,%50,%51,%52,%53,%54,%55,%56,%57,%58,%59,%60,%61,%62,%63,%64,%65,%66,%67,%68,%69,%70,%71,%72,%73,%74,%75,%76,%77,%78,%79,%80,%81,%82,%83,%84,%85,%86,%87,%88,%89,%90,%91,%92,%93,%94,%95,%96,%97,%98,%99,%100,%101,%102,%103,%104,%105,%106,%107,%108,%109,%110,%111,%112,%113,%114,%115,%116,%117,%118,%119,%120,%121,%122,%123,%124,%125,%126,%127}, %128, %129, 0, 1, 1, 1, 0;"
            : "=f"(d[0]), "=f"(d[1]), "=f"(d[2]), "=f"(d[3]), "=f"(d[4]), "=f"(d[5]), "=f"(d[6]), "=f"(d[7]), "=f"(d[8]), "=f"(d[9]), "=f"(d[10]), "=f"(d[11]), "=f"(d[12]), "=f"(d[13]), "=f"(d[14]), "=f"(d[15]), "=f"(d[16]), "=f"(d[17]), "=f"(d[18]), "=f"(d[19]), "=f"(d[20]), "=f"(d[21]), "=f"(d[22]), "=f"(d[23]), "=f"(d[24]), "=f"(d[25]), "=f"(d[26]), "=f"(d[27]), "=f"(d[28]), "=f"(d[29]), "=f"(d[30]), "=f"(d[31]), "=f"(d[32]), "=f"(d[33]), "=f"(d[34]), "=f"(d[35]), "=f"(d[36]), "=f"(d[37]), "=f"(d[38]), "=f"(d[39]), "=f"(d[40]), "=f"(d[41]), "=f"(d[42]), "=f"(d[43]), "=f"(d[44]), "=f"(d[45]), "=f"(d[46]), "=f"(d[47]), "=f"(d[48]), "=f"(d[49]), "=f"(d[50]), "=f"(d[51]), "=f"(d[52]), "=f"(d[53]), "=f"(d[54]), "=f"(d[55]), "=f"(d[56]), "=f"(d[57]), "=f"(d[58]), "=f"(d[59]), "=f"(d[60]), "=f"(d[61]), "=f"(d[62]), "=f"(d[63]), "=f"(d[64]), "=f"(d[65]), "=f"(d[66]), "=f"(d[67]), "=f"(d[68]), "=f"(d[69]), "=f"(d[70]), "=f"(d[71]), "=f"(d[72]), "=f"(d[73]), "=f"(d[74]), "=f"(d[75]), "=f"(d[76]), "=f"(d[77]), "=f"(d[78]), "=f"(d[79]), "=f"(d[80]), "=f"(d[81]), "=f"(d[82]), "=f"(d[83]), "=f"(d[84]), "=f"(d[85]), "=f"(d[86]), "=f"(d[87]), "=f"(d[88]), "=f"(d[89]), "=f"(d[90]), "=f"(d[91]), "=f"(d[92]), "=f"(d[93]), "=f"(d[94]), "=f"(d[95]), "=f"(d[96]), "=f"(d[97]), "=f"(d[98]), "=f"(d[99]), "=f"(d[100]), "=f"(d[101]), "=f"(d[102]), "=f"(d[103]), "=f"(d[104]), "=f"(d[105]), "=f"(d[106]), "=f"(d[107]), "=f"(d[108]), "=f"(d[109]), "=f"(d[110]), "=f"(d[111]), "=f"(d[112]), "=f"(d[113]), "=f"(d[114]), "=f"(d[115]), "=f"(d[116]), "=f"(d[117]), "=f"(d[118]), "=f"(d[119]), "=f"(d[120]), "=f"(d[121]), "=f"(d[122]), "=f"(d[123]), "=f"(d[124]), "=f"(d[125]), "=f"(d[126]), "=f"(d[127]) : "l"(a), "l"(b));
    else
        asm volatile("wgmma.mma_async.sync.aligned.m64n256k16.f32.bf16.bf16 {%0,%1,%2,%3,%4,%5,%6,%7,%8,%9,%10,%11,%12,%13,%14,%15,%16,%17,%18,%19,%20,%21,%22,%23,%24,%25,%26,%27,%28,%29,%30,%31,%32,%33,%34,%35,%36,%37,%38,%39,%40,%41,%42,%43,%44,%45,%46,%47,%48,%49,%50,%51,%52,%53,%54,%55,%56,%57,%58,%59,%60,%61,%62,%63,%64,%65,%66,%67,%68,%69,%70,%71,%72,%73,%74,%75,%76,%77,%78,%79,%80,%81,%82,%83,%84,%85,%86,%87,%88,%89,%90,%91,%92,%93,%94,%95,%96,%97,%98,%99,%100,%101,%102,%103,%104,%105,%106,%107,%108,%109,%110,%111,%112,%113,%114,%115,%116,%117,%118,%119,%120,%121,%122,%123,%124,%125,%126,%127}, %128, %129, 1, 1, 1, 1, 0;"
            : "+f"(d[0]), "+f"(d[1]), "+f"(d[2]), "+f"(d[3]), "+f"(d[4]), "+f"(d[5]), "+f"(d[6]), "+f"(d[7]), "+f"(d[8]), "+f"(d[9]), "+f"(d[10]), "+f"(d[11]), "+f"(d[12]), "+f"(d[13]), "+f"(d[14]), "+f"(d[15]), "+f"(d[16]), "+f"(d[17]), "+f"(d[18]), "+f"(d[19]), "+f"(d[20]), "+f"(d[21]), "+f"(d[22]), "+f"(d[23]), "+f"(d[24]), "+f"(d[25]), "+f"(d[26]), "+f"(d[27]), "+f"(d[28]), "+f"(d[29]), "+f"(d[30]), "+f"(d[31]), "+f"(d[32]), "+f"(d[33]), "+f"(d[34]), "+f"(d[35]), "+f"(d[36]), "+f"(d[37]), "+f"(d[38]), "+f"(d[39]), "+f"(d[40]), "+f"(d[41]), "+f"(d[42]), "+f"(d[43]), "+f"(d[44]), "+f"(d[45]), "+f"(d[46]), "+f"(d[47]), "+f"(d[48]), "+f"(d[49]), "+f"(d[50]), "+f"(d[51]), "+f"(d[52]), "+f"(d[53]), "+f"(d[54]), "+f"(d[55]), "+f"(d[56]), "+f"(d[57]), "+f"(d[58]), "+f"(d[59]), "+f"(d[60]), "+f"(d[61]), "+f"(d[62]), "+f"(d[63]), "+f"(d[64]), "+f"(d[65]), "+f"(d[66]), "+f"(d[67]), "+f"(d[68]), "+f"(d[69]), "+f"(d[70]), "+f"(d[71]), "+f"(d[72]), "+f"(d[73]), "+f"(d[74]), "+f"(d[75]), "+f"(d[76]), "+f"(d[77]), "+f"(d[78]), "+f"(d[79]), "+f"(d[80]), "+f"(d[81]), "+f"(d[82]), "+f"(d[83]), "+f"(d[84]), "+f"(d[85]), "+f"(d[86]), "+f"(d[87]), "+f"(d[88]), "+f"(d[89]), "+f"(d[90]), "+f"(d[91]), "+f"(d[92]), "+f"(d[93]), "+f"(d[94]), "+f"(d[95]), "+f"(d[96]), "+f"(d[97]), "+f"(d[98]), "+f"(d[99]), "+f"(d[100]), "+f"(d[101]), "+f"(d[102]), "+f"(d[103]), "+f"(d[104]), "+f"(d[105]), "+f"(d[106]), "+f"(d[107]), "+f"(d[108]), "+f"(d[109]), "+f"(d[110]), "+f"(d[111]), "+f"(d[112]), "+f"(d[113]), "+f"(d[114]), "+f"(d[115]), "+f"(d[116]), "+f"(d[117]), "+f"(d[118]), "+f"(d[119]), "+f"(d[120]), "+f"(d[121]), "+f"(d[122]), "+f"(d[123]), "+f"(d[124]), "+f"(d[125]), "+f"(d[126]), "+f"(d[127]) : "l"(a), "l"(b));
}
template <bool FIRST>
DEVI void wgmma_n128_ss(float* d, uint64_t a, uint64_t b) {
    if (FIRST)
        asm volatile("wgmma.mma_async.sync.aligned.m64n128k16.f32.bf16.bf16 {%0,%1,%2,%3,%4,%5,%6,%7,%8,%9,%10,%11,%12,%13,%14,%15,%16,%17,%18,%19,%20,%21,%22,%23,%24,%25,%26,%27,%28,%29,%30,%31,%32,%33,%34,%35,%36,%37,%38,%39,%40,%41,%42,%43,%44,%45,%46,%47,%48,%49,%50,%51,%52,%53,%54,%55,%56,%57,%58,%59,%60,%61,%62,%63}, %64, %65, 0, 1, 1, 1, 0;"
            : "=f"(d[0]), "=f"(d[1]), "=f"(d[2]), "=f"(d[3]), "=f"(d[4]), "=f"(d[5]), "=f"(d[6]), "=f"(d[7]), "=f"(d[8]), "=f"(d[9]), "=f"(d[10]), "=f"(d[11]), "=f"(d[12]), "=f"(d[13]), "=f"(d[14]), "=f"(d[15]), "=f"(d[16]), "=f"(d[17]), "=f"(d[18]), "=f"(d[19]), "=f"(d[20]), "=f"(d[21]), "=f"(d[22]), "=f"(d[23]), "=f"(d[24]), "=f"(d[25]), "=f"(d[26]), "=f"(d[27]), "=f"(d[28]), "=f"(d[29]), "=f"(d[30]), "=f"(d[31]), "=f"(d[32]), "=f"(d[33]), "=f"(d[34]), "=f"(d[35]), "=f"(d[36]), "=f"(d[37]), "=f"(d[38]), "=f"(d[39]), "=f"(d[40]), "=f"(d[41]), "=f"(d[42]), "=f"(d[43]), "=f"(d[44]), "=f"(d[45]), "=f"(d[46]), "=f"(d[47]), "=f"(d[48]), "=f"(d[49]), "=f"(d[50]), "=f"(d[51]), "=f"(d[52]), "=f"(d[53]), "=f"(d[54]), "=f"(d[55]), "=f"(d[56]), "=f"(d[57]), "=f"(d[58]), "=f"(d[59]), "=f"(d[60]), "=f"(d[61]), "=f"(d[62]), "=f"(d[63]) : "l"(a), "l"(b));
    else
        asm volatile("wgmma.mma_async.sync.aligned.m64n128k16.f32.bf16.bf16 {%0,%1,%2,%3,%4,%5,%6,%7,%8,%9,%10,%11,%12,%13,%14,%15,%16,%17,%18,%19,%20,%21,%22,%23,%24,%25,%26,%27,%28,%29,%30,%31,%32,%33,%34,%35,%36,%37,%38,%39,%40,%41,%42,%43,%44,%45,%46,%47,%48,%49,%50,%51,%52,%53,%54,%55,%56,%57,%58,%59,%60,%61,%62,%63}, %64, %65, 1, 1, 1, 1, 0;"
            : "+f"(d[0]), "+f"(d[1]), "+f"(d[2]), "+f"(d[3]), "+f"(d[4]), "+f"(d[5]), "+f"(d[6]), "+f"(d[7]), "+f"(d[8]), "+f"(d[9]), "+f"(d[10]), "+f"(d[11]), "+f"(d[12]), "+f"(d[13]), "+f"(d[14]), "+f"(d[15]), "+f"(d[16]), "+f"(d[17]), "+f"(d[18]), "+f"(d[19]), "+f"(d[20]), "+f"(d[21]), "+f"(d[22]), "+f"(d[23]), "+f"(d[24]), "+f"(d[25]), "+f"(d[26]), "+f"(d[27]), "+f"(d[28]), "+f"(d[29]), "+f"(d[30]), "+f"(d[31]), "+f"(d[32]), "+f"(d[33]), "+f"(d[34]), "+f"(d[35]), "+f"(d[36]), "+f"(d[37]), "+f"(d[38]), "+f"(d[39]), "+f"(d[40]), "+f"(d[41]), "+f"(d[42]), "+f"(d[43]), "+f"(d[44]), "+f"(d[45]), "+f"(d[46]), "+f"(d[47]), "+f"(d[48]), "+f"(d[49]), "+f"(d[50]), "+f"(d[51]), "+f"(d[52]), "+f"(d[53]), "+f"(d[54]), "+f"(d[55]), "+f"(d[56]), "+f"(d[57]), "+f"(d[58]), "+f"(d[59]), "+f"(d[60]), "+f"(d[61]), "+f"(d[62]), "+f"(d[63]) : "l"(a), "l"(b));
}

template <bool FIRST>
DEVI void wgmma_n64_ss(float* d, uint64_t a, uint64_t b) {
    if (FIRST)
        asm volatile("wgmma.mma_async.sync.aligned.m64n64k16.f32.bf16.bf16 {%0,%1,%2,%3,%4,%5,%6,%7,%8,%9,%10,%11,%12,%13,%14,%15,%16,%17,%18,%19,%20,%21,%22,%23,%24,%25,%26,%27,%28,%29,%30,%31}, %32, %33, 0, 1, 1, 1, 0;"
            : "=f"(d[0]), "=f"(d[1]), "=f"(d[2]), "=f"(d[3]), "=f"(d[4]), "=f"(d[5]), "=f"(d[6]), "=f"(d[7]), "=f"(d[8]), "=f"(d[9]), "=f"(d[10]), "=f"(d[11]), "=f"(d[12]), "=f"(d[13]), "=f"(d[14]), "=f"(d[15]), "=f"(d[16]), "=f"(d[17]), "=f"(d[18]), "=f"(d[19]), "=f"(d[20]), "=f"(d[21]), "=f"(d[22]), "=f"(d[23]), "=f"(d[24]), "=f"(d[25]), "=f"(d[26]), "=f"(d[27]), "=f"(d[28]), "=f"(d[29]), "=f"(d[30]), "=f"(d[31]) : "l"(a), "l"(b));
    else
        asm volatile("wgmma.mma_async.sync.aligned.m64n64k16.f32.bf16.bf16 {%0,%1,%2,%3,%4,%5,%6,%7,%8,%9,%10,%11,%12,%13,%14,%15,%16,%17,%18,%19,%20,%21,%22,%23,%24,%25,%26,%27,%28,%29,%30,%31}, %32, %33, 1, 1, 1, 1, 0;"
            : "+f"(d[0]), "+f"(d[1]), "+f"(d[2]), "+f"(d[3]), "+f"(d[4]), "+f"(d[5]), "+f"(d[6]), "+f"(d[7]), "+f"(d[8]), "+f"(d[9]), "+f"(d[10]), "+f"(d[11]), "+f"(d[12]), "+f"(d[13]), "+f"(d[14]), "+f"(d[15]), "+f"(d[16]), "+f"(d[17]), "+f"(d[18]), "+f"(d[19]), "+f"(d[20]), "+f"(d[21]), "+f"(d[22]), "+f"(d[23]), "+f"(d[24]), "+f"(d[25]), "+f"(d[26]), "+f"(d[27]), "+f"(d[28]), "+f"(d[29]), "+f"(d[30]), "+f"(d[31]) : "l"(a), "l"(b));
}

DEVI void mma16816(float* d, const uint32_t* a, uint32_t b0, uint32_t b1) {
    asm volatile("mma.sync.aligned.m16n8k16.row.col.f32.bf16.bf16.f32 {%0,%1,%2,%3}, {%4,%5,%6,%7}, {%8,%9}, {%0,%1,%2,%3};"
                 : "+f"(d[0]), "+f"(d[1]), "+f"(d[2]), "+f"(d[3])
                 : "r"(a[0]), "r"(a[1]), "r"(a[2]), "r"(a[3]), "r"(b0), "r"(b1));
}
DEVI void mma1688(float* d, uint32_t a0, uint32_t a1, uint32_t b0) {
    asm volatile("mma.sync.aligned.m16n8k8.row.col.f32.bf16.bf16.f32 {%0,%1,%2,%3}, {%4,%5}, {%6}, {%0,%1,%2,%3};"
                 : "+f"(d[0]), "+f"(d[1]), "+f"(d[2]), "+f"(d[3]) : "r"(a0), "r"(a1), "r"(b0));
}
DEVI void ldsm4(uint32_t* r, uint32_t addr) {
    asm volatile("ldmatrix.sync.aligned.m8n8.x4.shared.b16 {%0,%1,%2,%3}, [%4];"
                 : "=r"(r[0]), "=r"(r[1]), "=r"(r[2]), "=r"(r[3]) : "r"(addr) : "memory");
}
DEVI void ldsm4t(uint32_t* r, uint32_t addr) {
    asm volatile("ldmatrix.sync.aligned.m8n8.x4.trans.shared.b16 {%0,%1,%2,%3}, [%4];"
                 : "=r"(r[0]), "=r"(r[1]), "=r"(r[2]), "=r"(r[3]) : "r"(addr) : "memory");
}
DEVI void stsm4(uint32_t addr, uint32_t r0, uint32_t r1, uint32_t r2, uint32_t r3) {
    asm volatile("stmatrix.sync.aligned.m8n8.x4.shared.b16 [%0], {%1,%2,%3,%4};" :: "r"(addr), "r"(r0), "r"(r1), "r"(r2), "r"(r3) : "memory");
}
DEVI void stsm4t(uint32_t addr, uint32_t r0, uint32_t r1, uint32_t r2, uint32_t r3) {
    asm volatile("stmatrix.sync.aligned.m8n8.x4.trans.shared.b16 [%0], {%1,%2,%3,%4};" :: "r"(addr), "r"(r0), "r"(r1), "r"(r2), "r"(r3) : "memory");
}
DEVI uint32_t pack_bf16(float lo, float hi) {
    uint32_t r; asm("cvt.rn.bf16x2.f32 %0, %1, %2;" : "=r"(r) : "f"(hi), "f"(lo)); return r;
}
DEVI uint32_t add_bf16x2(uint32_t a, uint32_t b) { uint32_t r; asm("add.rn.bf16x2 %0, %1, %2;" : "=r"(r) : "r"(a), "r"(b)); return r; }
DEVI float ex2(float x) { float y; asm("ex2.approx.ftz.f32 %0, %1;" : "=f"(y) : "f"(x)); return y; }

DEVI uint4 ld_rlx4(const void* p) {
    uint4 v;
    asm volatile("ld.relaxed.gpu.global.v4.u32 {%0,%1,%2,%3}, [%4];" : "=r"(v.x), "=r"(v.y), "=r"(v.z), "=r"(v.w) : "l"(p) : "memory");
    return v;
}
DEVI void st_rlx4(void* p, uint32_t a, uint32_t b, uint32_t c, uint32_t d) {
    asm volatile("st.relaxed.gpu.global.v4.u32 [%0], {%1,%2,%3,%4};" :: "l"(p), "r"(a), "r"(b), "r"(c), "r"(d) : "memory");
}
DEVI void sts128(uint32_t addr, uint4 v) {
    asm volatile("st.shared.v4.u32 [%0], {%1,%2,%3,%4};" :: "r"(addr), "r"(v.x), "r"(v.y), "r"(v.z), "r"(v.w) : "memory");
}
DEVI void sts64(uint32_t addr, uint32_t a, uint32_t b) { asm volatile("st.shared.v2.u32 [%0], {%1,%2};" :: "r"(addr), "r"(a), "r"(b) : "memory"); }
DEVI void sts32(uint32_t addr, uint32_t v) { asm volatile("st.shared.u32 [%0], %1;" :: "r"(addr), "r"(v) : "memory"); }
DEVI uint4 lds128(uint32_t addr) {
    uint4 v; asm volatile("ld.shared.v4.u32 {%0,%1,%2,%3}, [%4];" : "=r"(v.x), "=r"(v.y), "=r"(v.z), "=r"(v.w) : "r"(addr) : "memory"); return v;
}
DEVI float2 lds64f(uint32_t addr) {
    float2 v; asm volatile("ld.shared.v2.f32 {%0,%1}, [%2];" : "=f"(v.x), "=f"(v.y) : "r"(addr) : "memory"); return v;
}
DEVI uint32_t lds32(uint32_t addr) { uint32_t v; asm volatile("ld.shared.u32 %0, [%1];" : "=r"(v) : "r"(addr) : "memory"); return v; }
DEVI float rcp_fast(float x) { float y; asm("rcp.approx.ftz.f32 %0, %1;" : "=f"(y) : "f"(x)); return y; }
DEVI uint32_t mapa(uint32_t addr, uint32_t rank) {
    uint32_t r; asm("mapa.shared::cluster.u32 %0, %1, %2;" : "=r"(r) : "r"(addr), "r"(rank)); return r;
}
DEVI void st_async32(uint32_t dst, uint32_t a, uint32_t bar) {
    asm volatile("st.async.weak.shared::cluster.mbarrier::complete_tx::bytes.b32 [%0], %1, [%2];" :: "r"(dst), "r"(a), "r"(bar) : "memory");
}

DEVI void st_async128(uint32_t dst, uint32_t a, uint32_t b, uint32_t c, uint32_t d, uint32_t bar) {
    asm volatile("st.async.weak.shared::cluster.mbarrier::complete_tx::bytes.v4.b32 [%0], {%1,%2,%3,%4}, [%5];"
                 :: "r"(dst), "r"(a), "r"(b), "r"(c), "r"(d), "r"(bar) : "memory");
}

DEVI uint32_t b_addr(uint32_t sb, int row, int which, int chunk) { const int l = 3 * row + which; return sb + l * 128 + ((chunk ^ (l & 7)) * 16); }
DEVI void battn_warp(uint32_t st, uint32_t ebar, int i0, int par, int head, int hh, int mt, int lane) {
    const int gq = lane >> 2, t = lane & 3, r = 16 * mt + (lane & 7), b3 = (lane >> 3) & 1, b4 = lane >> 4;
    uint32_t a[8], k[8], k2[4], v[8], v2[4];
#pragma unroll
    for (int ks = 0; ks < 2; ks++) {
        ldsm4(a + 4 * ks, b_addr(st, 8 + r + b3 * 8, 0, hh * 4 + ks * 2 + b4));
        ldsm4(k + 4 * ks, b_addr(st, r + b4 * 8, 1, hh * 4 + ks * 2 + b3));
    }
    ldsm4(k2, b_addr(st, r + 16, 1, hh * 4 + (lane >> 3)));
#pragma unroll
    for (int n = 0; n < 2; n++) ldsm4t(v + 4 * n, b_addr(st, r + b3 * 8, 2, hh * 4 + 2 * n + b4));
    ldsm4t(v2, b_addr(st, r + 16, 2, hh * 4 + (lane >> 3)));
    float s[3][4];
#pragma unroll
    for (int n = 0; n < 3; n++) { s[n][0] = s[n][1] = s[n][2] = s[n][3] = 0.f; }
#pragma unroll
    for (int ks = 0; ks < 2; ks++) {
        mma16816(s[0], a + 4 * ks, k[4 * ks], k[4 * ks + 1]);
        mma16816(s[1], a + 4 * ks, k[4 * ks + 2], k[4 * ks + 3]);
        mma16816(s[2], a + 4 * ks, k2[2 * ks], k2[2 * ks + 1]);
    }
    const bool ex = i0 + 16 * mt > 0;
    float x[4], y[4];
#pragma unroll
    for (int c = 0; c < 2; c++) {
        const bool low = 2 * t + c <= gq;
        x[c] = !low && ex ? s[0][c] : -INFINITY; x[2 + c] = low ? s[1][c] : -INFINITY;
        y[c] = !low ? s[1][2 + c] : -INFINITY;   y[2 + c] = low ? s[2][2 + c] : -INFINITY;
    }
    float m0 = fmaxf(fmaxf(x[0], x[1]), fmaxf(x[2], x[3])), m1 = fmaxf(fmaxf(y[0], y[1]), fmaxf(y[2], y[3]));
    m0 = fmaxf(fmaxf(m0, __shfl_xor_sync(0xffffffffu, m0, 1)), fmaxf(__shfl_xor_sync(0xffffffffu, m0, 2), __shfl_xor_sync(0xffffffffu, m0, 3)));
    m1 = fmaxf(fmaxf(m1, __shfl_xor_sync(0xffffffffu, m1, 1)), fmaxf(__shfl_xor_sync(0xffffffffu, m1, 2), __shfl_xor_sync(0xffffffffu, m1, 3)));
    constexpr float C = 0.17677669529663687f * 1.4426950408889634f;
    auto e = [](float v, float mx) { return ex2((v - mx) * C); };
    const uint32_t p0[4] = {pack_bf16(e(x[0], m0), e(x[1], m0)), 0u, pack_bf16(e(x[2], m0), e(x[3], m0)), pack_bf16(e(y[0], m1), e(y[1], m1))};
    const uint32_t p1 = pack_bf16(e(y[2], m1), e(y[3], m1));
    float o[4][4], l[4] = {0.f, 0.f, 0.f, 0.f};
#pragma unroll
    for (int n = 0; n < 4; n++) { o[n][0] = o[n][1] = o[n][2] = o[n][3] = 0.f; }
    mma16816(l, p0, 0x3F803F80u, 0x3F803F80u);
#pragma unroll
    for (int n = 0; n < 4; n++) mma16816(o[n], p0, v[2 * n], v[2 * n + 1]);
    mma1688(l, 0u, p1, 0x3F803F80u);
#pragma unroll
    for (int n = 0; n < 4; n++) mma1688(o[n], 0u, p1, v2[n]);
    if (lane == 0) mbar_arrive(ebar);
    const float i0f = rcp_fast(l[0]), i1f = rcp_fast(l[2]);
    uint4* dst = (uint4*)(g_bo + (uint32_t)((2 * (i0 + 16 * mt + gq) + par) * DM + head * 32 + t * 8));
    dst[0] = make_uint4(pack_bf16(o[0][0] * i0f, o[0][1] * i0f), pack_bf16(o[1][0] * i0f, o[1][1] * i0f),
                        pack_bf16(o[2][0] * i0f, o[2][1] * i0f), pack_bf16(o[3][0] * i0f, o[3][1] * i0f));
    dst[16 * DM / 8] = make_uint4(pack_bf16(o[0][2] * i1f, o[0][3] * i1f), pack_bf16(o[1][2] * i1f, o[1][3] * i1f),
                                  pack_bf16(o[2][2] * i1f, o[2][3] * i1f), pack_bf16(o[3][2] * i1f, o[3][3] * i1f));
}

constexpr float SCALE_LOG2E = 0.08838834764831845f * 1.4426950408889634f;

constexpr int P_UNITS = 12, P_STAGES = 6;
constexpr int PS_STG = P_UNITS * 16384;
constexpr int P_SMEM = 232448;
constexpr int PS_BAR = P_SMEM - 256;
static_assert(PS_STG + 32768 <= PS_BAR, "smem");
enum { K_Q, K_B1, K_B3, K_A4, K_QH, K_A3, K_SK, K_B2, K_SN, K_END };
struct PList { int n, nworker, late; int4 run[16]; };
struct PTask { int kind, a, b, c, id; };
DEVI PTask p_decode(const PList& pl, int id) {
    int i = pl.n - 1;
    if (id >= pl.run[i].w) return {K_END, 0, 0, 0, id};
    while (id < pl.run[i].z) i--;
    const int4 r = pl.run[i];
    const int j = id - r.z;
    if (r.x == K_Q || r.x == K_QH) return {r.x, j & 31, r.y + (j >> 5), 0, id};
    if (r.x == K_B1) return {r.x, j % 24, r.y + j / 24, 0, id};
    if (r.x == K_B2) return {r.x, 0, r.y + j, 0, id};
    if (r.x == K_SK || r.x == K_SN) return {r.x, (j / P_SPLIT) & 7, r.y + j / (8 * P_SPLIT), j % P_SPLIT, id};
    return {r.x, j & 7, r.y + (j >> 3), 0, id};
}
DEVI void wait_count_warp(const unsigned* p, unsigned target) {
    int n = 0;
    while (true) {
        unsigned v; asm volatile("ld.acquire.gpu.global.u32 %0, [%1];" : "=r"(v) : "l"(p) : "memory");
        if (__all_sync(0xffffffffu, (int)(v - target) >= 0)) break;
        __nanosleep(100);
        if (++n > SPIN_LIMIT) __trap();
    }
}
DEVI void signal_count(unsigned* p) { __threadfence(); atomicAdd(p, 1u); }

struct PMaps { CUtensorMap wq, bw, bwo, wo, x, bx, bo, ox, ox64, cb, cout, cq, b40; PList list; };
constexpr int PB_F = PS_BAR, PB_E = PB_F + 48, PB_TF = PB_F + 96, PB_TE = PB_F + 112, PB_S = PB_F + 128;
constexpr int PS_T = PB_F + 160, PS_SIG = PS_T + 32, PS_SK = PS_SIG + 16;

struct PRing {
    int st, ph, u;
    DEVI void next(int n) { u += n; if (u >= P_UNITS) u -= P_UNITS; if (++st == P_STAGES) { st = 0; ph ^= 1; } }
    DEVI uint32_t w(bool wide) const { return wide && u == P_UNITS - 2 ? 0u : u * 16384u; }
    DEVI uint32_t x(bool wide) const { return wide && u == P_UNITS - 2 ? u * 16384u : (u == P_UNITS - 1 ? 0u : (u + 1) * 16384u); }
};
struct POut { const CUtensorMap* map; int col, tok, cnt; bool blocked; };
DEVI void p_store(const uint32_t* pk, const POut& o, int c, uint32_t stg, int warp, int lane_, int barid) {
    const int lane = (int)opaque((uint32_t)lane_);
    const int mi = lane >> 3, r = lane & 7;
    const uint32_t buf = stg + (c & 1) * 8192;
    if (warp == 0) asm volatile("cp.async.bulk.wait_group.read 1;" ::: "memory");
    nbar_sync(barid, 128);
    if (o.blocked) {
#pragma unroll
        for (int j = 0; j < 8; j += 2)
            stsm4(buf + (j + (mi >> 1)) * 1024 + (warp * 16 + (mi & 1) * 8 + r) * 16, pk[2 * j], pk[2 * j + 1], pk[2 * j + 2], pk[2 * j + 3]);
    } else {
#pragma unroll
        for (int j = 0; j < 8; j += 2)
            stsm4t(buf + (8 * (j + (mi >> 1)) + r) * 128 + ((2 * warp + (mi & 1)) ^ r) * 16, pk[2 * j], pk[2 * j + 1], pk[2 * j + 2], pk[2 * j + 3]);
    }
    fence_proxy_async();
    nbar_sync(barid, 128);
    if (warp == 0 && elect_one()) {
        if (o.blocked)
            asm volatile("cp.async.bulk.tensor.4d.global.shared::cta.bulk_group [%0, {%2, %3, %4, %5}], [%1];"
                         :: "l"(o.map), "r"(buf), "r"(0), "r"((o.col >> 5) & 2), "r"((o.col >> 7) * 4), "r"((o.tok >> 5) + 2 * c) : "memory");
        else tma_store_2d(o.map, buf, o.col, o.tok + c * 64);
        bulk_commit();
    }
}
DEVI void p_signal(uint32_t sb, int g, int cnt, int& nsig) {
    if (elect_one()) {
        sts32(sb + PS_SIG + g * 8 + (nsig & 1) * 4, (uint32_t)cnt);
        mbar_arrive(sb + PB_S + g * 16 + (nsig & 1) * 8);
    }
    nsig++;
}
DEVI void p_release(uint32_t sb, const PRing& r) {
    if (elect_one()) mbar_arrive(sb + PB_E + (r.st ? r.st - 1 : P_STAGES - 1) * 8);
}
template <int BN, bool FIRST>
DEVI void p_kblock(float* d, uint32_t sb, int g, PRing& r) {
    mbar_wait(sb + PB_F + r.st * 8, r.ph);
    const uint64_t da = mk_desc(sb + r.w(BN == 256) + g * 8192, 16, 1024, 1), db = mk_desc(sb + r.x(BN == 256), 16, 1024, 1);
    wg_fence();
#pragma unroll
    for (int kk = 0; kk < 4; kk++) {
        if (BN == 256) { if (FIRST && kk == 0) wgmma_n256_ss<true>(d, da, db); else wgmma_n256_ss<false>(d, da + (uint64_t)(kk * 128), db + (uint64_t)(kk * 2)); }
        if (BN == 128) { if (FIRST && kk == 0) wgmma_n128_ss<true>(d, da, db); else wgmma_n128_ss<false>(d, da + (uint64_t)(kk * 128), db + (uint64_t)(kk * 2)); }
        if (BN == 64)  { if (FIRST && kk == 0) wgmma_n64_ss<true>(d, da, db); else wgmma_n64_ss<false>(d, da + (uint64_t)(kk * 128), db + (uint64_t)(kk * 2)); }
    }
    wg_commit();
    if (!FIRST) {
        wg_wait<1>();
        p_release(sb, r);
    }
    r.next(BN == 256 ? 3 : 2);
}

DEVI PTask post_claim(const PMaps& mp, unsigned E) {
    unsigned v = 0;
    if ((threadIdx.x & 31) == 0) v = atomicAdd(&g_qctr, 1u);
    return p_decode(mp.list, (int)(__shfl_sync(0xffffffffu, v, 0) - (E - 1) * (unsigned)(mp.list.run[mp.list.n - 1].w + mp.list.nworker)));
}
DEVI void post_producer(const PMaps& mp, uint32_t sb, unsigned E, bool early) {
    PRing r = {0, 0, 0};
    int ts = 0, tp = 0, used = 0;
    uint32_t big = 0;
    auto reserve = [&](int n) {
        while (used + n > P_UNITS) {
            mbar_wait(sb + PB_E + ts * 8, tp);
            used -= 2 + ((big >> ts) & 1);
            if (++ts == P_STAGES) { ts = 0; tp ^= 1; }
        }
        used += n;
        big = (big & ~(1u << r.st)) | ((uint32_t)(n & 1) << r.st);
    };
    for (int i = 0;; i++) {
        if (i > 0) mbar_wait(sb + PB_TE + (i & 1) * 8, ((i >> 1) & 1) ^ 1);
        else if (!early) nbar_sync(0, 384);
        const PTask tk = post_claim(mp, E);
        if (i == 0) { if (early) nbar_sync(0, 384); fence_proxy_async(); }
        const bool sn = tk.kind == K_SN, split = tk.kind == K_SK || sn, wide = tk.kind <= K_A4;
        const bool qk = tk.kind == K_Q || tk.kind == K_QH, ak = tk.kind == K_A4 || tk.kind == K_A3 || split;
        const int nk = split ? HD / 64 / P_SPLIT : (ak ? HD / 64 : DM / 64), kb0 = tk.c * (HD / 64 / P_SPLIT);
        const int tok0 = tk.b * (wide ? 256 : (sn ? 64 : 128)), grp = (tok0 >> 6) + (wide ? 3 : (sn ? 0 : 1));
        const uint32_t bytes = wide ? 49152 : (sn ? 24576 : 32768);
        const CUtensorMap* tx = tk.kind == K_B1 ? &mp.bx : (qk ? &mp.x : (sn ? &mp.ox64 : (ak ? &mp.ox : &mp.bo)));
        const int npre = split && (i == 0 || __any_sync(0xffffffffu, (int)(*(volatile unsigned*)&g_prog[grp] - 64 * E) < 0)) ? P_STAGES : 0;
        PRing rp = r;
        for (int kb = kb0; kb < kb0 + npre; kb++) {
            reserve(2);
            const uint32_t bar = sb + PB_F + r.st * 8;
            if (elect_one()) {
                mbar_expect_tx(bar, bytes);
                tma_load_wo(sb + r.w(false), &mp.wo, tk.a * 128, kb * 2, bar);
                tma_load_wo(sb + r.w(false) + 8192, &mp.wo, tk.a * 128 + 64, kb * 2, bar);
            }
            r.next(2);
        }
        if (tk.kind == K_B2) {
            wait_count_warp(&g_cnt[C_B1 + (tk.b >> 2)], 48 * E);
            if ((tk.b & 3) == 0 && tk.b > 0) wait_count_warp(&g_cnt[C_B1 + (tk.b >> 2) - 1], 48 * E);
        } else if (tk.kind == K_B3) wait_count_warp(&g_cnt[C_B2 + tk.b], 8 * E);
        else if (ak) wait_count_warp(&g_prog[grp], 64 * E);
        fence_proxy_global();
        for (int kb = kb0; kb < kb0 + npre; kb++) {
            if (elect_one()) tma_load_2d(sb + rp.x(false), tx, kb * 64, tok0, sb + PB_F + rp.st * 8);
            rp.next(2);
        }
        if (elect_one()) {
            sts128(sb + PS_T + (i & 1) * 16, make_uint4((uint32_t)tk.kind | ((uint32_t)tk.id << 8), (uint32_t)tk.a, (uint32_t)tk.b, (uint32_t)tk.c));
            mbar_arrive(sb + PB_TF + (i & 1) * 8);
        }
        if (tk.kind == K_END) break;
        if (tk.kind == K_B2) {
            for (int j = 0; j < 16; j++) {
                reserve(2);
                const uint32_t bar = sb + PB_F + r.st * 8;
                if (elect_one()) {
                    mbar_expect_tx(bar, 2 * 15360);
#pragma unroll
                    for (int u = 0; u < 2; u++) asm volatile("cp.async.bulk.tensor.4d.shared::cluster.global.mbarrier::complete_tx::bytes [%0], [%1, {%3, %4, %5, %6}], [%2];"
                                 :: "r"(sb + (u ? r.x(false) : r.w(false))), "l"(&mp.b40), "r"(bar), "r"(j * 64), "r"(0), "r"(u), "r"(tk.b * 32 - 8) : "memory");
                }
                r.next(2);
            }
            continue;
        }
        const CUtensorMap* tw = tk.kind == K_B1 ? &mp.bw : (qk ? &mp.wq : (ak ? &mp.wo : &mp.bwo));
        for (int kb = kb0 + npre; kb < kb0 + nk; kb++) {
            reserve(wide ? 3 : 2);
            const uint32_t aw = sb + r.w(wide), ax = sb + r.x(wide), bar = sb + PB_F + r.st * 8;
            if (elect_one()) {
                mbar_expect_tx(bar, bytes);
                if (ak || tk.kind == K_B3) {
                    tma_load_wo(aw, tw, tk.a * 128, kb * 2, bar);
                    tma_load_wo(aw + 8192, tw, tk.a * 128 + 64, kb * 2, bar);
                } else {
                    tma_load_2d(aw, tw, tk.a * 128, kb * 64, bar);
                    tma_load_2d(aw + 8192, tw, tk.a * 128 + 64, kb * 64, bar);
                }
                tma_load_2d(ax, tx, kb * 64, tok0, bar);
                if (wide) tma_load_2d(ax + 16384, tx, kb * 64, tok0 + 128, bar);
            }
            r.next(wide ? 3 : 2);
        }
        if (tk.id >= mp.list.late) { reserve(P_UNITS - 3); used -= P_UNITS - 3; }
    }
    if (elect_one()) {
        __threadfence();
        if (atomicAdd(&g_done, 1u) == E * mp.list.nworker - 1) { __threadfence(); *(volatile unsigned*)&g_epoch = E; }
    }
}
DEVI void post_helper(uint32_t sb, int g) {
    for (int n = 0;; n++) {
        mbar_wait_sleepy(sb + PB_S + g * 16 + (n & 1) * 8, (n >> 1) & 1);
        const int cnt = (int)lds32(sb + PS_SIG + g * 8 + (n & 1) * 4);
        if (cnt < 0) break;
        signal_count(&g_cnt[cnt]);
    }
}
template <int BN>
DEVI void p_narrow(const PMaps& mp, const PTask& tk, uint32_t sb, int g, int warp, PRing& r, int& nsig) {
    const int barid = 1 + g, tid = threadIdx.x;
    const bool split = BN == 64 || tk.kind == K_SK;
    constexpr int NV = BN / 16;
    float d[BN / 2];
    const int nk = split ? HD / 64 / P_SPLIT : (tk.kind == K_A3 ? HD / 64 : DM / 64);
    p_kblock<BN, true>(d, sb, g, r);
#pragma unroll 1
    for (int kb = 1; kb < nk; kb++) p_kblock<BN, false>(d, sb, g, r);
    wg_wait<0>();
    reg_fence<BN / 2>(d);
    p_release(sb, r);
    if (split) {
        const int tile = (tk.b * (BN / 64) - 2 * (16 - P_NSK)) * 8 + tk.a * (BN / 64);
        uint4* const base = g_skp + (uint32_t)(tile * P_SPLIT * 1024 + g * NV * 128 + (tid & 127));
#pragma unroll
        for (int j = 0; j < NV; j++)
            base[tk.c * NV * 256 + j * 128] = make_uint4(pack_bf16(d[8 * j], d[8 * j + 1]), pack_bf16(d[8 * j + 2], d[8 * j + 3]),
                                                         pack_bf16(d[8 * j + 4], d[8 * j + 5]), pack_bf16(d[8 * j + 6], d[8 * j + 7]));
        nbar_sync(barid, 128);
        if (warp == 0 && elect_one()) {
            unsigned old;
            asm volatile("atom.acq_rel.gpu.global.add.u32 %0, [%1], 1;" : "=r"(old) : "l"(&g_cnt_sk[tile * 2 + g]) : "memory");
            sts32(sb + PS_SK + g * 4, old % P_SPLIT);
        }
        nbar_sync(barid, 128);
        const bool last = __any_sync(0xffffffffu, lds32(sb + PS_SK + g * 4) == P_SPLIT - 1);
        nbar_sync(barid, 128);
        if (!last) return;
        uint4 v[(P_SPLIT - 1) * NV];
#pragma unroll
        for (int j = 0; j < (P_SPLIT - 1) * NV; j++) v[j] = __ldcg(base + ((tk.c + 1 + j / NV) % P_SPLIT) * NV * 256 + (j % NV) * 128);
#pragma unroll
        for (int j = 0; j < (P_SPLIT - 1) * NV; j++) {
            float* e = d + 8 * (j % NV);
            e[0] += __uint_as_float(v[j].x << 16); e[1] += __uint_as_float(v[j].x & 0xFFFF0000u);
            e[2] += __uint_as_float(v[j].y << 16); e[3] += __uint_as_float(v[j].y & 0xFFFF0000u);
            e[4] += __uint_as_float(v[j].z << 16); e[5] += __uint_as_float(v[j].z & 0xFFFF0000u);
            e[6] += __uint_as_float(v[j].w << 16); e[7] += __uint_as_float(v[j].w & 0xFFFF0000u);
        }
    }
    const bool qh = BN == 128 && tk.kind == K_QH;
    const POut o = {qh ? &mp.cq : &mp.cout, tk.a * 128 + g * 64, tk.b * BN, 0, qh};
    uint32_t q[BN / 4];
#pragma unroll
    for (int j = 0; j < BN / 4; j++) q[j] = pack_bf16(d[2 * j], d[2 * j + 1]);
    if (BN == 64 && warp == 0) bulk_wait_read();
#pragma unroll
    for (int c = 0; c < BN / 64; c++) p_store(q + 16 * c, o, c, sb + PS_STG + g * 16384, warp, tid & 31, barid);
    if (BN == 64 && warp == 0) bulk_wait_read();
    if (warp == 0 && qh) { bulk_wait_all(); p_signal(sb, g, tk.b == 0 ? C_QH : C_Q, nsig); }
}
DEVI void post_consumer(const PMaps& mp, uint32_t sb, int g, int warp) {
    const int barid = 1 + g, tid = threadIdx.x, lane = tid & 31;
    const uint32_t stg = sb + PS_STG + g * 16384;
    int nsig = 0;
    PRing r = {0, 0, 0};
    uint32_t pk[64];
    POut out;
    bool pend = false;
#pragma unroll
    for (int i = 0; i < 64; i++) pk[i] = 0u;
    for (int i = 0;; i++) {
        const uint32_t bTF = sb + PB_TF + (i & 1) * 8;
        if (pend) {
            uint32_t now;
            asm volatile("{.reg .pred p, q; mbarrier.test_wait.parity.shared::cta.b64 p, [%1], %2; bar.red.and.pred q, %3, 128, p; selp.u32 %0, 1, 0, q;}"
                         : "=r"(now) : "r"(bTF), "r"((i >> 1) & 1), "r"(barid) : "memory");
            if (__any_sync(0xffffffffu, !now || (lds32(sb + PS_T + (i & 1) * 16) & 255u) > K_A4)) {
#pragma unroll
                for (int c = 0; c < 4; c++) p_store(pk + 16 * c, out, c, stg, warp, lane, barid);
                if (warp == 0 && out.cnt != C_NONE) { bulk_wait_all(); p_signal(sb, g, out.cnt, nsig); }
                pend = false;
            }
        }
        mbar_wait(bTF, (i >> 1) & 1);
        uint4 tw = lds128(sb + PS_T + (i & 1) * 16);
        tw = make_uint4(__shfl_sync(0xffffffffu, tw.x, 0), __shfl_sync(0xffffffffu, tw.y, 0), __shfl_sync(0xffffffffu, tw.z, 0), __shfl_sync(0xffffffffu, tw.w, 0));
        mbar_arrive(sb + PB_TE + (i & 1) * 8);
        const PTask tk = {(int)(tw.x & 255u), (int)tw.y, (int)tw.z, (int)tw.w, 0};
        if (tk.kind == K_END) break;
        if (tk.kind <= K_A4) {
            float d[128];
            const int nk = tk.kind == K_A4 ? HD / 64 : DM / 64;
            p_kblock<256, true>(d, sb, g, r);
            if (pend) p_store(pk, out, 0, stg, warp, lane, barid);
#pragma unroll
            for (int c = 1; c < 4; c++) {
                p_kblock<256, false>(d, sb, g, r);
                if (pend) p_store(pk + 16 * c, out, c, stg, warp, lane, barid);
            }
#pragma unroll 1
            for (int kb = 4; kb < nk; kb++) {
                p_kblock<256, false>(d, sb, g, r);
                if (kb == 6 && pend && warp == 0 && out.cnt != C_NONE) { bulk_wait_all(); p_signal(sb, g, out.cnt, nsig); }
            }
            wg_wait<0>();
            reg_fence<128>(d);
            p_release(sb, r);
#pragma unroll
            for (int j = 0; j < 64; j++) pk[j] = pack_bf16(d[2 * j], d[2 * j + 1]);
            out.map = tk.kind == K_Q ? &mp.cq : (tk.kind == K_B1 ? &mp.cb : &mp.cout);
            out.col = tk.a * 128 + g * 64 + (tk.kind == K_B3 ? DM : 0);
            out.tok = tk.b * 256;
            out.cnt = tk.kind == K_Q ? C_Q + tk.b : (tk.kind == K_B1 ? C_B1 + tk.b : C_NONE);
            out.blocked = tk.kind == K_Q;
            pend = true;
        } else if (tk.kind == K_B2) {
#pragma unroll 2
            for (int j = 0; j < 16; j++) {
                mbar_wait(sb + PB_F + r.st * 8, r.ph);
                const uint32_t a = sb + (g ? r.x(false) : r.w(false));
                battn_warp(a, sb + PB_E + r.st * 8, tk.b * 32, g, j * 2 + (warp >> 1), warp >> 1, warp & 1, lane);
                r.next(2);
            }
            nbar_sync(barid, 128);
            if (warp == 0) p_signal(sb, g, C_B2 + (tk.b >> 2), nsig);
#pragma unroll
            for (int j = 0; j < 64; j++) pk[j] = 0u;
        } else {
            if (tk.kind == K_SN) p_narrow<64>(mp, tk, sb, g, warp, r, nsig); else p_narrow<128>(mp, tk, sb, g, warp, r, nsig);
#pragma unroll
            for (int j = 0; j < 64; j++) pk[j] = 0u;
        }
    }
    if (warp == 0) { bulk_wait_all(); p_signal(sb, g, -1, nsig); }
}
DEVI void post_init(uint32_t sb) {
    for (int i = 0; i < P_STAGES; i++) { mbar_init(sb + PB_F + i * 8, 1); mbar_init(sb + PB_E + i * 8, 8); }
    for (int i = 0; i < 2; i++) { mbar_init(sb + PB_TF + i * 8, 1); mbar_init(sb + PB_TE + i * 8, 256); }
    for (int i = 0; i < 4; i++) mbar_init(sb + PB_S + i * 8, 1);
    fence_mbar_init();
}

constexpr unsigned long long R_TORD_PACK = 0xafe9354d2c81760bull;
__host__ __device__ constexpr int r_tord(int pos) { return (int)((R_TORD_PACK >> (4 * pos)) & 15ull); }
__host__ __device__ constexpr int r_tinv(int T) { for (int p = 0; p < 16; p++) if (r_tord(p) == T) return p; return 0; }
__host__ __device__ constexpr bool r_pos_ss(int pos) { return (0xC0Eu >> r_tord(pos)) & 1u; }
constexpr unsigned long long r_table(bool since) {
    unsigned long long v = 0; int n = 0, d = 7;
    for (int p = 0; p < 16; p++) { n += r_pos_ss(p); d = r_pos_ss(p) ? 0 : (d < 7 ? d + 1 : 7); v |= (unsigned long long)(since ? d : n) << (4 * p); }
    return v;
}
constexpr unsigned long long R_CNT_PACK = r_table(false), R_SINCE_PACK = r_table(true);
__host__ __device__ constexpr int r_ss(int pos) { return pos ? (int)((R_CNT_PACK >> (4 * pos - 4)) & 15ull) : 0; }
__host__ __device__ constexpr int r_rs(int pos) { return pos - r_ss(pos); }
__host__ __device__ constexpr int r_since(int pos) { return (int)((R_SINCE_PACK >> (4 * pos)) & 15ull); }
constexpr int R_NRS = 11, R_NSS = 5;
constexpr int R_G1 = 3, R_G2 = 9, R_G3 = 12;
#define REG_KB 232
constexpr int X_SLOTS = 4;
constexpr int X_NST = 8;

constexpr int RS_WSS  = 0;
constexpr int RS_WO   = RS_WSS + R_NSS * 16384;
constexpr int RS_MEM  = RS_WO + 5 * 16384;
constexpr int RS_O    = RS_MEM + 16384;
constexpr int RS_SX   = RS_O + 2048;
constexpr int RS_BAR  = RS_SX + 2048;
constexpr int RS_TAIL = RS_BAR + 1024;
constexpr int RS_WO5  = RS_TAIL;
constexpr int RS_K    = RS_WO5 + 16384;
constexpr int RS_V    = RS_K + 10240;
constexpr int RS_Q    = RS_V + 10240;
constexpr int RS_QX   = RS_Q + 2048;
constexpr int RS_QEND = RS_QX + 8192;
constexpr int RS_X    = RS_TAIL;
constexpr int X_PITCH = X_SLOTS * 4096;
constexpr int RS_XD   = RS_X + 2 * X_PITCH;
constexpr int RS_WX   = RS_XD + 8192;
constexpr int RS_XE   = RS_WX + 4096;
constexpr int RS_KEND = RS_XE + 2048;
constexpr int RS_EV   = RS_BAR + 256;
constexpr int R_SMEM  = RS_KEND > RS_QEND ? RS_KEND : RS_QEND;
static_assert(R_SMEM <= 232448 && P_SMEM <= R_SMEM, "smem");
static_assert(RS_TAIL % 1024 == 0 && RS_MEM % 1024 == 0, "alignment");

constexpr int RB_G = RS_BAR, RB_K = RS_BAR + 24, RB_V = RS_BAR + 32, RB_KV = RS_BAR + 40, RB_QX = RS_BAR + 48, RB_O = RS_BAR + 56;
constexpr int RB_ATT = RS_BAR + 64, RB_W = RS_BAR + 72, RB_SF = RS_BAR + 80, RB_SE = RB_SF + 40, RB_XF = RB_SE + 40;
constexpr int RB_VX = RB_XF + 48, RB_WO = RB_XF + 56, RB_T = RB_XF + 64, RB_G3 = RB_XF + 72, RS_INV = RB_XF + 16;
static_assert(RB_G3 + 8 <= RS_EV, "barriers");
constexpr uint32_t SB0 = 1024;
__host__ __device__ constexpr uint32_t cdesc(uint32_t off, uint32_t lbo) { return ((SB0 + off) >> 4) | ((lbo >> 4) << 16); }
#define SCHED_FENCE() __syncwarp()
constexpr int NB_BIG = 1, NB_Q = 2, NB_AUX = 3, NB_WO = 4, NB_XS = 5, NB_WG = 6, NB_PAIR = 8, NB_PRO = 12;

DEVI int tid_now() { int t; asm volatile("mov.u32 %0, %%tid.x;" : "=r"(t)); return t; }
DEVI uint32_t a_frag_off(int lane, int warp) { return (uint32_t)((((lane >> 4) * 8 + (lane & 7)) * 128) + (((2 * warp + ((lane >> 3) & 1)) ^ (lane & 7)) * 16)); }
DEVI uint32_t b_frag_off(int lane) { return (uint32_t)((lane & 3) * 64 + (((lane >> 2) * 8) ^ ((lane & 2) * 16))); }
DEVI void lds_b(uint32_t* b, uint32_t a) {
    asm volatile("ld.shared.v2.u32 {%0,%1}, [%2];" : "=r"(b[0]), "=r"(b[1]) : "r"(a) : "memory");
    asm volatile("ld.shared.v2.u32 {%0,%1}, [%2];" : "=r"(b[2]), "=r"(b[3]) : "r"(a + 256) : "memory");
}
DEVI uint32_t clk32() { unsigned long long c; asm volatile("mov.u64 %0, %%clock64;" : "=l"(c)); return (uint32_t)c; }

__host__ __device__ constexpr int x_pair(int j) { return j < 2 || j > 5 ? j : (j == 2 ? 5 : j - 1); }
DEVI void x_load(uint32_t sb, int seg, int j, int g, const CUtensorMap* tmX) {
    const uint32_t bar = sb + RB_XF + g * 8;
    mbar_expect_tx(bar, 4096);
    tma_load_3d(sb + RS_X + g * X_PITCH + (j % X_SLOTS) * 4096, tmX + (j == 3), g * 32, seg * 32, x_pair(j) * 2, bar);
    if (j == 3) tma_load_3d(sb + RS_SX + g * (RS_XE - RS_SX), tmX + 1, g * 32, seg * 32, x_pair(3) * 2 + 1, bar);
}
DEVI void x_refill(uint32_t sb, int seg, int j, int g, int warp, const CUtensorMap* tmX) {
    const int sn = j + X_SLOTS < X_NST ? seg : seg + 1;
    if (warp == (j & 3) && sn < NSEG) {
        if (elect_one()) x_load(sb, sn, (j + X_SLOTS) % X_NST, g, tmX);
    }
}
template <int J, int Q0, int Q1, int DQ>
DEVI void x_steps(float* xa, const uint32_t* w, int g0) {
    const int g = (int)opaque((uint32_t)g0);
    const uint32_t dW0 = cdesc(RS_WSS, 16) + g * 768, dW1 = cdesc(RS_WSS + 8192, 16) - g * 256;
#pragma unroll
    for (int q = Q0; q < Q1; q += DQ) {
        const int pos = r_tinv(2 * x_pair(J) + (q >> 2)), kk = (q >> 1) & 1, mt = q & 1;
        const uint32_t db = (J == 3 && q >= 4 ? cdesc(RS_SX, 16) + g * ((RS_XE - RS_SX) >> 4)
                                                    : cdesc(RS_X + (J % X_SLOTS) * 4096, 16) + g * (X_PITCH >> 4) + (q >> 2) * 128) + kk * 2;
        if (J == 0 && q < 2)   wgmma_n32_rs_first(xa + 16 * mt, &w[((r_rs(pos) * 2 + kk) * 2 + mt) * 4], db);
        else if (J == 0 && q == 3) wgmma_n32_ss(xa + 16, cdesc(RS_WX, 16) + g * 128, db);
        else if (r_pos_ss(pos)) wgmma_n32_ss(xa + 16 * mt, (mt ? dW1 : dW0) + r_ss(pos) * 1024 + kk * 128, db);
        else                   wgmma_n32_rs(xa + 16 * mt, &w[((r_rs(pos) * 2 + kk) * 2 + mt) * 4], db);
    }
}
DEVI void x_first(float* xa, const uint32_t* w, uint32_t sb, int seg, int g0, int warp, const CUtensorMap* tmX) {
    wg_fence();
    x_steps<0, 0, 8, 1>(xa, w, g0); wg_commit();
    x_steps<1, 0, 8, 1>(xa, w, g0); wg_commit();
    x_steps<2, 0, 8, 1>(xa, w, g0); wg_commit();
    x_steps<3, 0, 4, 1>(xa, w, g0); wg_commit();
    const int g = (int)opaque((uint32_t)g0);
    wg_wait<3>(); x_refill(sb, seg, 0, g, warp, tmX);
    wg_wait<2>(); x_refill(sb, seg, 1, g, warp, tmX);
    wg_wait<1>(); x_refill(sb, seg, 2, g, warp, tmX);
    wg_wait<0>(); x_refill(sb, seg, 3, g, warp, tmX);
    reg_fence<32>(xa);
    if (seg > 0) nbar_sync(NB_Q, 384);
    wg_fence();
    x_steps<3, 4, 8, 1>(xa, w, g0); wg_commit();
    mbar_wait(sb + RB_XF + g * 8, 1);
}
DEVI void x_second(float* xa, uint32_t* a, uint32_t aA0, const uint32_t* w, uint32_t sb, int seg, int g0, int warp, const CUtensorMap* tmX) {
    wg_fence();
    x_steps<4, 0, 8, 1>(xa, w, g0); wg_commit();
    x_steps<5, 1, 8, 2>(xa, w, g0); x_steps<6, 1, 8, 2>(xa, w, g0); x_steps<7, 1, 8, 2>(xa, w, g0); wg_commit();
    x_steps<5, 0, 8, 2>(xa, w, g0); x_steps<6, 0, 8, 2>(xa, w, g0); x_steps<7, 0, 8, 2>(xa, w, g0); wg_commit();
    const int g = (int)opaque((uint32_t)g0);
    wg_wait<2>(); x_refill(sb, seg, 4, g, warp, tmX);
    SCHED_FENCE();
#pragma unroll
    for (int q = 0; q < 4; q++) ldsm4t(a + 4 * q, aA0 + (q & 1) * (8192 - g * 16384) + (q >> 1) * 2048);
    SCHED_FENCE();
    wg_wait<1>();
    reg_fence<16>(xa + 16);
}
DEVI void x_finish(float* xa, uint32_t sb, int g, int warp, int lane) {
    const uint32_t d = sb + RS_XD + (lane >> 4) * 2048 + warp * 256 + (lane & 15) * 16;
#pragma unroll
    for (int i = 0; i < 2; i++) {
        const float* x = xa + 16 + 8 * i;
        sts128(d + (g ^ 1) * 1024 + i * 4096, make_uint4(pack_bf16(x[0], x[1]), pack_bf16(x[2], x[3]), pack_bf16(x[4], x[5]), pack_bf16(x[6], x[7])));
    }
    nbar_sync(NB_PAIR + warp, 64);
    const uint4 v0 = lds128(d + g * 1024), v1 = lds128(d + g * 1024 + 4096);
    const uint32_t u[8] = {v0.x, v0.y, v0.z, v0.w, v1.x, v1.y, v1.z, v1.w};
    wg_wait<0>();
    reg_fence<16>(xa);
    uint32_t p[8];
#pragma unroll
    for (int j = 0; j < 8; j++) p[j] = add_bf16x2(pack_bf16(xa[2 * j], xa[2 * j + 1]), u[j]);
    __syncwarp();
    stsm4(d + g * 1024, p[0], p[1], p[2], p[3]);
    stsm4(d + g * 1024 + 4096, p[4], p[5], p[6], p[7]);
    nbar_arrive(NB_XS, 256 + 32);
}
DEVI void x_send(uint32_t sb, int seg, uint32_t rank, const CUtensorMap* tmX) {
    auto refill = [&]() {
        if (seg + 1 < NSEG && elect_one()) {
#pragma unroll
            for (int j = 1; j < 4; j++) { x_load(sb, seg + 1, j, 0, tmX); x_load(sb, seg + 1, j, 1, tmX); }
        }
        __syncwarp();
    };
    mbar_wait(sb + RB_ATT, (seg - 1) & 1);
    nbar_sync(NB_XS, 256 + 32);
    if (rank == 2) { refill(); mbar_wait(sb + RB_G3, (seg - 1) & 1); }
    if (elect_one()) {
        fence_proxy_async();
        bulk_copy_s2c(mapa(sb + (rank == 1 ? RS_K : RS_V) + 2048, 0), sb + RS_XD, 8192, mapa(sb + (rank == 1 ? RB_KV : RB_VX), 0));
    }
    __syncwarp();
    if (rank == 1) refill();
}

template <bool XP>
DEVI void mem_pass(float* c0, float* c1, uint32_t* a, const uint32_t* w, uint32_t sb, uint32_t aA0, uint32_t aB, int g, int warp, int s) {
    const uint32_t aA1 = aA0 + 8192 - g * 16384, par = (s - 1) & 1;
    uint32_t b[3][4], e[4];
    float d0[4], d1[4];
    if (XP) ldsm4t(e, aA0 + opaque((RS_WX - RS_WSS) - g * (8192 + 2048)));
#pragma unroll
    for (int q = XP ? 4 : 0; q < 4; q++) ldsm4t(a + 4 * q, ((q & 1) ? aA1 : aA0) + (q >> 1) * 2048);
#pragma unroll
    for (int i = 0; i < 4; i++) { c0[i] = 0.f; c1[i] = 0.f; d0[i] = 0.f; d1[i] = 0.f; }
    EV(EV_BIG0, s, 0);
    mbar_wait(sb + RB_G, par);
    EV(EV_BIG0, s, 1);
    lds_b(b[0], aB + r_tord(0) * 1024);
    lds_b(b[1], aB + r_tord(1) * 1024);
    bool in = false;
#pragma unroll
    for (int pos = 0; pos < 16; pos++) {
        if (pos + 2 < 16) {
            if (pos + 2 == R_G1 && !in) mbar_wait(sb + RB_G + 8, par);
            if (pos + 2 == R_G2 && !in) mbar_wait(sb + RB_G + 16, par);
            if (pos + 2 == R_G3) { if (!in) mbar_wait(sb + RB_G3, par); EV(EV_BIG0, s, 2); }
            lds_b(b[(pos + 2) % 3], aB + r_tord(pos + 2) * 1024);
        }
        if (pos + 3 == R_G1) in = mbar_try(sb + RB_G + 8, par);
        if (pos + 3 == R_G2) in = mbar_try(sb + RB_G + 16, par);
        if (pos + 3 == R_G3) in = mbar_try(sb + RB_G3, par);
        if (XP && pos == 14) in = mbar_try(sb + RB_ATT, par);
        const uint32_t* bb = b[pos % 3];
        const uint32_t* aa = r_pos_ss(pos) ? a : &w[r_rs(pos) * 16];
        mma16816(c1, aa + 4, bb[0], bb[1]);
        mma16816(d1, XP && r_tord(pos) == 0 ? e : aa + 12, bb[2], bb[3]);
        mma16816(c0, aa, bb[0], bb[1]);
        mma16816(d0, aa + 8, bb[2], bb[3]);
        if (r_ss(pos + 1) > 0 && r_ss(pos + 1) < R_NSS) {
            const uint32_t nx = r_ss(pos + 1) * 16384;
            if (r_since(pos) == 0) { ldsm4t(a + 4, aA1 + nx); ldsm4t(a + 12, aA1 + nx + 2048); }
            else if (r_since(pos) < 3) ldsm4t(a + 8 * (r_since(pos) - 1), aA0 + nx + (r_since(pos) - 1) * 2048);
        }
        SCHED_FENCE();
    }
    if (XP && !in) mbar_wait(sb + RB_ATT, par);
#pragma unroll
    for (int i = 0; i < 4; i++) { c1[i] += d1[i]; c0[i] += d0[i]; }
}

DEVI uint32_t k_frag_off(int lane) { return (uint32_t)((((lane >> 3) & 1) * 16 + (lane >> 4) * 8 + (lane & 7)) * 16); }
DEVI uint32_t v_frag_off(int lane) { return (uint32_t)(((lane >> 3) & 1) * 2048 + ((lane >> 4) * 8 + (lane & 7)) * 16); }
DEVI void pv_pair(float (*o)[4], const uint32_t* p, const uint32_t* v) {
#pragma unroll
    for (int n = 0; n < 4; n++) mma16816(o[n], p, v[2 * n], v[2 * n + 1]);
}
DEVI void pv_single(float (*o)[4], const uint32_t* p, const uint32_t* v) {
#pragma unroll
    for (int n = 0; n < 4; n++) mma1688(o[n], p[0], p[1], v[n]);
}
DEVI void s_tile(const uint32_t* qa, const uint32_t* k, float& s0, float& s1) {
    float c[4][4];
#pragma unroll
    for (int q = 0; q < 4; q++) { c[q][0] = c[q][1] = c[q][2] = c[q][3] = 0.f; }
#pragma unroll
    for (int q = 0; q < 4; q++) {
        mma16816(c[2 * (q & 1)], qa + 4 * q, k[4 * q], k[4 * q + 1]);
        mma16816(c[2 * (q & 1) + 1], qa + 4 * q, k[4 * q + 2], k[4 * q + 3]);
    }
    s0 = (c[0][0] + c[1][2]) + (c[2][0] + c[3][2]);
    s1 = (c[0][1] + c[1][3]) + (c[2][1] + c[3][3]);
}
DEVI void mem_scores(uint32_t sb, int s, int lane) {
    const uint32_t ka = sb + RS_K + k_frag_off(lane), sa = sb + RS_SX + 1024 + lane * 8;
    uint32_t qa[16], km[16];
    nbar_sync(NB_Q, 256);
#pragma unroll
    for (int q = 0; q < 4; q++) ldsm4t(qa + 4 * q, sb + RS_Q + q * 512 + lane * 16);
    mbar_wait(sb + RB_K, s & 1);
#pragma unroll
    for (int q = 0; q < 4; q++) ldsm4t(km + 4 * q, ka + q * 512);
    SCHED_FENCE();
    float s0, s1;
    s_tile(qa, km, s0, s1);
    asm volatile("st.shared.v2.f32 [%0], {%1,%2};" :: "r"(sa), "f"(s0 * SCALE_LOG2E), "f"(s1 * SCALE_LOG2E) : "memory");
    nbar_arrive(NB_XS, 128 + 32);
}
DEVI float quad_max(float m) {
    return fmaxf(fmaxf(m, __shfl_xor_sync(0xffffffffu, m, 1)), fmaxf(__shfl_xor_sync(0xffffffffu, m, 2), __shfl_xor_sync(0xffffffffu, m, 3)));
}
DEVI void mem_attn(uint32_t sb, int s, int warp, int lane) {
    const uint32_t va = sb + RS_V + warp * 512, sa = sb + RS_SX + lane * 8;
    [[maybe_unused]] constexpr int g = 0;
    float o[4][4], mx, l = 0.f;
    {
        const uint32_t ka = sb + RS_K + k_frag_off(lane) + (1 + warp) * 2048;
        uint32_t qa[16], kx[16];
        const bool in = mbar_try(sb + RB_KV, s & 1);
        nbar_sync(NB_Q, 256);
        EV(EV_BIG0 && lds32(sb + RS_Q) != 0x12345678u, s, 8);
#pragma unroll
        for (int q = 0; q < 4; q++) ldsm4t(qa + 4 * q, sb + RS_Q + q * 512 + lane * 16);
        if (!in) mbar_wait(sb + RB_KV, s & 1);
#pragma unroll
        for (int q = 0; q < 4; q++) ldsm4t(kx + 4 * q, ka + q * 512);
        const bool vin = mbar_try(sb + RB_VX, s & 1);
        SCHED_FENCE();
        float s0, s1;
        s_tile(qa, kx, s0, s1);
        asm volatile("st.shared.v2.f32 [%0], {%1,%2};" :: "r"(sa + warp * 256), "f"(s0 * SCALE_LOG2E), "f"(s1 * SCALE_LOG2E) : "memory");
        nbar_sync(NB_WG, 128);
        float sc[8];
#pragma unroll
        for (int n = 0; n < 4; n++) { const float2 v = lds64f(sa + n * 256); sc[2 * n] = v.x; sc[2 * n + 1] = v.y; }
        if (!vin) mbar_wait(sb + RB_VX, s & 1);
        mx = quad_max(fmaxf(fmaxf(fmaxf(sc[0], sc[1]), fmaxf(sc[2], sc[3])), fmaxf(fmaxf(sc[4], sc[5]), fmaxf(sc[6], sc[7]))));
        uint32_t vx[16], p[8];
#pragma unroll
        for (int q = 0; q < 4; q++) ldsm4(vx + 4 * q, va + 2048 + (q >> 1) * 4096 + (q & 1) * 256 + v_frag_off(lane));
#pragma unroll
        for (int n = 0; n < 4; n++) {
            const float e0 = ex2(sc[2 * n] - mx), e1 = ex2(sc[2 * n + 1] - mx);
            l += e0 + e1;
            p[2 * n] = pack_bf16(e0, e1); p[2 * n + 1] = __float_as_uint(e0);
        }
#pragma unroll
        for (int n = 0; n < 4; n++) { o[n][0] = o[n][1] = o[n][2] = o[n][3] = 0.f; }
        pv_pair(o, p, vx);
        pv_pair(o, p + 4, vx + 8);
    }
    const uint32_t dst = sb + RS_O + warp * 512 + (lane & 3) * 128 + (lane >> 2) * 16, dl = sb + RS_INV + (lane & 28);
    EV(EV_BIG0, s, 5);
    mbar_wait(sb + RB_V, s & 1);
    uint32_t vm[4], p[2];
    ldsm4(vm, va + lane * 16);
    nbar_sync(NB_XS, 128 + 32);
    EV(EV_BIG0 && lds32(sb + RS_Q) != 0x12345678u, s, 9);
    const float2 sm = lds64f(sa + 1024);
    const float s0 = sm.x, s1 = sm.y;
    const float m = quad_max(fmaxf(mx, fmaxf(s0, s1)));
    const float e0 = ex2(s0 - m), e1 = ex2(s1 - m), f = ex2(mx - m);
    p[0] = pack_bf16(e0, e1); p[1] = __float_as_uint(e0);
#pragma unroll
    for (int n = 0; n < 4; n++) { o[n][0] *= f; o[n][1] *= f; }
    pv_single(o, p, vm);
    l = fmaf(l, f, e0 + e1);
    l = (l + __shfl_xor_sync(0xffffffffu, l, 1)) + (__shfl_xor_sync(0xffffffffu, l, 2) + __shfl_xor_sync(0xffffffffu, l, 3));
    const uint4 u = make_uint4(pack_bf16(o[0][0], o[0][1]), pack_bf16(o[1][0], o[1][1]), pack_bf16(o[2][0], o[2][1]), pack_bf16(o[3][0], o[3][1]));
    st_async128(mapa(dst, 1), u.x, u.y, u.z, u.w, mapa(sb + RB_O, 1));
    st_async128(mapa(dst, 2), u.x, u.y, u.z, u.w, mapa(sb + RB_O, 2));
    st_async32(mapa(dl, 1 + (warp & 1)), __float_as_uint(l), mapa(sb + RB_O, 1 + (warp & 1)));
    sts128(dst, u);
    sts32(dl, __float_as_uint(l));
    __syncwarp();
    if (elect_one()) mbar_arrive(sb + RB_O);
    EV(EV_BIG0, s, 15);
}

DEVI void ta_mask(float* c, int cw, int lane) {
    const int mt = cw >= 3, over = 8 * (cw - 3 * mt - 1) + 2 * (lane & 3) - 16 * mt - (lane >> 2);
    if (over > 0) c[0] = -INFINITY;
    if (over >= 0) c[1] = -INFINITY;
    if (over > 8) c[2] = -INFINITY;
    if (over >= 8) c[3] = -INFINITY;
}
DEVI void ta_scores(uint32_t sb, int seg, int warp, int lane) {
    const int tx = warp == 3 ? 0 : (warp == 2 ? 1 : 4 + 2 * warp), ty = warp == 3 ? 3 : tx + 1;
    const uint32_t qa = sb + RS_QX + ((warp < 2 ? 2 : 0) + ((lane >> 3) & 1)) * 2048 + ((lane >> 4) * 8 + (lane & 7)) * 16;
    const uint32_t ka = sb + RS_K + (warp < 2 ? tx - 3 : tx) * 2048 + lane * 16;
    float x[4] = {0.f, 0.f, 0.f, 0.f}, y[4] = {0.f, 0.f, 0.f, 0.f};
    mbar_wait(sb + RB_QX, seg & 1);
    if (warp < 3) {
#pragma unroll
        for (int j = 0; j < 4; j++) {
            uint32_t a0[4], a1[4], bx[4], by[4];
            ldsm4t(a0, qa + j * 512); ldsm4t(bx, ka + j * 512); ldsm4t(by, ka + 2048 + j * 512); ldsm4t(a1, qa + j * 512 + 256);
            mma16816(x, a0, bx[0], bx[1]); mma16816(y, a0, by[0], by[1]);
            mma16816(x, a1, bx[2], bx[3]); mma16816(y, a1, by[2], by[3]);
        }
        ta_mask(x, tx, lane); ta_mask(y, ty, lane);
    } else {
        mbar_wait(sb + RB_K, seg & 1);
#pragma unroll
        for (int j = 0; j < 4; j++) {
            uint32_t a0[4], a1[4], a2[4], a3[4], b[4];
            ldsm4t(a0, qa + j * 512); ldsm4t(b, ka + j * 512); ldsm4t(a2, qa + 4096 + j * 512);
            ldsm4t(a1, qa + j * 512 + 256); ldsm4t(a3, qa + 4096 + j * 512 + 256);
            mma16816(x, a0, b[0], b[1]); mma16816(y, a2, b[0], b[1]);
            mma16816(x, a1, b[2], b[3]); mma16816(y, a3, b[2], b[3]);
        }
    }
    nbar_sync(NB_WG + 1, 128);
    asm volatile("st.shared.v2.f32 [%0], {%1,%2};" :: "r"(sb + RS_QX + 4096 + tx * 256 + lane * 8), "f"(fmaxf(x[0], x[1])), "f"(fmaxf(x[2], x[3])) : "memory");
    asm volatile("st.shared.v2.f32 [%0], {%1,%2};" :: "r"(sb + RS_QX + 4096 + ty * 256 + lane * 8), "f"(fmaxf(y[0], y[1])), "f"(fmaxf(y[2], y[3])) : "memory");
    nbar_sync(NB_WG + 1, 128);
    float m[4] = {-INFINITY, -INFINITY, -INFINITY, -INFINITY};
#pragma unroll
    for (int n = 0; n < 8; n++) {
        if (n < 3 ? warp >= 2 : warp != 2) {
            const float2 v = lds64f(sb + RS_QX + 4096 + n * 256 + lane * 8);
            m[n < 3 ? 0 : 2] = fmaxf(m[n < 3 ? 0 : 2], v.x); m[n < 3 ? 1 : 3] = fmaxf(m[n < 3 ? 1 : 3], v.y);
        }
    }
#pragma unroll
    for (int o = 1; o < 4; o <<= 1) {
#pragma unroll
        for (int i = 0; i < 4; i++) m[i] = fmaxf(m[i], __shfl_xor_sync(0xffffffffu, m[i], o));
    }
    const float x0 = warp < 2 ? m[2] : m[0], x1 = warp < 2 ? m[3] : m[1], y0 = warp == 2 ? m[0] : m[2], y1 = warp == 2 ? m[1] : m[3];
    auto e = [](float v, float mx) { return ex2((v - mx) * SCALE_LOG2E); };
    sts64(sb + RS_QX + tx * 256 + lane * 8, pack_bf16(e(x[0], x0), e(x[1], x0)), pack_bf16(e(x[2], x1), e(x[3], x1)));
    sts64(sb + RS_QX + ty * 256 + lane * 8, pack_bf16(e(y[0], y0), e(y[1], y0)), pack_bf16(e(y[2], y1), e(y[3], y1)));
}
template <int MT>
DEVI void ta_output(uint32_t sb, int seg, int head, int j, int lane) {
    const uint32_t pa = sb + RS_QX + MT * 768 + lane * 8, vb = sb + RS_V + j * 512;
    uint32_t p[6 + 4 * MT], v[12 + 8 * MT];
#pragma unroll
    for (int n = 0; n < 3 + 2 * MT; n++)
        asm volatile("ld.shared.v2.u32 {%0,%1}, [%2];" : "=r"(p[2 * n]), "=r"(p[2 * n + 1]) : "r"(pa + n * 256) : "memory");
#pragma unroll
    for (int q = 0; q < 2 + 2 * MT; q++) ldsm4(v + 4 * q, vb + (q >> 1) * 4096 + (q & 1) * 256 + v_frag_off(lane));
    ldsm4(v + 8 + 8 * MT, vb + 4096 + MT * 4096 + lane * 16);
    float o[4][4], l[4] = {0.f, 0.f, 0.f, 0.f};
#pragma unroll
    for (int n = 0; n < 4; n++) { o[n][0] = o[n][1] = o[n][2] = o[n][3] = 0.f; }
    mma16816(l, p, 0x3F803F80u, 0x3F803F80u);
    pv_pair(o, p, v);
    if (MT) { mma16816(l, p + 4, 0x3F803F80u, 0x3F803F80u); pv_pair(o, p + 4, v + 8); }
    mma1688(l, p[4 + 4 * MT], p[5 + 4 * MT], 0x3F803F80u);
    pv_single(o, p + 4 + 4 * MT, v + 8 + 8 * MT);
    const float i0 = rcp_fast(l[0]), i1 = rcp_fast(l[2]);
    bf16* dst = g_ox + (uint32_t)((seg * 32 + MT * 16 + (lane >> 2)) * HD + head * DH + j * 32 + (lane & 3) * 8);
    asm volatile("st.global.v4.u32 [%0], {%1,%2,%3,%4};" :: "l"(dst), "r"(pack_bf16(o[0][0] * i0, o[0][1] * i0)), "r"(pack_bf16(o[1][0] * i0, o[1][1] * i0)),
                 "r"(pack_bf16(o[2][0] * i0, o[2][1] * i0)), "r"(pack_bf16(o[3][0] * i0, o[3][1] * i0)) : "memory");
    asm volatile("st.global.v4.u32 [%0], {%1,%2,%3,%4};" :: "l"(dst + 8 * HD), "r"(pack_bf16(o[0][2] * i1, o[0][3] * i1)), "r"(pack_bf16(o[1][2] * i1, o[1][3] * i1)),
                 "r"(pack_bf16(o[2][2] * i1, o[2][3] * i1)), "r"(pack_bf16(o[3][2] * i1, o[3][3] * i1)) : "memory");
}

template <bool XP>
DEVI void big_main(const uint32_t* w, const uint32_t sb, const int g, const int warp, const uint32_t rank, const int head,
                   const CUtensorMap* tmX, const bf16* xg, const unsigned E) {
    float xa[32];
    uint32_t a[16];
    const uint32_t aB = __shfl_sync(0xffffffffu, sb + RS_MEM + (g * 32 + (tid_now() & 31)) * 16, tid_now() & 31);
#define lane0 ((int)(opaque(aB) >> 4) & 31)
    const uint32_t aA0 = sb + RS_WSS + g * (8192 + 4096) + a_frag_off(lane0, warp);
    const uint32_t aBf = sb + RS_MEM + g * 512 + b_frag_off(lane0);
    if constexpr (XP) {
        mbar_wait(sb + RB_XF + g * 8, 0);
        x_first(xa, w, sb, 0, g, warp, tmX);
        x_second(xa, a, aA0, w, sb, 0, g, warp, tmX);
        x_finish(xa, sb, g, warp, lane0);
    }
    nbar_sync(NB_BIG, 256);
    for (int s = 0; s < NSEG; s++) {
        float c0[4], c1[4];
        mem_pass<XP>(c0, c1, a, w, sb, aA0, aBf, g, warp, s);
        EV(EV_BIG0 && c0[0] != 1.2345e30f, s, 3);
        bool xin = true;
        const uint32_t xs = sb + RS_O + warp * 256 + lane0 * 8;
        sts64(xs + g * 1024, pack_bf16(c1[0], c1[1]), pack_bf16(c1[2], c1[3]));
        {
            const uint32_t d = sb + (XP ? (rank == 1 ? RS_K : RS_V) : RS_Q) + (g * 4 + warp) * 256 + lane0 * 4;
            const uint32_t rbar = XP ? mapa(sb + (rank == 1 ? RB_K : RB_V), 0) : 0u;
            nbar_sync(NB_PAIR + warp, 64);
            const float2 v = lds64f(xs + (g ^ 1) * 1024);
            if (XP) xin = mbar_test(sb + RB_XF + g * 8, 0);
            const uint32_t p0 = add_bf16x2(pack_bf16(c0[0], c0[1]), __float_as_uint(v.x)), p1 = add_bf16x2(pack_bf16(c0[2], c0[3]), __float_as_uint(v.y));
            if constexpr (XP) { st_async32(mapa(d, 0), p0, rbar); st_async32(mapa(d + 128, 0), p1, rbar); }
            else { sts32(d, p0); sts32(d + 128, p1); }
            EV(EV_BIG0, s, 4);
        }
        if constexpr (XP) {
            if (s == NSEG - 1) break;
            if (!xin) mbar_wait(sb + RB_XF + g * 8, 0);
            x_first(xa, w, sb, s + 1, g, warp, tmX);
            EV(EV_BIG0, s, 5);
            EVCAL(s);
            nbar_sync(NB_WO, 384);
            EV(EV_BIG0 && lds32(sb + RS_O) != 0x12345678u, s, 6);
            x_second(xa, a, aA0, w, sb, s + 1, g, warp, tmX);
            EV(EV_BIG0, s, 7);
            x_finish(xa, sb, g, warp, lane0);
        } else {
            if (g == 0) {
                if (s < NSEG - 1) mem_attn(sb, s, warp, lane0);
            } else {
                if (s < NSEG - 1) { if (warp == 3) mem_scores(sb, s, lane0); else nbar_arrive(NB_Q, 256); }
                mbar_wait(sb + RB_KV, s & 1);
                if (s == 0 && warp == 0) {
                    wait_count_warp(&g_cnt[C_QH], 64 * E);
                    if (elect_one()) {
                        fence_proxy_global();
                        mbar_expect_tx(sb + RB_QX, 8192);
                        bulk_load(sb + RS_QX, g_qx + (uint32_t)(head * 4096), 8192, sb + RB_QX);
                    }
                    __syncwarp();
                }
                ta_scores(sb, s, warp, lane0);
            }
            EVCAL(s);
            mbar_wait(sb + RB_V, s & 1);
            mbar_wait(sb + RB_VX, s & 1);
            if (s < NSEG - 1) nbar_sync(NB_WO, 384); else nbar_sync(NB_BIG, 256);
            EV(EV_BIG0 && lds32(sb + RS_O) != 0x12345678u, s, 6);
            if (g == 0) ta_output<0>(sb, s, head, warp, lane0); else ta_output<1>(sb, s, head, warp, lane0);
            nbar_sync(NB_BIG, 256);
            EV(EV_BIG0 && lds32(sb + RS_O) != 0x12345678u, s, 7);
            if (g == 0 && warp == 0 && s + 1 < NSEG) {
                if (elect_one()) {
                    mbar_arrive_remote(mapa(sb + RB_ATT, 1));
                    mbar_arrive_remote(mapa(sb + RB_ATT, 2));
                    mbar_expect_tx(sb + RB_KV, 8192);
                    mbar_expect_tx(sb + RB_K, 2048);
                    mbar_expect_tx(sb + RB_V, 2048); mbar_expect_tx(sb + RB_VX, 8192);
                    mbar_arrive(sb + RB_T);
                }
                __syncwarp();
            }
        }
    }
    if constexpr (!XP) { if (tid_now() == 0) signal_count(&g_prog[(NSEG - 1) >> 1]); }
#undef lane0
}

template <int T, int K0, int K1>
DEVI void wo_part(float* acc) {
    constexpr uint32_t dWo = cdesc(T < 5 ? RS_WO + T * 16384 : RS_WO5, 16), dO = cdesc(RS_O, 128);
#pragma unroll
    for (int kk = K0; kk < K1; kk++) {
        if (kk == 0) { if (T < 3) wgmma_n8_ss_first<0>(acc, dWo, dO); else wgmma_n8_ss<0, 0>(acc, dWo, dO); }
        else wgmma_n8_ss<0, 1>(acc, dWo + kk * 128, dO + kk * 16);
    }
    wg_commit();
}
DEVI void red3(uint8_t* p, uint32_t a, uint32_t b, uint32_t c, uint32_t one) {
    asm volatile("red.relaxed.gpu.global.add.noftz.v4.bf16x2 [%0], {%1,%2,%3,%4};" :: "l"(p), "r"(a), "r"(b), "r"(c), "r"(one) : "memory");
}
constexpr int ACC_CH = 3 * 16 * 1024;
template <bool Q>
DEVI void wo_phase(uint32_t sb, int s, int warp, uint8_t* p, uint32_t ainv, int gap) {
    float a0[4], a1[4], a2[4];
    fence_proxy_async();
    const float2 iv = lds64f(ainv);
    SCHED_FENCE();
    const float i0 = rcp_fast(iv.x), i1 = rcp_fast(iv.y);
#define WORD(a, h) pack_bf16(a[2 * h] * i0, a[2 * h + 1] * i1)
    wg_fence();
    wo_part<0, 0, 8>(a0); wo_part<1, 0, 8>(a1); wo_part<2, 0, 8>(a2);
    wg_wait<1>(); reg_fence<4>(a0); reg_fence<4>(a1);
    if (!Q) nbar_arrive(NB_Q, 384);
    red3(p, WORD(a0, 0), WORD(a0, 1), WORD(a1, 0), 0x3F80u);
    SCHED_FENCE();
    EV(warp == 0 && elect_one(), s, 11);
    wg_wait<0>(); reg_fence<4>(a2);
    red3(p + ACC_CH, WORD(a2, 0), WORD(a2, 1), WORD(a1, 1), 0x3F80u);
    SCHED_FENCE();
    { const uint32_t t = clk32() + gap; while ((int)(clk32() - t) < 0) { } }
    wg_fence();
    wo_part<3, 0, 8>(a0); wo_part<4, 0, 8>(a1);
    if (Q) {
        wo_part<5, 0, 8>(a2);
        wg_wait<1>(); reg_fence<4>(a0); reg_fence<4>(a1);
        red3(p + 2 * ACC_CH, WORD(a0, 0), WORD(a0, 1), WORD(a1, 0), 0x3F80u);
        SCHED_FENCE();
        wg_wait<0>(); reg_fence<4>(a2);
        red3(p + 3 * ACC_CH, WORD(a2, 0), WORD(a2, 1), WORD(a1, 1), 0x3F80u);
        nbar_arrive(NB_WO, 384);
    } else {
        wg_wait<1>();
        nbar_arrive(NB_WO, 384);
        wg_wait<0>(); reg_fence<4>(a0); reg_fence<4>(a1);
        red3(p + 2 * ACC_CH, WORD(a0, 0), WORD(a0, 1), WORD(a1, 0), 0x3F80u);
        red3(p + 3 * ACC_CH, 0u, 0u, WORD(a1, 1), 0x3F80u);
    }
#undef WORD
}
DEVI void unit_pack(uint32_t* u, uint32_t x0, uint32_t x1, uint32_t x2, uint32_t x3) {
    u[0] = __byte_perm(x0, x1, 0x5410); u[1] = __byte_perm(x2, x3, 0x5410); u[2] = __byte_perm(x0, x1, 0x7632); u[3] = __byte_perm(x2, x3, 0x7632);
}
DEVI void unit_send(uint32_t d, const uint32_t* u, uint32_t bar, uint32_t r1, uint32_t r2) {
    st_async128(mapa(d, r1), u[0], u[1], u[2], u[3], mapa(bar, r1));
    st_async128(mapa(d, r2), u[0], u[1], u[2], u[3], mapa(bar, r2));
}
template <bool Q>
DEVI void stage_sums(uint32_t sb, int s, uint32_t rank, int warp, const uint8_t* src, uint32_t l, uint32_t gate) {
    uint4 v[4];
    while ((int)(clk32() - gate) < 0) { }
    EV(elect_one(), s, 16 + warp);
#pragma unroll
    for (int j = 0; j < 4; j++) v[j] = ld_rlx4(src + j * 1024);
    const uint32_t col = sb + RS_MEM + ((Q ? 0 : (rank == 1 ? 6 : 11)) + 3 * (warp >> 1)) * 1024 + ((l >> 2) & 0x300) + (l & 0x70);
    const uint32_t d0 = col + (warp & 1) * 2048, d1 = d0 ^ 160, d2 = (col ^ ((warp & 1) * 160)) + 1024;
    const uint32_t r1 = Q ? 1 : 0, r2 = Q ? 2 : 3 - rank, bar = sb + (warp < 2 ? RB_G + 8 * warp : (Q ? RB_G + 16 : RB_G3));
    int n = 0;
    while (!__all_sync(0xffffffffu, v[0].w == 0x4200u && v[1].w == 0x4200u && v[2].w == 0x4200u && v[3].w == 0x4200u)) {
#pragma unroll
        for (int j = 0; j < 4; j++) v[j] = ld_rlx4(src + j * 1024);
        if (++n > SPIN_LIMIT) __trap();
    }
    EV(elect_one(), s, 24 + warp);
    uint32_t u[12];
    unit_pack(u + 8, v[0].z, v[1].z, v[2].z, v[3].z);
    unit_send(d2, u + 8, bar, r1, r2);
    if (Q || warp < 3) {
        unit_pack(u, v[0].x, v[1].x, v[2].x, v[3].x);
        unit_pack(u + 4, v[0].y, v[1].y, v[2].y, v[3].y);
        unit_send(d0, u, bar, r1, r2);
        unit_send(d1, u + 4, bar, r1, r2);
        sts128(d0, make_uint4(u[0], u[1], u[2], u[3]));
        sts128(d1, make_uint4(u[4], u[5], u[6], u[7]));
    }
    sts128(d2, make_uint4(u[8], u[9], u[10], u[11]));
    __syncwarp();
    if (elect_one()) {
        mbar_expect_tx(bar, warp < 2 ? 3072u : (Q ? 0u : 1024u));
        if (warp == 0) mbar_expect_tx(sb + (Q ? RB_G3 : RB_G + 16), Q ? 4096u : 3072u);
    }
    EV(elect_one(), s, 20 + warp);
}
DEVI void wo_permute(uint32_t tile, int t) {
    const uint32_t a = tile + t * 32 + ((t >> 2) & 1) * 16;
#pragma unroll
    for (int h = 0; h < 2; h++) {
        uint4 v[3], u[3];
#pragma unroll
        for (int i = 0; i < 3; i++) if (3 * h + i < 5 || t < 32) { v[i] = lds128(a + (3 * h + i) * 3072); u[i] = lds128((a ^ 16) + (3 * h + i) * 3072); }
#pragma unroll
        for (int i = 0; i < 3; i++) if (3 * h + i < 5 || t < 32) {
            sts128(a + (3 * h + i) * 3072, make_uint4(__byte_perm(v[i].x, v[i].y, 0x5410), __byte_perm(v[i].x, v[i].y, 0x7632),
                                                      __byte_perm(u[i].x, u[i].y, 0x5410), __byte_perm(u[i].x, u[i].y, 0x7632)));
            sts128((a ^ 16) + (3 * h + i) * 3072, make_uint4(__byte_perm(v[i].z, v[i].w, 0x5410), __byte_perm(v[i].z, v[i].w, 0x7632),
                                                             __byte_perm(u[i].z, u[i].w, 0x5410), __byte_perm(u[i].z, u[i].w, 0x7632)));
        }
    }
}
DEVI uint32_t acc_clear(int slot, int idx, uint32_t lo) {
    uint8_t* p = g_acc + (uint32_t)(slot * 128 + idx * 3072 + (lo < 3072 ? lo : lo - 1024));
    st_rlx4(p, 0u, 0u, 0u, 0u);
    uint32_t z; asm volatile("ld.relaxed.gpu.global.u32 %0, [%1];" : "=r"(z) : "l"(p) : "memory");
    return z;
}

template <bool Q>
DEVI void aux_main(uint32_t sb, int warp, uint32_t rank, int head, const CUtensorMap* tmX, const bf16* xg, unsigned E, const int delay, const int gap) {
    const uint32_t lo = __shfl_sync(0xffffffffu, ((tid_now() >> 3) & 3) * 1024 + (tid_now() & 7) * 16, tid_now() & 31);
    for (int s = 0; s < NSEG - 1; s++) {
        if (!Q && warp == 0 && elect_one()) mbar_expect_tx(sb + RB_O, 2048 + 256);
        __syncwarp();
        const uint32_t slot = (s & 3) * 128;
        mbar_wait(sb + RB_O, s & 1);
        EV(warp == 0 && elect_one(), s, 10);
        wo_phase<Q>(sb, s, warp, g_acc + (uint32_t)(slot + (rank * 4 + warp) * 4096 + opaque(lo)), sb + RS_INV + ((opaque(lo) >> 1) & 24), gap);
        SCHED_FENCE();
        const uint32_t t_o = clk32();
        EV(warp == 0 && elect_one(), s, 12);
        {
            const uint32_t l = opaque(lo);
            stage_sums<Q>(sb, s, rank, warp, g_acc + (uint32_t)(slot + rank * 16384 + warp * ACC_CH + (l & 0xC00) * 4 + (l & 0x70)), l, t_o + delay);
        }
        EV(warp == 2 && elect_one(), s, 14);
        if (warp == (Q ? 3 : 1)) {
            if (Q) {
                mbar_wait(sb + RB_T, s & 1);
                if (s == 3) wait_count_warp(&g_cnt[C_Q], 64 * E);
                if (elect_one()) {
                    if (s == 3) fence_proxy_global();
                    fence_proxy_async();
                    mbar_expect_tx(sb + RB_QX, 8192);
                    bulk_load(sb + RS_QX, g_qx + (uint32_t)(((s + 1) * NH + head) * 4096), 8192, sb + RB_QX);
                    if (head == 0) { TLOG(1400 + s, 0, gtime()); TLOG(1400 + s, 1, clock64()); }
                }
                __syncwarp();
                const bool fresh = (s & 7) == 6 && s + 2 < NSEG;
                if (fresh) wait_count_warp(&g_cnt[C_Q + ((s + 2) >> 3)], 64 * E);
                if (elect_one()) {
                    if (fresh) fence_proxy_global();
                    if (s + 2 < NSEG && s != 2) l2_prefetch(g_qx + (uint32_t)(((s + 2) * NH + head) * 4096), 8192);
                    if (s + 4 < NSEG) l2_prefetch(xg + (uint32_t)(((s + 4) * 32 + head) * DM), 2048);
                    signal_count(&g_prog[s >> 1]);
                }
                __syncwarp();
            } else {
                const uint32_t zero = acc_clear((s + 2) & 3, 2 * head + (int)rank - 1, opaque(lo));
                x_send(sb, s + 1, rank, tmX);
                if (__any_sync(0xffffffffu, zero != 0u)) __trap();
            }
        }
    }
}

DEVI void load_weights(uint32_t sb, const CUtensorMap* tmW, const CUtensorMap* tmWo, int head, uint32_t rank, int2 t0) {
    const uint32_t c0 = clk32();
    if (rank == 0) while ((int)(clk32() - c0) < t0.x) { }
    const uint32_t bW = sb + RB_W, bSF = sb + RB_SF, bSE = sb + RB_SE;
    const int tile0 = rank == 0 ? 0 : (rank == 1 ? 6 : 11);
    mbar_expect_tx(bW, R_NSS * 16384);
    for (int pass = 0; pass < 2; pass++) {
        for (int pos = 0; pos < 16; pos++) {
            const int k = (int)((R_TORD_PACK >> (4 * pos)) & 15ull) * 64, rd = r_rs(pos), slot = rd % 5;
            if (r_pos_ss(pos)) {
                if (pass) continue;
                const uint32_t dst = sb + RS_WSS + r_ss(pos) * 16384;
                tma_load_2d(dst, tmW, head * DH, k, bW);
                tma_load_2d(dst + 8192, tmW, head * DH + 64, k, bW);
            } else if (pass == (rd >= 5)) {
                if (rd >= 5) mbar_wait(bSE + 8 * slot, ((rd / 5) - 1) & 1);
                mbar_expect_tx(bSF + 8 * slot, 16384);
                const uint32_t dst = sb + RS_WO + slot * 16384;
                tma_load_2d(dst, tmW, head * DH, k, bSF + 8 * slot);
                tma_load_2d(dst + 8192, tmW, head * DH + 64, k, bSF + 8 * slot);
            }
        }
    }
    while ((int)(clk32() - c0) < t0.y) { }
    if (rank == 0) { mbar_expect_tx(sb + RB_WO, 16384); tma_load_wo(sb + RS_WO5, tmWo, 5 * 64, head * 4, sb + RB_WO); }
    for (int i = 1; i <= 5; i++) {
        const int slot = i % 5, last = slot + 10 < R_NRS ? slot + 10 : slot + 5;
        mbar_wait(bSE + 8 * slot, (last / 5) & 1);
        mbar_expect_tx(bSF + 8 * slot, 16384);
        tma_load_wo(sb + RS_WO + slot * 16384, tmWo, (tile0 + slot) * 64, head * 4, bSF + 8 * slot);
    }
}
template <bool XP>
DEVI void big_prologue(uint32_t* w, uint32_t sb, int g, int warp, const bf16* __restrict__ mem0) {
    const int tid = tid_now(), lane = tid & 31;
    {
        const uint32_t* m = (const uint32_t*)(mem0 + (lane >> 2) * DM + (tid >> 5) * 16) + (lane & 3);
        uint32_t u[16];
#pragma unroll
        for (int j = 0; j < 8; j++) { u[2 * j] = m[j * 64]; u[2 * j + 1] = m[j * 64 + 4]; }
#pragma unroll
        for (int j = 0; j < 8; j++) sts64(sb + RS_MEM + ((tid >> 5) + j * 8) * 256 + b_frag_off(lane), u[2 * j], u[2 * j + 1]);
    }
    const uint32_t a0 = sb + RS_WO + g * (8192 + 4096) + a_frag_off(lane, warp), a1 = a0 + 8192 - g * 16384;
#pragma unroll
    for (int rd = 0; rd < R_NRS; rd++) {
        const int slot = rd % 5;
        mbar_wait(sb + RB_SF + 8 * slot, (rd / 5) & 1);
#pragma unroll
        for (int q = 0; q < 4; q++) {
            if (XP && rd == 0 && q == 3) {
                sts128(sb + RS_WX + g * 2048 + (tid & 127) * 16, lds128(sb + RS_WO + 8192 - g * 4096 + 2048 + (tid & 127) * 16));
                fence_proxy_async();
                nbar_sync(NB_WG + g, 128);
            } else ldsm4t(&w[rd * 16 + q * 4], ((q & 1) ? a1 : a0) + slot * 16384 + (q >> 1) * 2048);
        }
        mbar_arrive(sb + RB_SE + 8 * slot);
    }
    mbar_wait(sb + RB_W, 0);
    if (tid == 0) TLOG(1500 + blockIdx.x, 2, gtime());
}

#define REC_END() do { if (tid_now() == 0) TLOG(1024 + blockIdx.x, 1, gtime()); } while (0)
struct XMaps { CUtensorMap m[2]; };
__global__ void __launch_bounds__(384, 1)
k_rec(const __grid_constant__ PMaps mp, const __grid_constant__ CUtensorMap tmWk, const __grid_constant__ CUtensorMap tmWv,
      const __grid_constant__ CUtensorMap tmWo, const __grid_constant__ XMaps xm, const bf16* __restrict__ mem0, const bf16* __restrict__ xg,
      int4 tq, int4 tk, int2 t0, int rec) {
    extern __shared__ __align__(1024) uint8_t smem_raw[];
    const uint32_t sb = smem_u32(smem_raw);
    if ((sb & 0x3FFFFu) != SB0) __trap();
    const int tid = threadIdx.x;
    const int wg = __shfl_sync(0xffffffffu, tid >> 7, 0), warp = __shfl_sync(0xffffffffu, (tid >> 5) & 3, 0);
    uint32_t rank; asm("mov.u32 %0, %%cluster_ctarank;" : "=r"(rank));
    int head; asm("mov.u32 %0, %%clusterid.x;" : "=r"(head));
    asm volatile("griddepcontrol.launch_dependents;");
    if (tid == 0 && rec) {
        mbar_init(sb + RB_G, 1);
        mbar_init(sb + RB_G + 8, 1);
        mbar_init(sb + RB_G + 16, rank == 0 ? 2 : 1);
        mbar_init(sb + RB_G3, rank == 0 ? 1 : 2);
        mbar_init(sb + RB_T, 1); mbar_init(sb + RB_VX, 1); mbar_init(sb + RB_WO, 1);
        mbar_init(sb + RB_K, 1); mbar_init(sb + RB_V, 1); mbar_init(sb + RB_KV, 1); mbar_init(sb + RB_QX, 1);
        mbar_init(sb + RB_O, rank == 0 ? 4 : 1); mbar_init(sb + RB_ATT, 1); mbar_init(sb + RB_W, 1);
        for (int i = 0; i < 5; i++) { mbar_init(sb + RB_SF + 8 * i, 1); mbar_init(sb + RB_SE + 8 * i, 256); }
        for (int i = 0; i < 2; i++) mbar_init(sb + RB_XF + 8 * i, X_SLOTS);
        fence_mbar_init();
        if (rank == 0) { mbar_expect_tx(sb + RB_KV, 8192); mbar_expect_tx(sb + RB_K, 2048); mbar_expect_tx(sb + RB_V, 2048); mbar_expect_tx(sb + RB_VX, 8192); }
    }
    __syncthreads();
    asm volatile("barrier.cluster.arrive.release.aligned;" ::: "memory");

    if (wg < 2) {
        reg_inc<REG_KB>();
        if (rank != 0) {
            uint32_t w[R_NRS * 16];
            if ((tid & 127) == 0) for (int j = 0; j < X_SLOTS; j++) x_load(sb, 0, j, wg, xm.m);
            __syncwarp();
            cluster_wait();
            big_prologue<true>(w, sb, wg, warp, mem0);
            big_main<true>(w, sb, wg, warp, rank, head, xm.m, xg, 0u);
            REC_END();
        } else if (rec) {
            uint32_t w[R_NRS * 16];
            cluster_wait();
            big_prologue<false>(w, sb, wg, warp, mem0);
            big_main<false>(w, sb, wg, warp, rank, head, xm.m, xg, *(volatile unsigned*)&g_epoch + 1);
            REC_END();
        } else cluster_wait();
        if (rank == 0 && rec) nbar_arrive(NB_PRO, 256 + 32);
        nbar_sync(0, 384);
        post_consumer(mp, sb, wg, warp);
    } else {
        reg_dec<504 - 2 * REG_KB>();
        if (rec) {
            if (tid == 256) {
                if (rank == 0) l2_prefetch(xg + (uint32_t)(head * 8 * DM), 16384);
                load_weights(sb, rank == 0 ? &mp.wq : (rank == 1 ? &tmWk : &tmWv), &tmWo, head, rank, t0);
            }
            if (warp == 3 && rank != 0) {
                const uint32_t lo = ((tid >> 3) & 3) * 1024 + (tid & 7) * 16;
                acc_clear(0, 2 * head + (int)rank - 1, lo); acc_clear(1, 2 * head + (int)rank - 1, lo);
                __threadfence();
                __syncwarp();
                if (tid == 256 + 96) atomicAdd(&g_zero, 1u);
            }
            __syncwarp();
        }
        cluster_wait();
        const unsigned E = __shfl_sync(0xffffffffu, *(volatile unsigned*)&g_epoch + 1, 0);
        if (rec) {
            if (warp == 1) wait_count_warp(&g_zero, E * 64u);
            if (warp == 3) { if (rank != 0) x_send(sb, 0, rank, xm.m); }
            else {
                nbar_sync(NB_PRO, 96);
#pragma unroll 1
                for (int i = rank == 0 ? 0 : 1; i <= 5; i++) {
                    mbar_wait(sb + (i == 0 ? RB_WO : RB_SF + 8 * (i % 5)), i == 5);
                    if (i == 5 && tid == 288) TLOG(1500 + blockIdx.x, 0, gtime());
                    wo_permute(sb + (i == 0 ? RS_WO5 : RS_WO + (i % 5) * 16384), tid & 127);
                }
            }
            fence_proxy_async();
            nbar_sync(NB_AUX, 128);
            if (tid == 288) { TLOG(1500 + blockIdx.x, 1, gtime()); }
            if (rank == 0) aux_main<true>(sb, warp, rank, head, xm.m, xg, E, warp == 0 ? tq.x : (warp == 1 ? tq.y : tq.z), tq.w);
            else           aux_main<false>(sb, warp, rank, head, xm.m, xg, E, warp == 0 ? tk.x : (warp == 1 ? tk.y : tk.z), tk.w);
        }
        const int t = tid_now();
        if (t >= 320 && t < 320 + 13) asm volatile("prefetch.tensormap [%0];" :: "l"(&mp.wq + (t - 320)) : "memory");
        __syncwarp();
        if (warp == 0) post_producer(mp, sb, E, rank != 0 || !rec);
        else {
            if (warp == 1) {
                if (rank == 0 && rec) nbar_sync(NB_PRO, 256 + 32);
                if (elect_one()) post_init(sb);
                __syncwarp();
            }
            nbar_sync(0, 384);
            if (t == 288 || t == 320) post_helper(sb, warp - 1);
        }
    }
    __syncthreads();
    asm volatile("griddepcontrol.wait;" ::: "memory");
}

typedef CUresult (*EncodeFn)(CUtensorMap*, CUtensorMapDataType, cuuint32_t, void*, const cuuint64_t*, const cuuint64_t*,
                             const cuuint32_t*, const cuuint32_t*, CUtensorMapInterleave, CUtensorMapSwizzle,
                             CUtensorMapL2promotion, CUtensorMapFloatOOBfill);

static CUtensorMap make_map(EncodeFn fn, const void* ptr, uint64_t inner, uint64_t outer, uint32_t box_inner, uint32_t box_outer) {
    CUtensorMap m;
    cuuint64_t dims[2] = {inner, outer};
    cuuint64_t strides[1] = {inner * 2};
    cuuint32_t box[2] = {box_inner, box_outer};
    cuuint32_t es[2] = {1, 1};
    fn(&m, CU_TENSOR_MAP_DATA_TYPE_BFLOAT16, 2, const_cast<void*>(ptr), dims, strides, box, es,
       CU_TENSOR_MAP_INTERLEAVE_NONE, CU_TENSOR_MAP_SWIZZLE_128B, CU_TENSOR_MAP_L2_PROMOTION_L2_256B, CU_TENSOR_MAP_FLOAT_OOB_FILL_NONE);
    return m;
}

static CUtensorMap make_wo_map(EncodeFn fn, const void* ptr, uint64_t rows, uint32_t ngrp) {
    CUtensorMap m;
    cuuint64_t dims[5] = {DM, 2, 4, 4, rows / 32};
    cuuint64_t strides[4] = {DM * 2, 8 * DM * 2, 2 * DM * 2, 32 * DM * 2};
    cuuint32_t box[5] = {64, 2, 4, 4, ngrp};
    cuuint32_t es[5] = {1, 1, 1, 1, 1};
    fn(&m, CU_TENSOR_MAP_DATA_TYPE_BFLOAT16, 5, const_cast<void*>(ptr), dims, strides, box, es,
       CU_TENSOR_MAP_INTERLEAVE_NONE, CU_TENSOR_MAP_SWIZZLE_128B, CU_TENSOR_MAP_L2_PROMOTION_L2_256B, CU_TENSOR_MAP_FLOAT_OOB_FILL_NONE);
    return m;
}

struct Maps {
    PMaps post;
    CUtensorMap wk16, wv16, wo128;
    XMaps x32;
};

extern "C" void kernel_launch(void* const* d_in, const int* in_sizes, int n_in, void* d_out, int out_size) {
    const bf16* A_x   = (const bf16*)d_in[0];
    const bf16* A_mem = (const bf16*)d_in[1];
    const bf16* A_Wq  = (const bf16*)d_in[2];
    const bf16* A_Wk  = (const bf16*)d_in[3];
    const bf16* A_Wv  = (const bf16*)d_in[4];
    const bf16* A_Wo  = (const bf16*)d_in[5];
    const bf16* B_x   = (const bf16*)d_in[7];
    const bf16* B_w   = (const bf16*)d_in[8];
    const bf16* B_wo  = (const bf16*)d_in[9];

    static EncodeFn fn = nullptr;
    static Maps mp;
    static const void* cached[10];
    const void* cur[10] = {A_x, A_mem, A_Wq, A_Wk, A_Wv, A_Wo, B_x, B_w, B_wo, d_out};
    bool same = fn != nullptr;
    for (int i = 0; i < 10 && same; i++) same = cached[i] == cur[i];
    if (!same) {
        if (!fn) {
            void* p = nullptr; cudaDriverEntryPointQueryResult qr;
            cudaGetDriverEntryPoint("cuTensorMapEncodeTiled", &p, cudaEnableDefault, &qr);
            fn = (EncodeFn)p;
            cudaFuncSetAttribute(k_rec, cudaFuncAttributeMaxDynamicSharedMemorySize, R_SMEM);
        }
        void *p_ox, *p_bqkv, *p_bo, *p_qx;
        cudaGetSymbolAddress(&p_qx, g_qx);
        cudaGetSymbolAddress(&p_ox, g_ox); cudaGetSymbolAddress(&p_bqkv, g_bqkv); cudaGetSymbolAddress(&p_bo, g_bo);
        mp.post.wq   = make_map(fn, A_Wq, HD, DM, 64, 64);
        mp.post.wo   = make_wo_map(fn, A_Wo, HD, 2);
        mp.post.bw   = make_map(fn, B_w, 3 * DM, DM, 64, 64);
        mp.post.bwo  = make_wo_map(fn, B_wo, DM, 2);
        mp.post.x    = make_map(fn, A_x, DM, S_TOK, 64, 128);
        mp.post.bx   = make_map(fn, B_x, DM, S_TOK, 64, 128);
        mp.post.bo   = make_map(fn, p_bo, DM, S_TOK, 64, 128);
        mp.post.ox   = make_map(fn, p_ox, HD, S_TOK, 64, 128);
        mp.post.ox64 = make_map(fn, p_ox, HD, S_TOK, 64, 64);
        mp.post.cb   = make_map(fn, p_bqkv, 3 * DM, S_TOK, 64, 64);
        mp.post.cout = make_map(fn, d_out, 2 * DM, S_TOK, 64, 64);
        {
            cuuint64_t dims[4] = {256, 4, NH * 4, NSEG};
            cuuint64_t strides[3] = {512, 2048, NH * 8192};
            cuuint32_t box[4] = {256, 2, 4, 2};
            cuuint32_t es[4] = {1, 1, 1, 1};
            fn(&mp.post.cq, CU_TENSOR_MAP_DATA_TYPE_BFLOAT16, 4, p_qx, dims, strides, box, es,
               CU_TENSOR_MAP_INTERLEAVE_NONE, CU_TENSOR_MAP_SWIZZLE_NONE, CU_TENSOR_MAP_L2_PROMOTION_NONE, CU_TENSOR_MAP_FLOAT_OOB_FILL_NONE);
        }
        {
            int runs[48] = {K_QH, 0, 2, K_Q, 1, 7, K_B1, 0, 8, K_A4, 0, 4, K_B2, 0, 32, K_A4, 4, 2, K_B3, 0, 2, K_A3, 12, 2, K_B3, 2, 6,
                            K_SK, 14, 2, -1};
            int nlate = 9;
            const int per[9] = {32, 24, 8, 8, 32, 8, 8 * P_SPLIT, 1, 8 * P_SPLIT};
            int n = 0, id = 0;
            for (; runs[3 * n] >= 0; n++) {
                mp.post.list.run[n] = make_int4(runs[3 * n], runs[3 * n + 1], id, id + runs[3 * n + 2] * per[runs[3 * n]]);
                id = mp.post.list.run[n].w;
            }
            mp.post.list.n = n;
            mp.post.list.late = mp.post.list.run[nlate].z;
            int dev = 0, nsm = 132;
            cudaGetDevice(&dev);
            cudaDeviceGetAttribute(&nsm, cudaDevAttrMultiProcessorCount, dev);
            mp.post.list.nworker = nsm > 96 ? nsm : 97;
        }
        {
            cuuint64_t dims[4] = {DM, 3, 2, S_TOK / 2};
            cuuint64_t strides[3] = {DM * 2, 3 * DM * 2, 3 * DM * 4};
            cuuint32_t box[4] = {64, 3, 1, 40};
            cuuint32_t es[4] = {1, 1, 1, 1};
            fn(&mp.post.b40, CU_TENSOR_MAP_DATA_TYPE_BFLOAT16, 4, p_bqkv, dims, strides, box, es,
               CU_TENSOR_MAP_INTERLEAVE_NONE, CU_TENSOR_MAP_SWIZZLE_128B, CU_TENSOR_MAP_L2_PROMOTION_L2_256B, CU_TENSOR_MAP_FLOAT_OOB_FILL_NONE);
        }
        mp.wk16 = make_map(fn, A_Wk, HD, DM, 64, 64);
        mp.wv16 = make_map(fn, A_Wv, HD, DM, 64, 64);
        mp.wo128 = make_wo_map(fn, A_Wo, HD, 4);
        for (int i = 0; i < 2; i++) {
            cuuint64_t dims[3] = {64, S_TOK, DM / 64};
            cuuint64_t strides[2] = {DM * 2, 128};
            cuuint32_t box[3] = {32, 32, 2u - i};
            cuuint32_t es[3] = {1, 1, 1};
            fn(&mp.x32.m[i], CU_TENSOR_MAP_DATA_TYPE_BFLOAT16, 3, const_cast<bf16*>(A_x), dims, strides, box, es,
               CU_TENSOR_MAP_INTERLEAVE_NONE, CU_TENSOR_MAP_SWIZZLE_64B, CU_TENSOR_MAP_L2_PROMOTION_L2_128B, CU_TENSOR_MAP_FLOAT_OOB_FILL_NONE);
        }
        for (int i = 0; i < 10; i++) cached[i] = cur[i];
    }

    cudaStream_t st = cudaStreamPerThread;
    int4 tq = make_int4(0, 100, 580, 80), tk = make_int4(0, 270, 720, 55);
    int2 t0 = make_int2(13000, 16000);
    cudaLaunchConfig_t cfg = {};
    cfg.gridDim = dim3(96); cfg.blockDim = dim3(384); cfg.dynamicSmemBytes = R_SMEM; cfg.stream = st;
    cudaLaunchAttribute at[1];
    at[0].id = cudaLaunchAttributeClusterDimension;
    at[0].val.clusterDim.x = 3; at[0].val.clusterDim.y = 1; at[0].val.clusterDim.z = 1;
    cfg.attrs = at; cfg.numAttrs = 1;
    cudaLaunchKernelEx(&cfg, k_rec, mp.post, mp.wk16, mp.wv16, mp.wo128, mp.x32, A_mem, A_x, tq, tk, t0, 1);
    cfg.gridDim = dim3(mp.post.list.nworker - 96);
    at[0].id = cudaLaunchAttributeProgrammaticStreamSerialization;
    at[0].val.programmaticStreamSerializationAllowed = 1;
    cudaLaunchKernelEx(&cfg, k_rec, mp.post, mp.wk16, mp.wv16, mp.wo128, mp.x32, A_mem, A_x, tq, tk, t0, 0);
}
```
